```python
import torch

def _softmax(x, axis=-1):
    return torch.softmax(x, dim=axis)

def _gelu(x):
    return torch.nn.functional.gelu(x, approximate='tanh')

def _silu(x):
    return torch.nn.functional.silu(x)

def _sigmoid(x):
    return torch.sigmoid(x)

def _layernorm(x, axis=-1, eps=1e-05):
    m = x.mean(dim=axis, keepdim=True)
    v = x.var(dim=axis, keepdim=True, unbiased=False)
    return (x - m) / torch.sqrt(v + eps)

def _scatter_add(tgt, idx, src, axis=0):
    return tgt.clone().index_add_(axis, idx, src)

def _segment_sum(src, seg, n):
    out = torch.zeros((n,) + src.shape[1:], dtype=src.dtype)
    return out.index_add_(0, seg, src)

def _pad(x, pw):
    flat = tuple((v for pair in reversed(pw) for v in pair))
    return torch.nn.functional.pad(x, flat)
kernel_name = 'gated_mix__memory_aug_recurrent_mem_tr__spectral_gfnet__prompt'

def setup_inputs():

    _w = lambda a: (lambda t: t.to(torch.bfloat16) if t.is_floating_point() else t)(torch.as_tensor(a))

    def _A_setup():
        B, S, Dm = (1, 2048, 1024)
        H, Dh = (32, 128)
        M, seg = (8, 32)
        seg = min(seg, S)
        S = S // seg * seg
        return {'x': _w((lambda *s: torch.randn(*s, dtype=torch.bfloat16) * 0.05)(B, S, Dm)), 'mem0': _w((lambda *s: torch.randn(*s, dtype=torch.bfloat16) * 0.4)(B, M, Dm)), 'Wq': _w((lambda *s: torch.randn(*s, dtype=torch.bfloat16) * 6.4)(Dm, H, Dh) * Dm ** (-0.5)), 'Wk': _w((lambda *s: torch.randn(*s, dtype=torch.bfloat16) * 6.4)(Dm, H, Dh) * Dm ** (-0.5)), 'Wv': _w((lambda *s: torch.randn(*s, dtype=torch.bfloat16) * 0.4)(Dm, H, Dh) * Dm ** (-0.5)), 'Wo': _w((lambda *s: torch.randn(*s, dtype=torch.bfloat16) * 0.4)(H, Dh, Dm) * (H * Dh) ** (-0.5)), 'seg_len': seg}
    _A_in = _A_setup()

    def _B_setup():
        B, S, D = (1, 2048, 1024)
        Df = D // 2 + 1
        return {'x': _w((lambda *s: torch.randn(*s, dtype=torch.bfloat16) * 0.05)(B, S, D)), 'w_r': _w((lambda *s: torch.randn(*s, dtype=torch.bfloat16) * 3.2)(S, Df) * 0.02), 'w_i': _w((lambda *s: torch.randn(*s, dtype=torch.bfloat16) * 3.2)(S, Df) * 0.02)}
    _B_in = _B_setup()
    return {'A_x': _A_in['x'], 'A_mem0': _A_in['mem0'], 'A_Wq': _A_in['Wq'], 'A_Wk': _A_in['Wk'], 'A_Wv': _A_in['Wv'], 'A_Wo': _A_in['Wo'], 'A_seg_len': _A_in['seg_len'], 'B_x': _B_in['x'], 'B_w_r': _B_in['w_r'], 'B_w_i': _B_in['w_i'], 'gate_w': _w((lambda *s: torch.randn(*s, dtype=torch.bfloat16) * 0.05)(1024) * 16.0)}

def reference(A_x, A_mem0, A_Wq, A_Wk, A_Wv, A_Wo, A_seg_len, B_x, B_w_r, B_w_i, gate_w):

    def _A_ref(x, mem0, Wq, Wk, Wv, Wo, seg_len):
        B, S, Dm = x.shape
        H, Dh = (Wq.shape[1], Wq.shape[2])
        M = mem0.shape[1]
        scale = Dh ** (-0.5)
        n_seg = S // seg_len
        L = M + seg_len
        idx = torch.arange(L)
        mask = (idx[:, None] < M) | (idx[:, None] >= idx[None, :])
        mem = mem0
        outs = []
        for s in range(n_seg):
            xs = x[:, s * seg_len:(s + 1) * seg_len, :].clone()
            h = torch.concatenate([mem, xs], axis=1)
            q = torch.einsum('btd,dhe->bhte', h, Wq)
            k = torch.einsum('btd,dhe->bhte', h, Wk)
            v = torch.einsum('btd,dhe->bhte', h, Wv)
            scores = torch.einsum('bhqe,bhke->bhqk', q, k) * scale
            scores = torch.where(mask[None, None], scores, -1000000000.0)
            p = _softmax(scores, axis=-1)
            o = torch.einsum('bhqk,bhke->bhqe', p, v)
            o = torch.einsum('bhte,hed->btd', o, Wo)
            mem = o[:, :M, :].clone()
            outs.append(o[:, M:, :])
        return torch.concatenate(outs, axis=1)

    def _B_ref(x, w_r, w_i):
        B, S, D = x.shape
        X = (lambda x, axes=(-2, -1): torch.fft.rfft2(x.float(), dim=axes))(x, axes=(-2, -1))
        W = w_r + 1j * w_i
        X = X * W
        y = (lambda x, s, axes=(-2, -1): torch.fft.irfft2(x, s=s, dim=axes).to(torch.bfloat16))(X, (S, D), axes=(-2, -1))
        return y
    x = A_x
    g = _sigmoid((x * gate_w).sum(-1, keepdims=True))
    a = _A_ref(x, A_mem0, A_Wq, A_Wk, A_Wv, A_Wo, A_seg_len)
    b = _B_ref(x, B_w_r, B_w_i)
    return g * a + (1 - g) * b
```

```cpp
#include <cuda_runtime.h>
#include <cuda_bf16.h>
#include <cuda.h>
#include <stdint.h>

#define DLY_E1 300
#define DLY_V 330
#define DLY_E2 400
#define DLY_E3 400
#define DLY_X 120
#define DLY_S 500
#define DLY_F 200
#define VM_AT 1
#define VM_F 0
#define OM_F 1
#define SXX_IN 0
#define C1_AT 1
#define NLAG 4
#define WO_D 2
#define WO_0 2
#define WO_1 12
#define PL_0 6
#define PL_1 12
#define PL_D 2
#define PL_L 0
#define DUAL 0
#define HV_D 3
#define DLY_FK 0
#define QX_SM 0
#define REG_F 216
#define REG_H 24
#define SC_F 1
#define E2_F 1
#define KVQ_AT 0
#define DLY_K 0
#define X_AT 0
#define W_PV 0
#define PL_2 12
#define BF_E 3
#define PL_E 2
#define ORDER 1
#define SSPOS 1
#define W_PUB 1
#define FIN_AT 1
#define AWARE 1
#define NPROBE 6
#define NP_ 12
#define USE_PDL 1
#define DLY_GRP 3000
#define P2_BULK 0

namespace {

constexpr int S_ = 2048, D_ = 1024, NSEG = 64;
constexpr uint32_t SENT = 0xFFFFFFFFu;
constexpr int NSLOT = 4;

constexpr uint32_t M_PAIR = 0, M_E3 = M_PAIR + 2 * 128 * 8192, M_REF = M_E3 + 16 * 8192, M_KVQ = M_REF + 8192,
                   MAIL_BYTES = M_KVQ + NSLOT * 32 * 24576;
__device__ __align__(1024) unsigned char g_mail[MAIL_BYTES + 8192];
constexpr int C_SEL = 0, C_P1 = C_SEL + 128, C_CHAIN_END = C_P1 + 32, C_ROWS = C_CHAIN_END, C_END = C_ROWS + 16 * 32;
__device__ __align__(1024) uint32_t g_ctl[C_END];
#define CLK(i)
#define TL(i)
__device__ __align__(1024) __nv_bfloat16 g_ox[S_ * 4096];
__device__ __align__(1024) float2 g_z[257 * 4096];
__device__ __align__(1024) uint32_t g_wp[257 * 4096];
__device__ __align__(1024) __nv_bfloat16 g_b[S_ * D_];
__device__ float g_gate[S_];

#define TRV(s, ev, val)
#define TR(s, ev)
#define TRSYNC(ev)
__device__ __forceinline__ uint32_t smem_u32(const void* p) { return (uint32_t)__cvta_generic_to_shared(p); }
__device__ __forceinline__ void watchdog(uint32_t& n, uint32_t limit) {
  asm volatile("{ .reg .pred p; add.u32 %0, %0, 1; setp.gt.u32 p, %0, %1; @p trap; }" : "+r"(n) : "r"(limit));
}
__device__ __forceinline__ void mbar_init(uint32_t bar, uint32_t cnt) {
  asm volatile("mbarrier.init.shared::cta.b64 [%0], %1;" :: "r"(bar), "r"(cnt) : "memory");
}
__device__ __forceinline__ void mbar_arrive_warp(uint32_t bar) {
  __syncwarp();
  asm volatile("{ .reg .pred p; elect.sync _|p, 0xffffffff; @p mbarrier.arrive.shared::cta.b64 _, [%0]; }" :: "r"(bar) : "memory");
}
__device__ __forceinline__ uint32_t clock_lo() {
  uint32_t r; asm volatile("{ .reg .u64 c; .reg .u32 h; mov.u64 c, %%clock64; mov.b64 {%0, h}, c; }" : "=r"(r) :: "memory"); return r;
}
__device__ __forceinline__ void delay_until(uint32_t t) {
  asm volatile("{ .reg .pred p; .reg .u64 c; .reg .u32 l, h;\n"
               "DLY: mov.u64 c, %%clock64; mov.b64 {l, h}, c; sub.s32 l, l, %0; setp.lt.s32 p, l, 0; @p bra.uni DLY; }" :: "r"(t) : "memory");
}
__device__ __forceinline__ void delay_cycles(uint32_t n) { delay_until(clock_lo() + n); }
__device__ __forceinline__ void sched_fence(uint32_t z) {
  asm volatile("{ .reg .pred p; setp.eq.u32 p, %0, 0x7fff0000; @p pmevent 1; }" :: "r"(z) : "memory");
}
__device__ __forceinline__ void pdl_wait() { asm volatile("griddepcontrol.wait;" ::: "memory"); }
__device__ __forceinline__ void pdl_launch() { asm volatile("griddepcontrol.launch_dependents;" ::: "memory"); }
__device__ __forceinline__ float ex2(float x) { float r; asm("ex2.approx.ftz.f32 %0, %1;" : "=f"(r) : "f"(x)); return r; }
__device__ __forceinline__ float rcp(float x) { float r; asm("rcp.approx.ftz.f32 %0, %1;" : "=f"(r) : "f"(x)); return r; }
__device__ __forceinline__ void mbar_expect(uint32_t bar, uint32_t bytes) {
  asm volatile("mbarrier.arrive.expect_tx.shared::cta.b64 _, [%0], %1;" :: "r"(bar), "r"(bytes) : "memory");
}
__device__ __forceinline__ bool mbar_try(uint32_t bar, uint32_t ph) {
  uint32_t ok;
  asm volatile("{ .reg .pred p; mbarrier.try_wait.parity.shared::cta.b64 p, [%1], %2; selp.u32 %0, 1, 0, p; }"
               : "=r"(ok) : "r"(bar), "r"(ph) : "memory");
  return ok;
}
__device__ __forceinline__ void mbar_wait(uint32_t bar, uint32_t ph) {
  uint32_t n = 0;
  while (!mbar_try(bar, ph)) { watchdog(n, (1u << 20)); }
}
__device__ __forceinline__ void mbar_spin(uint32_t bar, uint32_t ph) { while (!mbar_try(bar, ph)) {} }
__device__ __forceinline__ void mbar_spin_cluster(uint32_t bar, uint32_t ph) {
  uint32_t ok;
  do {
    asm volatile("{ .reg .pred p; mbarrier.try_wait.parity.acquire.cluster.shared::cta.b64 p, [%1], %2; selp.u32 %0, 1, 0, p; }"
                 : "=r"(ok) : "r"(bar), "r"(ph) : "memory");
  } while (!ok);
}
__device__ __forceinline__ void tma2d(uint32_t dst, const CUtensorMap* tm, int c0, int c1, uint32_t bar) {
  asm volatile("cp.async.bulk.tensor.2d.shared::cluster.global.mbarrier::complete_tx::bytes [%0], [%1, {%3, %4}], [%2];"
               :: "r"(dst), "l"(tm), "r"(bar), "r"(c0), "r"(c1) : "memory");
}
__device__ __forceinline__ void tma2d_store(const CUtensorMap* tm, int c0, int c1, uint32_t src) {
  asm volatile("cp.async.bulk.tensor.2d.global.shared::cta.bulk_group [%0, {%2, %3}], [%1];"
               :: "l"(tm), "r"(src), "r"(c0), "r"(c1) : "memory");
}
__device__ __forceinline__ void mbar_expect_e(uint32_t bar, uint32_t bytes) {
  asm volatile("{ .reg .pred p; elect.sync _|p, 0xffffffff; @p mbarrier.arrive.expect_tx.shared::cta.b64 _, [%0], %1; }" :: "r"(bar), "r"(bytes) : "memory");
}
__device__ __forceinline__ void tma2d_e(uint32_t dst, const CUtensorMap* tm, int c0, int c1, uint32_t bar) {
  asm volatile("{ .reg .pred p; elect.sync _|p, 0xffffffff;\n"
               "@p cp.async.bulk.tensor.2d.shared::cluster.global.mbarrier::complete_tx::bytes [%0], [%1, {%3, %4}], [%2]; }"
               :: "r"(dst), "l"(tm), "r"(bar), "r"(c0), "r"(c1) : "memory");
}
__device__ __forceinline__ void tma4d_e(uint32_t dst, const CUtensorMap* tm, int c2, int c3, uint32_t bar) {
  asm volatile("{ .reg .pred p; elect.sync _|p, 0xffffffff;\n"
               "@p cp.async.bulk.tensor.4d.shared::cluster.global.mbarrier::complete_tx::bytes [%0], [%1, {0, 0, %3, %4}], [%2]; }"
               :: "r"(dst), "l"(tm), "r"(bar), "r"(c2), "r"(c3) : "memory");
}
__device__ __forceinline__ void bulk_load_e(uint32_t dst, const void* src, uint32_t bytes, uint32_t bar) {
  asm volatile("{ .reg .pred p; elect.sync _|p, 0xffffffff;\n"
               "@p cp.async.bulk.shared::cluster.global.mbarrier::complete_tx::bytes [%0], [%1], %2, [%3]; }"
               :: "r"(dst), "l"(src), "r"(bytes), "r"(bar) : "memory");
}
__device__ __forceinline__ void prefetch2d_e(const CUtensorMap* tm, int c0, int c1) {
  asm volatile("{ .reg .pred p; elect.sync _|p, 0xffffffff;\n"
               "@p cp.async.bulk.prefetch.tensor.2d.L2.global [%0, {%1, %2}]; }" :: "l"(tm), "r"(c0), "r"(c1) : "memory");
}
__device__ __forceinline__ void st_pub4(void* p, uint4 v) {
  asm volatile("st.relaxed.gpu.global.v4.u32 [%0], {%1,%2,%3,%4};" :: "l"(p), "r"(v.x), "r"(v.y), "r"(v.z), "r"(v.w) : "memory");
}
__device__ __forceinline__ void st_pub_if(void* p, uint32_t v, bool on) {
  asm volatile("{ .reg .pred p; setp.ne.u32 p, %2, 0; @p st.relaxed.gpu.global.u32 [%0], %1; }" :: "l"(p), "r"(v), "r"((uint32_t)on) : "memory");
}
__device__ __forceinline__ uint32_t mapa(uint32_t a, uint32_t r) {
  uint32_t d; asm volatile("mapa.shared::cluster.u32 %0, %1, %2;" : "=r"(d) : "r"(a), "r"(r)); return d;
}
__device__ __forceinline__ void st_async4(uint32_t a, uint32_t x, uint32_t y, uint32_t z, uint32_t w, uint32_t bar) {
  asm volatile("st.async.shared::cluster.mbarrier::complete_tx::bytes.v4.u32 [%0], {%1,%2,%3,%4}, [%5];"
               :: "r"(a), "r"(x), "r"(y), "r"(z), "r"(w), "r"(bar) : "memory");
}
__device__ __forceinline__ uint4 ld_poll(const void* p) {
  uint4 v;
  asm volatile("ld.volatile.global.v4.u32 {%0,%1,%2,%3}, [%4];" : "=r"(v.x), "=r"(v.y), "=r"(v.z), "=r"(v.w) : "l"(p) : "memory");
  return v;
}
__device__ __forceinline__ uint2 ld_poll2(const void* p) {
  uint2 v; asm volatile("ld.volatile.global.v2.u32 {%0,%1}, [%2];" : "=r"(v.x), "=r"(v.y) : "l"(p) : "memory"); return v;
}
__device__ __forceinline__ void st_pub2(void* p, uint32_t a, uint32_t b) {
  asm volatile("st.relaxed.gpu.global.v2.u32 [%0], {%1,%2};" :: "l"(p), "r"(a), "r"(b) : "memory");
}
__device__ __forceinline__ uint32_t ld_poll1(const void* p) {
  uint32_t v; asm volatile("ld.volatile.global.u32 %0, [%1];" : "=r"(v) : "l"(p) : "memory"); return v;
}
__device__ __forceinline__ uint32_t ld_acquire(const uint32_t* p) {
  uint32_t v; asm volatile("ld.acquire.gpu.global.u32 %0, [%1];" : "=r"(v) : "l"(p) : "memory"); return v;
}
__device__ __forceinline__ void st_pub(void* p, uint32_t v) {
  asm volatile("st.relaxed.gpu.global.u32 [%0], %1;" :: "l"(p), "r"(v) : "memory");
}
__device__ __forceinline__ uint32_t lds32(uint32_t a) {
  uint32_t v; asm volatile("ld.shared.u32 %0, [%1];" : "=r"(v) : "r"(a) : "memory"); return v;
}
__device__ __forceinline__ uint32_t timed_init(void* p) {
  uint32_t t;
  asm volatile("{ .reg .pred q; .reg .u32 a, b, v; elect.sync _|q, 0xffffffff; mov.u32 v, 0; mov.u32 a, %%clock;\n"
               "@q atom.relaxed.gpu.global.exch.b32 v, [%1], 0xffffffff; shfl.sync.idx.b32 v, v, 0, 31, 0xffffffff;\n"
               "setp.eq.u32 q, v, 0x12345; @q pmevent 1; mov.u32 b, %%clock; sub.u32 %0, b, a; }" : "=r"(t) : "l"(p) : "memory");
  return t;
}
__device__ __forceinline__ uint4 lds128(uint32_t a) {
  uint4 v; asm volatile("ld.shared.v4.u32 {%0,%1,%2,%3}, [%4];" : "=r"(v.x), "=r"(v.y), "=r"(v.z), "=r"(v.w) : "r"(a) : "memory"); return v;
}
__device__ __forceinline__ uint2 lds64(uint32_t a) {
  uint2 v; asm volatile("ld.shared.v2.u32 {%0,%1}, [%2];" : "=r"(v.x), "=r"(v.y) : "r"(a) : "memory"); return v;
}
__device__ __forceinline__ void sts128(uint32_t a, uint4 v) {
  asm volatile("st.shared.v4.u32 [%0], {%1,%2,%3,%4};" :: "r"(a), "r"(v.x), "r"(v.y), "r"(v.z), "r"(v.w) : "memory");
}
__device__ __forceinline__ void sts64(uint32_t a, uint32_t x, uint32_t y) { asm volatile("st.shared.v2.u32 [%0], {%1,%2};" :: "r"(a), "r"(x), "r"(y) : "memory"); }
__device__ __forceinline__ void sts32(uint32_t a, uint32_t x) { asm volatile("st.shared.u32 [%0], %1;" :: "r"(a), "r"(x) : "memory"); }
__device__ __forceinline__ void ldsm4t(uint32_t (&r)[4], uint32_t a) {
  asm volatile("ldmatrix.sync.aligned.m8n8.x4.trans.shared.b16 {%0,%1,%2,%3}, [%4];"
               : "=r"(r[0]), "=r"(r[1]), "=r"(r[2]), "=r"(r[3]) : "r"(a) : "memory");
}
template<bool TRANS> __device__ __forceinline__ void stsm4(uint32_t a, uint32_t r0, uint32_t r1, uint32_t r2, uint32_t r3) {
  if (TRANS) asm volatile("stmatrix.sync.aligned.m8n8.x4.trans.shared.b16 [%0], {%1,%2,%3,%4};" :: "r"(a), "r"(r0), "r"(r1), "r"(r2), "r"(r3) : "memory");
  else       asm volatile("stmatrix.sync.aligned.m8n8.x4.shared.b16 [%0], {%1,%2,%3,%4};" :: "r"(a), "r"(r0), "r"(r1), "r"(r2), "r"(r3) : "memory");
}
__device__ __forceinline__ void mma16816(float (&d)[4], uint32_t a0, uint32_t a1, uint32_t a2, uint32_t a3, uint32_t b0, uint32_t b1) {
  asm volatile("mma.sync.aligned.m16n8k16.row.col.f32.bf16.bf16.f32 {%0,%1,%2,%3}, {%4,%5,%6,%7}, {%8,%9}, {%0,%1,%2,%3};"
               : "+f"(d[0]), "+f"(d[1]), "+f"(d[2]), "+f"(d[3]) : "r"(a0), "r"(a1), "r"(a2), "r"(a3), "r"(b0), "r"(b1));
}
__device__ __forceinline__ void mma1688(float (&d)[4], uint32_t a0, uint32_t a1, uint32_t b0) {
  asm volatile("mma.sync.aligned.m16n8k8.row.col.f32.bf16.bf16.f32 {%0,%1,%2,%3}, {%4,%5}, {%6}, {%0,%1,%2,%3};"
               : "+f"(d[0]), "+f"(d[1]), "+f"(d[2]), "+f"(d[3]) : "r"(a0), "r"(a1), "r"(b0));
}
__device__ __forceinline__ uint32_t pack_bf16(float lo, float hi) {
  uint32_t r; asm("cvt.rn.bf16x2.f32 %0, %1, %2;" : "=r"(r) : "f"(hi), "f"(lo)); return r;
}
__device__ __forceinline__ uint32_t add_bf16x2(uint32_t a, uint32_t b) {
  uint32_t r; asm("add.rn.bf16x2 %0, %1, %2;" : "=r"(r) : "r"(a), "r"(b)); return r;
}
__device__ __forceinline__ uint32_t umax4(uint4 v) { return max(max(v.x, v.y), max(v.z, v.w)); }
__device__ __forceinline__ uint32_t opaque(uint32_t x) { uint32_t r; asm volatile("mov.u32 %0, %1;" : "=r"(r) : "r"(x)); return r; }
template<class T> __device__ __forceinline__ void pin(T*& p) { asm volatile("" : "+l"(p)); }
__device__ __forceinline__ void pin(uint32_t& v) { asm volatile("" : "+r"(v)); }
__device__ __forceinline__ uint32_t desc_lo(uint32_t addr) { return ((addr & 0x3FFFF) >> 4) | 0x10000; }
__device__ __forceinline__ uint64_t desc128(uint32_t lo) {
  uint64_t d; asm("mov.b64 %0, {%1, %2};" : "=l"(d) : "r"(lo), "r"(0x40000040)); return d;
}
#define WG_FENCE()  asm volatile("wgmma.fence.sync.aligned;" ::: "memory")
#define WG_COMMIT() asm volatile("wgmma.commit_group.sync.aligned;" ::: "memory")
#define WG_WAIT(n)  asm volatile("wgmma.wait_group.sync.aligned " #n ";" ::: "memory")
#define FENCE_ASYNC_SMEM() asm volatile("fence.proxy.async.shared::cta;" ::: "memory")
__device__ __forceinline__ void bar_sync(int id, int n) { asm volatile("bar.sync %0, %1;" :: "r"(id), "r"(n) : "memory"); }

#define D16(c) c(d[0]), c(d[1]), c(d[2]), c(d[3]), c(d[4]), c(d[5]), c(d[6]), c(d[7]), \
               c(d[8]), c(d[9]), c(d[10]), c(d[11]), c(d[12]), c(d[13]), c(d[14]), c(d[15])
template<bool FIRST> __device__ __forceinline__ void wgmma_rs_n32(float (&d)[16], const uint32_t (&a)[4], uint64_t b) {
  if (FIRST)
    asm volatile("wgmma.mma_async.sync.aligned.m64n32k16.f32.bf16.bf16 {%0,%1,%2,%3,%4,%5,%6,%7,%8,%9,%10,%11,%12,%13,%14,%15}, {%16,%17,%18,%19}, %20, 0, 1, 1, 0;"
      : D16("=f") : "r"(a[0]), "r"(a[1]), "r"(a[2]), "r"(a[3]), "l"(b));
  else
    asm volatile("wgmma.mma_async.sync.aligned.m64n32k16.f32.bf16.bf16 {%0,%1,%2,%3,%4,%5,%6,%7,%8,%9,%10,%11,%12,%13,%14,%15}, {%16,%17,%18,%19}, %20, 1, 1, 1, 0;"
      : D16("+f") : "r"(a[0]), "r"(a[1]), "r"(a[2]), "r"(a[3]), "l"(b));
}
template<bool FIRST> __device__ __forceinline__ void wgmma_ss_n32_ta(float (&d)[16], uint64_t a, uint64_t b) {
  if (FIRST)
    asm volatile("wgmma.mma_async.sync.aligned.m64n32k16.f32.bf16.bf16 {%0,%1,%2,%3,%4,%5,%6,%7,%8,%9,%10,%11,%12,%13,%14,%15}, %16, %17, 0, 1, 1, 1, 0;"
      : D16("=f") : "l"(a), "l"(b));
  else
    asm volatile("wgmma.mma_async.sync.aligned.m64n32k16.f32.bf16.bf16 {%0,%1,%2,%3,%4,%5,%6,%7,%8,%9,%10,%11,%12,%13,%14,%15}, %16, %17, 1, 1, 1, 1, 0;"
      : D16("+f") : "l"(a), "l"(b));
}

struct cf { float x, y; };
__host__ __device__ constexpr float cos64(int k) {
  return k == 0 ? 1.0f : k == 1 ? 0.99518472667219689f : k == 2 ? 0.98078528040323045f : k == 3 ? 0.95694033573220887f :
         k == 4 ? 0.92387953251128676f : k == 5 ? 0.88192126434835503f : k == 6 ? 0.83146961230254524f : k == 7 ? 0.77301045336273696f :
         k == 8 ? 0.70710678118654752f : k == 9 ? 0.63439328416364550f : k == 10 ? 0.55557023301960222f : k == 11 ? 0.47139673682599765f :
         k == 12 ? 0.38268343236508977f : k == 13 ? 0.29028467725446236f : k == 14 ? 0.19509032201612827f : k == 15 ? 0.09801714032956060f : 0.0f;
}
__host__ __device__ constexpr float c64(int k) { return k <= 16 ? cos64(k) : -cos64(32 - k); }
__host__ __device__ constexpr float s64(int k) { return k <= 16 ? cos64(16 - k) : cos64(k - 16); }

template<int N, int ST, bool INV> struct Fft {
  template<int K> static __device__ __forceinline__ void bf(const cf* e, const cf* o, cf* out) {
    if constexpr (K < N / 2) {
      constexpr int idx = K * (64 / N);
      const cf a = e[K], b = o[K];
      if constexpr (idx == 0) {
        out[K] = {a.x + b.x, a.y + b.y}; out[K + N / 2] = {a.x - b.x, a.y - b.y};
      } else if constexpr (idx == 16) {
        if constexpr (INV) { out[K] = {a.x - b.y, a.y + b.x}; out[K + N / 2] = {a.x + b.y, a.y - b.x}; }
        else               { out[K] = {a.x + b.y, a.y - b.x}; out[K + N / 2] = {a.x - b.y, a.y + b.x}; }
      } else {
        constexpr float c = c64(idx), s = INV ? s64(idx) : -s64(idx);
        cf p; p.x = fmaf(-s, b.y, fmaf(c, b.x, a.x)); p.y = fmaf(s, b.x, fmaf(c, b.y, a.y));
        out[K] = p; out[K + N / 2] = {fmaf(2.0f, a.x, -p.x), fmaf(2.0f, a.y, -p.y)};
      }
      bf<K + 1>(e, o, out);
    }
  }
  static __device__ __forceinline__ void run(const cf* in, cf* out) {
    cf e[N / 2], o[N / 2];
    Fft<N / 2, 2 * ST, INV>::run(in, e);
    Fft<N / 2, 2 * ST, INV>::run(in + ST, o);
    bf<0>(e, o, out);
  }
};
template<int ST, bool INV> struct Fft<1, ST, INV> {
  static __device__ __forceinline__ void run(const cf* in, cf* out) { out[0] = in[0]; }
};
template<bool INV> __device__ __forceinline__ void fft32(cf (&v)[32]) {
  cf o[32]; Fft<32, 1, INV>::run(v, o);
#pragma unroll
  for (int i = 0; i < 32; i++) v[i] = o[i];
}
__device__ __forceinline__ cf cmul(cf a, float c, float s) { return {fmaf(-a.y, s, a.x * c), fmaf(a.x, s, a.y * c)}; }
__device__ __forceinline__ float bf2f(__nv_bfloat16 v) { return __bfloat162float(v); }

template<bool INV> __device__ __forceinline__ void warp_fft1024_a(cf (&v)[32], float2* __restrict__ buf, const float2* __restrict__ tw, int t) {
  fft32<INV>(v);
#pragma unroll
  for (int j = 1; j < 32; j++) { const float2 w = tw[j * 32 + t]; v[j] = cmul(v[j], w.x, INV ? -w.y : w.y); }
  if (INV) {
    float* f = (float*)buf;
#pragma unroll
    for (int j = 0; j < 32; j++) f[j * 33 + t] = v[j].x;
    __syncwarp();
#pragma unroll
    for (int j = 0; j < 32; j++) v[j].x = f[t * 33 + j];
    __syncwarp();
#pragma unroll
    for (int j = 0; j < 32; j++) f[j * 33 + t] = v[j].y;
    __syncwarp();
#pragma unroll
    for (int j = 0; j < 32; j++) v[j].y = f[t * 33 + j];
  } else {
#pragma unroll
    for (int j = 0; j < 32; j++) buf[j * 33 + t] = make_float2(v[j].x, v[j].y);
    __syncwarp();
#pragma unroll
    for (int j = 0; j < 32; j++) { const float2 r = buf[t * 33 + j]; v[j] = {r.x, r.y}; }
  }
  __syncwarp();
}
constexpr int W_CHUNK = 16 * 513 * 2;
constexpr int ROW_BUF = 32 * 33;

__device__ __forceinline__ void row_twiddles(float2* tw, int tid, int nthreads) {
  for (int i = tid; i < 1024; i += nthreads) {
    float s, c; sincospif(-(float)((i >> 5) * (i & 31)) * (1.0f / 512.0f), &s, &c); tw[i] = make_float2(c, s);
  }
}
__device__ __forceinline__ void fft_rows_fwd(float2* sm2, const __nv_bfloat16* gw, int cta, int tid, uint32_t full_bar, uint32_t release_bar) {
  const int t = tid & 31, w = tid >> 5, n = cta * 8 + w;
  row_twiddles(sm2, tid, 256);
  mbar_spin(full_bar, 0);
  if (tid == 0) TL(6);
  __syncwarp();
  const __nv_bfloat16* xa = (const __nv_bfloat16*)(sm2 + 1024 + w * ROW_BUF) + t;
  cf v[32];
  float ga = 0.f, gb = 0.f;
#pragma unroll
  for (int j = 0; j < 32; j++) {
    v[j] = {bf2f(xa[32 * j]), bf2f(xa[D_ + 32 * j])};
    const float g = bf2f(gw[32 * j + t]); ga = fmaf(v[j].x, g, ga); gb = fmaf(v[j].y, g, gb);
  }
#pragma unroll
  for (int o = 16; o; o >>= 1) { ga += __shfl_xor_sync(~0u, ga, o); gb += __shfl_xor_sync(~0u, gb, o); }
  if (t < 2) g_gate[n + 1024 * t] = __fdividef(1.0f, 1.0f + __expf(-(t ? gb : ga)));
  bar_sync(13, 256);
  warp_fft1024_a<false>(v, sm2 + 1024 + w * ROW_BUF, sm2, t);
  FENCE_ASYNC_SMEM();
  mbar_arrive_warp(release_bar);
  fft32<false>(v);
  float ws, wc; sincospif(-(float)n * (1.0f / 1024.0f), &ws, &wc);
  float4* z = (float4*)g_z + ((size_t)(t >> 1) * 1024 + n) * 2 + (t & 1);
#pragma unroll
  for (int j = 0; j < 17; j++) {
    cf q = v[(32 - j) & 31];
    if (j < 16) {
      const cf r = {__shfl_sync(~0u, v[31 - j].x, 32 - t), __shfl_sync(~0u, v[31 - j].y, 32 - t)};
      if (t != 0) q = r;
    }
    const cf a = {v[j].x + q.x, v[j].y - q.y}, b = {v[j].y + q.y, q.x - v[j].x};
    const cf d = cmul({a.x - b.x, a.y - b.y}, wc, ws);
    if (j < 16 || t == 0) z[j * 32768] = make_float4(a.x + b.x, a.y + b.y, d.x, d.y);
  }
}
__device__ __forceinline__ void repack_filter(const unsigned short* ws, int cta, int tid) {
  const int rp = tid & 7;
  for (int cp = tid >> 3; cp < 257; cp += 16) {
    const unsigned short* pr = ws + 2 * rp * 513 + 2 * cp;
    uint32_t o[4];
#pragma unroll
    for (int i = 0; i < 4; i++) { const int k = (i & 1) * 513 + (cp == 256 ? 0 : i >> 1); o[i] = (uint32_t)pr[k] | ((uint32_t)pr[k + W_CHUNK / 2] << 16); }
    *(uint4*)(g_wp + ((size_t)cp * 1024 + cta * 8 + rp) * 4) = make_uint4(o[0], o[1], o[2], o[3]);
  }
}

constexpr int COL_FS = 1060, COL_GROUP = 4 * COL_FS + 2048;
constexpr int COL_SMEM = (1024 + 4 * COL_GROUP) * 8 + 32;

__device__ __forceinline__ void fft_cols(float2* sm2, int cta) {
  const int grp = __shfl_sync(~0u, (int)(threadIdx.x >> 7), 0), tid = threadIdx.x & 127, t = tid >> 2;
  float2* stage = sm2 + 1024 + grp * COL_GROUP;
  float2* buf = stage + (tid & 3) * COL_FS;
  const uint32_t* wsm = (const uint32_t*)(stage + 4 * COL_FS);
  const uint32_t wbar = smem_u32(sm2) + COL_SMEM - 32 + grp * 8;
  if (tid == 0) { mbar_init(wbar, 1); asm volatile("fence.mbarrier_init.release.cluster;" ::: "memory"); }
  row_twiddles(sm2, threadIdx.x, 512);
  for (uint32_t n = 0; ld_acquire(g_ctl + C_P1) < 128; ) { watchdog(n, 1u << 22); __nanosleep(200); }
  __syncthreads();
  int item = cta * 4 + grp;
  if (tid < 32) {
    asm volatile("fence.proxy.async.global;" ::: "memory");
    mbar_expect_e(wbar, 16384); bulk_load_e(smem_u32(wsm), g_wp + (size_t)item * 4096, 16384, wbar);
  }
  delay_cycles(1 + grp * DLY_GRP);
  for (uint32_t ph = 0; item < 257; item += 16, ph ^= 1) {
    float2* zp = g_z + (size_t)item * 4096;
    cf v[32];
#pragma unroll
    for (int j = 0; j < 32; j++) { const float2 a = __ldcg(zp + tid + j * 128); v[j] = {a.x, a.y}; }
#pragma unroll 1
    for (int dir = 0; dir < 2; dir++) {
      fft32<false>(v);
#pragma unroll
      for (int j = 1; j < 32; j++) { const float2 w = sm2[j * 32 + t]; v[j] = cmul(v[j], w.x, w.y); }
      if (tid == 0) asm volatile("cp.async.bulk.wait_group.read 0;" ::: "memory");
      bar_sync(1 + grp, 128);
      if (dir == 1 && tid < 32 && item + 16 < 257) { mbar_expect_e(wbar, 16384); bulk_load_e(smem_u32(wsm), g_wp + (size_t)(item + 16) * 4096, 16384, wbar); }
#pragma unroll
      for (int j = 0; j < 32; j++) buf[j * 33 + t] = make_float2(v[j].x, v[j].y);
      bar_sync(1 + grp, 128);
#pragma unroll
      for (int j = 0; j < 32; j++) { const float2 a = buf[t * 33 + j]; v[j] = {a.x, a.y}; }
      fft32<false>(v);
      if (dir == 0) {
        mbar_wait(wbar, ph);
#pragma unroll
        for (int j = 0; j < 32; j++) {
          const uint32_t ww = wsm[j * 128 + tid];
          const cf r = cmul(v[j], __uint_as_float(ww << 16), __uint_as_float(ww & 0xFFFF0000u));
          v[j] = {r.y, r.x};
        }
      }
    }
#pragma unroll
    for (int j = 0; j < 32; j++) zp[tid + j * 128] = make_float2(v[j].y, v[j].x);
  }
  if (tid == 0) asm volatile("cp.async.bulk.wait_group 0;" ::: "memory");
}

__device__ __forceinline__ void fft_rows_inv(float2* buf, const float2* tw, int n, int t) {
  const float4* z = (const float4*)g_z + ((size_t)(t >> 1) * 1024 + n) * 2 + (t & 1);
  float ws, wc; sincospif((float)n * (1.0f / 1024.0f), &ws, &wc);
  cf v[32], q[17];
#pragma unroll
  for (int j = 0; j < 17; j++) {
    const float4 e = __ldcg(j < 16 ? z + j * 32768 : (const float4*)g_z + ((size_t)256 * 1024 + n) * 2);
    const cf d = cmul({e.z, e.w}, wc, ws);
    cf a = {e.x + d.x, e.y + d.y}, b = {e.x - d.x, e.y - d.y};
    if (j == 16 || (j == 0 && t == 0)) { a.y = 0.f; b.y = 0.f; }
    if (j < 16) v[j] = {a.x - b.y, a.y + b.x};
    q[j] = {a.x + b.y, b.x - a.y};
  }
#pragma unroll
  for (int j = 16; j < 32; j++) {
    v[j] = {__shfl_sync(~0u, q[31 - j].x, 32 - t), __shfl_sync(~0u, q[31 - j].y, 32 - t)};
    if (t == 0) v[j] = q[32 - j];
  }
  warp_fft1024_a<true>(v, buf, tw, t);
  fft32<true>(v);
  const float sc = 0.5f / (2048.0f * 1024.0f);
  __nv_bfloat16* o = g_b + (size_t)n * D_ + t;
#pragma unroll
  for (int j = 0; j < 32; j++) { o[32 * j] = __float2bfloat16(v[j].x * sc); o[1024 * D_ + 32 * j] = __float2bfloat16(v[j].y * sc); }
}

constexpr int NP = NP_, NHV = REG_F == 216 ? 5 : 7, NV = 16 - NHV;
constexpr int XEND = NSEG;
constexpr uint32_t SM_WO = 0, SM_V = 65536, SM_LAND = SM_V + 8192, SM_MEM = SM_LAND + 24576, SM_SP = SM_MEM, SM_SPM = SM_MEM + 5120, SM_OM = SM_MEM + 6144,
                   SM_OX = SM_MEM + 8192, SM_RED = SM_OX + 2048, SM_XCH = SM_RED + 1024, SM_SUM = SM_XCH + 4096, SM_VM = SM_SUM + 128, SM_TAB = SM_VM + 2048, SM_TRACE = SM_TAB + 2048,
                   ST_WG = (32 - NP + NV) * 2048,
                   SM_XT = 2 * ST_WG > 120 * 1024 ? 2 * ST_WG : 120 * 1024, SM_POOL = SM_XT + 32768, SM_HV = SM_POOL + 2 * NP * 2048,
                   SM_BAR = SM_HV + 2 * NHV * 2048, SM_SEL = SM_BAR + 320, CHAIN_SMEM = SM_SEL + 544;
constexpr uint32_t SM_WST = 76 * 1024;
static_assert(NP % 4 == 0 && SM_TRACE + 4096 <= SM_XT, "shared memory layout");
static_assert(CHAIN_SMEM <= 232448 && COL_SMEM <= CHAIN_SMEM && (1024 + 8 * ROW_BUF) * 8 + 2048 <= SM_WST && SM_WST + 2 * W_CHUNK <= SM_XT, "shared memory budget");
enum { B_WFULL = 0, B_WREAD = 2, B_WOFULL, B_XFULL, B_XEMPTY, B_E1TRIG, B_E2TRIG, B_PVDONE, B_PUB, B_SC, B_MEM, B_SPFREE,
       B_LAND, B_LFREE, B_DONE, B_SEL, B_PROBE, B_FILT, B_FREE, B_P1, B_ROWS, B_END };
static_assert(B_END * 8 <= 320, "barriers");

struct ChainCtx { char* mail; uint32_t sb, sel; int r, h, a, b, j, m, w, lane; };
#define BAR(i) (c.sb + SM_BAR + 8 * (i))

__device__ __forceinline__ uint32_t tile_off(int line, int lane) {
  return line * 128 + (((lane & 3) ^ line) << 5) + (lane >> 2) * 4;
}
__device__ __forceinline__ uint32_t read_off(int lane) {
  const int n = lane >> 2, jj = lane & 3, l = 2 * (jj >> 1) + (n & 1);
  return l * 128 + (((n >> 1) ^ l) << 5) + (jj & 1) * 16;
}
__device__ __forceinline__ uint32_t frag_off(int w, int lane) {
  const int mi = lane >> 3, r = lane & 7;
  return ((mi >> 1) * 8 + r) * 128 + (((2 * w + (mi & 1)) ^ r) << 4);
}
__device__ __forceinline__ uint32_t land_off(int w, int lane) { return w * 512 + ((lane ^ (((lane >> 4) | ((w & 1) << 1)) << 1)) << 4); }
__device__ __forceinline__ uint32_t tagged(uint32_t v, uint32_t tag) { return (v & ~1u) | tag; }
__device__ __forceinline__ void mma_a(float (&d)[4], const uint32_t (&a)[4], uint32_t b0, uint32_t b1) { mma16816(d, a[0], a[1], a[2], a[3], b0, b1); }
__device__ __forceinline__ void mma_q(float (&d)[4], const uint4& a, uint32_t b0, uint32_t b1) { mma16816(d, a.x, a.y, a.z, a.w, b0, b1); }
__device__ __forceinline__ uint4 add4(uint4 a, uint4 b) {
  return make_uint4(add_bf16x2(a.x, b.x), add_bf16x2(a.y, b.y), add_bf16x2(a.z, b.z), add_bf16x2(a.w, b.w));
}
__device__ __forceinline__ void mbar_arrive_both(uint32_t bar, int peer) {
  __syncwarp();
  asm volatile("{ .reg .pred p; .reg .u32 a; mapa.shared::cluster.u32 a, %0, %1; elect.sync _|p, 0xffffffff;\n"
               "@p mbarrier.arrive.shared::cta.b64 _, [%0]; @p mbarrier.arrive.shared::cluster.b64 _, [a]; }" :: "r"(bar), "r"(peer) : "memory");
}

__device__ __forceinline__ int lane_id() {
  int l; asm volatile("{ .reg .u32 t; mov.u32 t, %%laneid; shfl.sync.idx.b32 %0, t, t, 31, 0xffffffff; }" : "=r"(l)); return l;
}
__device__ __forceinline__ uint32_t tid_now() { uint32_t t; asm volatile("mov.u32 %0, %%tid.x;" : "=r"(t)); return t; }
enum { NB_ATT = 1, NB_OM = 2, NB_VM = 3, NB_XCH = 4, NB_MEM = 8, NB_HELP = 12 };
__device__ __forceinline__ uint32_t dep(uint32_t a, uint32_t v, uint32_t z) { uint32_t r; asm("shf.l.wrap.b32 %0, %2, %1, %3;" : "=r"(r) : "r"(a), "r"(v), "r"(z)); return r; }
__device__ __forceinline__ uint32_t vary(uint32_t a, int s, uint32_t z) { return dep(a, 0, z + 32 * s); }
__device__ __forceinline__ char* mk_ptr(uint32_t lo, uint32_t hi) { uint64_t r; asm("mov.b64 %0, {%1, %2};" : "=l"(r) : "r"(lo), "r"(hi)); return (char*)r; }
__device__ __forceinline__ void lds_frag(uint32_t (&r)[4], uint32_t a) {
  asm volatile("ld.shared.v4.u32 {%0,%1,%2,%3}, [%4];" : "=r"(r[0]), "=r"(r[1]), "=r"(r[2]), "=r"(r[3]) : "r"(a) : "memory");
}
__device__ __forceinline__ uint32_t stale2(uint32_t a, uint32_t b, uint32_t t) { uint32_t r; asm("lop3.b32 %0, %1, %2, %3, 0x7e;" : "=r"(r) : "r"(a), "r"(b), "r"(t)); return r; }
__device__ __forceinline__ uint32_t stale1(uint32_t acc, uint32_t a, uint32_t t) { uint32_t r; asm("lop3.b32 %0, %1, %2, %3, 0xf6;" : "=r"(r) : "r"(acc), "r"(a), "r"(t)); return r; }
__device__ __forceinline__ bool all_clear(uint32_t x, uint32_t m) {
  uint32_t r;
  asm volatile("{ .reg .pred p; .reg .u32 t; and.b32 t, %1, %2; setp.eq.u32 p, t, 0; vote.sync.all.pred p, p, 0xffffffff; selp.u32 %0, 1, 0, p; }" : "=r"(r) : "r"(x), "r"(m));
  return r;
}
__device__ __forceinline__ bool arrive_if_all(bool ok, int id, int n) {
  uint32_t r;
  asm volatile("{ .reg .pred p, q; setp.ne.u32 p, %1, 0; vote.sync.all.pred q, p, 0xffffffff; @q bar.arrive %2, %3; selp.u32 %0, 1, 0, q; }"
               : "=r"(r) : "r"((uint32_t)ok), "r"(id), "r"(n) : "memory");
  return r;
}
__device__ __forceinline__ bool arrive_if_clear(uint32_t x, uint32_t m, int id, int n) {
  uint32_t r;
  asm volatile("{ .reg .pred p; .reg .u32 t; and.b32 t, %1, %2; setp.eq.u32 p, t, 0; vote.sync.all.pred p, p, 0xffffffff; @p bar.arrive %3, %4; selp.u32 %0, 1, 0, p; }"
               : "=r"(r) : "r"(x), "r"(m), "r"(id), "r"(n) : "memory");
  return r;
}
__device__ __forceinline__ void touch(const void* p, uint32_t z) {
  asm volatile("{ .reg .pred p; setp.eq.u32 p, %1, 0x7fff0000; @p prefetch.global.L2 [%0]; }" :: "l"(p), "r"(z) : "memory");
}

__device__ __forceinline__ uint64_t desc_x(uint32_t lo, int k) {
  uint64_t d; asm("mov.b64 %0, {%1, %2};" : "=l"(d) : "r"(lo + (k >> 2) * 64 + (k & 3) * 2), "r"(0x40000200)); return d;
}
template<int K0, int K1> __device__ __forceinline__ void issue_qk(float (&xa)[16], const uint32_t (&wt)[16][4], uint32_t lo) {
  WG_FENCE();
#pragma unroll
  for (int k = K0; k < K1; k++) {
    if (k == 0) wgmma_rs_n32<true>(xa, wt[0], desc_x(lo, 0));
    else wgmma_rs_n32<false>(xa, wt[k], desc_x(lo, k));
  }
  WG_COMMIT();
}
__host__ __device__ constexpr int v_order(int i) { return SSPOS == 0 ? i : SSPOS == 2 ? (i + NV) % 16 : NHV == 5 ? (i % 3 == 2 ? NV + i / 3 : i - i / 3) : (i == 15 ? NV - 1 : i % 2 ? NV + i / 2 : i / 2); }
__device__ __forceinline__ void issue_v(float (&xa)[16], const uint32_t (&wv)[16][4], uint32_t lo, uint32_t la) {
  WG_FENCE();
#pragma unroll
  for (int i = 0; i < 16; i++) {
    const int k = v_order(i);
    const uint64_t b = desc_x(lo, k);
    if (k < NV) { if (i == 0) wgmma_rs_n32<true>(xa, wv[k], b); else wgmma_rs_n32<false>(xa, wv[k], b); }
    else        { if (i == 0) wgmma_ss_n32_ta<true>(xa, desc128(la + (k - NV) * 128), b); else wgmma_ss_n32_ta<false>(xa, desc128(la + (k - NV) * 128), b); }
  }
  WG_COMMIT();
}
template<bool ISV> __device__ __forceinline__ void park_own(uint32_t (&q)[4], float (&xa)[16], uint32_t dst, int slot, uint32_t z) {
  uint32_t p[8];
#pragma unroll
  for (int i = 0; i < 16; i++) asm volatile("" : "+f"(xa[i]) :: "memory");
#pragma unroll
  for (int i = 0; i < 2; i++) {
    const float* k = xa + 8 * i;
    if (ISV) { p[4 * i] = pack_bf16(k[0], k[1]); p[4 * i + 1] = pack_bf16(k[2], k[3]); p[4 * i + 2] = pack_bf16(k[4], k[5]); p[4 * i + 3] = pack_bf16(k[6], k[7]); }
    else     { p[4 * i] = pack_bf16(k[0], k[2]); p[4 * i + 1] = pack_bf16(k[4], k[6]); p[4 * i + 2] = pack_bf16(k[1], k[3]); p[4 * i + 3] = pack_bf16(k[5], k[7]); }
  }
  sts128(dep(dep(dst, p[4] ^ p[5] ^ p[6], z), p[7], z) + slot * 8192, make_uint4(p[0], p[1], p[2], p[3]));
#pragma unroll
  for (int i = 0; i < 4; i++) q[i] = p[4 + i];
}
__device__ __forceinline__ void park_peer(const uint32_t (&q)[4], uint32_t dst, int slot, const ChainCtx& c) {
  const uint32_t bar = BAR(B_LAND);
  st_async4(mapa(dst + slot * 8192, c.b ^ 1), q[0], q[1], q[2], q[3], mapa(bar, c.b ^ 1));
  mbar_arrive_warp(bar);
}
__device__ __forceinline__ uint32_t put_tag(uint32_t v, uint32_t bit, uint32_t t) {
  uint32_t r; asm("lop3.b32 %0, %1, %2, %3, 0xb8;" : "=r"(r) : "r"(v), "r"(bit), "r"(t)); return r;
}
__device__ __forceinline__ void mem_proj(const uint32_t (&wa)[16][4], const uint32_t (&wb)[16][4], uint32_t (&wv)[16][4], uint32_t (&af)[16][4],
                                         uint32_t& wo, const char*& pa, uint32_t tab, uint32_t t16, uint32_t pk, const ChainCtx& c, int s) {
  const uint32_t mp = t16 & ~0x600u, id = NB_MEM + (t16 >> 11);
  const uint4 tq = lds128(tab);
  char* dst = mk_ptr(tq.x | ((pk >> 16) & 511), tq.y);
  char* dst2 = mk_ptr(tq.z ^ ((pk >> 16) & 511), tq.w);
  touch(dst, c.sb); touch(dst2, c.sb);
  uint32_t r[8][4];
  float la[4][4] = {}, lg[NLAG][4] = {}, lv[4][4] = {};
  auto lead = [&](int k) { mma_a(la[k & 3], wa[k], r[k >> 1][2 * (k & 1)], r[k >> 1][2 * (k & 1) + 1]); };
  auto lag = [&](int k) { mma_a(lg[k % NLAG], wb[k], r[k >> 1][2 * (k & 1)], r[k >> 1][2 * (k & 1) + 1]); };
  auto sum = [](const float (&d)[4][4], int i) { return (d[0][i] + d[1][i]) + (d[2][i] + d[3][i]); };
  bar_sync(id, 160);
  TR(s, 0);
#pragma unroll
  for (int i = 0; i < 4; i++) ldsm4t(r[i], mp + (c.sb + SM_MEM + i * 512));
  bar_sync(id + 2, 160);
#pragma unroll
  for (int k = 0; k < 8; k++) lead(k);
  const uint32_t mp1 = dep(mp, __float_as_uint(la[C1_AT][0]), c.sb);
#pragma unroll
  for (int i = 4; i < 8; i++) ldsm4t(r[i], mp1 + (c.sb + SM_MEM + 2048 + i * 512));
#pragma unroll
  for (int k = 0; k < 8; k++) lag(k);
#pragma unroll
  for (int k = 8; k < 16; k++) lead(k);
  sts128(t16 + (c.sb + SM_XCH), make_uint4(__float_as_uint(sum(la, 0)), __float_as_uint(sum(la, 1)), __float_as_uint(sum(la, 2)), __float_as_uint(sum(la, 3))));
  bar_sync(NB_XCH | ((t16 >> 9) & 3), 64);
  const uint4 o = lds128((t16 ^ 2048) + (c.sb + SM_XCH));
#pragma unroll
  for (int k = 8; k < 16; k++) lag(k);
  float t[4];
#pragma unroll
  for (int i = 0; i < 4; i++) {
    const float oi = __uint_as_float(i == 0 ? o.x : i == 1 ? o.y : i == 2 ? o.z : o.w);
    t[i] = NLAG == 4 ? (((lg[0][i] + lg[1][i]) + lg[2 % NLAG][i]) + lg[3 % NLAG][i]) + oi : NLAG == 3 ? (lg[1][i] + lg[2 % NLAG][i]) + (lg[0][i] + oi) : (lg[0][i] + oi) + lg[1][i];
  }
  st_pub(dst, put_tag(pack_bf16(t[0], t[2]), pk >> 31, s >> 1));
  st_pub(dst2, put_tag(pack_bf16(t[1], t[3]), pk >> 31, s >> 1));
  mbar_arrive_warp(BAR(B_E1TRIG));
  TR(s, 1);
  const uint32_t hv = pk & 0xFFFF;
  sched_fence(c.sb);
  const uint4 tv = lds128(tab + 16);
#pragma unroll
  for (int k = NV; k < 16; k++) ldsm4t(wv[k], (k < NV + HV_D ? hv : dep(hv, k == NV + HV_D ? wv[k - HV_D][0] ^ tv.x : wv[k - HV_D][0], c.sb)) + (c.sb + SM_HV + (k - NV) * 2048));
  wo = (hv & 2047) | ((t16 & 2048) << 3);
  const uint32_t l8 = (t16 >> 1) & 255;
  char* dv = mk_ptr(tv.x | l8, tv.y);
  pa = mk_ptr(tv.z | l8, tv.w);
#pragma unroll
  for (int f = 0; f < WO_0; f++) ldsm4t(af[f], dep(wo, f < WO_D ? wv[16 - WO_D + f][0] : af[f < WO_D ? 0 : f - WO_D][0], c.sb) + (c.sb + SM_WO + f * 2048));
#pragma unroll
  for (int k = 0; k < 16; k++) mma_a(lv[k & 3], wv[k], r[k >> 1][2 * (k & 1)], r[k >> 1][2 * (k & 1) + 1]);
  st_pub2(dv, put_tag(pack_bf16(sum(lv, 0), sum(lv, 1)), (~t16 >> 4) & 1, s >> 1), pack_bf16(sum(lv, 2), sum(lv, 3)));
  TR(s, 2);
}
__device__ __forceinline__ uint32_t max_bf16x2(uint32_t a, uint32_t b) { uint32_t r; asm("max.bf16x2 %0, %1, %2;" : "=r"(r) : "r"(a), "r"(b)); return r; }
constexpr float SCL = 0.08838834764831845f * 1.4426950408889634f;
__device__ __forceinline__ uint32_t max5(const uint32_t (&sc)[5]) { return max_bf16x2(max_bf16x2(max_bf16x2(max_bf16x2(sc[0], sc[1]), sc[2]), sc[3]), sc[4]); }
__device__ __forceinline__ float row_off(uint32_t m) {
  const uint32_t m1 = __shfl_xor_sync(~0u, m, 1), m2 = __shfl_xor_sync(~0u, m, 2), m3 = __shfl_xor_sync(~0u, m, 3);
  const uint32_t mm = max_bf16x2(max_bf16x2(max_bf16x2(m, m1), m2), m3);
  return -SCL * fmaxf(__uint_as_float(mm << 16), __uint_as_float(mm & 0xFFFF0000u));
}
__device__ __forceinline__ void unpack(float (&f)[10], const uint32_t (&sc)[5]) {
#pragma unroll
  for (int i = 0; i < 5; i++) {
    asm volatile("shl.b32 %0, %1, 16;" : "=f"(f[2 * i]) : "r"(sc[i]));
    asm volatile("and.b32 %0, %1, 0xffff0000;" : "=f"(f[2 * i + 1]) : "r"(sc[i]));
  }
}
__device__ __forceinline__ uint32_t exp_pair(const float (&f)[10], int i, float off) {
  return pack_bf16(ex2(fmaf(f[2 * i], SCL, off)), ex2(fmaf(f[2 * i + 1], SCL, off)));
}
template<bool SPLIT> __device__ __forceinline__ void scores_x(float (&a)[2][4], const uint4 (&kf)[4], const uint4& q, uint32_t z) {
#pragma unroll
  for (int t = 0; t < 2; t++) { a[t][0] = a[t][1] = a[t][2] = a[t][3] = 0.f; }
  mma_q(a[0], kf[0], q.x, q.y); mma_q(a[1], kf[2], q.x, q.y);
  if (SPLIT) sched_fence(z);
  mma_q(a[0], kf[1], q.z, q.w); mma_q(a[1], kf[3], q.z, q.w);
}
__device__ __forceinline__ uint32_t scores_m(const uint4& q, const uint4& k) {
  float a[4] = {}, b[4] = {};
  mma_q(a, q, k.x, k.z); mma_q(b, q, k.y, k.w);
  return pack_bf16(a[0] + b[2], a[1] + b[3]);
}
__device__ __forceinline__ void store_scores(const float (&a)[2][4], uint32_t dst) {
  stsm4<true>(dst, pack_bf16(a[0][0], a[0][1]), pack_bf16(a[0][2], a[0][3]), pack_bf16(a[1][0], a[1][1]), pack_bf16(a[1][2], a[1][3]));
}
__device__ __forceinline__ uint32_t sum4(uint32_t a, uint32_t b, uint32_t d, uint32_t e) { return add_bf16x2(add_bf16x2(a, b), add_bf16x2(d, e)); }
__device__ __forceinline__ void load_scores(uint32_t (&sc)[5], uint32_t ax, uint32_t am) {
  uint4 p[4];
#pragma unroll
  for (int i = 0; i < 4; i++) p[i] = lds128(ax + i * 1280);
  const uint2 m0 = lds64(am), m1 = lds64(am + 256);
  const uint4 t = add4(add4(add4(p[0], p[1]), p[2]), p[3]);
  sc[1] = t.x; sc[2] = t.y; sc[3] = t.z; sc[4] = t.w;
  sc[0] = sum4(m0.x, m0.y, m1.x, m1.y);
}
constexpr uint32_t ONES = 0x3F803F80u;
__device__ __forceinline__ float pv(float (&o)[2][4], const uint32_t (&p)[5], const uint4 (&vf)[4], const uint4& vm) {
  float a[4] = {}, b[4] = {};
#pragma unroll
  for (int t = 0; t < 2; t++) { o[t][0] = o[t][1] = o[t][2] = o[t][3] = 0.f; }
  mma_q(o[0], vf[0], p[1], p[2]); mma_q(o[1], vf[2], p[1], p[2]);
  mma_q(o[0], vf[1], p[3], p[4]); mma_q(o[1], vf[3], p[3], p[4]);
  mma16816(a, p[1], p[2], p[3], p[4], ONES, ONES);
  mma1688(o[0], vm.x, vm.y, p[0]); mma1688(o[1], vm.z, vm.w, p[0]);
  mma1688(b, p[0], ONES, ONES);
  return (a[0] + a[2]) + b[0];
}
constexpr uint32_t POLL_LIMIT = 1u << 21;

__global__ void __cluster_dims__(2, 1, 1) __launch_bounds__(512, 1)
chain_kernel(const __grid_constant__ CUtensorMap tq, const __grid_constant__ CUtensorMap tk, const __grid_constant__ CUtensorMap tv,
             const __grid_constant__ CUtensorMap tv16, const __grid_constant__ CUtensorMap to, const __grid_constant__ CUtensorMap tx,
             const __nv_bfloat16* __restrict__ mem0, char* __restrict__ mail, const __nv_bfloat16* __restrict__ x,
             const __nv_bfloat16* __restrict__ gw, const char* __restrict__ wr, const char* __restrict__ wi) {
  extern __shared__ __align__(1024) unsigned char smraw[];
  pdl_launch();
  if (threadIdx.x == 0) TL(0);
  if (blockIdx.x >= 128) {
    if (blockIdx.x == 128) g_ctl[C_ROWS + threadIdx.x] = 0;
    fft_cols((float2*)smraw, blockIdx.x - 128);
    if ((threadIdx.x & 127) == 0) TL(7);
    return;
  }
  ChainCtx c;
  c.sb = __shfl_sync(~0u, smem_u32(smraw), 0);
  c.mail = mail; c.sel = 0; c.r = blockIdx.x;
  c.h = c.r >> 2; c.a = (c.r >> 1) & 1; c.b = c.r & 1; c.j = c.r & 3;
  c.m = __shfl_sync(~0u, (int)(threadIdx.x >> 7), 0); c.w = __shfl_sync(~0u, (int)((threadIdx.x >> 5) & 3), 0);
  if (threadIdx.x < B_END) {
    const int i = threadIdx.x;
    const uint32_t n = i == B_LAND ? 25 : (i == B_FREE || i == B_P1 || i == B_DONE) ? 12 :
                       (i == B_WREAD || i == B_XEMPTY || i == B_E1TRIG || i == B_E2TRIG || i == B_LFREE || i == B_PROBE) ? 8 :
                       (i == B_PVDONE || i == B_PUB || i == B_SC || i == B_MEM || i == B_SPFREE) ? 4 : 1;
    mbar_init(BAR(i), n);
    asm volatile("fence.mbarrier_init.release.cluster;" ::: "memory");
  }
  __syncthreads();
  asm volatile("barrier.cluster.arrive.relaxed.aligned;" ::: "memory");

  if (c.m == 3) {
    asm volatile("setmaxnreg.dec.sync.aligned.u32 %0;" :: "n"(REG_H));
    c.lane = lane_id();
    if (c.sb & 1023) asm volatile("trap;");
    const int col = c.h * 128 + c.a * 64;
    if (c.w == 0) {
      mbar_expect_e(BAR(B_ROWS), 32768 + 2048);
      for (int i = 0; i < 16; i++) bulk_load_e(c.sb + (1024 + (i >> 1) * ROW_BUF) * 8 + (i & 1) * 2048, x + (size_t)(c.r * 8 + (i >> 1) + (i & 1) * 1024) * D_, 2048, BAR(B_ROWS));
      bulk_load_e(c.sb + SM_WST - 2048, gw, 2048, BAR(B_ROWS));
      mbar_expect_e(BAR(B_FILT), 2 * W_CHUNK);
      bulk_load_e(c.sb + SM_WST, wr + (size_t)c.r * W_CHUNK, W_CHUNK, BAR(B_FILT));
      bulk_load_e(c.sb + SM_WST + W_CHUNK, wi + (size_t)c.r * W_CHUNK, W_CHUNK, BAR(B_FILT));
      mbar_expect_e(BAR(B_XFULL), 32768);
      for (int i = 0; i < 2; i++) tma4d_e(c.sb + SM_XT + i * 16384, &tx, c.b * 8, 2 * (c.b ^ i), BAR(B_XFULL));
      for (int m = 0; m < 2; m++) {
        const int row = c.b * 512 + m * 256;
        mbar_expect_e(BAR(B_WFULL + m), 48 * 2048);
        for (int i = 0; i < NP / 4; i++) tma2d_e(c.sb + SM_POOL + m * NP * 2048 + i * 8192, m ? &tq : &tk, col, row + i * 64, BAR(B_WFULL + m));
        for (int i = NV; i < 12; i++) tma2d_e(c.sb + SM_HV + (m * NHV + i - NV) * 2048, &tv16, col, row + i * 16, BAR(B_WFULL + m));
        tma2d_e(c.sb + SM_HV + (m * NHV + 12 - NV) * 2048, &tv, col, row + 192, BAR(B_WFULL + m));
      }
      for (int m = 0; m < 2; m++) {
        const int row = c.b * 512 + m * 256;
        for (int i = 0; i < 4; i++) prefetch2d_e(m ? &tk : &tq, col, row + i * 64);
        for (int i = NP / 4; i < 4; i++) prefetch2d_e(m ? &tq : &tk, col, row + i * 64);
        for (int i = 0; i < 3; i++) prefetch2d_e(&tv, col, row + i * 64);
      }
      for (int i = 0; i < 4; i++) prefetch2d_e(&to, c.j * 256 + i * 64, c.h * 128);
    }
    auto dst_x = [&](int e, int w) {
      const uint32_t g2 = 2 * c.a + (w >> 1), u = w & 1;
      return M_KVQ + c.h * 24576 + (e == 0 ? 8192 + g2 * 2048 + u * 1024 + c.b * 32 : e == 1 ? g2 * 2048 + (2 * c.b + u) * 512 : 16384 + (2 * c.b + u) * 2048 + g2 * 512);
    };
    auto v_off = [](int ln) { return (ln >> 4) * 512 + (ln & 14) * 32 + (ln & 1) * 16; };
    {
      const uint4 z = make_uint4(SENT, SENT, SENT, SENT);
      for (int i = 0; i < 8; i++) *(uint4*)(c.mail + (uint32_t)(M_PAIR + ((i >> 2) * 128 + c.r) * 8192 + ((i & 3) * 4 + c.w) * 512 + c.lane * 16)) = z;
      for (int i = 0; i < 2; i++) *(uint32_t*)(c.mail + (uint32_t)(M_E3 + (c.w * 4 + (c.r >> 5)) * 8192 + i * 4096 + (c.r & 31) * 128 + c.lane * 4)) = SENT;
      for (int i = 0; i < NSLOT; i++) {
        *(uint4*)(c.mail + (uint32_t)(dst_x(1, c.w) + i * 32 * 24576 + c.lane * 16)) = z;
        *(uint4*)(c.mail + (uint32_t)(dst_x(2, c.w) + i * 32 * 24576 + c.lane * 16)) = z;
        *(uint4*)(c.mail + (uint32_t)(dst_x(0, c.w) + i * 32 * 24576 + v_off(c.lane))) = z;
      }
      mbar_arrive_warp(BAR(B_PROBE));
    }
    mbar_wait(BAR(B_FILT), 0);
    repack_filter((const unsigned short*)(smraw + SM_WST), c.r, c.w * 32 + c.lane);
    mbar_arrive_warp(BAR(B_FREE));
    mbar_arrive_warp(BAR(B_P1));
    if (c.w == 0) {
      mbar_wait(BAR(B_FREE), 0);
      if (c.lane == 0) TL(2);
      __syncwarp();
      for (int m = 0; m < 2; m++) {
        const int row = c.b * 512 + m * 256;
        const uint32_t st = c.sb + m * ST_WG, sv = st + (32 - NP) * 2048;
        for (int i = 0; i < 4; i++) tma2d_e(st + i * 8192, m ? &tk : &tq, col, row + i * 64, BAR(B_WFULL + m));
        for (int i = NP / 4; i < 4; i++) tma2d_e(st + (4 + i - NP / 4) * 8192, m ? &tq : &tk, col, row + i * 64, BAR(B_WFULL + m));
        for (int i = 0; i < 2; i++) tma2d_e(sv + i * 8192, &tv, col, row + i * 64, BAR(B_WFULL + m));
        for (int i = 8; i < NV; i++) tma2d_e(sv + i * 2048, &tv16, col, row + i * 16, BAR(B_WFULL + m));
      }
    } else if (c.w == 1) {
      mbar_wait(BAR(B_P1), 0);
      asm volatile("fence.acq_rel.gpu;" ::: "memory");
      asm volatile("{ .reg .pred p; elect.sync _|p, 0xffffffff; @p red.relaxed.gpu.global.add.u32 [%0], 1; }" :: "l"(g_ctl + C_P1) : "memory");
    }
    asm volatile("barrier.cluster.wait;" ::: "memory");
    mbar_wait(BAR(B_WREAD), 0);
    mbar_arrive_both(BAR(B_LFREE), c.b ^ 1);
    {
      const int ln = tid_now() & 31, e = (ln >> 2) & 3, w = (tid_now() >> 5) & 3;
      const uintptr_t ad = (uintptr_t)(c.mail + (uint32_t)(dst_x(e, w) + (ln & 3) * 32 * 24576));
      sts64(c.sb + SM_TAB + 1536 + (ln & 3) * 128 + w * 32 + e * 8, (uint32_t)ad, (uint32_t)(ad >> 32));
      __syncwarp();
    }
    if (c.w == 0) {
      mbar_expect_e(BAR(B_WOFULL), 65536);
      for (int i = 0; i < 4; i++) tma2d_e(c.sb + SM_WO + i * 16384, &to, c.j * 256 + i * 64, c.h * 128, BAR(B_WOFULL));
    }
    for (int s = -1; s < NSEG; s++) {
      if (s == 0) {
        mbar_wait(BAR(B_SEL), 0);
        const int ln = tid_now() & 31, sl = ln & 3, e = (ln >> 2) & 3;
        const uint32_t t = c.sb + SM_SEL, own = lds32(t + c.r * 4);
        uint32_t votes = 0;
        for (int i = 0; i < 7; i++) { const uint32_t v = lds32(t + (sl * 4 + 2 * c.b + (c.w >> 1) + 16 * i) * 4); votes += ((v >> 2) ^ (v >> 3)) & 1; }
        const uint32_t off = e == 0 ? M_PAIR + ((~sl & 1) * 128 + c.r) * 8192 + ((own >> (~sl & 1)) & 1) * 4096 + c.w * 1024
                           : e == 2 ? M_E3 + (sl * 4 + c.b * 2 + (c.w >> 1)) * 8192 + (((votes >= 4 ? 1u : 0u) ^ (own >> 3)) & 1) * 4096 + (c.w & 1) * 2048
                           : M_E3 + ((sl ^ (e & 2)) * 4 + (c.r >> 5)) * 8192 + (c.w & 1) * 4096 + (c.r & 31) * 128;
        const uintptr_t ad = (uintptr_t)(c.mail + off);
        sts64(c.sb + SM_TAB + 1024 + sl * 128 + c.w * 32 + e * 8, (uint32_t)ad, (uint32_t)(ad >> 32));
        __syncwarp();
      }
      if (s >= 0) {
        const uint32_t tab = c.sb + SM_TAB + 1024 + (s & 3) * 128 + c.w * 32;
        uint32_t t0;
        if (s > 0) {
          const uint32_t ln = tid_now() & 31;
          const uint4 ta = lds128(tab);
          const char* src = mk_ptr(ta.x | ln * 4, ta.y);
          char* dst = mk_ptr(ta.z | ln * 4, ta.w);
          const uint32_t tg = (s - 1) >> 1, chk = (ln & 3) ? 0u : 1u, red = ln * 8;
          touch(src, dep(c.sb, chk, c.sb)); touch(dst, dep(c.sb, red, c.sb));
          mbar_wait(BAR(B_E2TRIG), (s - 1) & 1);
          TR(s, 0);
          delay_cycles(DLY_E2);
          uint32_t n = 0;
          while (true) {
            uint32_t v[8];
#pragma unroll
            for (int i = 0; i < 8; i++) v[i] = ld_poll1(src + i * 128);
            if (E2_F) sched_fence(c.sb);
            const uint32_t bad = stale1(stale1(stale2(v[0], v[1], tg), v[2], tg), v[3], tg) | stale1(stale1(stale2(v[4], v[5], tg), v[6], tg), v[7], tg);
            const bool ok = all_clear(bad, chk);
            float lo[8], hi[8];
#pragma unroll
            for (int i = 0; i < 8; i++) { lo[i] = __uint_as_float(v[i] << 16); hi[i] = __uint_as_float(v[i] & 0xFFFF0000u); }
            sts64(red + (c.sb + SM_RED + c.w * 256), __float_as_uint(((lo[0] + lo[1]) + (lo[2] + lo[3])) + ((lo[4] + lo[5]) + (lo[6] + lo[7]))),
                                                     __float_as_uint(((hi[0] + hi[1]) + (hi[2] + hi[3])) + ((hi[4] + hi[5]) + (hi[6] + hi[7]))));
            if (ok) break;
            n++;
          }
          bar_sync(NB_HELP, 128);
          const uint32_t rd = red + (c.sb + SM_RED);
          const uint2 p0 = lds64(rd), p1 = lds64(rd + 256), p2 = lds64(rd + 512), p3 = lds64(rd + 768);
          st_pub_if(dst, pack_bf16((__uint_as_float(p0.x) + __uint_as_float(p1.x)) + (__uint_as_float(p2.x) + __uint_as_float(p3.x)),
                                   (__uint_as_float(p0.y) + __uint_as_float(p1.y)) + (__uint_as_float(p2.y) + __uint_as_float(p3.y))), c.w < 2);
          t0 = clock_lo();
          mbar_arrive_warp(BAR(B_PUB));
          TRV(s, 15, n);
          mbar_wait(BAR(B_SPFREE), (s - 1) & 1);
        } else t0 = clock_lo();
        TRV(s, 1, t0);
        {
          const uint32_t l16 = (tid_now() & 31) * 16, dst = l16 + (c.sb + SM_MEM + (c.w & 1) * 4096 + (c.w >> 1) * 2048);
          const uint2 tb = lds64(tab + 16);
          const char* src = mk_ptr(tb.x | l16, tb.y);
          touch(src, dep(c.sb, dst, c.sb));
          delay_until(t0 + DLY_E3);
          uint32_t n = 0;
          while (true) {
            uint4 v[4];
#pragma unroll
            for (int i = 0; i < 4; i++) v[i] = ld_poll(src + i * 512);
#pragma unroll
            for (int i = 0; i < 4; i++) sts128(dst + i * 512, v[i]);
            if (arrive_if_all(max(max(v[0].x, v[1].x), max(v[2].x, v[3].x)) != SENT, NB_MEM + (c.w & 1) * 2 + (c.w >> 1), 160)) break;
            n++;
          }
          mbar_arrive_warp(BAR(B_MEM));
          TR(s, 2); TRV(s, 14, n);
        }
        bar_sync(NB_HELP, 128);
        const uint2 tr = lds64(tab + 24);
        st_pub_if(mk_ptr(tr.x | (tid_now() & 31) * 4, tr.y), SENT, c.w >= 2);
        if (s == 1) CLK(1); if (s == 8) CLK(2); if (s == 56) CLK(3);
        if (c.w == 2 && s == 15) TRSYNC(8);
        if (c.w == 2 && s == 21) TRSYNC(10);
      }
      const int g = s + 1;
      if (g < XEND) {
        const uint32_t tx_ = c.sb + SM_TAB + 1536 + (g & 3) * 128 + c.w * 32, tag = (g >> 2) & 1;
        if (c.w == 0) mbar_expect_e(BAR(B_LAND), 12288);
        auto load_x = [&]() {
          if (c.w == 3 && g + 1 < XEND) {
            mbar_wait(BAR(B_XEMPTY), g & 1);
            mbar_expect_e(BAR(B_XFULL), 32768);
            for (int i = 0; i < 2; i++) tma4d_e(c.sb + SM_XT + i * 16384, &tx, c.b * 8, (g + 1) * 4 + 2 * (c.b ^ i), BAR(B_XFULL));
          }
        };
        if (!X_AT || g == 0) load_x();
        mbar_wait(BAR(B_LAND), g & 1);
        if (g > 0) delay_cycles(DLY_F);
        {
          const int ln = tid_now() & 31;
          const uint32_t a0 = c.sb + SM_LAND + 16384 + land_off(c.w, ((ln & 14) << 1) + ((ln >> 4) << 1)) + (ln & 1) * 8;
          uint4 v;
          const uint2 p0 = lds64(a0), p1 = lds64(a0 + 2048), p2 = lds64(a0 + 4096), p3 = lds64(a0 + 6144);
          v.x = tagged(sum4(p0.x, p1.x, p2.x, p3.x), tag); v.y = sum4(p0.y, p1.y, p2.y, p3.y);
          const uint2 r0 = lds64(a0 + 16), r1 = lds64(a0 + 2064), r2 = lds64(a0 + 4112), r3 = lds64(a0 + 6160);
          v.z = sum4(r0.x, r1.x, r2.x, r3.x); v.w = sum4(r0.y, r1.y, r2.y, r3.y);
          const uint2 d = lds64(tx_);
          st_pub4(mk_ptr(d.x | v_off(ln), d.y), v);
        }
        TR(s, 3);
        if (FIN_AT && g > 0) { mbar_wait(BAR(B_SC), s & 1); if (DLY_FK) delay_cycles(DLY_FK); if (X_AT) load_x(); }
        const int ln = tid_now() & 31, n = ln >> 2, jj = ln & 3;
        const uint32_t base = c.sb + SM_LAND + ((c.w & 2) + (jj >> 1)) * 512 + (((16 * (jj & 1) + (n >> 1)) ^ (2 * jj)) << 4) + (n & 1) * 8;
        {
          const uint32_t a0 = base ^ ((c.w & 1) * 128), a1 = a0 ^ 64;
          uint4 v;
          const uint2 p0 = lds64(a0 + 8192), p1 = lds64(a0 + 2048), p2 = lds64(a0 + 12288), p3 = lds64(a0 + 6144);
          v.x = tagged(sum4(p0.x, p1.x, p2.x, p3.x), tag); v.y = sum4(p0.y, p1.y, p2.y, p3.y);
          const uint2 r0 = lds64(a1 + 8192), r1 = lds64(a1 + 2048), r2 = lds64(a1 + 12288), r3 = lds64(a1 + 6144);
          v.z = sum4(r0.x, r1.x, r2.x, r3.x); v.w = sum4(r0.y, r1.y, r2.y, r3.y);
          const uint2 d = lds64(tx_ + 8);
          st_pub4(mk_ptr(d.x | ln * 16, d.y), v);
        }
        TR(s, 4);
        uint32_t q[4];
#pragma unroll
        for (int e = 0; e < 4; e++) {
          const uint32_t a0 = (base ^ (e * 64)) + (c.w & 1) * 4;
          q[e] = sum4(lds32(a0), lds32(a0 + 10240), lds32(a0 + 4096), lds32(a0 + 14336));
        }
        const uint2 d = lds64(tx_ + 16);
        st_pub4(mk_ptr(d.x | ln * 16, d.y), make_uint4(tagged(q[0], tag), q[1], q[2], q[3]));
        mbar_arrive_both(BAR(B_LFREE), c.b ^ 1);
        TR(s, 5);
        if (!FIN_AT && X_AT && g > 0) { mbar_wait(BAR(B_SC), s & 1); if (DLY_FK) delay_cycles(DLY_FK); load_x(); }
      }
    }
    mbar_wait(BAR(B_DONE), 0);
    if (tid_now() == 384) TL(8);
    __syncwarp();
    asm volatile("barrier.cluster.arrive.relaxed; barrier.cluster.wait;" ::: "memory");
  } else if (c.m == 2) {
    asm volatile("setmaxnreg.dec.sync.aligned.u32 %0;" :: "n"(512 - 2 * REG_F - REG_H));
    c.lane = lane_id();
    CLK(0);
    {
      char* pa = c.mail + (uint32_t)(c.w < 2 ? M_PAIR + (c.w * 128 + c.r) * 8192 : c.w == 2 ? M_E3 + (c.r & 15) * 8192 + (c.r >> 4) * 128 : M_REF + c.r * 32);
      uint32_t a0 = ~0u, a1 = ~0u;
#pragma unroll 1
      for (int rep = 0; rep < NPROBE; rep++) { a0 = min(a0, timed_init(pa)); a1 = min(a1, timed_init(pa + 4096)); }
      sts32(c.sb + SM_SEL + 512 + c.w * 4, AWARE && a1 < a0 ? 1u << c.w : 0u);
      mbar_arrive_warp(BAR(B_PROBE));
      if (c.w == 0) {
        mbar_wait(BAR(B_PROBE), 0);
        const uint4 bits = lds128(c.sb + SM_SEL + 512);
        asm volatile("fence.acq_rel.gpu;" ::: "memory");
        st_pub_if(g_ctl + C_SEL + c.r, bits.x | bits.y | bits.z | bits.w | 0x100u, c.lane == 0);
        uint4 v; uint32_t n = 0;
        while (true) {
          v = ld_poll(g_ctl + C_SEL + c.lane * 4);
          if (__all_sync(~0u, v.x & v.y & v.z & v.w & 0x100u)) break;
          watchdog(n, POLL_LIMIT);
        }
        asm volatile("fence.acq_rel.gpu;" ::: "memory");
        sts128(c.sb + SM_SEL + c.lane * 16, v);
        mbar_arrive_warp(BAR(B_SEL));
        if (c.lane == 0) TL(13);
        __syncwarp();
        const unsigned short* mp = (const unsigned short*)mem0 + (2 * (c.lane & 3)) * D_ + 8 * c.r + (c.lane >> 2);
        uint32_t mv = (uint32_t)mp[0] | ((uint32_t)mp[D_] << 16);
        if (mv == SENT) mv = 0x7FFF7FFFu;
        char* dst = c.mail + (uint32_t)(M_E3 + (c.r >> 5) * 8192 + (c.r & 31) * 128 + c.lane * 4);
        st_pub(dst, mv); st_pub(dst + 4096, mv);
      }
    }
    asm volatile("barrier.cluster.wait;" ::: "memory");
    const int g = c.w, src0 = c.h * 4 + (g >> 1) * 2;
    mbar_wait(BAR(B_SEL), 0);
    c.sel = __shfl_sync(~0u, ~lds32(c.sb + SM_SEL + src0 * 4), 0);
    mbar_wait(BAR(B_WREAD), 0);
    uint32_t l16 = c.sb + g * 512 + c.lane * 16;
    auto lane = [&](uint32_t v) { l16 = dep(l16, v, c.sb); return (int)((l16 & 511) >> 4); };
    for (int s = 0; s < NSEG; s++) {
      l16 = vary(l16, s, c.sb);
      int ln = (l16 & 511) >> 4;
      uint4 kf[4], qx;
      {
        const int gs = min(s, XEND - 1);
        const char* pk = c.mail + (uint32_t)(M_KVQ + ((gs & (NSLOT - 1)) * 32 + c.h) * 24576 + g * 2048 + ln * 16);
        const char* pq = pk + (16384 + c.j * 2048 - g * 1536);
        const uint32_t tg = (gs / NSLOT) & 1;
        if (KVQ_AT) { mbar_wait(BAR(B_MEM), s & 1); if (DLY_K) delay_cycles(DLY_K); } else if (s > 0) mbar_wait(BAR(B_PUB), (s - 1) & 1);
        for (uint32_t n = 0; ; ) {
          uint4 v[4];
#pragma unroll
          for (int t = 0; t < 4; t++) v[t] = ld_poll(pk + 8192 + t * 512);
#pragma unroll
          for (int t = 0; t < 4; t++) kf[t] = ld_poll(pk + t * 512);
          qx = ld_poll(pq);
#pragma unroll
          for (int t = 0; t < 4; t++) sts128(l16 + SM_V + t * 2048, v[t]);
          if (QX_SM) sts128(l16 + SM_OX, qx);
          const uint32_t bad = stale1(stale1(stale2(v[0].x, v[1].x, tg), v[2].x, tg), v[3].x, tg)
                             | stale1(stale1(stale1(stale2(kf[0].x, kf[1].x, tg), kf[2].x, tg), kf[3].x, tg), qx.x, tg);
          if (all_clear(bad, 1)) break;
          watchdog(n, POLL_LIMIT);
        }
        TR(s, 2);
      }
      ln = lane(kf[0].y);
      const char* pa = c.mail + (uint32_t)(M_PAIR + ((s & 1) * 128 + src0) * 8192 + (c.sel >> (s & 1) & 1) * 4096 + (g & 1) * 512 + read_off(ln));
      const uint32_t spw = c.sb + SM_SP + g * 1280 + (ln >> 3) * 160 + (ln & 7) * 16, spr = c.sb + SM_SP + (ln & 3) * 160 + (ln >> 2) * 16, l8 = ln * 8;
      const uint32_t tg = s >> 1;
      float sx[2][4];
      uint32_t sm;
      uint4 km;
      touch(pa, c.sb);
      mbar_wait(BAR(B_E1TRIG), s & 1);
      const uint32_t t0 = clock_lo();
      TRV(s, 3, t0);
      scores_x<false>(sx, kf, qx, 0);
      store_scores(sx, spw + 640);
      delay_until(t0 + DLY_E1);
      uint32_t nr = 0;
      while (true) {
        const uint4 q0 = ld_poll(pa), q1 = ld_poll(pa + 2048), k0 = ld_poll(pa + 1024), k1 = ld_poll(pa + 3072);
        uint4 qm = add4(q0, q1);
        const uint32_t bq = stale2(q0.x, q1.x, tg);
        qm.x = dep(qm.x, bq, c.sb);
        scores_x<SC_F>(sx, kf, qm, c.sb);
        const uint32_t bk = stale2(k0.x, k1.x, tg);
        km = add4(k0, k1);
        km.x = dep(km.x, bk, c.sb);
        const bool ok = all_clear(bq | bk, 1);
        sm = scores_m(qm, km);
        store_scores(sx, spw);
        if (ok) break;
        nr++;
      }
      sts32(l8 + (c.sb + SM_SPM + (g >> 1) * 256 + (g & 1) * 4), sm);
      bar_sync(NB_ATT, 128);
      TR(s, 5); TRV(s, 13, nr);
      float o[2][4];
      uint32_t sp[5];
      uint4 vf[4];
      load_scores(sp, spr, l8 + (c.sb + SM_SPM));
      if (QX_SM) qx = lds128(l16 + SM_OX);
      const uint32_t m5 = max5(sp);
      float off = row_off(m5), f[10];
      l16 = dep(l16, m5, c.sb);
#pragma unroll
      for (int t = 0; t < 4; t++) vf[(t >> 1) + 2 * (t & 1)] = lds128(l16 + SM_V + ((t >> 1) + 2 * (t & 1)) * 2048);
      qx.x = dep(qx.x, sp[0], c.sb);
      sts32(l8 + (c.sb + SM_SPM + 512 + (g >> 1) * 256 + (g & 1) * 4), scores_m(qx, km));
      mbar_arrive_warp(BAR(B_SC));
      unpack(f, sp);
      sched_fence(c.sb);
      bar_sync(NB_VM, 384);
      sp[1] = exp_pair(f, 1, off);
      const uint32_t av = dep(l8, VM_AT ? sp[1] : __float_as_uint(off), c.sb) + (c.sb + g * 512 + SM_VM);
      const uint2 vm0 = lds64(av), vm1 = lds64(av + 256);
      const uint4 vm = make_uint4(vm0.x, vm0.y, vm1.x, vm1.y);
#pragma unroll
      for (int i = 2; i < 6; i++) sp[i % 5] = exp_pair(f, i % 5, off);
      float sum = pv(o, sp, vf, vm);
      stsm4<false>(l16 + SM_OM, pack_bf16(o[0][0], o[0][1]), pack_bf16(o[0][2], o[0][3]), pack_bf16(o[1][0], o[1][1]), pack_bf16(o[1][2], o[1][3]));
      sts32(c.sb + SM_SUM + ((l16 >> 4) & 28), __float_as_uint(sum));
      asm volatile("bar.arrive %0, 384;" :: "r"((int)NB_OM) : "memory");
      const uint32_t tom = clock_lo();
      TRV(s, 8, tom);
      sched_fence(c.sb);
      ln = lane(tom);
      const int n = ln >> 2, jj = ln & 3, tq_ = 8 * c.j + n, lim = 16 * (tq_ - 8 * jj + 1);
      if (DLY_X) delay_until(tom + DLY_X);
      load_scores(sp, spr + 640, c.sb + SM_SPM + 512 + ln * 8);
#pragma unroll
      for (int w = 0; w < 4; w++) {
        uint32_t m; asm("shl.b32 %0, 0xffffffff, %1;" : "=r"(m) : "r"(max(lim - 32 * w, 0)));
        sp[1 + w] = (sp[1 + w] & ~m) | (0xD029D029u & m);
      }
      mbar_arrive_warp(dep(dep(0, sp[0], c.sb), sp[1], c.sb) + BAR(B_SPFREE));
      off = row_off(max5(sp));
      unpack(f, sp);
#pragma unroll
      for (int i = 1; i < 6; i++) sp[i % 5] = exp_pair(f, i % 5, off);
      sum = pv(o, sp, vf, vm);
      if (W_PV) mbar_arrive_warp(dep(dep(0, __float_as_uint(o[1][0]), c.sb), __float_as_uint(sum), c.sb) + BAR(B_PVDONE));
      TR(s, 7);
      sum = rcp(sum);
      const float i0 = __shfl_sync(~0u, sum, 8 * jj), i1 = __shfl_sync(~0u, sum, 8 * jj + 4);
      const uint32_t oxs = c.sb + SM_OX + g * 512;
      stsm4<true>(oxs + (ln & 7) * 64 + (((ln >> 3) ^ ((ln >> 1) & 3)) << 4),
                  pack_bf16(o[0][0] * i0, o[0][1] * i1), pack_bf16(o[0][2] * i0, o[0][3] * i1), pack_bf16(o[1][0] * i0, o[1][1] * i1), pack_bf16(o[1][2] * i0, o[1][3] * i1));
      __syncwarp();
      *(uint4*)(g_ox + (uint32_t)((32 * s + tq_) * 4096 + c.h * 128 + 32 * g + 8 * jj)) = lds128(oxs + n * 64 + ((jj ^ (n >> 1)) << 4));
      TR(s, 9);
    }
    CLK(4);
    mbar_arrive_warp(BAR(B_DONE));
    asm volatile("barrier.cluster.arrive.relaxed;" ::: "memory");
  } else {
    asm volatile("setmaxnreg.inc.sync.aligned.u32 %0;" :: "n"(REG_F));
    c.lane = lane_id();
    uint32_t wa[16][4], wb[16][4], wv[16][4];
    fft_rows_fwd((float2*)smraw, (const __nv_bfloat16*)(smraw + SM_WST - 2048), c.r, threadIdx.x, BAR(B_ROWS), BAR(B_FREE));
    mbar_arrive_warp(BAR(B_P1));
    if (tid_now() == 0) TL(1);
    __syncwarp();
    mbar_spin(BAR(B_WFULL + c.m), 0);
    {
      const uint32_t st = c.sb + c.m * ST_WG + frag_off(c.w, c.lane);
#pragma unroll
      for (int k = 0; k < 16; k++) ldsm4t(wb[k], st + k * 2048);
#pragma unroll
      for (int k = NP; k < 16; k++) ldsm4t(wa[k], st + (16 + k - NP) * 2048);
#pragma unroll
      for (int k = 0; k < NV; k++) ldsm4t(wv[k], st + (32 - NP + k) * 2048);
      mbar_arrive_warp(BAR(B_WREAD));
#pragma unroll
      for (int k = 0; k < NP; k++) ldsm4t(wa[k], c.sb + SM_POOL + c.m * NP * 2048 + frag_off(c.w, c.lane) + k * 2048);
      bar_sync(NB_XCH, 256);
#pragma unroll
      for (int k = 0; k < NP; k++) sts128(c.sb + SM_POOL + c.m * 2048 + c.w * 512 + c.lane * 16 + k * 4096, make_uint4(wa[k][0], wa[k][1], wa[k][2], wa[k][3]));
    }
    if (tid_now() == 0) TL(12);
    __syncwarp();
    asm volatile("barrier.cluster.wait;" ::: "memory");
    uint32_t t16 = c.m * 2048 + c.w * 512 + c.lane * 16;
    uint32_t pk = (c.m * NHV * 2048 + frag_off(c.w, c.lane)) | (tile_off(2 * (c.w & 1), c.lane) << 16) | ((c.lane & 12) ? 0u : 0x80000000u);
    const uint32_t dx = desc_lo(c.sb + SM_XT + c.m * 4096), dh = desc_lo(c.sb + SM_HV + c.m * NHV * 2048);
    for (int s = -2; s < NSEG; s++) {
      t16 = vary(t16, s, c.sb); pk = vary(pk, s, c.sb);
      if (s >= 0) {
        uint32_t af[16][4], bf[4][4], wo;
        const uint32_t tab = ((t16 >> 3) & 0x1C0) + (c.sb + SM_TAB + (s & 1) * 512);
        const char* pa;
        mem_proj(wa, wb, wv, af, wo, pa, tab, t16, pk, c, s);
        const uint32_t t0 = clock_lo();
        t16 = dep(t16, t0, c.sb);
        auto ldwo = [&](int f) { ldsm4t(af[f], (f < WO_D ? wo : dep(wo, af[f < WO_D ? 0 : f - WO_D][0], c.sb)) + (c.sb + SM_WO + (f >> 3) * 32768 + (f & 7) * 2048)); };
        {
          const uint32_t tg = s >> 1, vm = t16 >> 1, chk = (~t16 >> 4) & 1;
#pragma unroll
          for (int f = WO_0; f < WO_1; f++) ldwo(f);
          delay_until(t0 + DLY_V);
          uint2 v0 = ld_poll2(pa), v1 = ld_poll2(pa + 1024), v2 = ld_poll2(pa + 2048), v3 = ld_poll2(pa + 3072);
          TR(s, 3);
#pragma unroll
          for (int f = WO_1; f < 16; f++) ldwo(f);
          TR(s, 4);
          uint32_t n = 0;
          while (true) {
            sts64(vm + (c.sb + SM_VM), sum4(v0.x, v1.x, v2.x, v3.x), sum4(v0.y, v1.y, v2.y, v3.y));
            if (arrive_if_clear(stale1(stale1(stale2(v0.x, v1.x, tg), v2.x, tg), v3.x, tg), chk, NB_VM, 384)) break;
            v0 = ld_poll2(pa); v1 = ld_poll2(pa + 1024); v2 = ld_poll2(pa + 2048); v3 = ld_poll2(pa + 3072);
            n++;
          }
          TR(s, 12); TRV(s, 15, n);
        }
        const uint32_t ob = dep(dep(t16 & 511, af[14][0], c.sb), af[15][0], c.sb), l4 = ob >> 2;
        const uint32_t bit = (t16 & 48) ? 0u : 1u;
        bar_sync(NB_OM, 384);
        TR(s, 5);
#pragma unroll
        for (int i = 0; i < 4; i++) ldsm4t(bf[i], ob + (c.sb + SM_OM + i * 512));
        uint2 sum = lds64(((t16 >> 1) & 24) + (c.sb + SM_SUM));
        if (OM_F) sched_fence(c.sb);
        float d[4][4] = {};
        uint4 d0, d1;
#pragma unroll
        for (int k = 0; k < 4; k++) {
#pragma unroll
          for (int t = 0; t < 2; t++) {
            mma_a(d[2 * t], af[8 * t + 2 * k], bf[k][0], bf[k][1]);
            mma_a(d[2 * t + 1], af[8 * t + 2 * k + 1], bf[k][2], bf[k][3]);
          }
          if (k == 0) {
            const uint32_t tb2 = dep((t16 >> 3) & 0x1C0, __float_as_uint(d[3][0]), c.sb) + (c.sb + SM_TAB + (s & 1) * 512);
            d0 = lds128(tb2 + 32); d1 = lds128(tb2 + 48);
          }
          if (k == 1) { sum.x = dep(sum.x, __float_as_uint(d[0][0]), c.sb); sum.y = dep(sum.y, __float_as_uint(d[0][0]), c.sb); }
        }
        char* dst[4] = {mk_ptr(d0.x | l4, d0.y), mk_ptr(d0.z | l4, d0.w), mk_ptr(d1.x | l4, d1.y), mk_ptr(d1.z | l4, d1.w)};
        const float i0 = rcp(__uint_as_float(sum.x)), i1 = rcp(__uint_as_float(sum.y));
#pragma unroll
        for (int i = 0; i < 4; i++) {
          const int t = i & 2, e = 2 * (i & 1);
          st_pub(dst[i], put_tag(pack_bf16((d[t][e] + d[t + 1][e]) * i0, (d[t][e + 1] + d[t + 1][e + 1]) * i1), bit, s >> 1));
        }
        mbar_arrive_warp(BAR(B_E2TRIG));
        TR(s, 6);
        sched_fence(c.sb);
      }
      auto ldp = [&](int k0, int k1, int d) {
#pragma unroll
        for (int k = k0; k < k1; k++) lds_frag(wa[k], (k < k0 + d ? t16 : dep(t16, wa[k < d ? 0 : k - d][0], c.sb)) + (c.sb + SM_POOL + k * 4096));
      };
      if (s + 2 < XEND) {
        float xa[16];
        uint32_t q[4];
        ldp(0, PL_0 / 2, PL_D);
        mbar_spin(BAR(B_XFULL), s & 1);
        ldp(PL_0 / 2, PL_0, PL_D);
        if (W_PV && s >= 0) mbar_spin(BAR(B_PVDONE), s & 1);
        TR(s, 7);
        if (ORDER) issue_qk<0, 16>(xa, wb, vary(dx, s, c.sb)); else issue_v(xa, wv, vary(dx, s, c.sb), vary(dh, s, c.sb));
        ldp(PL_0, PL_1, 1);
        const uint32_t land = (t16 ^ ((t16 >> 3) & 0x60)) + vary(c.sb + SM_LAND + c.b * 4096, s, c.sb);
        mbar_spin(BAR(B_LFREE), s & 1);
        WG_WAIT(0);
        TR(s, 8);
        park_own<!ORDER>(q, xa, land, ORDER ? 0 : 2, c.sb);
        if (ORDER) issue_v(xa, wv, vary(dx, s, c.sb + 32), vary(dh, s, c.sb)); else issue_qk<0, 16>(xa, wb, vary(dx, s, c.sb + 32));
        ldp(PL_1, PL_2, 1);
        if (W_PUB && s >= 0) mbar_spin(BAR(B_PUB), s & 1);
        const uint32_t tp = clock_lo();
        park_peer(q, land, ORDER ? 0 : 2, c);
        ldp(PL_2, NP - PL_L, 1);
        TR(s, 13);
        WG_WAIT(0);
        TR(s, 9);
        park_own<ORDER>(q, xa, land, ORDER ? 2 : 0, c.sb);
        issue_qk<0, PL_L ? NP - PL_L : 16>(xa, wa, vary(dx, s, c.sb + 64));
        ldp(NP - PL_L, NP, PL_E);
        if (PL_L) issue_qk<NP - PL_L, 16>(xa, wa, vary(dx, s, c.sb + 64));
        if (DLY_S && s >= 0) delay_until(tp + DLY_S);
        park_peer(q, land, ORDER ? 2 : 0, c);
        WG_WAIT(0);
        TR(s, 10);
        mbar_arrive_warp(BAR(B_XEMPTY));
        park_own<false>(q, xa, land, 1, c.sb);
        park_peer(q, land, 1, c);
        TR(s, 11);
      } else ldp(0, NP, 1);
      if (s == -1) {
        mbar_spin(BAR(B_WOFULL), 0);
        mbar_spin(BAR(B_SEL), 0);
        const int e = (t16 >> 4) & 7, sl = (t16 >> 7) & 1, m = t16 >> 11, w = (t16 >> 9) & 3;
        const int cta = e < 2 ? c.r & ~1 : e == 2 ? c.r | 1 : e == 3 ? c.h * 4 + 2 * m + 1 : c.j * 32 + m * 8 + 2 * w + (e & 2) * 8 + (e & 1);
        const uint32_t off = e < 2 ? c.b * 2048 + m * 1024 + (w >> 1) * 512 + e * 160 : e == 2 ? c.b * 2048 + m * 1024 + w * 256 : e == 3 ? w * 256 : c.h * 128;
        const uintptr_t ad = (uintptr_t)(c.mail + (uint32_t)(M_PAIR + (sl * 128 + cta) * 8192 + (((lds32(c.sb + SM_SEL + cta * 4) >> sl) ^ (e < 4)) & 1) * 4096 + off));
        sts64(c.sb + SM_TAB + sl * 512 + (m * 4 + w) * 64 + e * 8, (uint32_t)ad, (uint32_t)(ad >> 32));
        __syncwarp();
      }
    }
    mbar_arrive_warp(BAR(B_DONE));
    asm volatile("barrier.cluster.arrive.relaxed;" ::: "memory");
  }
}

constexpr int OP_STAGES = 5;
constexpr uint32_t OP_BT = OP_STAGES * 32768, OP_TW = OP_BT + 4 * ROW_BUF * 8, OP_BAR = OP_TW + 8192, OP_SMEM = OP_BAR + 128 + 1024;

__device__ __forceinline__ void wgmma_ss_n128_tb(float (&d)[64], uint64_t a, uint64_t b) {
  asm volatile("wgmma.mma_async.sync.aligned.m64n128k16.f32.bf16.bf16 "
    "{%0,%1,%2,%3,%4,%5,%6,%7,%8,%9,%10,%11,%12,%13,%14,%15,%16,%17,%18,%19,%20,%21,%22,%23,%24,%25,%26,%27,%28,%29,%30,%31,"
    "%32,%33,%34,%35,%36,%37,%38,%39,%40,%41,%42,%43,%44,%45,%46,%47,%48,%49,%50,%51,%52,%53,%54,%55,%56,%57,%58,%59,%60,%61,%62,%63}, "
    "%64, %65, 1, 1, 1, 0, 1;"
    : "+f"(d[0]), "+f"(d[1]), "+f"(d[2]), "+f"(d[3]), "+f"(d[4]), "+f"(d[5]), "+f"(d[6]), "+f"(d[7]),
      "+f"(d[8]), "+f"(d[9]), "+f"(d[10]), "+f"(d[11]), "+f"(d[12]), "+f"(d[13]), "+f"(d[14]), "+f"(d[15]),
      "+f"(d[16]), "+f"(d[17]), "+f"(d[18]), "+f"(d[19]), "+f"(d[20]), "+f"(d[21]), "+f"(d[22]), "+f"(d[23]),
      "+f"(d[24]), "+f"(d[25]), "+f"(d[26]), "+f"(d[27]), "+f"(d[28]), "+f"(d[29]), "+f"(d[30]), "+f"(d[31]),
      "+f"(d[32]), "+f"(d[33]), "+f"(d[34]), "+f"(d[35]), "+f"(d[36]), "+f"(d[37]), "+f"(d[38]), "+f"(d[39]),
      "+f"(d[40]), "+f"(d[41]), "+f"(d[42]), "+f"(d[43]), "+f"(d[44]), "+f"(d[45]), "+f"(d[46]), "+f"(d[47]),
      "+f"(d[48]), "+f"(d[49]), "+f"(d[50]), "+f"(d[51]), "+f"(d[52]), "+f"(d[53]), "+f"(d[54]), "+f"(d[55]),
      "+f"(d[56]), "+f"(d[57]), "+f"(d[58]), "+f"(d[59]), "+f"(d[60]), "+f"(d[61]), "+f"(d[62]), "+f"(d[63])
    : "l"(a), "l"(b));
}

__device__ __forceinline__ void tma2d_mc(uint32_t dst, const CUtensorMap* tm, int c0, int c1, uint32_t bar) {
  asm volatile("cp.async.bulk.tensor.2d.shared::cluster.global.mbarrier::complete_tx::bytes.multicast::cluster [%0], [%1, {%3, %4}], [%2], %5;"
               :: "r"(dst), "l"(tm), "r"(bar), "r"(c0), "r"(c1), "h"((uint16_t)3) : "memory");
}

__global__ void __cluster_dims__(2, 1, 1) __launch_bounds__(640, 1)
outproj_kernel(const __grid_constant__ CUtensorMap ta, const __grid_constant__ CUtensorMap tw,
               const __grid_constant__ CUtensorMap tb, const __grid_constant__ CUtensorMap tout) {
  extern __shared__ __align__(1024) unsigned char smraw[];
  const uint32_t sb = __shfl_sync(~0u, (smem_u32(smraw) + 1023) & ~1023u, 0);
  const uint32_t full = sb + OP_BAR, empty = full + 8 * OP_STAGES, bfull = empty + 8 * OP_STAGES;
  const int m0 = (blockIdx.x >> 3) * 128, n0 = (blockIdx.x & 7) * 128, rank = blockIdx.x & 1;
  if (threadIdx.x == 0) {
    for (int i = 0; i < OP_STAGES; i++) { mbar_init(full + 8 * i, 1); mbar_init(empty + 8 * i, 4); }
    mbar_init(bfull, 1);
    asm volatile("fence.mbarrier_init.release.cluster;" ::: "memory");
  }
  __syncthreads();
  asm volatile("barrier.cluster.arrive.relaxed.aligned; barrier.cluster.wait.aligned;" ::: "memory");
  const int role = __shfl_sync(~0u, (int)(threadIdx.x >> 7), 0);
  if (role == 4) {
    if (threadIdx.x == 512) {
      TL(9);
      for (int st = 0; st < OP_STAGES; st++) {
        mbar_expect(full + 8 * st, 32768);
        tma2d(sb + st * 32768 + 16384, &tw, n0, st * 64, full + 8 * st);
        tma2d(sb + st * 32768 + 24576, &tw, n0 + 64, st * 64, full + 8 * st);
      }
      pdl_wait();
      TL(10);
      uint32_t st = 0, ph = 1;
      for (int kb = 0; kb < 64; kb++) {
        const uint32_t dst = sb + st * 32768;
        if (kb >= OP_STAGES) {
          mbar_wait(empty + 8 * st, ph);
          mbar_expect(full + 8 * st, 32768);
          tma2d(dst + 16384, &tw, n0, kb * 64, full + 8 * st);
          tma2d(dst + 24576, &tw, n0 + 64, kb * 64, full + 8 * st);
        }
        tma2d_mc(dst + rank * 8192, &ta, kb * 64, m0 + rank * 64, full + 8 * st);
        if (++st == OP_STAGES) { st = 0; ph ^= 1; }
      }
      mbar_wait(full + 8 * (63 % OP_STAGES), (63 / OP_STAGES) & 1);
    }
  } else if (role >= 2) {
    unsigned char* base = smraw + (sb - smem_u32(smraw));
    const int t = threadIdx.x & 31, w = (threadIdx.x >> 5) & 7;
    row_twiddles((float2*)(base + OP_TW), threadIdx.x - 256, 256);
    bar_sync(2, 256);
    pdl_wait();
    { const int i = blockIdx.x * 256 + threadIdx.x - 256; if (i < C_CHAIN_END) g_ctl[i] = 0; }
    fft_rows_inv((float2*)(base + OP_BT) + w * (ROW_BUF / 2), (const float2*)(base + OP_TW),
                 (blockIdx.x & 63) * 16 + (blockIdx.x >> 6) * 8 + w, t);
    if (threadIdx.x == 256) TL(3);
    FENCE_ASYNC_SMEM();
    bar_sync(2, 256);
    if (threadIdx.x == 256) {
      uint32_t* cnt = g_ctl + C_ROWS + ((blockIdx.x >> 3) & 7) * 32;
      asm volatile("fence.acq_rel.gpu;" ::: "memory");
      asm volatile("red.relaxed.gpu.global.add.u32 [%0], 1;" :: "l"(cnt) : "memory");
      for (uint32_t n = 0; ld_acquire(cnt) < 16; ) { watchdog(n, 1u << 22); __nanosleep(100); }
      asm volatile("fence.proxy.async.global;" ::: "memory");
      mbar_expect(bfull, 32768);
      tma2d(sb + OP_BT, &tb, n0, m0, bfull); tma2d(sb + OP_BT + 16384, &tb, n0 + 64, m0, bfull);
      TL(5);
    }
  } else {
    const int wg = role, lane = threadIdx.x & 31, w = (threadIdx.x >> 5) & 3;
    float acc[64];
#pragma unroll
    for (int i = 0; i < 64; i++) acc[i] = 0.f;
    const uint32_t rel = mapa(empty, lane & 1), la = desc_lo(sb + wg * 8192), lb = ((sb + 16384) & 0x3FFFF) >> 4 | (8192 >> 4) << 16;
    const uint32_t relon = (threadIdx.x & 127) < 2;
    uint32_t st = 0, ph = 0, prev = 0;
#pragma unroll 1
    for (int kb = 0; kb < 64; kb++) {
      mbar_spin(full + 8 * st, ph);
      WG_FENCE();
#pragma unroll
      for (int k = 0; k < 4; k++) wgmma_ss_n128_tb(acc, desc128(la + st * 2048 + k * 2), desc128(lb + st * 2048 + k * 128));
      WG_COMMIT();
      WG_WAIT(1);
      asm volatile("{ .reg .pred p; setp.ne.u32 p, %1, 0; @p mbarrier.arrive.shared::cluster.b64 _, [%0]; }"
                   :: "r"(rel + 8 * prev), "r"(relon & (uint32_t)(kb > 0 && kb + OP_STAGES <= 64)) : "memory");
      prev = st;
      if (++st == OP_STAGES) { st = 0; ph ^= 1; }
    }
    WG_WAIT(0);
    const int r0 = wg * 64 + w * 16 + (lane >> 2);
    const float g0 = __ldcg(g_gate + m0 + r0), g1 = __ldcg(g_gate + m0 + r0 + 8);
    mbar_wait(bfull, 0);
#pragma unroll
    for (int t = 0; t < 16; t++) {
      const uint32_t a0 = sb + OP_BT + (t >> 3) * 16384 + r0 * 128 + (((t & 7) ^ (r0 & 7)) << 4) + (lane & 3) * 4, a1 = a0 + 1024;
      uint32_t b0, b1;
      asm volatile("ld.shared.u32 %0, [%1];" : "=r"(b0) : "r"(a0) : "memory");
      asm volatile("ld.shared.u32 %0, [%1];" : "=r"(b1) : "r"(a1) : "memory");
      const uint32_t o0 = pack_bf16(fmaf(g0, acc[4 * t], (1.f - g0) * __uint_as_float(b0 << 16)), fmaf(g0, acc[4 * t + 1], (1.f - g0) * __uint_as_float(b0 & 0xFFFF0000u)));
      const uint32_t o1 = pack_bf16(fmaf(g1, acc[4 * t + 2], (1.f - g1) * __uint_as_float(b1 << 16)), fmaf(g1, acc[4 * t + 3], (1.f - g1) * __uint_as_float(b1 & 0xFFFF0000u)));
      asm volatile("st.shared.u32 [%0], %1;" :: "r"(a0), "r"(o0) : "memory");
      asm volatile("st.shared.u32 [%0], %1;" :: "r"(a1), "r"(o1) : "memory");
    }
    FENCE_ASYNC_SMEM();
    bar_sync(1, 256);
    if (threadIdx.x == 0) {
      tma2d_store(&tout, n0, m0, sb + OP_BT); tma2d_store(&tout, n0 + 64, m0, sb + OP_BT + 16384);
      asm volatile("cp.async.bulk.commit_group; cp.async.bulk.wait_group 0;" ::: "memory");
      TL(11);
    }
  }
}

typedef CUresult (*EncodeFn)(CUtensorMap*, CUtensorMapDataType, cuuint32_t, void*, const cuuint64_t*, const cuuint64_t*,
                             const cuuint32_t*, const cuuint32_t*, CUtensorMapInterleave, CUtensorMapSwizzle,
                             CUtensorMapL2promotion, CUtensorMapFloatOOBfill);

void make_map(EncodeFn enc, CUtensorMap* tm, const void* p, int rank, const cuuint64_t* dims, const cuuint64_t* strides, const cuuint32_t* box) {
  const cuuint32_t es[4] = {1, 1, 1, 1};
  enc(tm, CU_TENSOR_MAP_DATA_TYPE_BFLOAT16, rank, (void*)p, dims, strides, box, es, CU_TENSOR_MAP_INTERLEAVE_NONE,
      CU_TENSOR_MAP_SWIZZLE_128B, CU_TENSOR_MAP_L2_PROMOTION_L2_128B, CU_TENSOR_MAP_FLOAT_OOB_FILL_NONE);
}
void make_map2(EncodeFn enc, CUtensorMap* tm, const void* p, uint64_t cols, uint64_t rows, uint32_t boxrows) {
  const cuuint64_t dims[2] = {cols, rows}, strides[1] = {cols * 2};
  const cuuint32_t box[2] = {64, boxrows};
  make_map(enc, tm, p, 2, dims, strides, box);
}

}

extern "C" void kernel_launch(void* const* d_in, const int* in_sizes, int n_in, void* d_out, int out_size) {
  (void)in_sizes; (void)n_in; (void)out_size;
  const __nv_bfloat16* x = (const __nv_bfloat16*)d_in[0];
  const __nv_bfloat16* mem0 = (const __nv_bfloat16*)d_in[1];
  const __nv_bfloat16* gw = (const __nv_bfloat16*)d_in[10];

  EncodeFn enc = nullptr;
  cudaDriverEntryPointQueryResult qr;
  cudaGetDriverEntryPoint("cuTensorMapEncodeTiled", (void**)&enc, cudaEnableDefault, &qr);
  void *p_ox, *p_b, *p_mail;
  cudaGetSymbolAddress(&p_ox, g_ox); cudaGetSymbolAddress(&p_b, g_b); cudaGetSymbolAddress(&p_mail, g_mail);
  CUtensorMap tq, tk, tv, tv16, to, tx, ta, tw, tb, tout;
  make_map2(enc, &tq, d_in[2], 4096, 1024, 64);
  make_map2(enc, &tk, d_in[3], 4096, 1024, 64);
  make_map2(enc, &tv, d_in[4], 4096, 1024, 64);
  make_map2(enc, &tv16, d_in[4], 4096, 1024, 16);
  make_map2(enc, &to, d_in[5], 1024, 4096, 128);
  make_map2(enc, &tw, d_in[5], 1024, 4096, 64);
  make_map2(enc, &ta, p_ox, 4096, 2048, 64);
  make_map2(enc, &tb, p_b, 1024, 2048, 128);
  make_map2(enc, &tout, d_out, 1024, 2048, 128);
  {
    const cuuint64_t dims[4] = {64, 8, 16, 256}, strides[3] = {2048, 128, 16384};
    const cuuint32_t box[4] = {64, 8, 8, 2};
    make_map(enc, &tx, x, 4, dims, strides, box);
  }
  cudaFuncSetAttribute(chain_kernel, cudaFuncAttributeMaxDynamicSharedMemorySize, CHAIN_SMEM);
  cudaFuncSetAttribute(outproj_kernel, cudaFuncAttributeMaxDynamicSharedMemorySize, OP_SMEM);

  cudaStream_t st = cudaStreamPerThread;
  char* mail = (char*)(((uintptr_t)p_mail + 8191) & ~(uintptr_t)8191);
  chain_kernel<<<132, 512, CHAIN_SMEM, st>>>(tq, tk, tv, tv16, to, tx, mem0, mail, x, gw, (const char*)d_in[8], (const char*)d_in[9]);
  cudaLaunchAttribute pdl;
  pdl.id = cudaLaunchAttributeProgrammaticStreamSerialization;
  pdl.val.programmaticStreamSerializationAllowed = 1;
  cudaLaunchConfig_t cfg = {};
  cfg.stream = st; cfg.attrs = &pdl; cfg.numAttrs = USE_PDL;
  cfg.gridDim = dim3(128); cfg.blockDim = dim3(544); cfg.dynamicSmemBytes = OP_SMEM;
  cudaLaunchKernelEx(&cfg, outproj_kernel, ta, tw, tb, tout);
}
```

```cpp
#include <cuda_runtime.h>
#include <cuda_bf16.h>
#include <cuda.h>
#include <stdint.h>

#define DLY_E1 300
#define DLY_V 330
#define DLY_E2 400
#define DLY_E3 500
#define DLY_X 120
#define DLY_S 500
#define DLY_F 200
#define VM_AT 1
#define VM_F 0
#define OM_F 1
#define SXX_IN 0
#define C1_AT 1
#define NLAG 4
#define WO_D 2
#define WO_0 2
#define WO_1 12
#define PL_0 8
#define PL_1 12
#define PL_D 2
#define PL_L 0
#define DUAL 0
#define HV_D 3
#define DLY_FK 0
#define QX_SM 0
#define REG_F 216
#define REG_H 24
#define SC_F 1
#define E2_F 1
#define KVQ_AT 0
#define DLY_K 0
#define X_AT 0
#define W_PV 0
#define PL_2 12
#define BF_E 3
#define PL_E 2
#define ORDER 1
#define SSPOS 1
#define W_PUB 1
#define FIN_AT 2
#define AWARE 1
#define NPROBE 6
#define NP_ 12
#define USE_PDL 1
#define DLY_GRP 3000
#define P2_BULK 0
#define EXP_NV 4
#define EXP_NK 4
#define EXP_CHK 1
#define EXP_NXT 2
#define EXP_PEER 1
#define EXP_FIN 7
#define EXP_NWG 16
#define ANCH2 1
#define XF_AT 1
#define IS_F 1
#define PL_D1 2
#define W_E2 0
#define V_TMA 2
#define V_W 2
#define RED_L 3
#define RED_T 1
#define RED_P 1
#define DLY_E3B 0
#define HV_E 0
#define HV_R 4

namespace {

constexpr int S_ = 2048, D_ = 1024, NSEG = 64;
constexpr uint32_t SENT = 0xFFFFFFFFu;
constexpr int NSLOT = 4;

constexpr uint32_t M_PAIR = 0, M_E3 = M_PAIR + 2 * 128 * 8192, M_REF = M_E3 + 16 * 8192, M_KVQ = M_REF + 8192,
                   MAIL_BYTES = M_KVQ + NSLOT * 32 * 24576;
__device__ __align__(1024) unsigned char g_mail[MAIL_BYTES + 8192];
constexpr int C_SEL = 0, C_P1 = C_SEL + 128, C_CHAIN_END = C_P1 + 32, C_ROWS = C_CHAIN_END, C_END = C_ROWS + 16 * 32;
__device__ __align__(1024) uint32_t g_ctl[C_END];
#define CLK(i)
#define TL(i)
#define CNT(i)
__device__ __align__(1024) __nv_bfloat16 g_ox[S_ * 4096];
__device__ __align__(1024) float2 g_z[257 * 4096];
__device__ __align__(1024) uint32_t g_wp[257 * 4096];
__device__ __align__(1024) __nv_bfloat16 g_b[S_ * D_];
__device__ float g_gate[S_];

#define TRV(s, ev, val)
#define TR(s, ev)
#define TRSYNC(ev)
__device__ __forceinline__ uint32_t smem_u32(const void* p) { return (uint32_t)__cvta_generic_to_shared(p); }
__device__ __forceinline__ void watchdog(uint32_t& n, uint32_t limit) {
  asm volatile("{ .reg .pred p; add.u32 %0, %0, 1; setp.gt.u32 p, %0, %1; @p trap; }" : "+r"(n) : "r"(limit));
}
__device__ __forceinline__ void mbar_init(uint32_t bar, uint32_t cnt) {
  asm volatile("mbarrier.init.shared::cta.b64 [%0], %1;" :: "r"(bar), "r"(cnt) : "memory");
}
__device__ __forceinline__ void mbar_arrive_warp(uint32_t bar) {
  __syncwarp();
  asm volatile("{ .reg .pred p; elect.sync _|p, 0xffffffff; @p mbarrier.arrive.shared::cta.b64 _, [%0]; }" :: "r"(bar) : "memory");
}
__device__ __forceinline__ uint32_t clock_lo() {
  uint32_t r; asm volatile("{ .reg .u64 c; .reg .u32 h; mov.u64 c, %%clock64; mov.b64 {%0, h}, c; }" : "=r"(r) :: "memory"); return r;
}
__device__ __forceinline__ void delay_until(uint32_t t) {
  asm volatile("{ .reg .pred p; .reg .u64 c; .reg .u32 l, h;\n"
               "DLY: mov.u64 c, %%clock64; mov.b64 {l, h}, c; sub.s32 l, l, %0; setp.lt.s32 p, l, 0; @p bra.uni DLY; }" :: "r"(t) : "memory");
}
__device__ __forceinline__ void delay_cycles(uint32_t n) { delay_until(clock_lo() + n); }
__device__ __forceinline__ void sched_fence(uint32_t z) {
  asm volatile("{ .reg .pred p; setp.eq.u32 p, %0, 0x7fff0000; @p pmevent 1; }" :: "r"(z) : "memory");
}
__device__ __forceinline__ void pdl_wait() { asm volatile("griddepcontrol.wait;" ::: "memory"); }
__device__ __forceinline__ void pdl_launch() { asm volatile("griddepcontrol.launch_dependents;" ::: "memory"); }
__device__ __forceinline__ float ex2(float x) { float r; asm("ex2.approx.ftz.f32 %0, %1;" : "=f"(r) : "f"(x)); return r; }
__device__ __forceinline__ float rcp(float x) { float r; asm("rcp.approx.ftz.f32 %0, %1;" : "=f"(r) : "f"(x)); return r; }
__device__ __forceinline__ void mbar_expect(uint32_t bar, uint32_t bytes) {
  asm volatile("mbarrier.arrive.expect_tx.shared::cta.b64 _, [%0], %1;" :: "r"(bar), "r"(bytes) : "memory");
}
__device__ __forceinline__ bool mbar_try(uint32_t bar, uint32_t ph) {
  uint32_t ok;
  asm volatile("{ .reg .pred p; mbarrier.try_wait.parity.shared::cta.b64 p, [%1], %2; selp.u32 %0, 1, 0, p; }"
               : "=r"(ok) : "r"(bar), "r"(ph) : "memory");
  return ok;
}
__device__ __forceinline__ void mbar_wait(uint32_t bar, uint32_t ph) {
  uint32_t n = 0;
  while (!mbar_try(bar, ph)) { watchdog(n, (1u << 20)); }
}
__device__ __forceinline__ void mbar_spin(uint32_t bar, uint32_t ph) { while (!mbar_try(bar, ph)) {} }
__device__ __forceinline__ void mbar_spin_if(uint32_t bar, uint32_t ph, bool on) {
  asm volatile("{ .reg .pred p, q; setp.ne.u32 p, %2, 0;\n"
               "SPN: setp.eq.u32 q, 0, 0; @p mbarrier.try_wait.parity.shared::cta.b64 q, [%0], %1; @!q bra.uni SPN; }" :: "r"(bar), "r"(ph), "r"((uint32_t)on) : "memory");
}
__device__ __forceinline__ void mbar_spin_cluster(uint32_t bar, uint32_t ph) {
  uint32_t ok;
  do {
    asm volatile("{ .reg .pred p; mbarrier.try_wait.parity.acquire.cluster.shared::cta.b64 p, [%1], %2; selp.u32 %0, 1, 0, p; }"
                 : "=r"(ok) : "r"(bar), "r"(ph) : "memory");
  } while (!ok);
}
__device__ __forceinline__ void tma2d(uint32_t dst, const CUtensorMap* tm, int c0, int c1, uint32_t bar) {
  asm volatile("cp.async.bulk.tensor.2d.shared::cluster.global.mbarrier::complete_tx::bytes [%0], [%1, {%3, %4}], [%2];"
               :: "r"(dst), "l"(tm), "r"(bar), "r"(c0), "r"(c1) : "memory");
}
__device__ __forceinline__ void tma2d_store(const CUtensorMap* tm, int c0, int c1, uint32_t src) {
  asm volatile("cp.async.bulk.tensor.2d.global.shared::cta.bulk_group [%0, {%2, %3}], [%1];"
               :: "l"(tm), "r"(src), "r"(c0), "r"(c1) : "memory");
}
__device__ __forceinline__ void mbar_expect_e(uint32_t bar, uint32_t bytes) {
  asm volatile("{ .reg .pred p; elect.sync _|p, 0xffffffff; @p mbarrier.arrive.expect_tx.shared::cta.b64 _, [%0], %1; }" :: "r"(bar), "r"(bytes) : "memory");
}
__device__ __forceinline__ void tma2d_e(uint32_t dst, const CUtensorMap* tm, int c0, int c1, uint32_t bar) {
  asm volatile("{ .reg .pred p; elect.sync _|p, 0xffffffff;\n"
               "@p cp.async.bulk.tensor.2d.shared::cluster.global.mbarrier::complete_tx::bytes [%0], [%1, {%3, %4}], [%2]; }"
               :: "r"(dst), "l"(tm), "r"(bar), "r"(c0), "r"(c1) : "memory");
}
__device__ __forceinline__ void tma4d_e(uint32_t dst, const CUtensorMap* tm, int c2, int c3, uint32_t bar) {
  asm volatile("{ .reg .pred p; elect.sync _|p, 0xffffffff;\n"
               "@p cp.async.bulk.tensor.4d.shared::cluster.global.mbarrier::complete_tx::bytes [%0], [%1, {0, 0, %3, %4}], [%2]; }"
               :: "r"(dst), "l"(tm), "r"(bar), "r"(c2), "r"(c3) : "memory");
}
__device__ __forceinline__ void bulk_load_e(uint32_t dst, const void* src, uint32_t bytes, uint32_t bar) {
  asm volatile("{ .reg .pred p; elect.sync _|p, 0xffffffff;\n"
               "@p cp.async.bulk.shared::cluster.global.mbarrier::complete_tx::bytes [%0], [%1], %2, [%3]; }"
               :: "r"(dst), "l"(src), "r"(bytes), "r"(bar) : "memory");
}
__device__ __forceinline__ void prefetch2d_e(const CUtensorMap* tm, int c0, int c1) {
  asm volatile("{ .reg .pred p; elect.sync _|p, 0xffffffff;\n"
               "@p cp.async.bulk.prefetch.tensor.2d.L2.global [%0, {%1, %2}]; }" :: "l"(tm), "r"(c0), "r"(c1) : "memory");
}
__device__ __forceinline__ void st_pub4(void* p, uint4 v) {
  asm volatile("st.relaxed.gpu.global.v4.u32 [%0], {%1,%2,%3,%4};" :: "l"(p), "r"(v.x), "r"(v.y), "r"(v.z), "r"(v.w) : "memory");
}
__device__ __forceinline__ void st_pub_if(void* p, uint32_t v, bool on) {
  asm volatile("{ .reg .pred p; setp.ne.u32 p, %2, 0; @p st.relaxed.gpu.global.u32 [%0], %1; }" :: "l"(p), "r"(v), "r"((uint32_t)on) : "memory");
}
__device__ __forceinline__ uint32_t mapa(uint32_t a, uint32_t r) {
  uint32_t d; asm volatile("mapa.shared::cluster.u32 %0, %1, %2;" : "=r"(d) : "r"(a), "r"(r)); return d;
}
__device__ __forceinline__ void st_async4(uint32_t a, uint32_t x, uint32_t y, uint32_t z, uint32_t w, uint32_t bar) {
  asm volatile("st.async.shared::cluster.mbarrier::complete_tx::bytes.v4.u32 [%0], {%1,%2,%3,%4}, [%5];"
               :: "r"(a), "r"(x), "r"(y), "r"(z), "r"(w), "r"(bar) : "memory");
}
__device__ __forceinline__ uint4 ld_poll(const void* p) {
  uint4 v;
  asm volatile("ld.volatile.global.v4.u32 {%0,%1,%2,%3}, [%4];" : "=r"(v.x), "=r"(v.y), "=r"(v.z), "=r"(v.w) : "l"(p) : "memory");
  return v;
}
__device__ __forceinline__ uint2 ld_poll2(const void* p) {
  uint2 v; asm volatile("ld.volatile.global.v2.u32 {%0,%1}, [%2];" : "=r"(v.x), "=r"(v.y) : "l"(p) : "memory"); return v;
}
__device__ __forceinline__ void st_pub2(void* p, uint32_t a, uint32_t b) {
  asm volatile("st.relaxed.gpu.global.v2.u32 [%0], {%1,%2};" :: "l"(p), "r"(a), "r"(b) : "memory");
}
__device__ __forceinline__ uint32_t ld_poll1(const void* p) {
  uint32_t v; asm volatile("ld.volatile.global.u32 %0, [%1];" : "=r"(v) : "l"(p) : "memory"); return v;
}
__device__ __forceinline__ uint32_t ld_acquire(const uint32_t* p) {
  uint32_t v; asm volatile("ld.acquire.gpu.global.u32 %0, [%1];" : "=r"(v) : "l"(p) : "memory"); return v;
}
__device__ __forceinline__ void st_pub(void* p, uint32_t v) {
  asm volatile("st.relaxed.gpu.global.u32 [%0], %1;" :: "l"(p), "r"(v) : "memory");
}
__device__ __forceinline__ uint32_t lds32(uint32_t a) {
  uint32_t v; asm volatile("ld.shared.u32 %0, [%1];" : "=r"(v) : "r"(a) : "memory"); return v;
}
__device__ __forceinline__ uint32_t timed_init(void* p) {
  uint32_t t;
  asm volatile("{ .reg .pred q; .reg .u32 a, b, v; elect.sync _|q, 0xffffffff; mov.u32 v, 0; mov.u32 a, %%clock;\n"
               "@q atom.relaxed.gpu.global.exch.b32 v, [%1], 0xffffffff; shfl.sync.idx.b32 v, v, 0, 31, 0xffffffff;\n"
               "setp.eq.u32 q, v, 0x12345; @q pmevent 1; mov.u32 b, %%clock; sub.u32 %0, b, a; }" : "=r"(t) : "l"(p) : "memory");
  return t;
}
__device__ __forceinline__ uint4 lds128(uint32_t a) {
  uint4 v; asm volatile("ld.shared.v4.u32 {%0,%1,%2,%3}, [%4];" : "=r"(v.x), "=r"(v.y), "=r"(v.z), "=r"(v.w) : "r"(a) : "memory"); return v;
}
__device__ __forceinline__ uint2 lds64(uint32_t a) {
  uint2 v; asm volatile("ld.shared.v2.u32 {%0,%1}, [%2];" : "=r"(v.x), "=r"(v.y) : "r"(a) : "memory"); return v;
}
__device__ __forceinline__ void sts128(uint32_t a, uint4 v) {
  asm volatile("st.shared.v4.u32 [%0], {%1,%2,%3,%4};" :: "r"(a), "r"(v.x), "r"(v.y), "r"(v.z), "r"(v.w) : "memory");
}
__device__ __forceinline__ void sts64(uint32_t a, uint32_t x, uint32_t y) { asm volatile("st.shared.v2.u32 [%0], {%1,%2};" :: "r"(a), "r"(x), "r"(y) : "memory"); }
__device__ __forceinline__ void sts32(uint32_t a, uint32_t x) { asm volatile("st.shared.u32 [%0], %1;" :: "r"(a), "r"(x) : "memory"); }
__device__ __forceinline__ void ldsm4t(uint32_t (&r)[4], uint32_t a) {
  asm volatile("ldmatrix.sync.aligned.m8n8.x4.trans.shared.b16 {%0,%1,%2,%3}, [%4];"
               : "=r"(r[0]), "=r"(r[1]), "=r"(r[2]), "=r"(r[3]) : "r"(a) : "memory");
}
template<bool TRANS> __device__ __forceinline__ void stsm4(uint32_t a, uint32_t r0, uint32_t r1, uint32_t r2, uint32_t r3) {
  if (TRANS) asm volatile("stmatrix.sync.aligned.m8n8.x4.trans.shared.b16 [%0], {%1,%2,%3,%4};" :: "r"(a), "r"(r0), "r"(r1), "r"(r2), "r"(r3) : "memory");
  else       asm volatile("stmatrix.sync.aligned.m8n8.x4.shared.b16 [%0], {%1,%2,%3,%4};" :: "r"(a), "r"(r0), "r"(r1), "r"(r2), "r"(r3) : "memory");
}
__device__ __forceinline__ void mma16816(float (&d)[4], uint32_t a0, uint32_t a1, uint32_t a2, uint32_t a3, uint32_t b0, uint32_t b1) {
  asm volatile("mma.sync.aligned.m16n8k16.row.col.f32.bf16.bf16.f32 {%0,%1,%2,%3}, {%4,%5,%6,%7}, {%8,%9}, {%0,%1,%2,%3};"
               : "+f"(d[0]), "+f"(d[1]), "+f"(d[2]), "+f"(d[3]) : "r"(a0), "r"(a1), "r"(a2), "r"(a3), "r"(b0), "r"(b1));
}
__device__ __forceinline__ void mma1688(float (&d)[4], uint32_t a0, uint32_t a1, uint32_t b0) {
  asm volatile("mma.sync.aligned.m16n8k8.row.col.f32.bf16.bf16.f32 {%0,%1,%2,%3}, {%4,%5}, {%6}, {%0,%1,%2,%3};"
               : "+f"(d[0]), "+f"(d[1]), "+f"(d[2]), "+f"(d[3]) : "r"(a0), "r"(a1), "r"(b0));
}
__device__ __forceinline__ uint32_t pack_bf16(float lo, float hi) {
  uint32_t r; asm("cvt.rn.bf16x2.f32 %0, %1, %2;" : "=r"(r) : "f"(hi), "f"(lo)); return r;
}
__device__ __forceinline__ uint32_t add_bf16x2(uint32_t a, uint32_t b) {
  uint32_t r; asm("add.rn.bf16x2 %0, %1, %2;" : "=r"(r) : "r"(a), "r"(b)); return r;
}
__device__ __forceinline__ uint32_t umax4(uint4 v) { return max(max(v.x, v.y), max(v.z, v.w)); }
__device__ __forceinline__ uint32_t opaque(uint32_t x) { uint32_t r; asm volatile("mov.u32 %0, %1;" : "=r"(r) : "r"(x)); return r; }
template<class T> __device__ __forceinline__ void pin(T*& p) { asm volatile("" : "+l"(p)); }
__device__ __forceinline__ void pin(uint32_t& v) { asm volatile("" : "+r"(v)); }
__device__ __forceinline__ uint32_t desc_lo(uint32_t addr) { return ((addr & 0x3FFFF) >> 4) | 0x10000; }
__device__ __forceinline__ uint64_t desc128(uint32_t lo) {
  uint64_t d; asm("mov.b64 %0, {%1, %2};" : "=l"(d) : "r"(lo), "r"(0x40000040)); return d;
}
#define WG_FENCE()  asm volatile("wgmma.fence.sync.aligned;" ::: "memory")
#define WG_COMMIT() asm volatile("wgmma.commit_group.sync.aligned;" ::: "memory")
#define WG_WAIT(n)  asm volatile("wgmma.wait_group.sync.aligned " #n ";" ::: "memory")
#define FENCE_ASYNC_SMEM() asm volatile("fence.proxy.async.shared::cta;" ::: "memory")
__device__ __forceinline__ void bar_sync(int id, int n) { asm volatile("bar.sync %0, %1;" :: "r"(id), "r"(n) : "memory"); }

#define D16(c) c(d[0]), c(d[1]), c(d[2]), c(d[3]), c(d[4]), c(d[5]), c(d[6]), c(d[7]), \
               c(d[8]), c(d[9]), c(d[10]), c(d[11]), c(d[12]), c(d[13]), c(d[14]), c(d[15])
template<bool FIRST> __device__ __forceinline__ void wgmma_rs_n32(float (&d)[16], const uint32_t (&a)[4], uint64_t b) {
  if (FIRST)
    asm volatile("wgmma.mma_async.sync.aligned.m64n32k16.f32.bf16.bf16 {%0,%1,%2,%3,%4,%5,%6,%7,%8,%9,%10,%11,%12,%13,%14,%15}, {%16,%17,%18,%19}, %20, 0, 1, 1, 0;"
      : D16("=f") : "r"(a[0]), "r"(a[1]), "r"(a[2]), "r"(a[3]), "l"(b));
  else
    asm volatile("wgmma.mma_async.sync.aligned.m64n32k16.f32.bf16.bf16 {%0,%1,%2,%3,%4,%5,%6,%7,%8,%9,%10,%11,%12,%13,%14,%15}, {%16,%17,%18,%19}, %20, 1, 1, 1, 0;"
      : D16("+f") : "r"(a[0]), "r"(a[1]), "r"(a[2]), "r"(a[3]), "l"(b));
}
template<bool FIRST> __device__ __forceinline__ void wgmma_ss_n32_ta(float (&d)[16], uint64_t a, uint64_t b) {
  if (FIRST)
    asm volatile("wgmma.mma_async.sync.aligned.m64n32k16.f32.bf16.bf16 {%0,%1,%2,%3,%4,%5,%6,%7,%8,%9,%10,%11,%12,%13,%14,%15}, %16, %17, 0, 1, 1, 1, 0;"
      : D16("=f") : "l"(a), "l"(b));
  else
    asm volatile("wgmma.mma_async.sync.aligned.m64n32k16.f32.bf16.bf16 {%0,%1,%2,%3,%4,%5,%6,%7,%8,%9,%10,%11,%12,%13,%14,%15}, %16, %17, 1, 1, 1, 1, 0;"
      : D16("+f") : "l"(a), "l"(b));
}

struct cf { float x, y; };
__host__ __device__ constexpr float cos64(int k) {
  return k == 0 ? 1.0f : k == 1 ? 0.99518472667219689f : k == 2 ? 0.98078528040323045f : k == 3 ? 0.95694033573220887f :
         k == 4 ? 0.92387953251128676f : k == 5 ? 0.88192126434835503f : k == 6 ? 0.83146961230254524f : k == 7 ? 0.77301045336273696f :
         k == 8 ? 0.70710678118654752f : k == 9 ? 0.63439328416364550f : k == 10 ? 0.55557023301960222f : k == 11 ? 0.47139673682599765f :
         k == 12 ? 0.38268343236508977f : k == 13 ? 0.29028467725446236f : k == 14 ? 0.19509032201612827f : k == 15 ? 0.09801714032956060f : 0.0f;
}
__host__ __device__ constexpr float c64(int k) { return k <= 16 ? cos64(k) : -cos64(32 - k); }
__host__ __device__ constexpr float s64(int k) { return k <= 16 ? cos64(16 - k) : cos64(k - 16); }

template<int N, int ST, bool INV> struct Fft {
  template<int K> static __device__ __forceinline__ void bf(const cf* e, const cf* o, cf* out) {
    if constexpr (K < N / 2) {
      constexpr int idx = K * (64 / N);
      const cf a = e[K], b = o[K];
      if constexpr (idx == 0) {
        out[K] = {a.x + b.x, a.y + b.y}; out[K + N / 2] = {a.x - b.x, a.y - b.y};
      } else if constexpr (idx == 16) {
        if constexpr (INV) { out[K] = {a.x - b.y, a.y + b.x}; out[K + N / 2] = {a.x + b.y, a.y - b.x}; }
        else               { out[K] = {a.x + b.y, a.y - b.x}; out[K + N / 2] = {a.x - b.y, a.y + b.x}; }
      } else {
        constexpr float c = c64(idx), s = INV ? s64(idx) : -s64(idx);
        cf p; p.x = fmaf(-s, b.y, fmaf(c, b.x, a.x)); p.y = fmaf(s, b.x, fmaf(c, b.y, a.y));
        out[K] = p; out[K + N / 2] = {fmaf(2.0f, a.x, -p.x), fmaf(2.0f, a.y, -p.y)};
      }
      bf<K + 1>(e, o, out);
    }
  }
  static __device__ __forceinline__ void run(const cf* in, cf* out) {
    cf e[N / 2], o[N / 2];
    Fft<N / 2, 2 * ST, INV>::run(in, e);
    Fft<N / 2, 2 * ST, INV>::run(in + ST, o);
    bf<0>(e, o, out);
  }
};
template<int ST, bool INV> struct Fft<1, ST, INV> {
  static __device__ __forceinline__ void run(const cf* in, cf* out) { out[0] = in[0]; }
};
template<bool INV> __device__ __forceinline__ void fft32(cf (&v)[32]) {
  cf o[32]; Fft<32, 1, INV>::run(v, o);
#pragma unroll
  for (int i = 0; i < 32; i++) v[i] = o[i];
}
__device__ __forceinline__ cf cmul(cf a, float c, float s) { return {fmaf(-a.y, s, a.x * c), fmaf(a.x, s, a.y * c)}; }
__device__ __forceinline__ float bf2f(__nv_bfloat16 v) { return __bfloat162float(v); }

template<bool INV> __device__ __forceinline__ void warp_fft1024_a(cf (&v)[32], float2* __restrict__ buf, const float2* __restrict__ tw, int t) {
  fft32<INV>(v);
#pragma unroll
  for (int j = 1; j < 32; j++) { const float2 w = tw[j * 32 + t]; v[j] = cmul(v[j], w.x, INV ? -w.y : w.y); }
  if (INV) {
    float* f = (float*)buf;
#pragma unroll
    for (int j = 0; j < 32; j++) f[j * 33 + t] = v[j].x;
    __syncwarp();
#pragma unroll
    for (int j = 0; j < 32; j++) v[j].x = f[t * 33 + j];
    __syncwarp();
#pragma unroll
    for (int j = 0; j < 32; j++) f[j * 33 + t] = v[j].y;
    __syncwarp();
#pragma unroll
    for (int j = 0; j < 32; j++) v[j].y = f[t * 33 + j];
  } else {
#pragma unroll
    for (int j = 0; j < 32; j++) buf[j * 33 + t] = make_float2(v[j].x, v[j].y);
    __syncwarp();
#pragma unroll
    for (int j = 0; j < 32; j++) { const float2 r = buf[t * 33 + j]; v[j] = {r.x, r.y}; }
  }
  __syncwarp();
}
constexpr int W_CHUNK = 16 * 513 * 2;
constexpr int ROW_BUF = 32 * 33;

__device__ __forceinline__ void row_twiddles(float2* tw, int tid, int nthreads) {
  for (int i = tid; i < 1024; i += nthreads) {
    float s, c; sincospif(-(float)((i >> 5) * (i & 31)) * (1.0f / 512.0f), &s, &c); tw[i] = make_float2(c, s);
  }
}
__device__ __forceinline__ void fft_rows_fwd(float2* sm2, const __nv_bfloat16* gw, int cta, int tid, uint32_t full_bar, uint32_t release_bar) {
  const int t = tid & 31, w = tid >> 5, n = cta * 8 + w;
  row_twiddles(sm2, tid, 256);
  mbar_spin(full_bar, 0);
  if (tid == 0) TL(6);
  __syncwarp();
  const __nv_bfloat16* xa = (const __nv_bfloat16*)(sm2 + 1024 + w * ROW_BUF) + t;
  cf v[32];
  float ga = 0.f, gb = 0.f;
#pragma unroll
  for (int j = 0; j < 32; j++) {
    v[j] = {bf2f(xa[32 * j]), bf2f(xa[D_ + 32 * j])};
    const float g = bf2f(gw[32 * j + t]); ga = fmaf(v[j].x, g, ga); gb = fmaf(v[j].y, g, gb);
  }
#pragma unroll
  for (int o = 16; o; o >>= 1) { ga += __shfl_xor_sync(~0u, ga, o); gb += __shfl_xor_sync(~0u, gb, o); }
  if (t < 2) g_gate[n + 1024 * t] = __fdividef(1.0f, 1.0f + __expf(-(t ? gb : ga)));
  bar_sync(13, 256);
  warp_fft1024_a<false>(v, sm2 + 1024 + w * ROW_BUF, sm2, t);
  FENCE_ASYNC_SMEM();
  mbar_arrive_warp(release_bar);
  fft32<false>(v);
  float ws, wc; sincospif(-(float)n * (1.0f / 1024.0f), &ws, &wc);
  float4* z = (float4*)g_z + ((size_t)(t >> 1) * 1024 + n) * 2 + (t & 1);
#pragma unroll
  for (int j = 0; j < 17; j++) {
    cf q = v[(32 - j) & 31];
    if (j < 16) {
      const cf r = {__shfl_sync(~0u, v[31 - j].x, 32 - t), __shfl_sync(~0u, v[31 - j].y, 32 - t)};
      if (t != 0) q = r;
    }
    const cf a = {v[j].x + q.x, v[j].y - q.y}, b = {v[j].y + q.y, q.x - v[j].x};
    const cf d = cmul({a.x - b.x, a.y - b.y}, wc, ws);
    if (j < 16 || t == 0) z[j * 32768] = make_float4(a.x + b.x, a.y + b.y, d.x, d.y);
  }
}
__device__ __forceinline__ void repack_filter(const unsigned short* ws, int cta, int tid) {
  const int rp = tid & 7;
  for (int cp = tid >> 3; cp < 257; cp += 16) {
    const unsigned short* pr = ws + 2 * rp * 513 + 2 * cp;
    uint32_t o[4];
#pragma unroll
    for (int i = 0; i < 4; i++) { const int k = (i & 1) * 513 + (cp == 256 ? 0 : i >> 1); o[i] = (uint32_t)pr[k] | ((uint32_t)pr[k + W_CHUNK / 2] << 16); }
    *(uint4*)(g_wp + ((size_t)cp * 1024 + cta * 8 + rp) * 4) = make_uint4(o[0], o[1], o[2], o[3]);
  }
}

constexpr int COL_FS = 1060, COL_GROUP = 4 * COL_FS + 2048;
constexpr int COL_SMEM = (1024 + 4 * COL_GROUP) * 8 + 32;

__device__ __forceinline__ void fft_cols(float2* sm2, int cta) {
  const int grp = __shfl_sync(~0u, (int)(threadIdx.x >> 7), 0), tid = threadIdx.x & 127, t = tid >> 2;
  float2* stage = sm2 + 1024 + grp * COL_GROUP;
  float2* buf = stage + (tid & 3) * COL_FS;
  const uint32_t* wsm = (const uint32_t*)(stage + 4 * COL_FS);
  const uint32_t wbar = smem_u32(sm2) + COL_SMEM - 32 + grp * 8;
  if (tid == 0) { mbar_init(wbar, 1); asm volatile("fence.mbarrier_init.release.cluster;" ::: "memory"); }
  row_twiddles(sm2, threadIdx.x, 512);
  for (uint32_t n = 0; ld_acquire(g_ctl + C_P1) < 128; ) { watchdog(n, 1u << 22); __nanosleep(200); }
  __syncthreads();
  int item = cta * 4 + grp;
  if (tid < 32) {
    asm volatile("fence.proxy.async.global;" ::: "memory");
    mbar_expect_e(wbar, 16384); bulk_load_e(smem_u32(wsm), g_wp + (size_t)item * 4096, 16384, wbar);
  }
  delay_cycles(1 + grp * DLY_GRP);
  for (uint32_t ph = 0; item < 257; item += 16, ph ^= 1) {
    float2* zp = g_z + (size_t)item * 4096;
    cf v[32];
#pragma unroll
    for (int j = 0; j < 32; j++) { const float2 a = __ldcg(zp + tid + j * 128); v[j] = {a.x, a.y}; }
#pragma unroll 1
    for (int dir = 0; dir < 2; dir++) {
      fft32<false>(v);
#pragma unroll
      for (int j = 1; j < 32; j++) { const float2 w = sm2[j * 32 + t]; v[j] = cmul(v[j], w.x, w.y); }
      if (tid == 0) asm volatile("cp.async.bulk.wait_group.read 0;" ::: "memory");
      bar_sync(1 + grp, 128);
      if (dir == 1 && tid < 32 && item + 16 < 257) { mbar_expect_e(wbar, 16384); bulk_load_e(smem_u32(wsm), g_wp + (size_t)(item + 16) * 4096, 16384, wbar); }
#pragma unroll
      for (int j = 0; j < 32; j++) buf[j * 33 + t] = make_float2(v[j].x, v[j].y);
      bar_sync(1 + grp, 128);
#pragma unroll
      for (int j = 0; j < 32; j++) { const float2 a = buf[t * 33 + j]; v[j] = {a.x, a.y}; }
      fft32<false>(v);
      if (dir == 0) {
        mbar_wait(wbar, ph);
#pragma unroll
        for (int j = 0; j < 32; j++) {
          const uint32_t ww = wsm[j * 128 + tid];
          const cf r = cmul(v[j], __uint_as_float(ww << 16), __uint_as_float(ww & 0xFFFF0000u));
          v[j] = {r.y, r.x};
        }
      }
    }
#pragma unroll
    for (int j = 0; j < 32; j++) zp[tid + j * 128] = make_float2(v[j].y, v[j].x);
  }
  if (tid == 0) asm volatile("cp.async.bulk.wait_group 0;" ::: "memory");
}

__device__ __forceinline__ void fft_rows_inv(float2* buf, const float2* tw, int n, int t) {
  const float4* z = (const float4*)g_z + ((size_t)(t >> 1) * 1024 + n) * 2 + (t & 1);
  float ws, wc; sincospif((float)n * (1.0f / 1024.0f), &ws, &wc);
  cf v[32], q[17];
#pragma unroll
  for (int j = 0; j < 17; j++) {
    const float4 e = __ldcg(j < 16 ? z + j * 32768 : (const float4*)g_z + ((size_t)256 * 1024 + n) * 2);
    const cf d = cmul({e.z, e.w}, wc, ws);
    cf a = {e.x + d.x, e.y + d.y}, b = {e.x - d.x, e.y - d.y};
    if (j == 16 || (j == 0 && t == 0)) { a.y = 0.f; b.y = 0.f; }
    if (j < 16) v[j] = {a.x - b.y, a.y + b.x};
    q[j] = {a.x + b.y, b.x - a.y};
  }
#pragma unroll
  for (int j = 16; j < 32; j++) {
    v[j] = {__shfl_sync(~0u, q[31 - j].x, 32 - t), __shfl_sync(~0u, q[31 - j].y, 32 - t)};
    if (t == 0) v[j] = q[32 - j];
  }
  warp_fft1024_a<true>(v, buf, tw, t);
  fft32<true>(v);
  const float sc = 0.5f / (2048.0f * 1024.0f);
  __nv_bfloat16* o = g_b + (size_t)n * D_ + t;
#pragma unroll
  for (int j = 0; j < 32; j++) { o[32 * j] = __float2bfloat16(v[j].x * sc); o[1024 * D_ + 32 * j] = __float2bfloat16(v[j].y * sc); }
}

constexpr int NP = NP_, NHV = REG_F == 216 ? 5 : 7, NV = 16 - NHV;
constexpr int XEND = NSEG;
constexpr uint32_t SM_WO = 0, SM_V = 65536, SM_LAND = SM_V + 8192, SM_MEM = SM_LAND + 24576, SM_SP = SM_MEM, SM_SPM = SM_MEM + 5120, SM_OM = SM_MEM + 6144,
                   SM_OX = SM_MEM + 8192, SM_RED = SM_OX + 2048, SM_XCH = SM_RED + 1024, SM_SUM = SM_XCH + 4096, SM_VM = SM_SUM + 128, SM_TAB = SM_VM + 2048, SM_TRACE = SM_TAB + 2048,
                   ST_WG = (32 - NP + NV) * 2048,
                   SM_XT = 2 * ST_WG > 120 * 1024 ? 2 * ST_WG : 120 * 1024, SM_POOL = SM_XT + 32768, SM_HV = SM_POOL + 2 * NP * 2048,
                   SM_BAR = SM_HV + 2 * NHV * 2048, SM_SEL = SM_BAR + 320, CHAIN_SMEM = SM_SEL + 544;
constexpr uint32_t SM_WST = 76 * 1024;
static_assert(NP % 4 == 0 && SM_TRACE + 4096 <= SM_XT, "shared memory layout");
static_assert(CHAIN_SMEM <= 232448 && COL_SMEM <= CHAIN_SMEM && (1024 + 8 * ROW_BUF) * 8 + 2048 <= SM_WST && SM_WST + 2 * W_CHUNK <= SM_XT, "shared memory budget");
enum { B_WFULL = 0, B_WREAD = 2, B_WOFULL, B_XFULL, B_XEMPTY, B_E1TRIG, B_E2TRIG, B_PVDONE, B_PUB, B_SC, B_MEM, B_SPFREE,
       B_LAND, B_LFREE, B_DONE, B_SEL, B_PROBE, B_FILT, B_FREE, B_P1, B_ROWS, B_VFULL, B_END };
static_assert(B_END * 8 <= 320, "barriers");

struct ChainCtx { char* mail; uint32_t sb, sel; int r, h, a, b, j, m, w, lane; };
#define BAR(i) (c.sb + SM_BAR + 8 * (i))

__device__ __forceinline__ uint32_t tile_off(int line, int lane) {
  return line * 128 + (((lane & 3) ^ line) << 5) + (lane >> 2) * 4;
}
__device__ __forceinline__ uint32_t read_off(int lane) {
  const int n = lane >> 2, jj = lane & 3, l = 2 * (jj >> 1) + (n & 1);
  return l * 128 + (((n >> 1) ^ l) << 5) + (jj & 1) * 16;
}
__device__ __forceinline__ uint32_t frag_off(int w, int lane) {
  const int mi = lane >> 3, r = lane & 7;
  return ((mi >> 1) * 8 + r) * 128 + (((2 * w + (mi & 1)) ^ r) << 4);
}
__device__ __forceinline__ uint32_t land_off(int w, int lane) { return w * 512 + ((lane ^ (((lane >> 4) | ((w & 1) << 1)) << 1)) << 4); }
__device__ __forceinline__ uint32_t tagged(uint32_t v, uint32_t tag) { return (v & ~1u) | tag; }
__device__ __forceinline__ void mma_a(float (&d)[4], const uint32_t (&a)[4], uint32_t b0, uint32_t b1) { mma16816(d, a[0], a[1], a[2], a[3], b0, b1); }
__device__ __forceinline__ void mma_q(float (&d)[4], const uint4& a, uint32_t b0, uint32_t b1) { mma16816(d, a.x, a.y, a.z, a.w, b0, b1); }
__device__ __forceinline__ uint4 add4(uint4 a, uint4 b) {
  return make_uint4(add_bf16x2(a.x, b.x), add_bf16x2(a.y, b.y), add_bf16x2(a.z, b.z), add_bf16x2(a.w, b.w));
}
__device__ __forceinline__ void mbar_arrive_both(uint32_t bar, int peer) {
  __syncwarp();
  asm volatile("{ .reg .pred p; .reg .u32 a; mapa.shared::cluster.u32 a, %0, %1; elect.sync _|p, 0xffffffff;\n"
               "@p mbarrier.arrive.shared::cta.b64 _, [%0]; @p mbarrier.arrive.shared::cluster.b64 _, [a]; }" :: "r"(bar), "r"(peer) : "memory");
}

__device__ __forceinline__ int lane_id() {
  int l; asm volatile("{ .reg .u32 t; mov.u32 t, %%laneid; shfl.sync.idx.b32 %0, t, t, 31, 0xffffffff; }" : "=r"(l)); return l;
}
__device__ __forceinline__ uint32_t tid_now() { uint32_t t; asm volatile("mov.u32 %0, %%tid.x;" : "=r"(t)); return t; }
enum { NB_ATT = 1, NB_OM = 2, NB_VM = 3, NB_XCH = 4, NB_MEM = 8, NB_HELP = 12 };
__device__ __forceinline__ uint32_t dep(uint32_t a, uint32_t v, uint32_t z) { uint32_t r; asm("shf.l.wrap.b32 %0, %2, %1, %3;" : "=r"(r) : "r"(a), "r"(v), "r"(z)); return r; }
__device__ __forceinline__ uint32_t vary(uint32_t a, int s, uint32_t z) { return dep(a, 0, z + 32 * s); }
__device__ __forceinline__ char* mk_ptr(uint32_t lo, uint32_t hi) { uint64_t r; asm("mov.b64 %0, {%1, %2};" : "=l"(r) : "r"(lo), "r"(hi)); return (char*)r; }
__device__ __forceinline__ void lds_frag(uint32_t (&r)[4], uint32_t a) {
  asm volatile("ld.shared.v4.u32 {%0,%1,%2,%3}, [%4];" : "=r"(r[0]), "=r"(r[1]), "=r"(r[2]), "=r"(r[3]) : "r"(a) : "memory");
}
__device__ __forceinline__ uint32_t stale2(uint32_t a, uint32_t b, uint32_t t) { uint32_t r; asm("lop3.b32 %0, %1, %2, %3, 0x7e;" : "=r"(r) : "r"(a), "r"(b), "r"(t)); return r; }
__device__ __forceinline__ uint32_t stale1(uint32_t acc, uint32_t a, uint32_t t) { uint32_t r; asm("lop3.b32 %0, %1, %2, %3, 0xf6;" : "=r"(r) : "r"(acc), "r"(a), "r"(t)); return r; }
__device__ __forceinline__ bool all_clear(uint32_t x, uint32_t m) {
  uint32_t r;
  asm volatile("{ .reg .pred p; .reg .u32 t; and.b32 t, %1, %2; setp.eq.u32 p, t, 0; vote.sync.all.pred p, p, 0xffffffff; selp.u32 %0, 1, 0, p; }" : "=r"(r) : "r"(x), "r"(m));
  return r;
}
__device__ __forceinline__ bool arrive_if_all(bool ok, int id, int n) {
  uint32_t r;
  asm volatile("{ .reg .pred p, q; setp.ne.u32 p, %1, 0; vote.sync.all.pred q, p, 0xffffffff; @q bar.arrive %2, %3; selp.u32 %0, 1, 0, q; }"
               : "=r"(r) : "r"((uint32_t)ok), "r"(id), "r"(n) : "memory");
  return r;
}
__device__ __forceinline__ bool arrive_if_clear(uint32_t x, uint32_t m, int id, int n) {
  uint32_t r;
  asm volatile("{ .reg .pred p; .reg .u32 t; and.b32 t, %1, %2; setp.eq.u32 p, t, 0; vote.sync.all.pred p, p, 0xffffffff; @p bar.arrive %3, %4; selp.u32 %0, 1, 0, p; }"
               : "=r"(r) : "r"(x), "r"(m), "r"(id), "r"(n) : "memory");
  return r;
}
__device__ __forceinline__ void touch(const void* p, uint32_t z) {
  asm volatile("{ .reg .pred p; setp.eq.u32 p, %1, 0x7fff0000; @p prefetch.global.L2 [%0]; }" :: "l"(p), "r"(z) : "memory");
}

__device__ __forceinline__ uint64_t desc_x(uint32_t lo, int k) {
  uint64_t d; asm("mov.b64 %0, {%1, %2};" : "=l"(d) : "r"(lo + (k >> 2) * 64 + (k & 3) * 2), "r"(0x40000200)); return d;
}
template<int K0, int K1> __device__ __forceinline__ void issue_qk(float (&xa)[16], const uint32_t (&wt)[16][4], uint32_t lo) {
  WG_FENCE();
#pragma unroll
  for (int k = K0; k < K1; k++) {
    if (k >= EXP_NWG) continue;
    if (k == 0) wgmma_rs_n32<true>(xa, wt[0], desc_x(lo, 0));
    else wgmma_rs_n32<false>(xa, wt[k], desc_x(lo, k));
  }
  WG_COMMIT();
}
__host__ __device__ constexpr int v_order(int i) { return SSPOS == 0 ? i : SSPOS == 2 ? (i + NV) % 16 : NHV == 5 ? (i % 3 == 2 ? NV + i / 3 : i - i / 3) : (i == 15 ? NV - 1 : i % 2 ? NV + i / 2 : i / 2); }
__device__ __forceinline__ void issue_v(float (&xa)[16], const uint32_t (&wv)[16][4], uint32_t lo, uint32_t la) {
  WG_FENCE();
#pragma unroll
  for (int i = 0; i < EXP_NWG; i++) {
    const int k = v_order(i);
    const uint64_t b = desc_x(lo, k);
    if (k < NV) { if (i == 0) wgmma_rs_n32<true>(xa, wv[k], b); else wgmma_rs_n32<false>(xa, wv[k], b); }
    else        { if (i == 0) wgmma_ss_n32_ta<true>(xa, desc128(la + (k - NV) * 128), b); else wgmma_ss_n32_ta<false>(xa, desc128(la + (k - NV) * 128), b); }
  }
  WG_COMMIT();
}
template<bool ISV> __device__ __forceinline__ void park_own(uint32_t (&q)[4], float (&xa)[16], uint32_t dst, int slot, uint32_t z) {
  uint32_t p[8];
#pragma unroll
  for (int i = 0; i < 16; i++) asm volatile("" : "+f"(xa[i]) :: "memory");
#pragma unroll
  for (int i = 0; i < 2; i++) {
    const float* k = xa + 8 * i;
    if (ISV) { p[4 * i] = pack_bf16(k[0], k[1]); p[4 * i + 1] = pack_bf16(k[2], k[3]); p[4 * i + 2] = pack_bf16(k[4], k[5]); p[4 * i + 3] = pack_bf16(k[6], k[7]); }
    else     { p[4 * i] = pack_bf16(k[0], k[2]); p[4 * i + 1] = pack_bf16(k[4], k[6]); p[4 * i + 2] = pack_bf16(k[1], k[3]); p[4 * i + 3] = pack_bf16(k[5], k[7]); }
  }
  sts128(dep(dep(dst, p[4] ^ p[5] ^ p[6], z), p[7], z) + slot * 8192, make_uint4(p[0], p[1], p[2], p[3]));
#pragma unroll
  for (int i = 0; i < 4; i++) q[i] = p[4 + i];
}
__device__ __forceinline__ void park_peer(const uint32_t (&q)[4], uint32_t dst, int slot, const ChainCtx& c) {
  const uint32_t bar = BAR(B_LAND);
  if (EXP_PEER) st_async4(mapa(dst + slot * 8192, c.b ^ 1), q[0], q[1], q[2], q[3], mapa(bar, c.b ^ 1));
  else touch((void*)(uintptr_t)(q[0] ^ q[1] ^ q[2] ^ q[3]), c.sb);
  mbar_arrive_warp(bar);
}
__device__ __forceinline__ uint32_t put_tag(uint32_t v, uint32_t bit, uint32_t t) {
  uint32_t r; asm("lop3.b32 %0, %1, %2, %3, 0xb8;" : "=r"(r) : "r"(v), "r"(bit), "r"(t)); return r;
}
__device__ __forceinline__ void mem_proj(const uint32_t (&wa)[16][4], const uint32_t (&wb)[16][4], uint32_t (&wv)[16][4], uint32_t (&af)[16][4],
                                         uint32_t& wo, const char*& pa, uint32_t tab, uint32_t t16, uint32_t pk, const ChainCtx& c, int s) {
  const uint32_t mp = t16 & ~0x600u, id = NB_MEM + (t16 >> 11);
  uint32_t r[8][4];
  float la[4][4] = {}, lg[NLAG][4] = {}, lv[4][4] = {};
  auto lead = [&](int k) { mma_a(la[k & 3], wa[k], r[k >> 1][2 * (k & 1)], r[k >> 1][2 * (k & 1) + 1]); };
  auto lag = [&](int k) { mma_a(lg[k % NLAG], wb[k], r[k >> 1][2 * (k & 1)], r[k >> 1][2 * (k & 1) + 1]); };
  auto sum = [](const float (&d)[4][4], int i) { return (d[0][i] + d[1][i]) + (d[2][i] + d[3][i]); };
  bar_sync(id, 160);
  TR(s, 0);
#pragma unroll
  for (int i = 0; i < 4; i++) ldsm4t(r[i], mp + (c.sb + SM_MEM + i * 512));
  const uint4 tq = lds128(tab);
  bar_sync(id + 2, 160);
#pragma unroll
  for (int k = 0; k < 8; k++) lead(k);
  const uint32_t ta = tq.x | ((pk >> 16) & 511), tb = tq.z ^ ((pk >> 16) & 511);
  char* dst = mk_ptr(ta, tq.y);
  char* dst2 = mk_ptr(tb, tq.w);
  const uint32_t mp1 = dep(mp, __float_as_uint(la[C1_AT][0]) ^ ta ^ tb, c.sb);
#pragma unroll
  for (int i = 4; i < 8; i++) ldsm4t(r[i], mp1 + (c.sb + SM_MEM + 2048 + i * 512));
  const uint32_t hv = pk & 0xFFFF;
#pragma unroll
  for (int k = NV; k < NV + HV_E; k++) ldsm4t(wv[k], dep(hv, r[HV_R][0], c.sb) + (c.sb + SM_HV + (k - NV) * 2048));
#pragma unroll
  for (int k = 0; k < 8; k++) lag(k);
#pragma unroll
  for (int k = 8; k < 16; k++) lead(k);
  sts128((HV_E ? dep(t16, wv[NV][0] ^ wv[NV + HV_E / 2][1] ^ wv[NV + HV_E - (HV_E > 0)][2], c.sb) : t16) + (c.sb + SM_XCH), make_uint4(__float_as_uint(sum(la, 0)), __float_as_uint(sum(la, 1)), __float_as_uint(sum(la, 2)), __float_as_uint(sum(la, 3))));
  bar_sync(NB_XCH | ((t16 >> 9) & 3), 64);
  const uint4 o = lds128((t16 ^ 2048) + (c.sb + SM_XCH));
#pragma unroll
  for (int k = 8; k < 16; k++) lag(k);
  float t[4];
#pragma unroll
  for (int i = 0; i < 4; i++) {
    const float oi = __uint_as_float(i == 0 ? o.x : i == 1 ? o.y : i == 2 ? o.z : o.w);
    t[i] = NLAG == 4 ? (((lg[0][i] + lg[1][i]) + lg[2 % NLAG][i]) + lg[3 % NLAG][i]) + oi : NLAG == 3 ? (lg[1][i] + lg[2 % NLAG][i]) + (lg[0][i] + oi) : (lg[0][i] + oi) + lg[1][i];
  }
  st_pub(dst, put_tag(pack_bf16(t[0], t[2]), pk >> 31, s >> 1));
  st_pub(dst2, put_tag(pack_bf16(t[1], t[3]), pk >> 31, s >> 1));
  mbar_arrive_warp(BAR(B_E1TRIG));
  TR(s, 1);
  sched_fence(c.sb);
  const uint4 tv = lds128(tab + 16);
#pragma unroll
  for (int k = NV + HV_E; k < 16; k++) ldsm4t(wv[k], (k < NV + HV_E + HV_D ? hv : dep(hv, k == NV + HV_E + HV_D ? wv[k - HV_D][0] ^ tv.x : wv[k - HV_D][0], c.sb)) + (c.sb + SM_HV + (k - NV) * 2048));
  wo = (hv & 2047) | ((t16 & 2048) << 3);
  const uint32_t l8 = (t16 >> 1) & 255;
  char* dv = mk_ptr(tv.x | l8, tv.y);
  pa = mk_ptr(tv.z | l8, tv.w);
#pragma unroll
  for (int f = 0; f < WO_0; f++) ldsm4t(af[f], dep(wo, f < WO_D ? wv[16 - WO_D + f][0] : af[f < WO_D ? 0 : f - WO_D][0], c.sb) + (c.sb + SM_WO + f * 2048));
#pragma unroll
  for (int k = 0; k < 16; k++) mma_a(lv[k & 3], wv[k], r[k >> 1][2 * (k & 1)], r[k >> 1][2 * (k & 1) + 1]);
  st_pub2(dv, put_tag(pack_bf16(sum(lv, 0), sum(lv, 1)), (~t16 >> 4) & 1, s >> 1), pack_bf16(sum(lv, 2), sum(lv, 3)));
  TR(s, 2);
}
__device__ __forceinline__ uint32_t max_bf16x2(uint32_t a, uint32_t b) { uint32_t r; asm("max.bf16x2 %0, %1, %2;" : "=r"(r) : "r"(a), "r"(b)); return r; }
constexpr float SCL = 0.08838834764831845f * 1.4426950408889634f;
__device__ __forceinline__ uint32_t max5(const uint32_t (&sc)[5]) { return max_bf16x2(max_bf16x2(max_bf16x2(max_bf16x2(sc[0], sc[1]), sc[2]), sc[3]), sc[4]); }
__device__ __forceinline__ float row_off(uint32_t m) {
  const uint32_t m1 = __shfl_xor_sync(~0u, m, 1), m2 = __shfl_xor_sync(~0u, m, 2), m3 = __shfl_xor_sync(~0u, m, 3);
  const uint32_t mm = max_bf16x2(max_bf16x2(max_bf16x2(m, m1), m2), m3);
  return -SCL * fmaxf(__uint_as_float(mm << 16), __uint_as_float(mm & 0xFFFF0000u));
}
__device__ __forceinline__ void unpack(float (&f)[10], const uint32_t (&sc)[5]) {
#pragma unroll
  for (int i = 0; i < 5; i++) {
    asm volatile("shl.b32 %0, %1, 16;" : "=f"(f[2 * i]) : "r"(sc[i]));
    asm volatile("and.b32 %0, %1, 0xffff0000;" : "=f"(f[2 * i + 1]) : "r"(sc[i]));
  }
}
__device__ __forceinline__ uint32_t exp_pair(const float (&f)[10], int i, float off) {
  return pack_bf16(ex2(fmaf(f[2 * i], SCL, off)), ex2(fmaf(f[2 * i + 1], SCL, off)));
}
template<bool SPLIT> __device__ __forceinline__ void scores_x(float (&a)[2][4], const uint4 (&kf)[4], const uint4& q, uint32_t z) {
#pragma unroll
  for (int t = 0; t < 2; t++) { a[t][0] = a[t][1] = a[t][2] = a[t][3] = 0.f; }
  mma_q(a[0], kf[0], q.x, q.y); mma_q(a[1], kf[2], q.x, q.y);
  if (SPLIT) sched_fence(z);
  mma_q(a[0], kf[1], q.z, q.w); mma_q(a[1], kf[3], q.z, q.w);
}
__device__ __forceinline__ uint32_t scores_m(const uint4& q, const uint4& k) {
  float a[4] = {}, b[4] = {};
  mma_q(a, q, k.x, k.z); mma_q(b, q, k.y, k.w);
  return pack_bf16(a[0] + b[2], a[1] + b[3]);
}
__device__ __forceinline__ void store_scores(const float (&a)[2][4], uint32_t dst) {
  stsm4<true>(dst, pack_bf16(a[0][0], a[0][1]), pack_bf16(a[0][2], a[0][3]), pack_bf16(a[1][0], a[1][1]), pack_bf16(a[1][2], a[1][3]));
}
__device__ __forceinline__ uint32_t sum4(uint32_t a, uint32_t b, uint32_t d, uint32_t e) { return add_bf16x2(add_bf16x2(a, b), add_bf16x2(d, e)); }
__device__ __forceinline__ void load_scores(uint32_t (&sc)[5], uint32_t ax, uint32_t am) {
  uint4 p[4];
#pragma unroll
  for (int i = 0; i < 4; i++) p[i] = lds128(ax + i * 1280);
  const uint2 m0 = lds64(am), m1 = lds64(am + 256);
  const uint4 t = add4(add4(add4(p[0], p[1]), p[2]), p[3]);
  sc[1] = t.x; sc[2] = t.y; sc[3] = t.z; sc[4] = t.w;
  sc[0] = sum4(m0.x, m0.y, m1.x, m1.y);
}
constexpr uint32_t ONES = 0x3F803F80u;
__device__ __forceinline__ float pv(float (&o)[2][4], const uint32_t (&p)[5], const uint4 (&vf)[4], const uint4& vm) {
  float a[4] = {}, b[4] = {};
#pragma unroll
  for (int t = 0; t < 2; t++) { o[t][0] = o[t][1] = o[t][2] = o[t][3] = 0.f; }
  mma_q(o[0], vf[0], p[1], p[2]); mma_q(o[1], vf[2], p[1], p[2]);
  mma_q(o[0], vf[1], p[3], p[4]); mma_q(o[1], vf[3], p[3], p[4]);
  mma16816(a, p[1], p[2], p[3], p[4], ONES, ONES);
  mma1688(o[0], vm.x, vm.y, p[0]); mma1688(o[1], vm.z, vm.w, p[0]);
  mma1688(b, p[0], ONES, ONES);
  return (a[0] + a[2]) + b[0];
}
constexpr uint32_t POLL_LIMIT = 1u << 21;

__global__ void __cluster_dims__(2, 1, 1) __launch_bounds__(512, 1)
chain_kernel(const __grid_constant__ CUtensorMap tq, const __grid_constant__ CUtensorMap tk, const __grid_constant__ CUtensorMap tv,
             const __grid_constant__ CUtensorMap tv16, const __grid_constant__ CUtensorMap to, const __grid_constant__ CUtensorMap tx,
             const __nv_bfloat16* __restrict__ mem0, char* __restrict__ mail, const __nv_bfloat16* __restrict__ x,
             const __nv_bfloat16* __restrict__ gw, const char* __restrict__ wr, const char* __restrict__ wi) {
  extern __shared__ __align__(1024) unsigned char smraw[];
  pdl_launch();
  if (threadIdx.x == 0) TL(0);
  if (blockIdx.x >= 128) {
    if (blockIdx.x == 128) g_ctl[C_ROWS + threadIdx.x] = 0;
    fft_cols((float2*)smraw, blockIdx.x - 128);
    if ((threadIdx.x & 127) == 0) TL(7);
    return;
  }
  ChainCtx c;
  c.sb = __shfl_sync(~0u, smem_u32(smraw), 0);
  c.mail = mail; c.sel = 0; c.r = blockIdx.x;
  c.h = c.r >> 2; c.a = (c.r >> 1) & 1; c.b = c.r & 1; c.j = c.r & 3;
  c.m = __shfl_sync(~0u, (int)(threadIdx.x >> 7), 0); c.w = __shfl_sync(~0u, (int)((threadIdx.x >> 5) & 3), 0);
  if (threadIdx.x < B_END) {
    const int i = threadIdx.x;
    const uint32_t n = i == B_LAND ? 25 : (i == B_FREE || i == B_P1 || i == B_DONE) ? 12 :
                       (i == B_WREAD || i == B_XEMPTY || i == B_E1TRIG || i == B_E2TRIG || i == B_LFREE || i == B_PROBE) ? 8 :
                       (i == B_PVDONE || i == B_PUB || i == B_SC || i == B_MEM || i == B_SPFREE) ? 4 : 1;
    mbar_init(BAR(i), n);
    asm volatile("fence.mbarrier_init.release.cluster;" ::: "memory");
  }
  __syncthreads();
  asm volatile("barrier.cluster.arrive.relaxed.aligned;" ::: "memory");

  if (c.m == 3) {
    asm volatile("setmaxnreg.dec.sync.aligned.u32 %0;" :: "n"(REG_H));
    c.lane = lane_id();
    if (c.sb & 1023) asm volatile("trap;");
    const int col = c.h * 128 + c.a * 64;
    if (c.w == 0) {
      mbar_expect_e(BAR(B_ROWS), 32768 + 2048);
      for (int i = 0; i < 16; i++) bulk_load_e(c.sb + (1024 + (i >> 1) * ROW_BUF) * 8 + (i & 1) * 2048, x + (size_t)(c.r * 8 + (i >> 1) + (i & 1) * 1024) * D_, 2048, BAR(B_ROWS));
      bulk_load_e(c.sb + SM_WST - 2048, gw, 2048, BAR(B_ROWS));
      mbar_expect_e(BAR(B_FILT), 2 * W_CHUNK);
      bulk_load_e(c.sb + SM_WST, wr + (size_t)c.r * W_CHUNK, W_CHUNK, BAR(B_FILT));
      bulk_load_e(c.sb + SM_WST + W_CHUNK, wi + (size_t)c.r * W_CHUNK, W_CHUNK, BAR(B_FILT));
      mbar_expect_e(BAR(B_XFULL), 32768);
      for (int i = 0; i < 2; i++) tma4d_e(c.sb + SM_XT + i * 16384, &tx, c.b * 8, 2 * (c.b ^ i), BAR(B_XFULL));
      for (int m = 0; m < 2; m++) {
        const int row = c.b * 512 + m * 256;
        mbar_expect_e(BAR(B_WFULL + m), 48 * 2048);
        for (int i = 0; i < NP / 4; i++) tma2d_e(c.sb + SM_POOL + m * NP * 2048 + i * 8192, m ? &tq : &tk, col, row + i * 64, BAR(B_WFULL + m));
        for (int i = NV; i < 12; i++) tma2d_e(c.sb + SM_HV + (m * NHV + i - NV) * 2048, &tv16, col, row + i * 16, BAR(B_WFULL + m));
        tma2d_e(c.sb + SM_HV + (m * NHV + 12 - NV) * 2048, &tv, col, row + 192, BAR(B_WFULL + m));
      }
      for (int m = 0; m < 2; m++) {
        const int row = c.b * 512 + m * 256;
        for (int i = 0; i < 4; i++) prefetch2d_e(m ? &tk : &tq, col, row + i * 64);
        for (int i = NP / 4; i < 4; i++) prefetch2d_e(m ? &tq : &tk, col, row + i * 64);
        for (int i = 0; i < 3; i++) prefetch2d_e(&tv, col, row + i * 64);
      }
      for (int i = 0; i < 4; i++) prefetch2d_e(&to, c.j * 256 + i * 64, c.h * 128);
    }
    auto dst_x = [&](int e, int w) {
      const uint32_t g2 = 2 * c.a + (w >> 1), u = w & 1;
      return M_KVQ + c.h * 24576 + (e == 0 ? 8192 + u * 4096 + g2 * 512 + c.b * 32 : e == 1 ? g2 * 2048 + (2 * c.b + u) * 512 : 16384 + (2 * c.b + u) * 2048 + g2 * 512);
    };
    auto v_off = [](int ln) { return (ln >> 4) * 2048 + (ln & 14) * 32 + (ln & 1) * 16; };
    {
      const uint4 z = make_uint4(SENT, SENT, SENT, SENT);
      for (int i = 0; i < 8; i++) *(uint4*)(c.mail + (uint32_t)(M_PAIR + ((i >> 2) * 128 + c.r) * 8192 + ((i & 3) * 4 + c.w) * 512 + c.lane * 16)) = z;
      for (int i = 0; i < 2; i++) *(uint32_t*)(c.mail + (uint32_t)(M_E3 + (c.w * 4 + (c.r >> 5)) * 8192 + i * 4096 + (c.r & 31) * 128 + c.lane * 4)) = SENT;
      for (int i = 0; i < NSLOT; i++) {
        *(uint4*)(c.mail + (uint32_t)(dst_x(1, c.w) + i * 32 * 24576 + c.lane * 16)) = z;
        *(uint4*)(c.mail + (uint32_t)(dst_x(2, c.w) + i * 32 * 24576 + c.lane * 16)) = z;
        *(uint4*)(c.mail + (uint32_t)(dst_x(0, c.w) + i * 32 * 24576 + v_off(c.lane))) = z;
      }
      mbar_arrive_warp(BAR(B_PROBE));
    }
    mbar_wait(BAR(B_FILT), 0);
    repack_filter((const unsigned short*)(smraw + SM_WST), c.r, c.w * 32 + c.lane);
    mbar_arrive_warp(BAR(B_FREE));
    mbar_arrive_warp(BAR(B_P1));
    if (c.w == 0) {
      mbar_wait(BAR(B_FREE), 0);
      if (c.lane == 0) TL(2);
      __syncwarp();
      for (int m = 0; m < 2; m++) {
        const int row = c.b * 512 + m * 256;
        const uint32_t st = c.sb + m * ST_WG, sv = st + (32 - NP) * 2048;
        for (int i = 0; i < 4; i++) tma2d_e(st + i * 8192, m ? &tk : &tq, col, row + i * 64, BAR(B_WFULL + m));
        for (int i = NP / 4; i < 4; i++) tma2d_e(st + (4 + i - NP / 4) * 8192, m ? &tq : &tk, col, row + i * 64, BAR(B_WFULL + m));
        for (int i = 0; i < 2; i++) tma2d_e(sv + i * 8192, &tv, col, row + i * 64, BAR(B_WFULL + m));
        for (int i = 8; i < NV; i++) tma2d_e(sv + i * 2048, &tv16, col, row + i * 16, BAR(B_WFULL + m));
      }
    } else if (c.w == 1) {
      mbar_wait(BAR(B_P1), 0);
      asm volatile("fence.acq_rel.gpu;" ::: "memory");
      asm volatile("{ .reg .pred p; elect.sync _|p, 0xffffffff; @p red.relaxed.gpu.global.add.u32 [%0], 1; }" :: "l"(g_ctl + C_P1) : "memory");
    }
    asm volatile("barrier.cluster.wait;" ::: "memory");
    mbar_wait(BAR(B_WREAD), 0);
    mbar_arrive_both(BAR(B_LFREE), c.b ^ 1);
    {
      const int ln = tid_now() & 31, e = (ln >> 2) & 3, w = (tid_now() >> 5) & 3;
      const uintptr_t ad = (uintptr_t)(c.mail + (uint32_t)(dst_x(e, w) + (ln & 3) * 32 * 24576));
      sts64(c.sb + SM_TAB + 1536 + (ln & 3) * 128 + w * 32 + e * 8, (uint32_t)ad, (uint32_t)(ad >> 32));
      __syncwarp();
    }
    if (c.w == 0) {
      mbar_expect_e(BAR(B_WOFULL), 65536);
      for (int i = 0; i < 4; i++) tma2d_e(c.sb + SM_WO + i * 16384, &to, c.j * 256 + i * 64, c.h * 128, BAR(B_WOFULL));
    }
    for (int s = -1; s < NSEG; s++) {
      if (s == 0) {
        mbar_wait(BAR(B_SEL), 0);
        const int ln = tid_now() & 31, sl = ln & 3, e = (ln >> 2) & 3;
        const uint32_t t = c.sb + SM_SEL, own = lds32(t + c.r * 4);
        uint32_t votes = 0;
        for (int i = 0; i < 7; i++) { const uint32_t v = lds32(t + (sl * 4 + 2 * c.b + (c.w >> 1) + 16 * i) * 4); votes += ((v >> 2) ^ (v >> 3)) & 1; }
        const uint32_t off = e == 0 ? M_PAIR + ((~sl & 1) * 128 + c.r) * 8192 + ((own >> (~sl & 1)) & 1) * 4096 + c.w * 1024
                           : e == 2 ? M_E3 + (sl * 4 + c.b * 2 + (c.w >> 1)) * 8192 + (((votes >= 4 ? 1u : 0u) ^ (own >> 3)) & 1) * 4096 + (c.w & 1) * 2048
                           : M_E3 + ((sl ^ (e & 2)) * 4 + (c.r >> 5)) * 8192 + (c.w & 1) * 4096 + (c.r & 31) * 128;
        const uintptr_t ad = (uintptr_t)(c.mail + off);
        sts64(c.sb + SM_TAB + 1024 + sl * 128 + c.w * 32 + e * 8, (uint32_t)ad, (uint32_t)(ad >> 32));
        {
          const int i = tid_now() & 127, e = i & 7, w = (i >> 3) & 3, m = (i >> 5) & 1, sl = i >> 6;
          const int cta = e < 2 ? c.r & ~1 : e == 2 ? c.r | 1 : e == 3 ? c.h * 4 + 2 * m + 1 : c.j * 32 + m * 8 + 2 * w + (e & 2) * 8 + (e & 1);
          const uint32_t off = e < 2 ? c.b * 2048 + m * 1024 + (w >> 1) * 512 + e * 160 : e == 2 ? c.b * 2048 + m * 1024 + w * 256 : e == 3 ? w * 256 : c.h * 128;
          const uintptr_t ad = (uintptr_t)(c.mail + (uint32_t)(M_PAIR + (sl * 128 + cta) * 8192 + (((lds32(t + cta * 4) >> sl) ^ (e < 4)) & 1) * 4096 + off));
          sts64(c.sb + SM_TAB + i * 8, (uint32_t)ad, (uint32_t)(ad >> 32));
        }
        mbar_wait(BAR(B_WOFULL), 0);
        bar_sync(NB_HELP, 128);
      }
      if (s >= 0) {
        const uint32_t tab = c.sb + SM_TAB + 1024 + (s & 3) * 128 + c.w * 32;
        uint32_t t0;
        if (s > 0) {
          const uint32_t ln = tid_now() & 31;
          const uint4 ta = lds128(tab);
          const char* src = mk_ptr(ta.x | ln * 4, ta.y);
          char* dst = mk_ptr(ta.z | ln * 4, ta.w);
          const uint32_t tg = (s - 1) >> 1, chk = (ln & 3) ? 0u : 1u, red = ln * (RED_L == 3 ? 4 : 8);
          touch(src, dep(c.sb, chk, c.sb)); touch(dst, dep(c.sb, red, c.sb));
          mbar_wait(BAR(B_E2TRIG), (s - 1) & 1);
          TR(s, 0);
          if (ANCH2) delay_until(lds32(c.sb + SM_SUM + 64) + DLY_E2); else delay_cycles(DLY_E2);
          uint32_t n = 0;
          while (true) {
            uint32_t v[8];
#pragma unroll
            for (int i = 0; i < 8; i++) v[i] = ld_poll1(src + i * 128);
            if (E2_F) sched_fence(c.sb);
            const uint32_t bad = RED_T ? (stale2(v[0], v[1], tg) | stale2(v[2], v[3], tg) | stale2(v[4], v[5], tg)) | stale2(v[6], v[7], tg)
                                       : stale1(stale1(stale2(v[0], v[1], tg), v[2], tg), v[3], tg) | stale1(stale1(stale2(v[4], v[5], tg), v[6], tg), v[7], tg);
            const bool ok = all_clear(bad, chk);
#pragma unroll
            for (int l = 0; l < RED_L; l++)
#pragma unroll
              for (int i = 0; i < (4 >> l); i++) v[i] = add_bf16x2(v[2 * i], v[2 * i + 1]);
            if (RED_L == 3) sts32(red + (c.sb + SM_RED + c.w * 128), v[0]);
            else {
              float lo[8], hi[8];
#pragma unroll
              for (int i = 0; i < (8 >> RED_L); i++) { lo[i] = __uint_as_float(v[i] << 16); hi[i] = __uint_as_float(v[i] & 0xFFFF0000u); }
#pragma unroll
              for (int l = RED_L; l < 3; l++)
#pragma unroll
                for (int i = 0; i < (4 >> l); i++) { lo[i] = lo[2 * i] + lo[2 * i + 1]; hi[i] = hi[2 * i] + hi[2 * i + 1]; }
              sts64(red + (c.sb + SM_RED + c.w * 256), __float_as_uint(lo[0]), __float_as_uint(hi[0]));
            }
            if (ok) break;
            n++; CNT(0);
          }
          bar_sync(NB_HELP, 128);
          const uint32_t rd = red + (c.sb + SM_RED);
          if (!RED_P || c.w < 2) {
            if (RED_L == 3) st_pub_if(dst, sum4(lds32(rd), lds32(rd + 128), lds32(rd + 256), lds32(rd + 384)), c.w < 2);
            else {
              const uint2 p0 = lds64(rd), p1 = lds64(rd + 256), p2 = lds64(rd + 512), p3 = lds64(rd + 768);
              st_pub_if(dst, pack_bf16((__uint_as_float(p0.x) + __uint_as_float(p1.x)) + (__uint_as_float(p2.x) + __uint_as_float(p3.x)),
                                       (__uint_as_float(p0.y) + __uint_as_float(p1.y)) + (__uint_as_float(p2.y) + __uint_as_float(p3.y))), c.w < 2);
            }
          }
          t0 = clock_lo();
          mbar_arrive_warp(BAR(B_PUB));
          TRV(s, 15, n);
          mbar_wait(BAR(B_SPFREE), (s - 1) & 1);
        } else t0 = clock_lo();
        TRV(s, 1, t0);
        {
          const uint32_t l16 = (tid_now() & 31) * 16, dst = l16 + (c.sb + SM_MEM + (c.w & 1) * 4096 + (c.w >> 1) * 2048);
          const uint2 tb = lds64(tab + 16);
          const char* src = mk_ptr(tb.x | l16, tb.y);
          touch(src, dep(c.sb, dst, c.sb));
          delay_until(t0 + (DLY_E3 + (c.w & 1) * DLY_E3B));
          uint32_t n = 0;
          while (true) {
            uint4 v[4];
#pragma unroll
            for (int i = 0; i < 4; i++) v[i] = ld_poll(src + i * 512);
#pragma unroll
            for (int i = 0; i < 4; i++) sts128(dst + i * 512, v[i]);
            if (arrive_if_all(max(max(v[0].x, v[1].x), max(v[2].x, v[3].x)) != SENT, NB_MEM + (c.w & 1) * 2 + (c.w >> 1), 160)) break;
            n++; CNT(1);
          }
          mbar_arrive_warp(BAR(B_MEM));
          TR(s, 2); TRV(s, 14, n);
        }
        bar_sync(NB_HELP, 128);
        const uint2 tr = lds64(tab + 24);
        st_pub_if(mk_ptr(tr.x | (tid_now() & 31) * 4, tr.y), SENT, c.w >= 2);
        if (s == 1) CLK(1); if (s == 8) CLK(2); if (s == 56) CLK(3);
        if (c.w == 2 && s == 15) TRSYNC(8);
        if (c.w == 2 && s == 21) TRSYNC(10);
      }
      const int g = s + 1;
      auto load_v = [&]() {
        if (V_TMA && c.w == V_W) {
          mbar_expect_e(BAR(B_VFULL), 8192);
          bulk_load_e(c.sb + SM_V, c.mail + (uint32_t)(M_KVQ + ((min(g, XEND - 1) & (NSLOT - 1)) * 32 + c.h) * 24576 + 8192), 8192, BAR(B_VFULL));
        }
      };
      if (XEND < NSEG && g >= XEND && g < NSEG) { mbar_wait(BAR(B_SC), s & 1); load_v(); }
      if (g < XEND) {
        const uint32_t tx_ = c.sb + SM_TAB + 1536 + (g & 3) * 128 + c.w * 32, tag = (g >> 2) & 1;
        if (c.w == 0) mbar_expect_e(BAR(B_LAND), EXP_PEER * 12288);
        auto load_x = [&]() {
          if (c.w == 3 && g + 1 < XEND) {
            mbar_wait(BAR(B_XEMPTY), g & 1);
            mbar_expect_e(BAR(B_XFULL), 16384 * EXP_NXT);
            for (int i = 0; i < EXP_NXT; i++) tma4d_e(c.sb + SM_XT + i * 16384, &tx, c.b * 8, (g + 1) * 4 + 2 * (c.b ^ i), BAR(B_XFULL));
          }
        };
        if (!X_AT || g == 0) load_x();
        mbar_wait(BAR(B_LAND), g & 1);
        if (g > 0) delay_cycles(DLY_F);
        if (EXP_FIN & 1) {
          const int ln = tid_now() & 31;
          const uint32_t a0 = c.sb + SM_LAND + 16384 + land_off(c.w, ((ln & 14) << 1) + ((ln >> 4) << 1)) + (ln & 1) * 8;
          uint4 v;
          const uint2 p0 = lds64(a0), p1 = lds64(a0 + 2048), p2 = lds64(a0 + 4096), p3 = lds64(a0 + 6144);
          v.x = tagged(sum4(p0.x, p1.x, p2.x, p3.x), tag); v.y = sum4(p0.y, p1.y, p2.y, p3.y);
          const uint2 r0 = lds64(a0 + 16), r1 = lds64(a0 + 2064), r2 = lds64(a0 + 4112), r3 = lds64(a0 + 6160);
          v.z = sum4(r0.x, r1.x, r2.x, r3.x); v.w = sum4(r0.y, r1.y, r2.y, r3.y);
          const uint2 d = lds64(tx_);
          st_pub4(mk_ptr(d.x | v_off(ln), d.y), v);
        }
        TR(s, 3);
        if (FIN_AT == 1 && g > 0) { mbar_wait(BAR(B_SC), s & 1); if (DLY_FK) delay_cycles(DLY_FK); if (X_AT) load_x(); }
        if (V_TMA == 1) load_v();
        const int ln = tid_now() & 31, n = ln >> 2, jj = ln & 3;
        const uint32_t base = c.sb + SM_LAND + ((c.w & 2) + (jj >> 1)) * 512 + (((16 * (jj & 1) + (n >> 1)) ^ (2 * jj)) << 4) + (n & 1) * 8;
        if (EXP_FIN & 2) {
          const uint32_t a0 = base ^ ((c.w & 1) * 128), a1 = a0 ^ 64;
          uint4 v;
          const uint2 p0 = lds64(a0 + 8192), p1 = lds64(a0 + 2048), p2 = lds64(a0 + 12288), p3 = lds64(a0 + 6144);
          v.x = tagged(sum4(p0.x, p1.x, p2.x, p3.x), tag); v.y = sum4(p0.y, p1.y, p2.y, p3.y);
          const uint2 r0 = lds64(a1 + 8192), r1 = lds64(a1 + 2048), r2 = lds64(a1 + 12288), r3 = lds64(a1 + 6144);
          v.z = sum4(r0.x, r1.x, r2.x, r3.x); v.w = sum4(r0.y, r1.y, r2.y, r3.y);
          const uint2 d = lds64(tx_ + 8);
          st_pub4(mk_ptr(d.x | ln * 16, d.y), v);
        }
        TR(s, 4);
        if (FIN_AT == 2 && g > 0) { mbar_wait(BAR(B_SC), s & 1); if (DLY_FK) delay_cycles(DLY_FK); if (X_AT) load_x(); }
        if (V_TMA == 2) load_v();
        if (EXP_FIN & 4) {
        uint32_t q[4];
#pragma unroll
        for (int e = 0; e < 4; e++) {
          const uint32_t a0 = (base ^ (e * 64)) + (c.w & 1) * 4;
          q[e] = sum4(lds32(a0), lds32(a0 + 10240), lds32(a0 + 4096), lds32(a0 + 14336));
        }
        const uint2 d = lds64(tx_ + 16);
        st_pub4(mk_ptr(d.x | ln * 16, d.y), make_uint4(tagged(q[0], tag), q[1], q[2], q[3]));
        }
        mbar_arrive_both(BAR(B_LFREE), c.b ^ 1);
        if (V_TMA == 3) load_v();
        TR(s, 5);
        if (!FIN_AT && X_AT && g > 0) { mbar_wait(BAR(B_SC), s & 1); if (DLY_FK) delay_cycles(DLY_FK); load_x(); }
      }
    }
    mbar_wait(BAR(B_DONE), 0);
    if (tid_now() == 384) TL(8);
    __syncwarp();
    asm volatile("barrier.cluster.arrive.relaxed; barrier.cluster.wait;" ::: "memory");
  } else if (c.m == 2) {
    asm volatile("setmaxnreg.dec.sync.aligned.u32 %0;" :: "n"(512 - 2 * REG_F - REG_H));
    c.lane = lane_id();
    CLK(0);
    {
      char* pa = c.mail + (uint32_t)(c.w < 2 ? M_PAIR + (c.w * 128 + c.r) * 8192 : c.w == 2 ? M_E3 + (c.r & 15) * 8192 + (c.r >> 4) * 128 : M_REF + c.r * 32);
      uint32_t a0 = ~0u, a1 = ~0u;
#pragma unroll 1
      for (int rep = 0; rep < NPROBE; rep++) { a0 = min(a0, timed_init(pa)); a1 = min(a1, timed_init(pa + 4096)); }
      sts32(c.sb + SM_SEL + 512 + c.w * 4, AWARE && a1 < a0 ? 1u << c.w : 0u);
      mbar_arrive_warp(BAR(B_PROBE));
      if (c.w == 0) {
        mbar_wait(BAR(B_PROBE), 0);
        const uint4 bits = lds128(c.sb + SM_SEL + 512);
        asm volatile("fence.acq_rel.gpu;" ::: "memory");
        st_pub_if(g_ctl + C_SEL + c.r, bits.x | bits.y | bits.z | bits.w | 0x100u, c.lane == 0);
        uint4 v; uint32_t n = 0;
        while (true) {
          v = ld_poll(g_ctl + C_SEL + c.lane * 4);
          if (__all_sync(~0u, v.x & v.y & v.z & v.w & 0x100u)) break;
          watchdog(n, POLL_LIMIT);
        }
        asm volatile("fence.acq_rel.gpu;" ::: "memory");
        sts128(c.sb + SM_SEL + c.lane * 16, v);
        mbar_arrive_warp(BAR(B_SEL));
        if (c.lane == 0) TL(13);
        __syncwarp();
        const unsigned short* mp = (const unsigned short*)mem0 + (2 * (c.lane & 3)) * D_ + 8 * c.r + (c.lane >> 2);
        uint32_t mv = (uint32_t)mp[0] | ((uint32_t)mp[D_] << 16);
        if (mv == SENT) mv = 0x7FFF7FFFu;
        char* dst = c.mail + (uint32_t)(M_E3 + (c.r >> 5) * 8192 + (c.r & 31) * 128 + c.lane * 4);
        st_pub(dst, mv); st_pub(dst + 4096, mv);
      }
    }
    asm volatile("barrier.cluster.wait;" ::: "memory");
    const int g = c.w, src0 = c.h * 4 + (g >> 1) * 2;
    mbar_wait(BAR(B_SEL), 0);
    c.sel = __shfl_sync(~0u, ~lds32(c.sb + SM_SEL + src0 * 4), 0);
    mbar_wait(BAR(B_WREAD), 0);
    uint32_t l16 = c.sb + g * 512 + c.lane * 16;
    auto lane = [&](uint32_t v) { l16 = dep(l16, v, c.sb); return (int)((l16 & 511) >> 4); };
    for (int s = 0; s < NSEG; s++) {
      l16 = vary(l16, s, c.sb);
      int ln = (l16 & 511) >> 4;
      uint4 kf[4], qx;
      {
        const int gs = min(s, XEND - 1);
        const char* pk = c.mail + (uint32_t)(M_KVQ + ((gs & (NSLOT - 1)) * 32 + c.h) * 24576 + g * 2048 + ln * 16);
        const char* pq = pk + (16384 + c.j * 2048 - g * 1536);
        const uint32_t tg = (gs / NSLOT) & 1;
        if (KVQ_AT) { mbar_wait(BAR(B_MEM), s & 1); if (DLY_K) delay_cycles(DLY_K); } else if (s > 0) mbar_wait(BAR(B_PUB), (s - 1) & 1);
        const char* pv_ = pk + (8192 - g * 1536);
        bool ok = false;
        if (V_TMA) {
#pragma unroll
          for (int t = 0; t < 4; t++) kf[t] = t < EXP_NK ? ld_poll(pk + t * 512) : lds128(l16 + SM_V + t * 2048);
          qx = ld_poll(pq);
          mbar_wait(BAR(B_VFULL), s & 1);
          const uint32_t bad = stale1(stale1(stale2(lds32(l16 + SM_V), lds32(l16 + SM_V + 2048), tg), lds32(l16 + SM_V + 4096), tg), lds32(l16 + SM_V + 6144), tg)
                             | stale1(stale1(stale1(stale2(kf[0].x, kf[1].x, tg), kf[2].x, tg), kf[3].x, tg), qx.x, tg);
          ok = all_clear(bad, EXP_CHK);
          TRV(s, 14, (uint32_t)!ok);
        }
        for (uint32_t n = 0; !ok; ) {
          uint4 v[4];
#pragma unroll
          for (int t = 0; t < 4; t++) v[t] = t < EXP_NV ? ld_poll(pv_ + t * 2048) : lds128(l16 + SM_V + t * 2048);
#pragma unroll
          for (int t = 0; t < 4; t++) kf[t] = t < EXP_NK ? ld_poll(pk + t * 512) : lds128(l16 + SM_V + t * 2048);
          qx = ld_poll(pq);
#pragma unroll
          for (int t = 0; t < 4; t++) sts128(l16 + SM_V + t * 2048, v[t]);
          if (V_TMA) FENCE_ASYNC_SMEM();
          const uint32_t bad = stale1(stale1(stale2(v[0].x, v[1].x, tg), v[2].x, tg), v[3].x, tg)
                             | stale1(stale1(stale1(stale2(kf[0].x, kf[1].x, tg), kf[2].x, tg), kf[3].x, tg), qx.x, tg);
          ok = all_clear(bad, EXP_CHK);
          watchdog(n, POLL_LIMIT); CNT(4);
        }
        TR(s, 2);
      }
      ln = lane(kf[0].y);
      const char* pa = c.mail + (uint32_t)(M_PAIR + ((s & 1) * 128 + src0) * 8192 + (c.sel >> (s & 1) & 1) * 4096 + (g & 1) * 512 + read_off(ln));
      const uint32_t spw = c.sb + SM_SP + g * 1280 + (ln >> 3) * 160 + (ln & 7) * 16, spr = c.sb + SM_SP + (ln & 3) * 160 + (ln >> 2) * 16, l8 = ln * 8;
      const uint32_t tg = s >> 1;
      float sx[2][4];
      uint32_t sm;
      uint4 km;
      touch(pa, c.sb);
      mbar_wait(BAR(B_E1TRIG), s & 1);
      const uint32_t t0 = clock_lo();
      TRV(s, 3, t0);
      scores_x<false>(sx, kf, qx, 0);
      store_scores(sx, spw + 640);
      delay_until(t0 + DLY_E1);
      uint32_t nr = 0;
      while (true) {
        const uint4 q0 = ld_poll(pa), q1 = ld_poll(pa + 2048), k0 = ld_poll(pa + 1024), k1 = ld_poll(pa + 3072);
        uint4 qm = add4(q0, q1);
        const uint32_t bq = stale2(q0.x, q1.x, tg);
        qm.x = dep(qm.x, bq, c.sb);
        scores_x<SC_F>(sx, kf, qm, c.sb);
        const uint32_t bk = stale2(k0.x, k1.x, tg);
        km = add4(k0, k1);
        km.x = dep(km.x, bk, c.sb);
        const bool ok = all_clear(bq | bk, 1);
        sm = scores_m(qm, km);
        store_scores(sx, spw);
        if (ok) break;
        nr++; CNT(2);
      }
      sts32(l8 + (c.sb + SM_SPM + (g >> 1) * 256 + (g & 1) * 4), sm);
      bar_sync(NB_ATT, 128);
      TR(s, 5); TRV(s, 13, nr);
      float o[2][4];
      uint32_t sp[5];
      uint4 vf[4];
      load_scores(sp, spr, l8 + (c.sb + SM_SPM));
      const uint32_t m5 = max5(sp);
      float off = row_off(m5), f[10];
      l16 = dep(l16, m5, c.sb);
#pragma unroll
      for (int t = 0; t < 4; t++) vf[(t >> 1) + 2 * (t & 1)] = lds128(l16 + SM_V + ((t >> 1) + 2 * (t & 1)) * 2048);
      qx.x = dep(qx.x, sp[0], c.sb);
      sts32(l8 + (c.sb + SM_SPM + 512 + (g >> 1) * 256 + (g & 1) * 4), scores_m(qx, km));
      mbar_arrive_warp(BAR(B_SC));
      unpack(f, sp);
      sched_fence(c.sb);
      uint4 vm;
      if (VM_AT < 2) {
        bar_sync(NB_VM, 384);
        sp[1] = exp_pair(f, 1, off);
        const uint32_t av = dep(l8, VM_AT ? sp[1] : __float_as_uint(off), c.sb) + (c.sb + g * 512 + SM_VM);
        const uint2 vm0 = lds64(av), vm1 = lds64(av + 256);
        vm = make_uint4(vm0.x, vm0.y, vm1.x, vm1.y);
#pragma unroll
        for (int i = 2; i < 6; i++) sp[i % 5] = exp_pair(f, i % 5, off);
      } else {
#pragma unroll
        for (int i = 1; i < 6; i++) sp[i % 5] = exp_pair(f, i % 5, off);
        bar_sync(VM_AT == 2 ? dep(dep(0, sp[1] ^ sp[2], c.sb) + NB_VM, sp[0], c.sb) : dep(dep(0, sp[0] ^ sp[1] ^ sp[2], c.sb) + NB_VM, sp[3], c.sb), 384);
        const uint32_t av = l8 + (c.sb + g * 512 + SM_VM);
        const uint2 vm0 = lds64(av), vm1 = lds64(av + 256);
        vm = make_uint4(vm0.x, vm0.y, vm1.x, vm1.y);
      }
      float sum = pv(o, sp, vf, vm);
      stsm4<false>(l16 + SM_OM, pack_bf16(o[0][0], o[0][1]), pack_bf16(o[0][2], o[0][3]), pack_bf16(o[1][0], o[1][1]), pack_bf16(o[1][2], o[1][3]));
      sts32(c.sb + SM_SUM + ((l16 >> 4) & 28), __float_as_uint(sum));
      asm volatile("bar.arrive %0, 384;" :: "r"((int)NB_OM) : "memory");
      const uint32_t tom = clock_lo();
      TRV(s, 8, tom);
      sched_fence(c.sb);
      ln = lane(tom);
      const int n = ln >> 2, jj = ln & 3, tq_ = 8 * c.j + n, lim = 16 * (tq_ - 8 * jj + 1);
      if (DLY_X) delay_until(tom + DLY_X);
      load_scores(sp, spr + 640, c.sb + SM_SPM + 512 + ln * 8);
#pragma unroll
      for (int w = 0; w < 4; w++) {
        uint32_t m; asm("shl.b32 %0, 0xffffffff, %1;" : "=r"(m) : "r"(max(lim - 32 * w, 0)));
        sp[1 + w] = (sp[1 + w] & ~m) | (0xD029D029u & m);
      }
      mbar_arrive_warp(dep(dep(0, sp[0], c.sb), sp[1], c.sb) + BAR(B_SPFREE));
      off = row_off(max5(sp));
      unpack(f, sp);
#pragma unroll
      for (int i = 1; i < 6; i++) sp[i % 5] = exp_pair(f, i % 5, off);
      sum = pv(o, sp, vf, vm);
      if (W_PV) mbar_arrive_warp(dep(dep(0, __float_as_uint(o[1][0]), c.sb), __float_as_uint(sum), c.sb) + BAR(B_PVDONE));
      TR(s, 7);
      sum = rcp(sum);
      const float i0 = __shfl_sync(~0u, sum, 8 * jj), i1 = __shfl_sync(~0u, sum, 8 * jj + 4);
      const uint32_t oxs = c.sb + SM_OX + g * 512;
      stsm4<true>(oxs + (ln & 7) * 64 + (((ln >> 3) ^ ((ln >> 1) & 3)) << 4),
                  pack_bf16(o[0][0] * i0, o[0][1] * i1), pack_bf16(o[0][2] * i0, o[0][3] * i1), pack_bf16(o[1][0] * i0, o[1][1] * i1), pack_bf16(o[1][2] * i0, o[1][3] * i1));
      __syncwarp();
      *(uint4*)(g_ox + (uint32_t)((32 * s + tq_) * 4096 + c.h * 128 + 32 * g + 8 * jj)) = lds128(oxs + n * 64 + ((jj ^ (n >> 1)) << 4));
      TR(s, 9);
    }
    CLK(4);
    mbar_arrive_warp(BAR(B_DONE));
    asm volatile("barrier.cluster.arrive.relaxed;" ::: "memory");
  } else {
    asm volatile("setmaxnreg.inc.sync.aligned.u32 %0;" :: "n"(REG_F));
    c.lane = lane_id();
    uint32_t wa[16][4], wb[16][4], wv[16][4];
    fft_rows_fwd((float2*)smraw, (const __nv_bfloat16*)(smraw + SM_WST - 2048), c.r, threadIdx.x, BAR(B_ROWS), BAR(B_FREE));
    mbar_arrive_warp(BAR(B_P1));
    if (tid_now() == 0) TL(1);
    __syncwarp();
    mbar_spin(BAR(B_WFULL + c.m), 0);
    {
      const uint32_t st = c.sb + c.m * ST_WG + frag_off(c.w, c.lane);
#pragma unroll
      for (int k = 0; k < 16; k++) ldsm4t(wb[k], st + k * 2048);
#pragma unroll
      for (int k = NP; k < 16; k++) ldsm4t(wa[k], st + (16 + k - NP) * 2048);
#pragma unroll
      for (int k = 0; k < NV; k++) ldsm4t(wv[k], st + (32 - NP + k) * 2048);
      mbar_arrive_warp(BAR(B_WREAD));
#pragma unroll
      for (int k = 0; k < NP; k++) ldsm4t(wa[k], c.sb + SM_POOL + c.m * NP * 2048 + frag_off(c.w, c.lane) + k * 2048);
      bar_sync(NB_XCH, 256);
#pragma unroll
      for (int k = 0; k < NP; k++) sts128(c.sb + SM_POOL + c.m * 2048 + c.w * 512 + c.lane * 16 + k * 4096, make_uint4(wa[k][0], wa[k][1], wa[k][2], wa[k][3]));
    }
    if (tid_now() == 0) TL(12);
    __syncwarp();
    asm volatile("barrier.cluster.wait;" ::: "memory");
    uint32_t t16 = c.m * 2048 + c.w * 512 + c.lane * 16;
    uint32_t pk = (c.m * NHV * 2048 + frag_off(c.w, c.lane)) | (tile_off(2 * (c.w & 1), c.lane) << 16) | ((c.lane & 12) ? 0u : 0x80000000u);
    const uint32_t dx = desc_lo(c.sb + SM_XT + c.m * 4096), dh = desc_lo(c.sb + SM_HV + c.m * NHV * 2048);
    for (int s = -2; s < NSEG; s++) {
      t16 = vary(t16, s, c.sb); pk = vary(pk, s, c.sb);
      if (s >= 0) {
        uint32_t af[16][4], bf[4][4], wo;
        const uint32_t tab = ((t16 >> 3) & 0x1C0) + (c.sb + SM_TAB + (s & 1) * 512);
        const char* pa;
        mem_proj(wa, wb, wv, af, wo, pa, tab, t16, pk, c, s);
        const uint32_t t0 = clock_lo();
        t16 = dep(t16, t0, c.sb);
        auto ldwo = [&](int f) { ldsm4t(af[f], (f < WO_D ? wo : dep(wo, af[f < WO_D ? 0 : f - WO_D][0], c.sb)) + (c.sb + SM_WO + (f >> 3) * 32768 + (f & 7) * 2048)); };
        {
          const uint32_t tg = s >> 1, vm = t16 >> 1, chk = (~t16 >> 4) & 1;
#pragma unroll
          for (int f = WO_0; f < WO_1; f++) ldwo(f);
          delay_until(t0 + DLY_V);
          uint2 v0 = ld_poll2(pa), v1 = ld_poll2(pa + 1024), v2 = ld_poll2(pa + 2048), v3 = ld_poll2(pa + 3072);
          TR(s, 3);
#pragma unroll
          for (int f = WO_1; f < 16; f++) ldwo(f);
          TR(s, 4);
          uint32_t n = 0;
          while (true) {
            sts64(vm + (c.sb + SM_VM), sum4(v0.x, v1.x, v2.x, v3.x), sum4(v0.y, v1.y, v2.y, v3.y));
            if (arrive_if_clear(stale1(stale1(stale2(v0.x, v1.x, tg), v2.x, tg), v3.x, tg), chk, NB_VM, 384)) break;
            v0 = ld_poll2(pa); v1 = ld_poll2(pa + 1024); v2 = ld_poll2(pa + 2048); v3 = ld_poll2(pa + 3072);
            n++; CNT(3);
          }
          TR(s, 12); TRV(s, 15, n);
        }
        const uint32_t ob = dep(dep(t16 & 511, af[14][0], c.sb), af[15][0], c.sb), l4 = ob >> 2;
        const uint32_t bit = (t16 & 48) ? 0u : 1u;
        mbar_spin_if(BAR(B_XFULL), s & 1, s + 2 < XEND);
        bar_sync(NB_OM, 384);
        TR(s, 5);
#pragma unroll
        for (int i = 0; i < 4; i++) ldsm4t(bf[i], ob + (c.sb + SM_OM + i * 512));
        uint2 sum = lds64(((t16 >> 1) & 24) + (c.sb + SM_SUM));
        if (OM_F) sched_fence(c.sb);
        float d[4][4] = {};
        uint4 d0, d1;
#pragma unroll
        for (int k = 0; k < 4; k++) {
#pragma unroll
          for (int t = 0; t < 2; t++) {
            mma_a(d[2 * t], af[8 * t + 2 * k], bf[k][0], bf[k][1]);
            mma_a(d[2 * t + 1], af[8 * t + 2 * k + 1], bf[k][2], bf[k][3]);
          }
          if (k == 0) {
            const uint32_t tb2 = dep((t16 >> 3) & 0x1C0, __float_as_uint(d[3][0]), c.sb) + (c.sb + SM_TAB + (s & 1) * 512);
            d0 = lds128(tb2 + 32); d1 = lds128(tb2 + 48);
          }
          if (k == 1) { sum.x = dep(sum.x, __float_as_uint(d[0][0]), c.sb); sum.y = dep(sum.y, __float_as_uint(d[0][0]), c.sb); }
        }
        char* dst[4] = {mk_ptr(d0.x | l4, d0.y), mk_ptr(d0.z | l4, d0.w), mk_ptr(d1.x | l4, d1.y), mk_ptr(d1.z | l4, d1.w)};
        const float i0 = rcp(__uint_as_float(sum.x)), i1 = rcp(__uint_as_float(sum.y));
#pragma unroll
        for (int i = 0; i < 4; i++) {
          const int t = i & 2, e = 2 * (i & 1);
          st_pub(dst[i], put_tag(pack_bf16((d[t][e] + d[t + 1][e]) * i0, (d[t][e + 1] + d[t + 1][e + 1]) * i1), bit, s >> 1));
        }
        if (ANCH2) sts32(c.sb + SM_SUM + 64, clock_lo());
        mbar_arrive_warp(BAR(B_E2TRIG));
        TR(s, 6);
        sched_fence(c.sb);
        if (W_E2 == 2) mbar_spin(BAR(B_E2TRIG), s & 1);
      }
      auto ldp = [&](int k0, int k1, int d, int back = 0) {
#pragma unroll
        for (int k = k0; k < k1; k++) lds_frag(wa[k], (k < k0 + d - back ? t16 : dep(t16, wa[k < d ? 0 : k - d][0], c.sb)) + (c.sb + SM_POOL + k * 4096));
      };
      ldp(0, PL_0 < PL_D ? PL_0 : PL_D, PL_D);
      mbar_spin_if(BAR(B_XFULL), s & 1, s < 0);
      ldp(PL_D, PL_0, PL_D, PL_D);
      if (s + 2 < XEND) {
        float xa[16];
        uint32_t q[4];
        if (W_E2 == 1 && s >= 0) mbar_spin(BAR(B_E2TRIG), s & 1);
        if (W_PV && s >= 0) mbar_spin(BAR(B_PVDONE), s & 1);
        TR(s, 7);
        constexpr int S1 = ORDER ? 0 : 2, S2 = ORDER == 0 ? 0 : ORDER == 1 ? 2 : 1, S3 = ORDER == 2 ? 2 : 1;
        if (ORDER) issue_qk<0, 16>(xa, wb, vary(dx, s, c.sb)); else issue_v(xa, wv, vary(dx, s, c.sb), vary(dh, s, c.sb));
        if (IS_F) sched_fence(c.sb);
        ldp(PL_0, PL_1, PL_D1);
        const uint32_t land = (t16 ^ ((t16 >> 3) & 0x60)) + vary(c.sb + SM_LAND + c.b * 4096, s, c.sb);
        mbar_spin(BAR(B_LFREE), s & 1);
        WG_WAIT(0);
        TR(s, 8);
        park_own<S1 == 2>(q, xa, land, S1, c.sb);
        if (W_PUB == 4 && s >= 0) mbar_spin(BAR(B_PUB), s & 1);
        if (ORDER == 1) issue_v(xa, wv, vary(dx, s, c.sb + 32), vary(dh, s, c.sb)); else issue_qk<0, 16>(xa, ORDER ? wa : wb, vary(dx, s, c.sb + 32));
        if (IS_F) sched_fence(c.sb);
        ldp(PL_1, PL_2, PL_D1);
        if (W_PUB == 1) mbar_spin_if(BAR(B_PUB), s & 1, s >= 0);
        uint32_t tp = clock_lo(), q1[4] = {q[0], q[1], q[2], q[3]};
        if (W_PUB != 3) park_peer(q, land, S1, c);
        ldp(PL_2, NP - PL_L, PL_D1);
        TR(s, 13);
        WG_WAIT(0);
        TR(s, 9);
        park_own<S2 == 2>(q, xa, land, S2, c.sb);
        if (ORDER == 2) issue_v(xa, wv, vary(dx, s, c.sb + 64), vary(dh, s, c.sb));
        else {
          issue_qk<0, PL_L ? NP - PL_L : 16>(xa, wa, vary(dx, s, c.sb + 64));
          ldp(NP - PL_L, NP, PL_E);
          if (PL_L) issue_qk<NP - PL_L, 16>(xa, wa, vary(dx, s, c.sb + 64));
        }
        if ((W_PUB == 2 || W_PUB == 3) && s >= 0) { mbar_spin(BAR(B_PUB), s & 1); tp = clock_lo(); }
        if (W_PUB == 3) park_peer(q1, land, S1, c);
        if (DLY_S && s >= 0) delay_until(tp + DLY_S);
        park_peer(q, land, S2, c);
        WG_WAIT(0);
        TR(s, 10);
        mbar_arrive_warp(BAR(B_XEMPTY));
        park_own<S3 == 2>(q, xa, land, S3, c.sb);
        park_peer(q, land, S3, c);
        TR(s, 11);
      } else ldp(PL_0, NP, 1);
    }
    mbar_arrive_warp(BAR(B_DONE));
    asm volatile("barrier.cluster.arrive.relaxed;" ::: "memory");
  }
}

constexpr int OP_STAGES = 5;
constexpr uint32_t OP_BT = OP_STAGES * 32768, OP_TW = OP_BT + 4 * ROW_BUF * 8, OP_BAR = OP_TW + 8192, OP_SMEM = OP_BAR + 128 + 1024;

__device__ __forceinline__ void wgmma_ss_n128_tb(float (&d)[64], uint64_t a, uint64_t b) {
  asm volatile("wgmma.mma_async.sync.aligned.m64n128k16.f32.bf16.bf16 "
    "{%0,%1,%2,%3,%4,%5,%6,%7,%8,%9,%10,%11,%12,%13,%14,%15,%16,%17,%18,%19,%20,%21,%22,%23,%24,%25,%26,%27,%28,%29,%30,%31,"
    "%32,%33,%34,%35,%36,%37,%38,%39,%40,%41,%42,%43,%44,%45,%46,%47,%48,%49,%50,%51,%52,%53,%54,%55,%56,%57,%58,%59,%60,%61,%62,%63}, "
    "%64, %65, 1, 1, 1, 0, 1;"
    : "+f"(d[0]), "+f"(d[1]), "+f"(d[2]), "+f"(d[3]), "+f"(d[4]), "+f"(d[5]), "+f"(d[6]), "+f"(d[7]),
      "+f"(d[8]), "+f"(d[9]), "+f"(d[10]), "+f"(d[11]), "+f"(d[12]), "+f"(d[13]), "+f"(d[14]), "+f"(d[15]),
      "+f"(d[16]), "+f"(d[17]), "+f"(d[18]), "+f"(d[19]), "+f"(d[20]), "+f"(d[21]), "+f"(d[22]), "+f"(d[23]),
      "+f"(d[24]), "+f"(d[25]), "+f"(d[26]), "+f"(d[27]), "+f"(d[28]), "+f"(d[29]), "+f"(d[30]), "+f"(d[31]),
      "+f"(d[32]), "+f"(d[33]), "+f"(d[34]), "+f"(d[35]), "+f"(d[36]), "+f"(d[37]), "+f"(d[38]), "+f"(d[39]),
      "+f"(d[40]), "+f"(d[41]), "+f"(d[42]), "+f"(d[43]), "+f"(d[44]), "+f"(d[45]), "+f"(d[46]), "+f"(d[47]),
      "+f"(d[48]), "+f"(d[49]), "+f"(d[50]), "+f"(d[51]), "+f"(d[52]), "+f"(d[53]), "+f"(d[54]), "+f"(d[55]),
      "+f"(d[56]), "+f"(d[57]), "+f"(d[58]), "+f"(d[59]), "+f"(d[60]), "+f"(d[61]), "+f"(d[62]), "+f"(d[63])
    : "l"(a), "l"(b));
}

__device__ __forceinline__ void tma2d_mc(uint32_t dst, const CUtensorMap* tm, int c0, int c1, uint32_t bar) {
  asm volatile("cp.async.bulk.tensor.2d.shared::cluster.global.mbarrier::complete_tx::bytes.multicast::cluster [%0], [%1, {%3, %4}], [%2], %5;"
               :: "r"(dst), "l"(tm), "r"(bar), "r"(c0), "r"(c1), "h"((uint16_t)3) : "memory");
}

__global__ void __cluster_dims__(2, 1, 1) __launch_bounds__(640, 1)
outproj_kernel(const __grid_constant__ CUtensorMap ta, const __grid_constant__ CUtensorMap tw,
               const __grid_constant__ CUtensorMap tb, const __grid_constant__ CUtensorMap tout) {
  extern __shared__ __align__(1024) unsigned char smraw[];
  const uint32_t sb = __shfl_sync(~0u, (smem_u32(smraw) + 1023) & ~1023u, 0);
  const uint32_t full = sb + OP_BAR, empty = full + 8 * OP_STAGES, bfull = empty + 8 * OP_STAGES;
  const int m0 = (blockIdx.x >> 3) * 128, n0 = (blockIdx.x & 7) * 128, rank = blockIdx.x & 1;
  if (threadIdx.x == 0) {
    for (int i = 0; i < OP_STAGES; i++) { mbar_init(full + 8 * i, 1); mbar_init(empty + 8 * i, 4); }
    mbar_init(bfull, 1);
    asm volatile("fence.mbarrier_init.release.cluster;" ::: "memory");
  }
  __syncthreads();
  asm volatile("barrier.cluster.arrive.relaxed.aligned; barrier.cluster.wait.aligned;" ::: "memory");
  const int role = __shfl_sync(~0u, (int)(threadIdx.x >> 7), 0);
  if (role == 4) {
    if (threadIdx.x == 512) {
      TL(9);
      for (int st = 0; st < OP_STAGES; st++) {
        mbar_expect(full + 8 * st, 32768);
        tma2d(sb + st * 32768 + 16384, &tw, n0, st * 64, full + 8 * st);
        tma2d(sb + st * 32768 + 24576, &tw, n0 + 64, st * 64, full + 8 * st);
      }
      pdl_wait();
      TL(10);
      uint32_t st = 0, ph = 1;
      for (int kb = 0; kb < 64; kb++) {
        const uint32_t dst = sb + st * 32768;
        if (kb >= OP_STAGES) {
          mbar_wait(empty + 8 * st, ph);
          mbar_expect(full + 8 * st, 32768);
          tma2d(dst + 16384, &tw, n0, kb * 64, full + 8 * st);
          tma2d(dst + 24576, &tw, n0 + 64, kb * 64, full + 8 * st);
        }
        tma2d_mc(dst + rank * 8192, &ta, kb * 64, m0 + rank * 64, full + 8 * st);
        if (++st == OP_STAGES) { st = 0; ph ^= 1; }
      }
      mbar_wait(full + 8 * (63 % OP_STAGES), (63 / OP_STAGES) & 1);
    }
  } else if (role >= 2) {
    unsigned char* base = smraw + (sb - smem_u32(smraw));
    const int t = threadIdx.x & 31, w = (threadIdx.x >> 5) & 7;
    row_twiddles((float2*)(base + OP_TW), threadIdx.x - 256, 256);
    bar_sync(2, 256);
    pdl_wait();
    { const int i = blockIdx.x * 256 + threadIdx.x - 256; if (i < C_CHAIN_END) g_ctl[i] = 0; }
    fft_rows_inv((float2*)(base + OP_BT) + w * (ROW_BUF / 2), (const float2*)(base + OP_TW),
                 (blockIdx.x & 63) * 16 + (blockIdx.x >> 6) * 8 + w, t);
    if (threadIdx.x == 256) TL(3);
    FENCE_ASYNC_SMEM();
    bar_sync(2, 256);
    if (threadIdx.x == 256) {
      uint32_t* cnt = g_ctl + C_ROWS + ((blockIdx.x >> 3) & 7) * 32;
      asm volatile("fence.acq_rel.gpu;" ::: "memory");
      asm volatile("red.relaxed.gpu.global.add.u32 [%0], 1;" :: "l"(cnt) : "memory");
      for (uint32_t n = 0; ld_acquire(cnt) < 16; ) { watchdog(n, 1u << 22); __nanosleep(100); }
      asm volatile("fence.proxy.async.global;" ::: "memory");
      mbar_expect(bfull, 32768);
      tma2d(sb + OP_BT, &tb, n0, m0, bfull); tma2d(sb + OP_BT + 16384, &tb, n0 + 64, m0, bfull);
      TL(5);
    }
  } else {
    const int wg = role, lane = threadIdx.x & 31, w = (threadIdx.x >> 5) & 3;
    float acc[64];
#pragma unroll
    for (int i = 0; i < 64; i++) acc[i] = 0.f;
    const uint32_t rel = mapa(empty, lane & 1), la = desc_lo(sb + wg * 8192), lb = ((sb + 16384) & 0x3FFFF) >> 4 | (8192 >> 4) << 16;
    const uint32_t relon = (threadIdx.x & 127) < 2;
    uint32_t st = 0, ph = 0, prev = 0;
#pragma unroll 1
    for (int kb = 0; kb < 64; kb++) {
      mbar_spin(full + 8 * st, ph);
      WG_FENCE();
#pragma unroll
      for (int k = 0; k < 4; k++) wgmma_ss_n128_tb(acc, desc128(la + st * 2048 + k * 2), desc128(lb + st * 2048 + k * 128));
      WG_COMMIT();
      WG_WAIT(1);
      asm volatile("{ .reg .pred p; setp.ne.u32 p, %1, 0; @p mbarrier.arrive.shared::cluster.b64 _, [%0]; }"
                   :: "r"(rel + 8 * prev), "r"(relon & (uint32_t)(kb > 0 && kb + OP_STAGES <= 64)) : "memory");
      prev = st;
      if (++st == OP_STAGES) { st = 0; ph ^= 1; }
    }
    WG_WAIT(0);
    const int r0 = wg * 64 + w * 16 + (lane >> 2);
    const float g0 = __ldcg(g_gate + m0 + r0), g1 = __ldcg(g_gate + m0 + r0 + 8);
    mbar_wait(bfull, 0);
#pragma unroll
    for (int t = 0; t < 16; t++) {
      const uint32_t a0 = sb + OP_BT + (t >> 3) * 16384 + r0 * 128 + (((t & 7) ^ (r0 & 7)) << 4) + (lane & 3) * 4, a1 = a0 + 1024;
      uint32_t b0, b1;
      asm volatile("ld.shared.u32 %0, [%1];" : "=r"(b0) : "r"(a0) : "memory");
      asm volatile("ld.shared.u32 %0, [%1];" : "=r"(b1) : "r"(a1) : "memory");
      const uint32_t o0 = pack_bf16(fmaf(g0, acc[4 * t], (1.f - g0) * __uint_as_float(b0 << 16)), fmaf(g0, acc[4 * t + 1], (1.f - g0) * __uint_as_float(b0 & 0xFFFF0000u)));
      const uint32_t o1 = pack_bf16(fmaf(g1, acc[4 * t + 2], (1.f - g1) * __uint_as_float(b1 << 16)), fmaf(g1, acc[4 * t + 3], (1.f - g1) * __uint_as_float(b1 & 0xFFFF0000u)));
      asm volatile("st.shared.u32 [%0], %1;" :: "r"(a0), "r"(o0) : "memory");
      asm volatile("st.shared.u32 [%0], %1;" :: "r"(a1), "r"(o1) : "memory");
    }
    FENCE_ASYNC_SMEM();
    bar_sync(1, 256);
    if (threadIdx.x == 0) {
      tma2d_store(&tout, n0, m0, sb + OP_BT); tma2d_store(&tout, n0 + 64, m0, sb + OP_BT + 16384);
      asm volatile("cp.async.bulk.commit_group; cp.async.bulk.wait_group 0;" ::: "memory");
      TL(11);
    }
  }
}

typedef CUresult (*EncodeFn)(CUtensorMap*, CUtensorMapDataType, cuuint32_t, void*, const cuuint64_t*, const cuuint64_t*,
                             const cuuint32_t*, const cuuint32_t*, CUtensorMapInterleave, CUtensorMapSwizzle,
                             CUtensorMapL2promotion, CUtensorMapFloatOOBfill);

void make_map(EncodeFn enc, CUtensorMap* tm, const void* p, int rank, const cuuint64_t* dims, const cuuint64_t* strides, const cuuint32_t* box) {
  const cuuint32_t es[4] = {1, 1, 1, 1};
  enc(tm, CU_TENSOR_MAP_DATA_TYPE_BFLOAT16, rank, (void*)p, dims, strides, box, es, CU_TENSOR_MAP_INTERLEAVE_NONE,
      CU_TENSOR_MAP_SWIZZLE_128B, CU_TENSOR_MAP_L2_PROMOTION_L2_128B, CU_TENSOR_MAP_FLOAT_OOB_FILL_NONE);
}
void make_map2(EncodeFn enc, CUtensorMap* tm, const void* p, uint64_t cols, uint64_t rows, uint32_t boxrows) {
  const cuuint64_t dims[2] = {cols, rows}, strides[1] = {cols * 2};
  const cuuint32_t box[2] = {64, boxrows};
  make_map(enc, tm, p, 2, dims, strides, box);
}

}

extern "C" void kernel_launch(void* const* d_in, const int* in_sizes, int n_in, void* d_out, int out_size) {
  (void)in_sizes; (void)n_in; (void)out_size;
  const __nv_bfloat16* x = (const __nv_bfloat16*)d_in[0];
  const __nv_bfloat16* mem0 = (const __nv_bfloat16*)d_in[1];
  const __nv_bfloat16* gw = (const __nv_bfloat16*)d_in[10];

  EncodeFn enc = nullptr;
  cudaDriverEntryPointQueryResult qr;
  cudaGetDriverEntryPoint("cuTensorMapEncodeTiled", (void**)&enc, cudaEnableDefault, &qr);
  void *p_ox, *p_b, *p_mail;
  cudaGetSymbolAddress(&p_ox, g_ox); cudaGetSymbolAddress(&p_b, g_b); cudaGetSymbolAddress(&p_mail, g_mail);
  CUtensorMap tq, tk, tv, tv16, to, tx, ta, tw, tb, tout;
  make_map2(enc, &tq, d_in[2], 4096, 1024, 64);
  make_map2(enc, &tk, d_in[3], 4096, 1024, 64);
  make_map2(enc, &tv, d_in[4], 4096, 1024, 64);
  make_map2(enc, &tv16, d_in[4], 4096, 1024, 16);
  make_map2(enc, &to, d_in[5], 1024, 4096, 128);
  make_map2(enc, &tw, d_in[5], 1024, 4096, 64);
  make_map2(enc, &ta, p_ox, 4096, 2048, 64);
  make_map2(enc, &tb, p_b, 1024, 2048, 128);
  make_map2(enc, &tout, d_out, 1024, 2048, 128);
  {
    const cuuint64_t dims[4] = {64, 8, 16, 256}, strides[3] = {2048, 128, 16384};
    const cuuint32_t box[4] = {64, 8, 8, 2};
    make_map(enc, &tx, x, 4, dims, strides, box);
  }
  cudaFuncSetAttribute(chain_kernel, cudaFuncAttributeMaxDynamicSharedMemorySize, CHAIN_SMEM);
  cudaFuncSetAttribute(outproj_kernel, cudaFuncAttributeMaxDynamicSharedMemorySize, OP_SMEM);

  cudaStream_t st = cudaStreamPerThread;
  char* mail = (char*)(((uintptr_t)p_mail + 8191) & ~(uintptr_t)8191);
  chain_kernel<<<132, 512, CHAIN_SMEM, st>>>(tq, tk, tv, tv16, to, tx, mem0, mail, x, gw, (const char*)d_in[8], (const char*)d_in[9]);
  cudaLaunchAttribute pdl;
  pdl.id = cudaLaunchAttributeProgrammaticStreamSerialization;
  pdl.val.programmaticStreamSerializationAllowed = 1;
  cudaLaunchConfig_t cfg = {};
  cfg.stream = st; cfg.attrs = &pdl; cfg.numAttrs = USE_PDL;
  cfg.gridDim = dim3(128); cfg.blockDim = dim3(544); cfg.dynamicSmemBytes = OP_SMEM;
  cudaLaunchKernelEx(&cfg, outproj_kernel, ta, tw, tb, tout);
}
```

```cpp
#include <cuda_runtime.h>
#include <cuda_bf16.h>
#include <cuda.h>
#include <stdint.h>

#define DLY_E1 300
#define DLY_V 330
#define DLY_E2 400
#define DLY_E3 500
#define DLY_X 120
#define DLY_S 500
#define DLY_F 0
#define VM_AT 1
#define VM_F 0
#define OM_F 1
#define SXX_IN 0
#define C1_AT 1
#define NLAG 4
#define WO_D 2
#define WO_0 2
#define WO_1 12
#define PL_0 8
#define PL_1 NP_
#define PL_D 2
#define PL_L 0
#define DUAL 0
#define HV_D 3
#define DLY_FK 0
#define QX_SM 0
#define REG_F 216
#define REG_H 24
#define SC_F 1
#define E2_F 1
#define KVQ_AT 0
#define DLY_K 0
#define X_AT 2
#define W_PV 0
#define PL_2 NP_
#define BF_E 3
#define PL_E 2
#define ORDER 1
#define SSPOS 1
#define W_PUB 1
#define FIN_AT 5
#define AWARE 1
#define NPROBE 2
#define NP_ 12
#define USE_PDL 1
#define DLY_GRP 3000
#define P2_BULK 0
#define EXP_NV 4
#define EXP_NK 4
#define EXP_CHK 1
#define EXP_NXT 2
#define EXP_PEER 1
#define EXP_FIN 7
#define EXP_NWG 16
#define ANCH2 1
#define XF_AT 1
#define IS_F 1
#define PL_D1 2
#define W_E2 0
#define V_TMA 2
#define V_W 2
#define RED_L 3
#define RED_T 1
#define RED_P 1
#define DLY_E3B 0
#define HV_E 0
#define HV_R 4
#define HOLD 2
#define PACE 550
#define PACE0 0
#define EXP_ST 7
#define HOLD_AT NPROBE
#define WO_AT 34
#define WO_P 2
#define DLY_SEL 500
#define P1_AT 1
#define EXP_ZG 1
#define TMA_W tma2d_once
#define BULK_F bulk_once
#define TMA_O tma2d_e
#define PACE_Z 500
#define PACE_F 800
#define EXP_INV 1
#define VF_AT 0
#define UP_F 1
#define WO_L (12 - NP_)
#define WO_C 4
#define WO_T 3
#define WO_LD 0
#define EXP_LIN 0
#define PL_W 0
#define PL_WA 4
#define PL_WD 0
#define PL_WF 1
#define STAG 0
#define EXP_FL 0
#define DLY_FS 0
#define DLY_F2 0

namespace {

constexpr int S_ = 2048, D_ = 1024, NSEG = 64;
constexpr uint32_t SENT = 0xFFFFFFFFu;
constexpr int NSLOT = 4;

constexpr uint32_t M_PAIR = 0, M_E3 = M_PAIR + 2 * 128 * 8192, M_REF = M_E3 + 16 * 8192, M_KVQ = M_REF + 8192,
                   MAIL_BYTES = M_KVQ + NSLOT * 32 * 24576;
__device__ __align__(1024) unsigned char g_mail[MAIL_BYTES + 8192];
constexpr int C_SEL = 0, C_P1 = C_SEL + 128, C_CHAIN_END = C_P1 + 32, C_ROWS = C_CHAIN_END, C_END = C_ROWS + 16 * 32;
__device__ __align__(1024) uint32_t g_ctl[C_END];
#define CLK(i)
#define TL(i)
#define TL2(i)
#define CNT(i)
__device__ __align__(1024) __nv_bfloat16 g_ox[S_ * 4096];
__device__ __align__(1024) float2 g_z[257 * 4096];
__device__ __align__(1024) __nv_bfloat16 g_b[S_ * D_];
__device__ float g_gate[S_];

#define TRV(s, ev, val)
#define TR(s, ev)
#define TRSYNC(ev)
__device__ __forceinline__ uint32_t smem_u32(const void* p) { return (uint32_t)__cvta_generic_to_shared(p); }
__device__ __forceinline__ void watchdog(uint32_t& n, uint32_t limit) {
  asm volatile("{ .reg .pred p; add.u32 %0, %0, 1; setp.gt.u32 p, %0, %1; @p trap; }" : "+r"(n) : "r"(limit));
}
__device__ __forceinline__ void mbar_init(uint32_t bar, uint32_t cnt) {
  asm volatile("mbarrier.init.shared::cta.b64 [%0], %1;" :: "r"(bar), "r"(cnt) : "memory");
}
__device__ __forceinline__ void mbar_arrive_warp(uint32_t bar) {
  __syncwarp();
  asm volatile("{ .reg .pred p; elect.sync _|p, 0xffffffff; @p mbarrier.arrive.shared::cta.b64 _, [%0]; }" :: "r"(bar) : "memory");
}
__device__ __forceinline__ uint32_t clock_lo() {
  uint32_t r; asm volatile("{ .reg .u64 c; .reg .u32 h; mov.u64 c, %%clock64; mov.b64 {%0, h}, c; }" : "=r"(r) :: "memory"); return r;
}
__device__ __forceinline__ void delay_until(uint32_t t) {
  asm volatile("{ .reg .pred p; .reg .u64 c; .reg .u32 l, h;\n"
               "DLY: mov.u64 c, %%clock64; mov.b64 {l, h}, c; sub.s32 l, l, %0; setp.lt.s32 p, l, 0; @p bra.uni DLY; }" :: "r"(t) : "memory");
}
__device__ __forceinline__ void delay_cycles(uint32_t n) { delay_until(clock_lo() + n); }
__device__ __forceinline__ void sched_fence(uint32_t z) {
  asm volatile("{ .reg .pred p; setp.eq.u32 p, %0, 0x7fff0000; @p pmevent 1; }" :: "r"(z) : "memory");
}
__device__ __forceinline__ void pdl_wait() { asm volatile("griddepcontrol.wait;" ::: "memory"); }
__device__ __forceinline__ void pdl_launch() { asm volatile("griddepcontrol.launch_dependents;" ::: "memory"); }
__device__ __forceinline__ float ex2(float x) { float r; asm("ex2.approx.ftz.f32 %0, %1;" : "=f"(r) : "f"(x)); return r; }
__device__ __forceinline__ float rcp(float x) { float r; asm("rcp.approx.ftz.f32 %0, %1;" : "=f"(r) : "f"(x)); return r; }
__device__ __forceinline__ void mbar_expect(uint32_t bar, uint32_t bytes) {
  asm volatile("mbarrier.arrive.expect_tx.shared::cta.b64 _, [%0], %1;" :: "r"(bar), "r"(bytes) : "memory");
}
__device__ __forceinline__ bool mbar_try(uint32_t bar, uint32_t ph) {
  uint32_t ok;
  asm volatile("{ .reg .pred p; mbarrier.try_wait.parity.shared::cta.b64 p, [%1], %2; selp.u32 %0, 1, 0, p; }"
               : "=r"(ok) : "r"(bar), "r"(ph) : "memory");
  return ok;
}
__device__ __forceinline__ void mbar_wait(uint32_t bar, uint32_t ph) {
  uint32_t n = 0;
  while (!mbar_try(bar, ph)) { watchdog(n, (1u << 20)); }
}
__device__ __forceinline__ void mbar_spin(uint32_t bar, uint32_t ph) { while (!mbar_try(bar, ph)) {} }
__device__ __forceinline__ void mbar_spin_if(uint32_t bar, uint32_t ph, bool on) {
  asm volatile("{ .reg .pred p, q; setp.ne.u32 p, %2, 0;\n"
               "SPN: setp.eq.u32 q, 0, 0; @p mbarrier.try_wait.parity.shared::cta.b64 q, [%0], %1; @!q bra.uni SPN; }" :: "r"(bar), "r"(ph), "r"((uint32_t)on) : "memory");
}
__device__ __forceinline__ void mbar_spin_cluster(uint32_t bar, uint32_t ph) {
  uint32_t ok;
  do {
    asm volatile("{ .reg .pred p; mbarrier.try_wait.parity.acquire.cluster.shared::cta.b64 p, [%1], %2; selp.u32 %0, 1, 0, p; }"
                 : "=r"(ok) : "r"(bar), "r"(ph) : "memory");
  } while (!ok);
}
__device__ __forceinline__ void tma2d(uint32_t dst, const CUtensorMap* tm, int c0, int c1, uint32_t bar) {
  asm volatile("cp.async.bulk.tensor.2d.shared::cluster.global.mbarrier::complete_tx::bytes [%0], [%1, {%3, %4}], [%2];"
               :: "r"(dst), "l"(tm), "r"(bar), "r"(c0), "r"(c1) : "memory");
}
__device__ __forceinline__ void tma2d_store(const CUtensorMap* tm, int c0, int c1, uint32_t src) {
  asm volatile("cp.async.bulk.tensor.2d.global.shared::cta.bulk_group [%0, {%2, %3}], [%1];"
               :: "l"(tm), "r"(src), "r"(c0), "r"(c1) : "memory");
}
__device__ __forceinline__ void mbar_expect_e(uint32_t bar, uint32_t bytes) {
  asm volatile("{ .reg .pred p; elect.sync _|p, 0xffffffff; @p mbarrier.arrive.expect_tx.shared::cta.b64 _, [%0], %1; }" :: "r"(bar), "r"(bytes) : "memory");
}
__device__ __forceinline__ void tma2d_e(uint32_t dst, const CUtensorMap* tm, int c0, int c1, uint32_t bar) {
  asm volatile("{ .reg .pred p; elect.sync _|p, 0xffffffff;\n"
               "@p cp.async.bulk.tensor.2d.shared::cluster.global.mbarrier::complete_tx::bytes [%0], [%1, {%3, %4}], [%2]; }"
               :: "r"(dst), "l"(tm), "r"(bar), "r"(c0), "r"(c1) : "memory");
}
__device__ __forceinline__ void tma2d_once(uint32_t dst, const CUtensorMap* tm, int c0, int c1, uint32_t bar) {
  asm volatile("{ .reg .pred p; .reg .b64 h; createpolicy.fractional.L2::evict_first.b64 h; elect.sync _|p, 0xffffffff;\n"
               "@p cp.async.bulk.tensor.2d.shared::cluster.global.mbarrier::complete_tx::bytes.L2::cache_hint [%0], [%1, {%3, %4}], [%2], h; }"
               :: "r"(dst), "l"(tm), "r"(bar), "r"(c0), "r"(c1) : "memory");
}
__device__ __forceinline__ void bulk_once(uint32_t dst, const void* src, uint32_t bytes, uint32_t bar) {
  asm volatile("{ .reg .pred p; .reg .b64 h; createpolicy.fractional.L2::evict_first.b64 h; elect.sync _|p, 0xffffffff;\n"
               "@p cp.async.bulk.shared::cluster.global.mbarrier::complete_tx::bytes.L2::cache_hint [%0], [%1], %2, [%3], h; }"
               :: "r"(dst), "l"(src), "r"(bytes), "r"(bar) : "memory");
}
__device__ __forceinline__ void tma4d_e(uint32_t dst, const CUtensorMap* tm, int c2, int c3, uint32_t bar) {
  asm volatile("{ .reg .pred p; elect.sync _|p, 0xffffffff;\n"
               "@p cp.async.bulk.tensor.4d.shared::cluster.global.mbarrier::complete_tx::bytes [%0], [%1, {0, 0, %3, %4}], [%2]; }"
               :: "r"(dst), "l"(tm), "r"(bar), "r"(c2), "r"(c3) : "memory");
}
__device__ __forceinline__ void bulk_load_e(uint32_t dst, const void* src, uint32_t bytes, uint32_t bar) {
  asm volatile("{ .reg .pred p; elect.sync _|p, 0xffffffff;\n"
               "@p cp.async.bulk.shared::cluster.global.mbarrier::complete_tx::bytes [%0], [%1], %2, [%3]; }"
               :: "r"(dst), "l"(src), "r"(bytes), "r"(bar) : "memory");
}
__device__ __forceinline__ void prefetch2d_e(const CUtensorMap* tm, int c0, int c1) {
  asm volatile("{ .reg .pred p; elect.sync _|p, 0xffffffff;\n"
               "@p cp.async.bulk.prefetch.tensor.2d.L2.global [%0, {%1, %2}]; }" :: "l"(tm), "r"(c0), "r"(c1) : "memory");
}
__device__ __forceinline__ void st_pub4(void* p, uint4 v) {
  asm volatile("st.relaxed.gpu.global.v4.u32 [%0], {%1,%2,%3,%4};" :: "l"(p), "r"(v.x), "r"(v.y), "r"(v.z), "r"(v.w) : "memory");
}
__device__ __forceinline__ void st_pub_if(void* p, uint32_t v, bool on) {
  asm volatile("{ .reg .pred p; setp.ne.u32 p, %2, 0; @p st.relaxed.gpu.global.u32 [%0], %1; }" :: "l"(p), "r"(v), "r"((uint32_t)on) : "memory");
}
__device__ __forceinline__ uint32_t mapa(uint32_t a, uint32_t r) {
  uint32_t d; asm volatile("mapa.shared::cluster.u32 %0, %1, %2;" : "=r"(d) : "r"(a), "r"(r)); return d;
}
__device__ __forceinline__ void st_async4(uint32_t a, uint32_t x, uint32_t y, uint32_t z, uint32_t w, uint32_t bar) {
  asm volatile("st.async.shared::cluster.mbarrier::complete_tx::bytes.v4.u32 [%0], {%1,%2,%3,%4}, [%5];"
               :: "r"(a), "r"(x), "r"(y), "r"(z), "r"(w), "r"(bar) : "memory");
}
__device__ __forceinline__ uint4 ld_poll(const void* p) {
  uint4 v;
  asm volatile("ld.volatile.global.v4.u32 {%0,%1,%2,%3}, [%4];" : "=r"(v.x), "=r"(v.y), "=r"(v.z), "=r"(v.w) : "l"(p) : "memory");
  return v;
}
__device__ __forceinline__ uint2 ld_poll2(const void* p) {
  uint2 v; asm volatile("ld.volatile.global.v2.u32 {%0,%1}, [%2];" : "=r"(v.x), "=r"(v.y) : "l"(p) : "memory"); return v;
}
__device__ __forceinline__ void st_pub2(void* p, uint32_t a, uint32_t b) {
  asm volatile("st.relaxed.gpu.global.v2.u32 [%0], {%1,%2};" :: "l"(p), "r"(a), "r"(b) : "memory");
}
__device__ __forceinline__ uint32_t ld_poll1(const void* p) {
  uint32_t v; asm volatile("ld.volatile.global.u32 %0, [%1];" : "=r"(v) : "l"(p) : "memory"); return v;
}
__device__ __forceinline__ uint32_t ld_acquire(const uint32_t* p) {
  uint32_t v; asm volatile("ld.acquire.gpu.global.u32 %0, [%1];" : "=r"(v) : "l"(p) : "memory"); return v;
}
__device__ __forceinline__ void st_pub(void* p, uint32_t v) {
  asm volatile("st.relaxed.gpu.global.u32 [%0], %1;" :: "l"(p), "r"(v) : "memory");
}
__device__ __forceinline__ uint32_t lds32(uint32_t a) {
  uint32_t v; asm volatile("ld.shared.u32 %0, [%1];" : "=r"(v) : "r"(a) : "memory"); return v;
}
__device__ __forceinline__ int race_init(void* p0, void* p1, uint32_t val) {
  int t;
  asm volatile("{ .reg .pred r; .reg .u32 a, b, u, v;\n"
               "atom.relaxed.gpu.global.exch.b32 u, [%1], %3; atom.relaxed.gpu.global.exch.b32 v, [%2], %3;\n"
               "setp.eq.u32 r, u, 0x12345; @r pmevent 1; mov.u32 a, %%clock;\n"
               "setp.eq.u32 r, v, 0x12345; @r pmevent 1; mov.u32 b, %%clock; sub.u32 %0, b, a; }" : "=r"(t) : "l"(p0), "l"(p1), "r"(val) : "memory");
  return t;
}
__device__ __forceinline__ uint4 lds128(uint32_t a) {
  uint4 v; asm volatile("ld.shared.v4.u32 {%0,%1,%2,%3}, [%4];" : "=r"(v.x), "=r"(v.y), "=r"(v.z), "=r"(v.w) : "r"(a) : "memory"); return v;
}
__device__ __forceinline__ uint2 lds64(uint32_t a) {
  uint2 v; asm volatile("ld.shared.v2.u32 {%0,%1}, [%2];" : "=r"(v.x), "=r"(v.y) : "r"(a) : "memory"); return v;
}
__device__ __forceinline__ void sts128(uint32_t a, uint4 v) {
  asm volatile("st.shared.v4.u32 [%0], {%1,%2,%3,%4};" :: "r"(a), "r"(v.x), "r"(v.y), "r"(v.z), "r"(v.w) : "memory");
}
__device__ __forceinline__ void sts64(uint32_t a, uint32_t x, uint32_t y) { asm volatile("st.shared.v2.u32 [%0], {%1,%2};" :: "r"(a), "r"(x), "r"(y) : "memory"); }
__device__ __forceinline__ void sts32(uint32_t a, uint32_t x) { asm volatile("st.shared.u32 [%0], %1;" :: "r"(a), "r"(x) : "memory"); }
__device__ __forceinline__ void ldsm4t(uint32_t (&r)[4], uint32_t a) {
  asm volatile("ldmatrix.sync.aligned.m8n8.x4.trans.shared.b16 {%0,%1,%2,%3}, [%4];"
               : "=r"(r[0]), "=r"(r[1]), "=r"(r[2]), "=r"(r[3]) : "r"(a) : "memory");
}
template<bool TRANS> __device__ __forceinline__ void stsm4(uint32_t a, uint32_t r0, uint32_t r1, uint32_t r2, uint32_t r3) {
  if (TRANS) asm volatile("stmatrix.sync.aligned.m8n8.x4.trans.shared.b16 [%0], {%1,%2,%3,%4};" :: "r"(a), "r"(r0), "r"(r1), "r"(r2), "r"(r3) : "memory");
  else       asm volatile("stmatrix.sync.aligned.m8n8.x4.shared.b16 [%0], {%1,%2,%3,%4};" :: "r"(a), "r"(r0), "r"(r1), "r"(r2), "r"(r3) : "memory");
}
__device__ __forceinline__ void mma16816(float (&d)[4], uint32_t a0, uint32_t a1, uint32_t a2, uint32_t a3, uint32_t b0, uint32_t b1) {
  asm volatile("mma.sync.aligned.m16n8k16.row.col.f32.bf16.bf16.f32 {%0,%1,%2,%3}, {%4,%5,%6,%7}, {%8,%9}, {%0,%1,%2,%3};"
               : "+f"(d[0]), "+f"(d[1]), "+f"(d[2]), "+f"(d[3]) : "r"(a0), "r"(a1), "r"(a2), "r"(a3), "r"(b0), "r"(b1));
}
__device__ __forceinline__ void mma1688(float (&d)[4], uint32_t a0, uint32_t a1, uint32_t b0) {
  asm volatile("mma.sync.aligned.m16n8k8.row.col.f32.bf16.bf16.f32 {%0,%1,%2,%3}, {%4,%5}, {%6}, {%0,%1,%2,%3};"
               : "+f"(d[0]), "+f"(d[1]), "+f"(d[2]), "+f"(d[3]) : "r"(a0), "r"(a1), "r"(b0));
}
__device__ __forceinline__ uint32_t pack_bf16(float lo, float hi) {
  uint32_t r; asm("cvt.rn.bf16x2.f32 %0, %1, %2;" : "=r"(r) : "f"(hi), "f"(lo)); return r;
}
__device__ __forceinline__ uint32_t add_bf16x2(uint32_t a, uint32_t b) {
  uint32_t r; asm("add.rn.bf16x2 %0, %1, %2;" : "=r"(r) : "r"(a), "r"(b)); return r;
}
__device__ __forceinline__ uint32_t umax4(uint4 v) { return max(max(v.x, v.y), max(v.z, v.w)); }
__device__ __forceinline__ uint32_t opaque(uint32_t x) { uint32_t r; asm volatile("mov.u32 %0, %1;" : "=r"(r) : "r"(x)); return r; }
template<class T> __device__ __forceinline__ void pin(T*& p) { asm volatile("" : "+l"(p)); }
__device__ __forceinline__ void pin(uint32_t& v) { asm volatile("" : "+r"(v)); }
__device__ __forceinline__ uint32_t desc_lo(uint32_t addr) { return ((addr & 0x3FFFF) >> 4) | 0x10000; }
__device__ __forceinline__ uint64_t desc128(uint32_t lo) {
  uint64_t d; asm("mov.b64 %0, {%1, %2};" : "=l"(d) : "r"(lo), "r"(0x40000040)); return d;
}
#define WG_FENCE()  asm volatile("wgmma.fence.sync.aligned;" ::: "memory")
#define WG_COMMIT() asm volatile("wgmma.commit_group.sync.aligned;" ::: "memory")
#define WG_WAIT(n)  asm volatile("wgmma.wait_group.sync.aligned " #n ";" ::: "memory")
#define FENCE_ASYNC_SMEM() asm volatile("fence.proxy.async.shared::cta;" ::: "memory")
__device__ __forceinline__ void bar_sync(int id, int n) { asm volatile("bar.sync %0, %1;" :: "r"(id), "r"(n) : "memory"); }

#define D16(c) c(d[0]), c(d[1]), c(d[2]), c(d[3]), c(d[4]), c(d[5]), c(d[6]), c(d[7]), \
               c(d[8]), c(d[9]), c(d[10]), c(d[11]), c(d[12]), c(d[13]), c(d[14]), c(d[15])
template<bool FIRST> __device__ __forceinline__ void wgmma_rs_n32(float (&d)[16], const uint32_t (&a)[4], uint64_t b) {
  if (FIRST)
    asm volatile("wgmma.mma_async.sync.aligned.m64n32k16.f32.bf16.bf16 {%0,%1,%2,%3,%4,%5,%6,%7,%8,%9,%10,%11,%12,%13,%14,%15}, {%16,%17,%18,%19}, %20, 0, 1, 1, 0;"
      : D16("=f") : "r"(a[0]), "r"(a[1]), "r"(a[2]), "r"(a[3]), "l"(b));
  else
    asm volatile("wgmma.mma_async.sync.aligned.m64n32k16.f32.bf16.bf16 {%0,%1,%2,%3,%4,%5,%6,%7,%8,%9,%10,%11,%12,%13,%14,%15}, {%16,%17,%18,%19}, %20, 1, 1, 1, 0;"
      : D16("+f") : "r"(a[0]), "r"(a[1]), "r"(a[2]), "r"(a[3]), "l"(b));
}
template<bool FIRST> __device__ __forceinline__ void wgmma_ss_n32_ta(float (&d)[16], uint64_t a, uint64_t b) {
  if (FIRST)
    asm volatile("wgmma.mma_async.sync.aligned.m64n32k16.f32.bf16.bf16 {%0,%1,%2,%3,%4,%5,%6,%7,%8,%9,%10,%11,%12,%13,%14,%15}, %16, %17, 0, 1, 1, 1, 0;"
      : D16("=f") : "l"(a), "l"(b));
  else
    asm volatile("wgmma.mma_async.sync.aligned.m64n32k16.f32.bf16.bf16 {%0,%1,%2,%3,%4,%5,%6,%7,%8,%9,%10,%11,%12,%13,%14,%15}, %16, %17, 1, 1, 1, 1, 0;"
      : D16("+f") : "l"(a), "l"(b));
}

struct cf { float x, y; };
__host__ __device__ constexpr float cos64(int k) {
  return k == 0 ? 1.0f : k == 1 ? 0.99518472667219689f : k == 2 ? 0.98078528040323045f : k == 3 ? 0.95694033573220887f :
         k == 4 ? 0.92387953251128676f : k == 5 ? 0.88192126434835503f : k == 6 ? 0.83146961230254524f : k == 7 ? 0.77301045336273696f :
         k == 8 ? 0.70710678118654752f : k == 9 ? 0.63439328416364550f : k == 10 ? 0.55557023301960222f : k == 11 ? 0.47139673682599765f :
         k == 12 ? 0.38268343236508977f : k == 13 ? 0.29028467725446236f : k == 14 ? 0.19509032201612827f : k == 15 ? 0.09801714032956060f : 0.0f;
}
__host__ __device__ constexpr float c64(int k) { return k <= 16 ? cos64(k) : -cos64(32 - k); }
__host__ __device__ constexpr float s64(int k) { return k <= 16 ? cos64(16 - k) : cos64(k - 16); }

template<int N, int ST, bool INV> struct Fft {
  template<int K> static __device__ __forceinline__ void bf(const cf* e, const cf* o, cf* out) {
    if constexpr (K < N / 2) {
      constexpr int idx = K * (64 / N);
      const cf a = e[K], b = o[K];
      if constexpr (idx == 0) {
        out[K] = {a.x + b.x, a.y + b.y}; out[K + N / 2] = {a.x - b.x, a.y - b.y};
      } else if constexpr (idx == 16) {
        if constexpr (INV) { out[K] = {a.x - b.y, a.y + b.x}; out[K + N / 2] = {a.x + b.y, a.y - b.x}; }
        else               { out[K] = {a.x + b.y, a.y - b.x}; out[K + N / 2] = {a.x - b.y, a.y + b.x}; }
      } else {
        constexpr float c = c64(idx), s = INV ? s64(idx) : -s64(idx);
        cf p; p.x = fmaf(-s, b.y, fmaf(c, b.x, a.x)); p.y = fmaf(s, b.x, fmaf(c, b.y, a.y));
        out[K] = p; out[K + N / 2] = {fmaf(2.0f, a.x, -p.x), fmaf(2.0f, a.y, -p.y)};
      }
      bf<K + 1>(e, o, out);
    }
  }
  static __device__ __forceinline__ void run(const cf* in, cf* out) {
    cf e[N / 2], o[N / 2];
    Fft<N / 2, 2 * ST, INV>::run(in, e);
    Fft<N / 2, 2 * ST, INV>::run(in + ST, o);
    bf<0>(e, o, out);
  }
};
template<int ST, bool INV> struct Fft<1, ST, INV> {
  static __device__ __forceinline__ void run(const cf* in, cf* out) { out[0] = in[0]; }
};
template<bool INV> __device__ __forceinline__ void fft32(cf (&v)[32]) {
  cf o[32]; Fft<32, 1, INV>::run(v, o);
#pragma unroll
  for (int i = 0; i < 32; i++) v[i] = o[i];
}
__device__ __forceinline__ cf cmul(cf a, float c, float s) { return {fmaf(-a.y, s, a.x * c), fmaf(a.x, s, a.y * c)}; }
__device__ __forceinline__ float bf2f(__nv_bfloat16 v) { return __bfloat162float(v); }

template<bool INV> __device__ __forceinline__ void warp_fft1024_a(cf (&v)[32], float2* __restrict__ buf, const float2* __restrict__ tw, int t) {
  fft32<INV>(v);
#pragma unroll
  for (int j = 1; j < 32; j++) { const float2 w = tw[j * 32 + t]; v[j] = cmul(v[j], w.x, INV ? -w.y : w.y); }
  if (INV) {
    float* f = (float*)buf;
#pragma unroll
    for (int j = 0; j < 32; j++) f[j * 33 + t] = v[j].x;
    __syncwarp();
#pragma unroll
    for (int j = 0; j < 32; j++) v[j].x = f[t * 33 + j];
    __syncwarp();
#pragma unroll
    for (int j = 0; j < 32; j++) f[j * 33 + t] = v[j].y;
    __syncwarp();
#pragma unroll
    for (int j = 0; j < 32; j++) v[j].y = f[t * 33 + j];
  } else {
#pragma unroll
    for (int j = 0; j < 32; j++) buf[j * 33 + t] = make_float2(v[j].x, v[j].y);
    __syncwarp();
#pragma unroll
    for (int j = 0; j < 32; j++) { const float2 r = buf[t * 33 + j]; v[j] = {r.x, r.y}; }
  }
  __syncwarp();
}
constexpr int ROW_BUF = 32 * 33;

__device__ __forceinline__ int z_row(int p) { return (p & ~31) | (p & 7) << 2 | (p & 31) >> 3; }
template<bool PERM> __device__ __forceinline__ void row_twiddles(float2* tw, int tid, int nthreads) {
  for (int i = tid; i < 1024; i += nthreads) {
    float s, c; sincospif(-(float)((i >> 5) * ((PERM ? z_row(i) : i) & 31)) * (1.0f / 512.0f), &s, &c); tw[i] = make_float2(c, s);
  }
}
__device__ __forceinline__ void fft_rows_fwd(float2* sm2, const __nv_bfloat16* gw, int cta, int tid, uint32_t full_bar, uint32_t release_bar) {
  const int t = tid & 31, w = tid >> 5, n = z_row(cta * 8 + w);
  row_twiddles<false>(sm2, tid, 256);
  mbar_spin(full_bar, 0);
  if (tid == 0) TL2(6);
  __syncwarp();
  const __nv_bfloat16* xa = (const __nv_bfloat16*)(sm2 + 1024 + w * ROW_BUF) + t;
  cf v[32];
  float ga = 0.f, gb = 0.f;
#pragma unroll
  for (int j = 0; j < 32; j++) {
    v[j] = {bf2f(xa[32 * j]), bf2f(xa[D_ + 32 * j])};
    const float g = bf2f(gw[32 * j + t]); ga = fmaf(v[j].x, g, ga); gb = fmaf(v[j].y, g, gb);
  }
#pragma unroll
  for (int o = 16; o; o >>= 1) { ga += __shfl_xor_sync(~0u, ga, o); gb += __shfl_xor_sync(~0u, gb, o); }
  if (t < 2) g_gate[n + 1024 * t] = __fdividef(1.0f, 1.0f + __expf(-(t ? gb : ga)));
  bar_sync(13, 256);
  warp_fft1024_a<false>(v, sm2 + 1024 + w * ROW_BUF, sm2, t);
  FENCE_ASYNC_SMEM();
  mbar_arrive_warp(release_bar);
  fft32<false>(v);
  float ws, wc; sincospif(-(float)n * (1.0f / 1024.0f), &ws, &wc);
  uint32_t tz = clock_lo();
  float4* z = (float4*)g_z + ((size_t)(t >> 1) * 1024 + cta * 8 + w) * 2 + (t & 1);
#pragma unroll
  for (int j = 0; j < 17; j++) {
    cf q = v[(32 - j) & 31];
    if (j < 16) {
      const cf r = {__shfl_sync(~0u, v[31 - j].x, 32 - t), __shfl_sync(~0u, v[31 - j].y, 32 - t)};
      if (t != 0) q = r;
    }
    const cf a = {v[j].x + q.x, v[j].y - q.y}, b = {v[j].y + q.y, q.x - v[j].x};
    const cf d = cmul({a.x - b.x, a.y - b.y}, wc, ws);
    if (PACE_Z && j && j < 16) delay_until(tz += PACE_Z);
    if ((j < 16 || t == 0) && ((EXP_ST & 4) || d.x == 123.f)) z[j * 32768] = make_float4(a.x + b.x, a.y + b.y, d.x, d.y);
  }
}
constexpr int COL_FS = 1057, COL_W = (8192 + 16 * COL_FS * 4 + 127) & ~127, COL_SMEM = COL_W + 131072 + 16;

__device__ __forceinline__ void fft_cols(float2* sm2, int cta, const CUtensorMap* twr, const CUtensorMap* twi) {
  const int grp = __shfl_sync(~0u, (int)(threadIdx.x >> 7), 0), tid = threadIdx.x & 127, tp = tid >> 2, t = z_row(tp);
  float* buf = (float*)(sm2 + 1024) + (grp * 4 + (tid & 3)) * COL_FS;
  const uint32_t wsm = smem_u32(sm2) + COL_W, wbar = wsm + 131072;
  const int res = (tid >> 5) * 2 + (tid & 1), el = res + grp * 2 + ((tid >> 1) & 1);
  uint32_t wa = (el >> 3) * 65536 + res * 4096 + (tp & 7) * 16 + (el & 7) * 2;
  auto load_w = [&](int q) { for (int i = 0; i < 16; i++) tma2d(wsm + (q & 1) * 65536 + i * 4096, i < 8 ? twr : twi, (i & 7) * 512 + q * 8, 0, wbar); };
  if (threadIdx.x == 0) { mbar_init(wbar, 1); sts32(wbar + 8, 0); asm volatile("fence.mbarrier_init.release.cluster;" ::: "memory"); }
  row_twiddles<true>(sm2, threadIdx.x, 512);
  for (uint32_t n = 0; ld_acquire(g_ctl + C_P1) < 128; ) { watchdog(n, 1u << 22); __nanosleep(200); }
  __syncthreads();
  if (threadIdx.x == 0) { mbar_expect(wbar, 131072); load_w(cta * 16); load_w(cta * 16 + 1); }
  __syncwarp();
  delay_cycles(1 + grp * DLY_GRP);
  const int end = cta * 64 + 64 + (cta == 3);
  for (int item = cta * 64 + grp; item < end; item += 4, wa ^= 65536) {
    float2* zp = g_z + (size_t)item * 4096;
    cf v[32];
#pragma unroll
    for (int j = 0; j < 32; j++) { const float2 a = __ldcg(zp + tid + j * 128); v[j] = {a.x, a.y}; }
#pragma unroll 1
    for (int dir = 0; dir < 2; dir++) {
      fft32<false>(v);
#pragma unroll
      for (int j = 1; j < 32; j++) { const float2 w = sm2[j * 32 + tp]; v[j] = cmul(v[j], w.x, w.y); }
      bar_sync(1 + grp, 128);
      if (dir == 1 && tid == 0) {
        uint32_t n; asm volatile("atom.shared.inc.u32 %0, [%1], 3;" : "=r"(n) : "r"(wbar + 8) : "memory");
        if (n == 3 && item - grp + 4 < end) { mbar_expect(wbar, 65536); load_w((item >> 2) + 2); }
      }
      __syncwarp();
#pragma unroll
      for (int j = 0; j < 32; j++) buf[j * 33 + t] = v[j].x;
      bar_sync(1 + grp, 128);
#pragma unroll
      for (int j = 0; j < 32; j++) v[j].x = buf[t * 33 + j];
      bar_sync(1 + grp, 128);
#pragma unroll
      for (int j = 0; j < 32; j++) buf[j * 33 + t] = v[j].y;
      bar_sync(1 + grp, 128);
#pragma unroll
      for (int j = 0; j < 32; j++) v[j].y = buf[t * 33 + j];
      fft32<false>(v);
      if (dir == 0) {
        mbar_wait(wbar, (item >> 2) & 1);
#pragma unroll
        for (int j = 0; j < 32; j++) {
          uint32_t re, im;
          asm volatile("ld.shared.u16 %0, [%1];" : "=r"(re) : "r"(wsm + wa + j * 128) : "memory");
          asm volatile("ld.shared.u16 %0, [%1];" : "=r"(im) : "r"(wsm + wa + 32768 + j * 128) : "memory");
          const cf r = cmul(v[j], __uint_as_float(re << 16), __uint_as_float(im << 16));
          v[j] = {r.y, r.x};
        }
      }
    }
#pragma unroll
    for (int j = 0; j < 32; j++) zp[tid + j * 128] = make_float2(v[j].y, v[j].x);
  }
}

__device__ __forceinline__ void fft_rows_inv(float2* buf, const float2* tw, int p, int t) {
  const int n = z_row(p);
  const float4* z = (const float4*)g_z + ((size_t)(t >> 1) * 1024 + p) * 2 + (t & 1);
  float ws, wc; sincospif((float)n * (1.0f / 1024.0f), &ws, &wc);
  cf v[32], q[17];
#pragma unroll
  for (int j = 0; j < 17; j++) {
    const float4 e = __ldcg(j < 16 ? z + j * 32768 : (const float4*)g_z + ((size_t)256 * 1024 + p) * 2);
    const cf d = cmul({e.z, e.w}, wc, ws);
    cf a = {e.x + d.x, e.y + d.y}, b = {e.x - d.x, e.y - d.y};
    if (j == 16 || (j == 0 && t == 0)) { a.y = 0.f; b.y = 0.f; }
    if (j < 16) v[j] = {a.x - b.y, a.y + b.x};
    q[j] = {a.x + b.y, b.x - a.y};
  }
#pragma unroll
  for (int j = 16; j < 32; j++) {
    v[j] = {__shfl_sync(~0u, q[31 - j].x, 32 - t), __shfl_sync(~0u, q[31 - j].y, 32 - t)};
    if (t == 0) v[j] = q[32 - j];
  }
  warp_fft1024_a<true>(v, buf, tw, t);
  fft32<true>(v);
  const float sc = 0.5f / (2048.0f * 1024.0f);
  __nv_bfloat16* o = g_b + (size_t)n * D_ + t;
#pragma unroll
  for (int j = 0; j < 32; j++) { o[32 * j] = __float2bfloat16(v[j].x * sc); o[1024 * D_ + 32 * j] = __float2bfloat16(v[j].y * sc); }
}

constexpr int NP = NP_, NHV = REG_F == 216 ? 5 : 7, NV = 16 - NHV;
constexpr int XEND = NSEG;
constexpr uint32_t SM_WO = 0, SM_V = 65536, SM_LAND = SM_V + 8192, SM_MEM = SM_LAND + 24576, SM_SP = SM_MEM, SM_SPM = SM_MEM + 5120, SM_OM = SM_MEM + 6144,
                   SM_OX = SM_MEM + 8192, SM_RED = SM_OX + 2048, SM_XCH = SM_RED + 1024, SM_SUM = SM_XCH + 4096, SM_VM = SM_SUM + 128, SM_TAB = SM_VM + 2048, SM_TRACE = SM_TAB + 2048,
                   ST_WG = (32 - NP + NV) * 2048,
                   SM_XT = 2 * ST_WG, SM_POOL = SM_XT + 32768, SM_HV = SM_POOL + 2 * NP * 2048,
                   SM_BAR = SM_HV + 2 * NHV * 2048, SM_SEL = SM_BAR + 320, CHAIN_SMEM = SM_SEL + 544;
constexpr uint32_t SM_GW = 74 * 1024;
static_assert(NP % 4 == 0 && NV == 11 && SM_TRACE + 4096 <= SM_XT, "shared memory layout");
static_assert(CHAIN_SMEM <= 232448 && COL_SMEM <= CHAIN_SMEM && (1024 + 8 * ROW_BUF) * 8 <= SM_GW && SM_GW + 2048 > ST_WG, "shared memory budget");
enum { B_WFULL = 0, B_WREAD = 2, B_WOFULL, B_XFULL, B_XEMPTY, B_E1TRIG, B_E2TRIG, B_PVDONE, B_PUB, B_SC, B_MEM, B_SPFREE,
       B_LAND, B_LFREE, B_DONE, B_SEL, B_PROBE, B_FREE, B_P1, B_ROWS, B_VFULL, B_VST, B_END };
static_assert(B_END * 8 <= 320, "barriers");

struct ChainCtx { char* mail; uint32_t sb, sel; int r, h, a, b, j, m, w, lane; };
#define BAR(i) (c.sb + SM_BAR + 8 * (i))

__device__ __forceinline__ uint32_t tile_off(int line, int lane) {
  return line * 128 + (((lane & 3) ^ line) << 5) + (lane >> 2) * 4;
}
__device__ __forceinline__ uint32_t read_off(int lane) {
  const int n = lane >> 2, jj = lane & 3, l = 2 * (jj >> 1) + (n & 1);
  return l * 128 + (((n >> 1) ^ l) << 5) + (jj & 1) * 16;
}
__device__ __forceinline__ uint32_t frag_off(int w, int lane) {
  const int mi = lane >> 3, r = lane & 7;
  return ((mi >> 1) * 8 + r) * 128 + (((2 * w + (mi & 1)) ^ r) << 4);
}
__device__ __forceinline__ uint32_t land_off(int w, int lane) { return w * 512 + ((lane ^ (((lane >> 4) | ((w & 1) << 1)) << 1)) << 4); }
__device__ __forceinline__ uint32_t tagged(uint32_t v, uint32_t tag) { return (v | 1u) ^ tag; }
__device__ __forceinline__ void mma_a(float (&d)[4], const uint32_t (&a)[4], uint32_t b0, uint32_t b1) { mma16816(d, a[0], a[1], a[2], a[3], b0, b1); }
__device__ __forceinline__ void mma_q(float (&d)[4], const uint4& a, uint32_t b0, uint32_t b1) { mma16816(d, a.x, a.y, a.z, a.w, b0, b1); }
__device__ __forceinline__ uint4 add4(uint4 a, uint4 b) {
  return make_uint4(add_bf16x2(a.x, b.x), add_bf16x2(a.y, b.y), add_bf16x2(a.z, b.z), add_bf16x2(a.w, b.w));
}
__device__ __forceinline__ void mbar_arrive_both(uint32_t bar, int peer) {
  __syncwarp();
  asm volatile("{ .reg .pred p; .reg .u32 a; mapa.shared::cluster.u32 a, %0, %1; elect.sync _|p, 0xffffffff;\n"
               "@p mbarrier.arrive.shared::cta.b64 _, [%0]; @p mbarrier.arrive.shared::cluster.b64 _, [a]; }" :: "r"(bar), "r"(peer) : "memory");
}

__device__ __forceinline__ int lane_id() {
  int l; asm volatile("{ .reg .u32 t; mov.u32 t, %%laneid; shfl.sync.idx.b32 %0, t, t, 31, 0xffffffff; }" : "=r"(l)); return l;
}
__device__ __forceinline__ uint32_t tid_now() { uint32_t t; asm volatile("mov.u32 %0, %%tid.x;" : "=r"(t)); return t; }
enum { NB_ATT = 1, NB_OM = 2, NB_VM = 3, NB_XCH = 4, NB_MEM = 8, NB_HELP = 12 };
__device__ __forceinline__ uint32_t dep(uint32_t a, uint32_t v, uint32_t z) { uint32_t r; asm("shf.l.wrap.b32 %0, %2, %1, %3;" : "=r"(r) : "r"(a), "r"(v), "r"(z)); return r; }
__device__ __forceinline__ uint32_t vary(uint32_t a, int s, uint32_t z) { return dep(a, 0, z + 32 * s); }
__device__ __forceinline__ char* mk_ptr(uint32_t lo, uint32_t hi) { uint64_t r; asm("mov.b64 %0, {%1, %2};" : "=l"(r) : "r"(lo), "r"(hi)); return (char*)r; }
__device__ __forceinline__ void lds_frag(uint32_t (&r)[4], uint32_t a) {
  asm volatile("ld.shared.v4.u32 {%0,%1,%2,%3}, [%4];" : "=r"(r[0]), "=r"(r[1]), "=r"(r[2]), "=r"(r[3]) : "r"(a) : "memory");
}
__device__ __forceinline__ uint32_t stale2(uint32_t a, uint32_t b, uint32_t t) { uint32_t r; asm("lop3.b32 %0, %1, %2, %3, 0xbd;" : "=r"(r) : "r"(a), "r"(b), "r"(t)); return r; }
__device__ __forceinline__ uint32_t stale1(uint32_t acc, uint32_t a, uint32_t t) { uint32_t r; asm("lop3.b32 %0, %1, %2, %3, 0xf9;" : "=r"(r) : "r"(acc), "r"(a), "r"(t)); return r; }
__device__ __forceinline__ bool all_clear(uint32_t x, uint32_t m) {
  uint32_t r;
  asm volatile("{ .reg .pred p; .reg .u32 t; and.b32 t, %1, %2; setp.eq.u32 p, t, 0; vote.sync.all.pred p, p, 0xffffffff; selp.u32 %0, 1, 0, p; }" : "=r"(r) : "r"(x), "r"(m));
  return r;
}
__device__ __forceinline__ bool arrive_if_all(bool ok, int id, int n) {
  uint32_t r;
  asm volatile("{ .reg .pred p, q; setp.ne.u32 p, %1, 0; vote.sync.all.pred q, p, 0xffffffff; @q bar.arrive %2, %3; selp.u32 %0, 1, 0, q; }"
               : "=r"(r) : "r"((uint32_t)ok), "r"(id), "r"(n) : "memory");
  return r;
}
__device__ __forceinline__ bool arrive_if_clear(uint32_t x, uint32_t m, int id, int n) {
  uint32_t r;
  asm volatile("{ .reg .pred p; .reg .u32 t; and.b32 t, %1, %2; setp.eq.u32 p, t, 0; vote.sync.all.pred p, p, 0xffffffff; @p bar.arrive %3, %4; selp.u32 %0, 1, 0, p; }"
               : "=r"(r) : "r"(x), "r"(m), "r"(id), "r"(n) : "memory");
  return r;
}
__device__ __forceinline__ void touch(const void* p, uint32_t z) {
  asm volatile("{ .reg .pred p; setp.eq.u32 p, %1, 0x7fff0000; @p prefetch.global.L2 [%0]; }" :: "l"(p), "r"(z) : "memory");
}

__device__ __forceinline__ uint64_t desc_x(uint32_t lo, int k) {
  uint64_t d; asm("mov.b64 %0, {%1, %2};" : "=l"(d) : "r"(lo + (k >> 2) * 64 + (k & 3) * 2), "r"(0x40000200)); return d;
}
template<int K0, int K1> __device__ __forceinline__ void issue_qk(float (&xa)[16], const uint32_t (&wt)[16][4], uint32_t lo) {
  WG_FENCE();
#pragma unroll
  for (int k = K0; k < K1; k++) {
    if (k >= EXP_NWG) continue;
    if (k == 0) wgmma_rs_n32<true>(xa, wt[0], desc_x(lo, 0));
    else wgmma_rs_n32<false>(xa, wt[k], desc_x(lo, k));
  }
  WG_COMMIT();
}
__host__ __device__ constexpr int v_order(int i) { return SSPOS == 0 ? i : SSPOS == 2 ? (i + NV) % 16 : NHV == 5 ? (i % 3 == 2 ? NV + i / 3 : i - i / 3) : (i == 15 ? NV - 1 : i % 2 ? NV + i / 2 : i / 2); }
__device__ __forceinline__ void issue_v(float (&xa)[16], const uint32_t (&wv)[16][4], uint32_t lo, uint32_t la) {
  WG_FENCE();
#pragma unroll
  for (int i = 0; i < EXP_NWG; i++) {
    const int k = v_order(i);
    const uint64_t b = desc_x(lo, k);
    if (k < NV) { if (i == 0) wgmma_rs_n32<true>(xa, wv[k], b); else wgmma_rs_n32<false>(xa, wv[k], b); }
    else        { if (i == 0) wgmma_ss_n32_ta<true>(xa, desc128(la + (k - NV) * 128), b); else wgmma_ss_n32_ta<false>(xa, desc128(la + (k - NV) * 128), b); }
  }
  WG_COMMIT();
}
template<bool ISV> __device__ __forceinline__ void park_own(uint32_t (&q)[4], float (&xa)[16], uint32_t dst, int slot, uint32_t z) {
  uint32_t p[8];
#pragma unroll
  for (int i = 0; i < 16; i++) asm volatile("" : "+f"(xa[i]) :: "memory");
#pragma unroll
  for (int i = 0; i < 2; i++) {
    const float* k = xa + 8 * i;
    if (ISV) { p[4 * i] = pack_bf16(k[0], k[1]); p[4 * i + 1] = pack_bf16(k[2], k[3]); p[4 * i + 2] = pack_bf16(k[4], k[5]); p[4 * i + 3] = pack_bf16(k[6], k[7]); }
    else     { p[4 * i] = pack_bf16(k[0], k[2]); p[4 * i + 1] = pack_bf16(k[1], k[3]); p[4 * i + 2] = pack_bf16(k[4], k[6]); p[4 * i + 3] = pack_bf16(k[5], k[7]); }
  }
  sts128(dep(dep(dst, p[4] ^ p[5] ^ p[6], z), p[7], z) + slot * 8192, make_uint4(p[0], p[1], p[2], p[3]));
#pragma unroll
  for (int i = 0; i < 4; i++) q[i] = p[4 + i];
}
__device__ __forceinline__ void park_peer(const uint32_t (&q)[4], uint32_t dst, int slot, const ChainCtx& c) {
  const uint32_t bar = BAR(B_LAND);
  if (EXP_PEER) st_async4(mapa(dst + slot * 8192, c.b ^ 1), q[0], q[1], q[2], q[3], mapa(bar, c.b ^ 1));
  else touch((void*)(uintptr_t)(q[0] ^ q[1] ^ q[2] ^ q[3]), c.sb);
  mbar_arrive_warp(bar);
}
__device__ __forceinline__ uint32_t put_tag(uint32_t v, uint32_t bit, uint32_t t) {
  uint32_t r; asm("lop3.b32 %0, %1, %2, %3, 0x74;" : "=r"(r) : "r"(v), "r"(bit), "r"(t)); return r;
}
__device__ __forceinline__ void mem_proj(const uint32_t (&wa)[16][4], const uint32_t (&wb)[16][4], uint32_t (&wv)[16][4], uint32_t (&af)[16][4],
                                         uint32_t& wo, const char*& pa, uint32_t tab, uint32_t t16, uint32_t pk, const ChainCtx& c, int s) {
  const uint32_t mp = t16 & ~0x600u, id = NB_MEM + (t16 >> 11);
  uint32_t r[8][4];
  float la[4][4] = {}, lg[NLAG][4] = {}, lv[4][4] = {};
  auto lead = [&](int k) { mma_a(la[k & 3], wa[k], r[k >> 1][2 * (k & 1)], r[k >> 1][2 * (k & 1) + 1]); };
  auto lag = [&](int k) { mma_a(lg[k % NLAG], wb[k], r[k >> 1][2 * (k & 1)], r[k >> 1][2 * (k & 1) + 1]); };
  auto sum = [](const float (&d)[4][4], int i) { return (d[0][i] + d[1][i]) + (d[2][i] + d[3][i]); };
  bar_sync(id, 160);
  TR(s, 0);
#pragma unroll
  for (int i = 0; i < 4; i++) ldsm4t(r[i], mp + (c.sb + SM_MEM + i * 512));
  const uint4 tq = lds128(tab);
  bar_sync(id + 2, 160);
#pragma unroll
  for (int k = 0; k < 8; k++) lead(k);
  const uint32_t ta = tq.x | ((pk >> 16) & 511), tb = tq.z ^ ((pk >> 16) & 511);
  char* dst = mk_ptr(ta, tq.y);
  char* dst2 = mk_ptr(tb, tq.w);
  const uint32_t mp1 = dep(mp, __float_as_uint(la[C1_AT][0]) ^ ta ^ tb, c.sb);
#pragma unroll
  for (int i = 4; i < 8; i++) ldsm4t(r[i], mp1 + (c.sb + SM_MEM + 2048 + i * 512));
  const uint32_t hv = pk & 0xFFFF;
#pragma unroll
  for (int k = NV; k < NV + HV_E; k++) ldsm4t(wv[k], dep(hv, r[HV_R][0], c.sb) + (c.sb + SM_HV + (k - NV) * 2048));
#pragma unroll
  for (int k = 0; k < 8; k++) lag(k);
#pragma unroll
  for (int k = 8; k < 16; k++) lead(k);
  sts128((HV_E ? dep(t16, wv[NV][0] ^ wv[NV + HV_E / 2][1] ^ wv[NV + HV_E - (HV_E > 0)][2], c.sb) : t16) + (c.sb + SM_XCH), make_uint4(__float_as_uint(sum(la, 0)), __float_as_uint(sum(la, 1)), __float_as_uint(sum(la, 2)), __float_as_uint(sum(la, 3))));
  bar_sync(NB_XCH | ((t16 >> 9) & 3), 64);
  const uint4 o = lds128((t16 ^ 2048) + (c.sb + SM_XCH));
#pragma unroll
  for (int k = 8; k < 16; k++) lag(k);
  float t[4];
#pragma unroll
  for (int i = 0; i < 4; i++) {
    const float oi = __uint_as_float(i == 0 ? o.x : i == 1 ? o.y : i == 2 ? o.z : o.w);
    t[i] = NLAG == 4 ? (((lg[0][i] + lg[1][i]) + lg[2 % NLAG][i]) + lg[3 % NLAG][i]) + oi : NLAG == 3 ? (lg[1][i] + lg[2 % NLAG][i]) + (lg[0][i] + oi) : (lg[0][i] + oi) + lg[1][i];
  }
  const uint32_t y0 = put_tag(pack_bf16(t[0], t[2]), pk >> 31, s >> 1), y1 = put_tag(pack_bf16(t[1], t[3]), pk >> 31, s >> 1);
  st_pub(dst, y0); st_pub(dst2, y1);
  mbar_arrive_warp(BAR(B_E1TRIG));
  TR(s, 1);
  sched_fence(c.sb);
  const uint4 tv = lds128(tab + 16);
#pragma unroll
  for (int k = NV + HV_E; k < 16; k++) ldsm4t(wv[k], (k < NV + HV_E + HV_D ? hv : dep(hv, k == NV + HV_E + HV_D ? wv[k - HV_D][0] ^ tv.x : wv[k - HV_D][0], c.sb)) + (c.sb + SM_HV + (k - NV) * 2048));
  wo = (hv & 2047) | ((t16 & 2048) << 3);
  const uint32_t l8 = (t16 >> 1) & 255;
  char* dv = mk_ptr(tv.x | l8, tv.y);
  pa = mk_ptr(tv.z | l8, tv.w);
#pragma unroll
  for (int f = 0; f < WO_0; f++) ldsm4t(af[f], dep(wo, f < WO_D ? wv[16 - WO_D + f][0] : af[f < WO_D ? 0 : f - WO_D][0], c.sb) + (c.sb + SM_WO + (f & 1) * 32768 + (f >> 1) * 2048));
#pragma unroll
  for (int k = 0; k < 16; k++) mma_a(lv[k & 3], wv[k], r[k >> 1][2 * (k & 1)], r[k >> 1][2 * (k & 1) + 1]);
  const uint32_t z0 = put_tag(pack_bf16(sum(lv, 0), sum(lv, 1)), (~t16 >> 4) & 1, s >> 1), z1 = pack_bf16(sum(lv, 2), sum(lv, 3));
  st_pub2(dv, z0, z1);
  if (FIN_AT >= 3) mbar_arrive_warp(BAR(B_VST));
  TR(s, 2);
}
__device__ __forceinline__ uint32_t max_bf16x2(uint32_t a, uint32_t b) { uint32_t r; asm("max.bf16x2 %0, %1, %2;" : "=r"(r) : "r"(a), "r"(b)); return r; }
constexpr float SCL = 0.08838834764831845f * 1.4426950408889634f;
__device__ __forceinline__ uint32_t max5(const uint32_t (&sc)[5]) { return max_bf16x2(max_bf16x2(max_bf16x2(max_bf16x2(sc[0], sc[1]), sc[2]), sc[3]), sc[4]); }
__device__ __forceinline__ float row_off(uint32_t m, uint32_t& m1) {
  m1 = __shfl_xor_sync(~0u, m, 1);
  const uint32_t m2 = __shfl_xor_sync(~0u, m, 2), m3 = __shfl_xor_sync(~0u, m, 3);
  const uint32_t mm = max_bf16x2(max_bf16x2(max_bf16x2(m, m1), m2), m3);
  return -SCL * fmaxf(__uint_as_float(mm << 16), __uint_as_float(mm & 0xFFFF0000u));
}
__device__ __forceinline__ void unpack(float (&f)[10], const uint32_t (&sc)[5]) {
#pragma unroll
  for (int i = 0; i < 5; i++) {
    asm volatile("shl.b32 %0, %1, 16;" : "=f"(f[2 * i]) : "r"(sc[i]));
    asm volatile("and.b32 %0, %1, 0xffff0000;" : "=f"(f[2 * i + 1]) : "r"(sc[i]));
  }
}
__device__ __forceinline__ uint32_t exp_pair(const float (&f)[10], int i, float off) {
  return pack_bf16(ex2(fmaf(f[2 * i], SCL, off)), ex2(fmaf(f[2 * i + 1], SCL, off)));
}
template<bool SPLIT> __device__ __forceinline__ void scores_x(float (&a)[2][4], const uint4 (&kf)[4], const uint4& q, uint32_t z) {
#pragma unroll
  for (int t = 0; t < 2; t++) { a[t][0] = a[t][1] = a[t][2] = a[t][3] = 0.f; }
  mma_q(a[0], kf[0], q.x, q.y); mma_q(a[1], kf[2], q.x, q.y);
  if (SPLIT) sched_fence(z);
  mma_q(a[0], kf[1], q.z, q.w); mma_q(a[1], kf[3], q.z, q.w);
}
__device__ __forceinline__ uint32_t scores_m(const uint4& q, const uint4& k) {
  float a[4] = {}, b[4] = {};
  mma_q(a, q, k.x, k.z); mma_q(b, q, k.y, k.w);
  return pack_bf16(a[0] + b[2], a[1] + b[3]);
}
__device__ __forceinline__ void store_scores(const float (&a)[2][4], uint32_t dst) {
  sts64(dst, pack_bf16(a[0][0], a[0][2]), pack_bf16(a[1][0], a[1][2]));
  sts64(dst + 320, pack_bf16(a[0][1], a[0][3]), pack_bf16(a[1][1], a[1][3]));
}
__device__ __forceinline__ uint32_t sum4(uint32_t a, uint32_t b, uint32_t d, uint32_t e) { return add_bf16x2(add_bf16x2(a, b), add_bf16x2(d, e)); }
__device__ __forceinline__ void load_scores(uint32_t (&sc)[5], uint32_t ax, uint32_t am) {
  uint4 p[4];
#pragma unroll
  for (int i = 0; i < 4; i++) p[i] = lds128(ax + i * 1280);
  const uint2 m0 = lds64(am), m1 = lds64(am + 256);
  const uint4 t = add4(add4(add4(p[0], p[1]), p[2]), p[3]);
  sc[1] = t.x; sc[2] = t.y; sc[3] = t.z; sc[4] = t.w;
  sc[0] = sum4(m0.x, m0.y, m1.x, m1.y);
}
constexpr uint32_t ONES = 0x3F803F80u;
__device__ __forceinline__ float pv(float (&o)[2][4], const uint32_t (&p)[5], const uint4 (&vf)[4], const uint4& vm) {
  float a[4] = {}, b[4] = {};
#pragma unroll
  for (int t = 0; t < 2; t++) { o[t][0] = o[t][1] = o[t][2] = o[t][3] = 0.f; }
  mma_q(o[0], vf[0], p[1], p[2]); mma_q(o[1], vf[2], p[1], p[2]);
  mma_q(o[0], vf[1], p[3], p[4]); mma_q(o[1], vf[3], p[3], p[4]);
  mma16816(a, p[1], p[2], p[3], p[4], ONES, ONES);
  mma1688(o[0], vm.x, vm.y, p[0]); mma1688(o[1], vm.z, vm.w, p[0]);
  mma1688(b, p[0], ONES, ONES);
  return (a[0] + a[2]) + b[0];
}
constexpr uint32_t POLL_LIMIT = 1u << 21;
__device__ __forceinline__ void probe_pair(const ChainCtx& c, uint32_t off, int i, uint32_t val) {
  if (c.lane == 0) {
    char* pa = c.mail + off;
    int far1 = 0;
#pragma unroll 1
    for (int rep = 0; rep <= NPROBE; rep++) {
      const int lag = race_init(pa + (rep & 1) * 4096, pa + (~rep & 1) * 4096, val);
      if (rep) far1 += (rep & 1 ? -1 : 1) * min(lag, 200);
    }
    sts32(c.sb + SM_SEL + 512 + i * 4, AWARE && far1 < 0 ? 1u << i : 0u);
  }
}

__global__ void __cluster_dims__(2, 1, 1) __launch_bounds__(512, 1)
chain_kernel(const __grid_constant__ CUtensorMap tq, const __grid_constant__ CUtensorMap tk, const __grid_constant__ CUtensorMap tv,
             const __grid_constant__ CUtensorMap tv16, const __grid_constant__ CUtensorMap to, const __grid_constant__ CUtensorMap tx,
             const __grid_constant__ CUtensorMap twr, const __grid_constant__ CUtensorMap twi,
             const __nv_bfloat16* __restrict__ mem0, char* __restrict__ mail, const __nv_bfloat16* __restrict__ x,
             const __nv_bfloat16* __restrict__ gw) {
  extern __shared__ __align__(1024) unsigned char smraw[];
  pdl_launch();
  if (threadIdx.x == 0) TL(0);
  if (blockIdx.x >= 128) {
    if (blockIdx.x == 128) g_ctl[C_ROWS + threadIdx.x] = 0;
    fft_cols((float2*)smraw, blockIdx.x - 128, &twr, &twi);
    if ((threadIdx.x & 127) == 0) TL(7);
    return;
  }
  ChainCtx c;
  c.sb = __shfl_sync(~0u, smem_u32(smraw), 0);
  c.mail = mail; c.sel = 0; c.r = blockIdx.x;
  c.h = c.r >> 2; c.a = (c.r >> 1) & 1; c.b = c.r & 1; c.j = c.r & 3;
  c.m = __shfl_sync(~0u, (int)(threadIdx.x >> 7), 0); c.w = __shfl_sync(~0u, (int)((threadIdx.x >> 5) & 3), 0);
  if (threadIdx.x < B_END) {
    const int i = threadIdx.x;
    const uint32_t n = i == B_LAND ? 25 : i == B_DONE ? 12 :
                       (i == B_WREAD || i == B_XEMPTY || i == B_E1TRIG || i == B_E2TRIG || i == B_LFREE || i == B_FREE || i == B_PROBE || i == B_VST || i == B_P1) ? 8 :
                       (i == B_PVDONE || i == B_PUB || i == B_SC || i == B_MEM || i == B_SPFREE) ? 4 : 1;
    mbar_init(BAR(i), n);
    asm volatile("fence.mbarrier_init.release.cluster;" ::: "memory");
  }
  __syncthreads();
  asm volatile("barrier.cluster.arrive.relaxed.aligned;" ::: "memory");

  if (c.m == 3) {
    asm volatile("setmaxnreg.dec.sync.aligned.u32 %0;" :: "n"(REG_H));
    c.lane = lane_id();
    if (c.sb & 1023) asm volatile("trap;");
    const int col = c.h * 128 + c.a * 64;
    {
      char* own = c.mail + (uint32_t)(M_E3 + (c.w * 4 + (c.r >> 5)) * 8192 + (c.r & 31) * 128 + c.lane * 4);
      race_init(own, own + 4096, SENT);
      mbar_arrive_warp(BAR(B_PROBE));
    }
    uint32_t tl = 0;
    if (c.w == 0) {
      if (HOLD == 2) mbar_wait(BAR(B_PROBE), 0);
      if (HOLD == 3) mbar_wait(BAR(B_SEL), 0);
      mbar_expect_e(BAR(B_ROWS), 32768 + 2048);
      for (int i = 0; i < 16; i++) bulk_load_e(c.sb + (1024 + (i >> 1) * ROW_BUF) * 8 + (i & 1) * 2048, x + (size_t)(z_row(c.r * 8 + (i >> 1)) + (i & 1) * 1024) * D_, 2048, BAR(B_ROWS));
      bulk_load_e(c.sb + SM_GW, gw, 2048, BAR(B_ROWS));
      if (HOLD == 1) mbar_wait(BAR(B_PROBE), 0);
      tl = clock_lo();
      mbar_expect_e(BAR(B_WFULL), 48 * 2048);
      mbar_expect_e(BAR(B_WFULL + 1), 48 * 2048);
    }
    auto dst_x = [&](int e, int w) {
      const uint32_t g2 = 2 * c.a + (w >> 1), u = w & 1;
      return M_KVQ + c.h * 24576 + (e == 0 ? 8192 + (2 * u + c.b) * 2048 + g2 * 512 : e == 1 ? g2 * 2048 + u * 1024 + c.b * 128 : 16384 + c.b * 4096 + g2 * 512 + u * 256);
    };
    if (c.w == 0) {
      tl += PACE0;
      constexpr int P = NP / 4, LATE = P + 13 - (SM_GW + 2048 - ST_WG + 8191) / 8192;
      for (int i = 0; i < 24; i++) {
        const int m = i > P && i < P + 13, k = i <= P ? i : m ? i - P - 1 : i - 12;
        const int row = c.b * 512 + m * 256;
        const uint32_t st = c.sb + m * ST_WG, bar = BAR(B_WFULL + m);
        if (PACE) delay_until(tl += PACE);
        if (i == LATE) { mbar_wait(BAR(B_FREE), 0); if (c.lane == 0) TL2(2); __syncwarp(); }
        if (k < P) TMA_W(c.sb + SM_POOL + m * NP * 2048 + k * 8192, m ? &tq : &tk, col, row + k * 64, bar);
        else if (k == P) TMA_W(c.sb + SM_HV + (m * NHV + 1) * 2048, &tv, col, row + 192, bar);
        else if (k == P + 1) for (int j = 8; j < 12; j++) TMA_W(j < NV ? st + (32 - NP + j) * 2048 : c.sb + SM_HV + m * NHV * 2048, &tv16, col, row + j * 16, bar);
        else if (k < P + 4) TMA_W(st + (32 - NP) * 2048 + (k - P - 2) * 8192, &tv, col, row + (k - P - 2) * 64, bar);
        else if (k < 8) TMA_W(st + (k - P) * 8192, m ? &tq : &tk, col, row + (k - 4) * 64, bar);
        else TMA_W(st + (11 - k) * 8192, m ? &tk : &tq, col, row + (11 - k) * 64, bar);
      }
    } else if (c.w == 3) {
      mbar_wait(BAR(B_FREE), 0);
      mbar_expect_e(BAR(B_XFULL), 32768);
      for (int i = 0; i < 2; i++) tma4d_e(c.sb + SM_XT + i * 16384, &tx, c.b * 8, 2 * (c.b ^ i), BAR(B_XFULL));
    } else if (c.w == 1) {
      mbar_wait(BAR(B_P1), 0);
      if (P1_AT) { mbar_wait(BAR(B_WFULL), 0); mbar_wait(BAR(B_WFULL + 1), 0); }
      asm volatile("fence.acq_rel.gpu;" ::: "memory");
      asm volatile("{ .reg .pred p; elect.sync _|p, 0xffffffff; @p red.relaxed.gpu.global.add.u32 [%0], 1; }" :: "l"(g_ctl + C_P1) : "memory");
    }
    asm volatile("barrier.cluster.wait;" ::: "memory");
    mbar_wait(BAR(B_WREAD), 0);
    mbar_arrive_both(BAR(B_LFREE), c.b ^ 1);
    if (c.w == 0) {
      mbar_expect_e(BAR(B_WOFULL), 65536);
      for (int i = 0; i < 4; i++) TMA_O(c.sb + SM_WO + i * 16384, &to, c.j * 256 + i * 64, c.h * 128, BAR(B_WOFULL));
    }
    {
      const int ln = tid_now() & 31, e = (ln >> 2) & 3, w = (tid_now() >> 5) & 3;
      const uintptr_t ad = (uintptr_t)(c.mail + (uint32_t)(dst_x(e, w) + (ln & 3) * 32 * 24576));
      sts64(c.sb + SM_TAB + 1536 + (ln & 3) * 128 + w * 32 + e * 8, (uint32_t)ad, (uint32_t)(ad >> 32));
      __syncwarp();
    }
    {
      mbar_wait(BAR(B_SEL), 0);
      const int ln = tid_now() & 31, sl = ln & 3, e = (ln >> 2) & 3;
      const uint32_t t = c.sb + SM_SEL, own = lds32(t + c.r * 4);
      uint32_t votes = 0;
      for (int i = 0; i < 7; i++) { const uint32_t v = lds32(t + (sl * 4 + 2 * c.b + (c.w >> 1) + 16 * i) * 4); votes += ((v >> 2) ^ (v >> 3)) & 1; }
      const uint32_t off = e == 0 ? M_PAIR + ((~sl & 1) * 128 + c.r) * 8192 + ((own >> (~sl & 1)) & 1) * 4096 + c.w * 1024
                         : e == 2 ? M_E3 + (sl * 4 + c.b * 2 + (c.w >> 1)) * 8192 + (((votes >= 4 ? 1u : 0u) ^ (own >> 3)) & 1) * 4096 + (c.w & 1) * 2048
                         : M_E3 + ((sl ^ (e & 2)) * 4 + (c.r >> 5)) * 8192 + (c.w & 1) * 4096 + (c.r & 31) * 128;
      const uintptr_t ad = (uintptr_t)(c.mail + off);
      sts64(c.sb + SM_TAB + 1024 + sl * 128 + c.w * 32 + e * 8, (uint32_t)ad, (uint32_t)(ad >> 32));
      {
        const int i = tid_now() & 127, e = i & 7, w = (i >> 3) & 3, m = (i >> 5) & 1, sl = i >> 6;
        const int cta = e < 2 ? c.r & ~1 : e == 2 ? c.r | 1 : e == 3 ? c.h * 4 + 2 * m + 1 : c.j * 32 + m * 8 + 2 * w + (e & 2) * 8 + (e & 1);
        const uint32_t off = e < 2 ? c.b * 2048 + m * 1024 + (w >> 1) * 512 + e * 160 : e == 2 ? c.b * 2048 + m * 1024 + w * 256 : e == 3 ? w * 256 : c.h * 128;
        const uintptr_t ad = (uintptr_t)(c.mail + (uint32_t)(M_PAIR + (sl * 128 + cta) * 8192 + (((lds32(t + cta * 4) >> sl) ^ (e < 4)) & 1) * 4096 + off));
        sts64(c.sb + SM_TAB + i * 8, (uint32_t)ad, (uint32_t)(ad >> 32));
      }
      if (tid_now() == 384) TL2(25);
      __syncwarp();
      bar_sync(NB_HELP, 128);
    }
    for (int s = -1; s < NSEG; s++) {
      if (s >= 0) {
        const uint32_t tab = c.sb + SM_TAB + 1024 + (s & 3) * 128 + c.w * 32;
        uint32_t t0;
        if (s > 0) {
          const uint32_t ln = tid_now() & 31;
          const uint4 ta = lds128(tab);
          const char* src = mk_ptr(ta.x | ln * 4, ta.y);
          char* dst = mk_ptr(ta.z | ln * 4, ta.w);
          const uint32_t tg = (s - 1) >> 1, chk = (ln & 3) ? 0u : 1u, red = ln * (RED_L == 3 ? 4 : 8);
          touch(src, dep(c.sb, chk, c.sb)); touch(dst, dep(c.sb, red, c.sb));
          mbar_wait(BAR(B_E2TRIG), (s - 1) & 1);
          TR(s, 0);
          if (ANCH2) delay_until(lds32(c.sb + SM_SUM + 64) + DLY_E2); else delay_cycles(DLY_E2);
          uint32_t n = 0;
          while (true) {
            uint32_t v[8];
#pragma unroll
            for (int i = 0; i < 8; i++) v[i] = ld_poll1(src + i * 128);
            if (E2_F) sched_fence(c.sb);
            const uint32_t bad = RED_T ? (stale2(v[0], v[1], tg) | stale2(v[2], v[3], tg) | stale2(v[4], v[5], tg)) | stale2(v[6], v[7], tg)
                                       : stale1(stale1(stale2(v[0], v[1], tg), v[2], tg), v[3], tg) | stale1(stale1(stale2(v[4], v[5], tg), v[6], tg), v[7], tg);
            const bool ok = all_clear(bad, chk);
#pragma unroll
            for (int l = 0; l < RED_L; l++)
#pragma unroll
              for (int i = 0; i < (4 >> l); i++) v[i] = add_bf16x2(v[2 * i], v[2 * i + 1]);
            if (RED_L == 3) sts32(red + (c.sb + SM_RED + c.w * 128), v[0]);
            else {
              float lo[8], hi[8];
#pragma unroll
              for (int i = 0; i < (8 >> RED_L); i++) { lo[i] = __uint_as_float(v[i] << 16); hi[i] = __uint_as_float(v[i] & 0xFFFF0000u); }
#pragma unroll
              for (int l = RED_L; l < 3; l++)
#pragma unroll
                for (int i = 0; i < (4 >> l); i++) { lo[i] = lo[2 * i] + lo[2 * i + 1]; hi[i] = hi[2 * i] + hi[2 * i + 1]; }
              sts64(red + (c.sb + SM_RED + c.w * 256), __float_as_uint(lo[0]), __float_as_uint(hi[0]));
            }
            if (ok) break;
            n++; CNT(0);
          }
          bar_sync(NB_HELP, 128);
          const uint32_t rd = red + (c.sb + SM_RED);
          if (!RED_P || c.w < 2) {
            if (RED_L == 3) st_pub_if(dst, sum4(lds32(rd), lds32(rd + 128), lds32(rd + 256), lds32(rd + 384)), c.w < 2);
            else {
              const uint2 p0 = lds64(rd), p1 = lds64(rd + 256), p2 = lds64(rd + 512), p3 = lds64(rd + 768);
              st_pub_if(dst, pack_bf16((__uint_as_float(p0.x) + __uint_as_float(p1.x)) + (__uint_as_float(p2.x) + __uint_as_float(p3.x)),
                                       (__uint_as_float(p0.y) + __uint_as_float(p1.y)) + (__uint_as_float(p2.y) + __uint_as_float(p3.y))), c.w < 2);
            }
          }
          t0 = clock_lo();
          mbar_arrive_warp(BAR(B_PUB));
          TRV(s, 15, n);
          mbar_wait(BAR(B_SPFREE), (s - 1) & 1);
        } else {
          if (tid_now() == 384) TL2(24);
          __syncwarp();
          mbar_wait(BAR(B_WOFULL), 0);
          if (tid_now() == 384) TL2(19);
          __syncwarp();
          t0 = clock_lo() - DLY_E3;
        }
        TRV(s, 1, t0);
        {
          const uint32_t l16 = (tid_now() & 31) * 16, dst = l16 + (c.sb + SM_MEM + (c.w & 1) * 4096 + (c.w >> 1) * 2048);
          const uint4 tb = lds128(tab + 16);
          st_pub_if(mk_ptr(tb.z | l16 >> 2, tb.w), SENT, c.w >= 2);
          const char* src = mk_ptr(tb.x | l16, tb.y);
          touch(src, dep(c.sb, dst, c.sb));
          delay_until(t0 + (DLY_E3 + (c.w & 1) * DLY_E3B));
          uint32_t n = 0;
          while (true) {
            uint4 v[4];
#pragma unroll
            for (int i = 0; i < 4; i++) v[i] = ld_poll(src + i * 512);
#pragma unroll
            for (int i = 0; i < 4; i++) sts128(dst + i * 512, v[i]);
            if (arrive_if_all(max(max(v[0].x, v[1].x), max(v[2].x, v[3].x)) != SENT, NB_MEM + (c.w & 1) * 2 + (c.w >> 1), 160)) break;
            n++; CNT(1);
          }
          mbar_arrive_warp(BAR(B_MEM));
          TR(s, 2); TRV(s, 14, n);
        }
        if (s == 1) CLK(1); if (s == 8) CLK(2); if (s == 56) CLK(3);
        if (c.w == 2 && s == 15) TRSYNC(8);
        if (c.w == 2 && s == 21) TRSYNC(10);
      }
      const int g = s + 1;
      auto load_v = [&]() {
        if (V_TMA && c.w == V_W) {
          mbar_expect_e(BAR(B_VFULL), 8192);
          bulk_load_e(c.sb + SM_V, c.mail + (uint32_t)(M_KVQ + ((min(g, XEND - 1) & (NSLOT - 1)) * 32 + c.h) * 24576 + 8192), 8192, BAR(B_VFULL));
        }
      };
      if (XEND < NSEG && g >= XEND && g < NSEG) { mbar_wait(BAR(B_SC), s & 1); load_v(); }
      if (g < XEND) {
        const uint32_t tx_ = c.sb + SM_TAB + 1536 + (g & 3) * 128 + c.w * 32, tag = (g >> 2) & 1;
        if (c.w == 0) mbar_expect_e(BAR(B_LAND), EXP_PEER * 12288);
        auto load_x = [&]() {
          if (c.w == 3 && g + 1 < XEND) {
            mbar_wait(BAR(B_XEMPTY), g & 1);
            mbar_expect_e(BAR(B_XFULL), 16384 * EXP_NXT);
            for (int i = 0; i < EXP_NXT; i++) tma4d_e(c.sb + SM_XT + i * 16384, &tx, c.b * 8, (g + 1) * 4 + 2 * (c.b ^ i), BAR(B_XFULL));
          }
        };
        if (X_AT == 0 || g == 0) load_x();
        mbar_wait(BAR(B_LAND), g & 1);
        if (DLY_F && g > 0) delay_cycles(DLY_F);
        auto total = [&](int w, int lane, uint32_t o0, uint32_t o1) {
          const uint32_t a = c.sb + SM_LAND + land_off(w, lane);
          if (EXP_FL == 1) return make_uint4(a, a, a, a);
          const uint4 t = add4(lds128(a + o0), lds128(a + o1 + 2048));
          const uint32_t a2 = dep(dep(a, t.x ^ t.y ^ t.z, c.sb), t.w, c.sb);
          return add4(t, add4(lds128(a2 + o0 + 4096), lds128(a2 + o1 + 6144)));
        };
        auto get = [&](int e) {
          const int ln = tid_now() & 31;
          return e == 0 ? total(c.w, ln, 16384, 16384)
               : e == 1 ? total((c.w & 2) + ((ln >> 1) & 1), (ln & 1) * 16 + (c.w & 1) * 8 + (ln >> 2), 8192, 0)
                        : total((c.w & 2) + ((ln >> 1) & 1), (ln & 1) * 16 + (ln >> 3) * 4 + (c.w & 1) * 2 + ((ln >> 2) & 1), 0, 8192);
        };
        auto put = [&](int e, uint4 v) {
          const int ln = tid_now() & 31;
          const uint2 d = lds64(tx_ + e * 8);
          if (e < 2) {
            v.x = tagged(v.x, tag);
            st_pub4(mk_ptr(d.x | (e ? (ln & 24) * 32 + (ln & 7) * 16 : ln * 16), d.y), v);
          } else {
            char* dst = mk_ptr(d.x | ((ln & 7) * 16 + (ln >> 3) * 4), d.y);
            const uint32_t bit = ln < 8;
            st_pub(dst, put_tag(v.x, bit, tag)); st_pub(dst + 128, put_tag(v.y, bit, tag));
            st_pub(dst + 2048, put_tag(v.z, bit, tag)); st_pub(dst + 2176, put_tag(v.w, bit, tag));
          }
        };
        auto after_sc = [&]() { if (g > 0) { mbar_wait(BAR(B_SC), s & 1); if (DLY_FK) delay_cycles(DLY_FK); if (X_AT == 1) load_x(); } };
        if (FIN_AT == 5) {
          put(0, get(0));
          if (DLY_F2 && g > 0) delay_cycles(DLY_F2); else sched_fence(c.sb);
          const uint4 k = get(1);
          sched_fence(c.sb);
          const uint4 q = get(2);
          if (g > 0) { mbar_wait(BAR(B_VST), s & 1); if (DLY_FS) delay_cycles(DLY_FS); }
          put(1, k); put(2, q);
          mbar_arrive_both(BAR(B_LFREE), c.b ^ 1);
          after_sc();
          load_v();
          continue;
        }
        if (FIN_AT < 3) {
          if (EXP_FIN & 1) put(0, get(0));
          TR(s, 3);
          if (FIN_AT == 1) after_sc();
          if (V_TMA == 1) load_v();
          if (EXP_FIN & 2) put(1, get(1));
        } else {
          const uint4 v = get(0);
          sched_fence(c.sb);
          const uint4 k = get(1);
          if (g > 0) { mbar_wait(BAR(B_VST), s & 1); if (DLY_FS) delay_cycles(DLY_FS); }
          put(0, v); put(1, k);
        }
        TR(s, 4);
        if (FIN_AT == 4) {
          const uint4 q = get(2);
          after_sc();
          load_v();
          put(2, q);
        } else {
          if (FIN_AT >= 2) after_sc();
          if (V_TMA == 2) load_v();
          if (EXP_FIN & 4) put(2, get(2));
        }
        mbar_arrive_both(BAR(B_LFREE), c.b ^ 1);
        if (V_TMA == 3) load_v();
        TR(s, 5);
        if (!FIN_AT && X_AT && g > 0) { mbar_wait(BAR(B_SC), s & 1); if (DLY_FK) delay_cycles(DLY_FK); load_x(); }
      }
    }
    mbar_wait(BAR(B_DONE), 0);
    if (tid_now() == 384) TL(8);
    __syncwarp();
    asm volatile("barrier.cluster.arrive.relaxed; barrier.cluster.wait;" ::: "memory");
  } else if (c.m == 2) {
    asm volatile("setmaxnreg.dec.sync.aligned.u32 %0;" :: "n"(512 - 2 * REG_F - REG_H));
    c.lane = lane_id();
    {
      char* own = c.mail + (uint32_t)(M_E3 + (c.r >> 5) * 8192 + (c.r & 31) * 128 + c.lane * 4);
      probe_pair(c, c.w < 2 ? M_PAIR + (c.w * 128 + c.r) * 8192 : c.w == 2 ? M_E3 + (c.r & 15) * 8192 + (c.r >> 4) * 128 : M_REF + c.r * 32, c.w, c.w == 2 ? SENT : 0u);
      if (tid_now() == 256) TL2(14);
      __syncwarp();
      uint32_t tl = clock_lo() + (PACE0 + WO_AT * PACE);
      mbar_arrive_warp(BAR(B_PROBE));
      if (c.w == 0) {
        const unsigned short* mp = (const unsigned short*)mem0 + (2 * (c.lane & 3)) * D_ + 8 * c.r + (c.lane >> 2);
        uint32_t mv = (uint32_t)mp[0] | ((uint32_t)mp[D_] << 16);
        if (mv == SENT) mv = 0x7FFF7FFFu;
        mbar_wait(BAR(B_PROBE), 0);
        const uint4 bits = lds128(c.sb + SM_SEL + 512);
        st_pub_if(g_ctl + C_SEL + c.r, bits.x | bits.y | bits.z | bits.w | 0x100u, c.lane == 0);
        uint4 v; uint32_t n = 0;
        while (true) {
          delay_cycles(DLY_SEL);
          v = ld_poll(g_ctl + C_SEL + c.lane * 4);
          if (__all_sync(~0u, v.x & v.y & v.z & v.w & 0x100u)) break;
          watchdog(n, POLL_LIMIT);
        }
        st_pub(own, mv); st_pub(own + 4096, mv);
        sts128(c.sb + SM_SEL + c.lane * 16, v);
        mbar_arrive_warp(BAR(B_SEL));
        if (c.lane == 0) TL2(13);
        __syncwarp();
      }
      if (c.w == 1) for (int i = 0; i < 4; i++) { delay_until(tl += WO_P * PACE); prefetch2d_e(&to, c.j * 256 + i * 64, c.h * 128); }
    }
    asm volatile("barrier.cluster.wait;" ::: "memory");
    const int g = c.w, src0 = c.h * 4 + (g >> 1) * 2;
    mbar_wait(BAR(B_SEL), 0);
    c.sel = __shfl_sync(~0u, ~lds32(c.sb + SM_SEL + src0 * 4), 0);
    mbar_wait(BAR(B_WREAD), 0);
    uint32_t l16 = c.sb + g * 512 + c.lane * 16;
    auto lane = [&](uint32_t v) { l16 = dep(l16, v, c.sb); return (int)((l16 & 511) >> 4); };
    for (int s = 0; s < NSEG; s++) {
      l16 = vary(l16, s, c.sb);
      int ln = (l16 & 511) >> 4;
      uint4 kf[4], qx;
      {
        const int gs = min(s, XEND - 1);
        const char* pk = c.mail + (uint32_t)(M_KVQ + ((gs & (NSLOT - 1)) * 32 + c.h) * 24576 + g * 2048 + ln * 16);
        const char* pq = pk + (16384 + c.j * 2048 - g * 1536);
        const uint32_t tg = (gs / NSLOT) & 1;
        touch(pk, c.sb); touch(pq, c.sb);
        mbar_wait(BAR(B_VFULL), s & 1);
        if (KVQ_AT) { mbar_wait(BAR(B_MEM), s & 1); if (DLY_K) delay_cycles(DLY_K); } else if (s > 0) mbar_wait(BAR(B_PUB), (s - 1) & 1);
        for (uint32_t n = 0; ; ) {
          uint4 k[4];
#pragma unroll
          for (int t = 0; t < 4; t++) k[t] = ld_poll(pk + t * 512);
          qx = ld_poll(pq);
#pragma unroll
          for (int t = 0; t < 2; t++) {
            auto cp = [&](uint32_t v) { return dep(v, 0, c.sb); };
            kf[t] = make_uint4(cp(k[2 * t].x), cp(k[2 * t].y), cp(k[2 * t + 1].x), cp(k[2 * t + 1].y));
            kf[2 + t] = make_uint4(cp(k[2 * t].z), cp(k[2 * t].w), cp(k[2 * t + 1].z), cp(k[2 * t + 1].w));
          }
          if (all_clear(stale1(stale2(k[0].x, k[1].x, tg) | stale2(k[2].x, k[3].x, tg), qx.x, tg), EXP_CHK)) break;
          watchdog(n, POLL_LIMIT); CNT(4);
        }
        TR(s, 2);
      }
      if (X_AT >= 2 && g == 0 && s + 2 < XEND) {
        mbar_wait(BAR(B_XEMPTY), ~s & 1);
        if (X_AT == 3) mbar_wait(BAR(B_MEM), s & 1);
        mbar_expect_e(BAR(B_XFULL), 16384 * EXP_NXT);
        for (int i = 0; i < EXP_NXT; i++) tma4d_e(c.sb + SM_XT + i * 16384, &tx, c.b * 8, (s + 2) * 4 + 2 * (c.b ^ i), BAR(B_XFULL));
      }
      ln = lane(kf[0].y);
      const char* pa = c.mail + (uint32_t)(M_PAIR + ((s & 1) * 128 + src0) * 8192 + (c.sel >> (s & 1) & 1) * 4096 + (g & 1) * 512 + (EXP_LIN ? ln * 16 : read_off(ln)));
      const uint32_t spw = c.sb + SM_SP + g * 1280 + (ln & 3) * 64 + ((((ln >> 3) ^ ln) & 2) << 4) + (ln & 4) * 4 + (ln & 8),
                     spr = c.sb + SM_SP + (ln & 4) * 80 + (ln >> 3) * 64 + (((ln & 3) ^ ((ln >> 3) & 2)) << 4), l8 = ln * 8;
      const uint32_t tg = s >> 1;
      float sx[2][4];
      uint32_t sm;
      uint4 km;
      touch(pa, c.sb);
      mbar_wait(BAR(B_E1TRIG), s & 1);
      const uint32_t t0 = clock_lo();
      TRV(s, 3, t0);
      scores_x<false>(sx, kf, qx, 0);
      store_scores(sx, spw + 640);
      delay_until(t0 + DLY_E1);
      uint32_t nr = 0;
      while (true) {
        const uint4 q0 = ld_poll(pa), q1 = ld_poll(pa + 2048), k0 = ld_poll(pa + 1024), k1 = ld_poll(pa + 3072);
        uint4 qm = add4(q0, q1);
        const uint32_t bq = stale2(q0.x, q1.x, tg);
        qm.x = dep(qm.x, bq, c.sb);
        scores_x<SC_F>(sx, kf, qm, c.sb);
        const uint32_t bk = stale2(k0.x, k1.x, tg);
        km = add4(k0, k1);
        km.x = dep(km.x, bk, c.sb);
        const bool ok = all_clear(bq | bk, 1);
        sm = scores_m(qm, km);
        store_scores(sx, spw);
        if (ok) break;
        nr++; CNT(2);
      }
      sts32(l8 + (c.sb + SM_SPM + (g >> 1) * 256 + (g & 1) * 4), sm);
      bar_sync(NB_ATT, 128);
      TR(s, 5); TRV(s, 13, nr);
      float o[2][4];
      uint32_t sp[5];
      uint4 vf[4];
      load_scores(sp, spr, l8 + (c.sb + SM_SPM));
      const uint32_t m5 = max5(sp);
      uint32_t m1;
      float off = row_off(m5, m1), f[10];
      l16 = dep(l16, VF_AT ? m1 : m5, c.sb);
#pragma unroll
      for (int t = 0; t < 4; t++) vf[(t >> 1) + 2 * (t & 1)] = lds128(l16 + SM_V + ((t >> 1) + 2 * (t & 1)) * 2048);
      qx.x = dep(qx.x, sp[0], c.sb);
      sts32(l8 + (c.sb + SM_SPM + 512 + (g >> 1) * 256 + (g & 1) * 4), scores_m(qx, km));
      mbar_arrive_warp(BAR(B_SC));
      unpack(f, sp);
      if (UP_F) sched_fence(c.sb);
      uint4 vm;
      if (VM_AT < 2) {
        bar_sync(NB_VM, 384);
        sp[1] = exp_pair(f, 1, off);
        const uint32_t av = dep(l8, VM_AT ? sp[1] : __float_as_uint(off), c.sb) + (c.sb + g * 512 + SM_VM);
        const uint2 vm0 = lds64(av), vm1 = lds64(av + 256);
        vm = make_uint4(vm0.x, vm0.y, vm1.x, vm1.y);
#pragma unroll
        for (int i = 2; i < 6; i++) sp[i % 5] = exp_pair(f, i % 5, off);
      } else {
#pragma unroll
        for (int i = 1; i < 6; i++) sp[i % 5] = exp_pair(f, i % 5, off);
        bar_sync(VM_AT == 2 ? dep(dep(0, sp[1] ^ sp[2], c.sb) + NB_VM, sp[0], c.sb) : dep(dep(0, sp[0] ^ sp[1] ^ sp[2], c.sb) + NB_VM, sp[3], c.sb), 384);
        const uint32_t av = l8 + (c.sb + g * 512 + SM_VM);
        const uint2 vm0 = lds64(av), vm1 = lds64(av + 256);
        vm = make_uint4(vm0.x, vm0.y, vm1.x, vm1.y);
      }
      float sum;
      auto rows_m = [&]() {
        const uint32_t tv = min(s, XEND - 1) / NSLOT;
        sum = pv(o, sp, vf, vm);
        stsm4<false>(l16 + SM_OM, pack_bf16(o[0][0], o[0][1]), pack_bf16(o[0][2], o[0][3]), pack_bf16(o[1][0], o[1][1]), pack_bf16(o[1][2], o[1][3]));
        sts32(c.sb + SM_SUM + ((l16 >> 4) & 28), __float_as_uint(sum));
        return arrive_if_clear(stale2(vf[0].x, vf[1].x, tv) | stale2(vf[2].x, vf[3].x, tv), EXP_CHK, NB_OM, 384);
      };
      if (!rows_m()) {
        const char* pv_ = c.mail + (uint32_t)(M_KVQ + ((min(s, XEND - 1) & (NSLOT - 1)) * 32 + c.h) * 24576 + 8192 + (l16 - c.sb));
        uint32_t n = 0;
        do {
#pragma unroll
          for (int t = 0; t < 4; t++) vf[t] = ld_poll(pv_ + t * 2048);
          watchdog(n, POLL_LIMIT); CNT(5);
        } while (!rows_m());
      }
      const uint32_t tom = clock_lo();
      TRV(s, 8, tom);
      sched_fence(c.sb);
      ln = lane(tom);
      const int n = ln >> 2, jj = ln & 3, tq_ = 8 * c.j + (n & 4) + 2 * (n & 1) + ((n >> 1) & 1), lim = 16 * (tq_ - 2 * jj + 1);
      if (DLY_X) delay_until(tom + DLY_X);
      load_scores(sp, spr + 640, c.sb + SM_SPM + 512 + ln * 8);
#pragma unroll
      for (int w = 0; w < 4; w++) {
        uint32_t m; asm("shl.b32 %0, 0xffffffff, %1;" : "=r"(m) : "r"(max(lim - 128 * w, 0)));
        sp[1 + w] = (sp[1 + w] & ~m) | (0xD029D029u & m);
      }
      mbar_arrive_warp(dep(dep(0, sp[0], c.sb), sp[1], c.sb) + BAR(B_SPFREE));
      off = row_off(max5(sp), m1);
      unpack(f, sp);
#pragma unroll
      for (int i = 1; i < 6; i++) sp[i % 5] = exp_pair(f, i % 5, off);
      sum = pv(o, sp, vf, vm);
      if (W_PV) mbar_arrive_warp(dep(dep(0, __float_as_uint(o[1][0]), c.sb), __float_as_uint(sum), c.sb) + BAR(B_PVDONE));
      TR(s, 7);
      sum = rcp(sum);
      const float i0 = __shfl_sync(~0u, sum, 8 * jj), i1 = __shfl_sync(~0u, sum, 8 * jj + 4);
      const uint32_t oxs = c.sb + SM_OX + g * 512;
      stsm4<true>(oxs + (ln & 7) * 64 + (((ln >> 3) ^ ((ln >> 1) & 3)) << 4),
                  pack_bf16(o[0][0] * i0, o[0][1] * i1), pack_bf16(o[0][2] * i0, o[0][3] * i1), pack_bf16(o[1][0] * i0, o[1][1] * i1), pack_bf16(o[1][2] * i0, o[1][3] * i1));
      __syncwarp();
      *(uint4*)(g_ox + (uint32_t)((32 * s + tq_) * 4096 + c.h * 128 + 32 * g + 8 * jj)) = lds128(oxs + n * 64 + ((jj ^ (n >> 1)) << 4));
      TR(s, 9);
    }
    mbar_arrive_warp(BAR(B_DONE));
    asm volatile("barrier.cluster.arrive.relaxed;" ::: "memory");
  } else {
    asm volatile("setmaxnreg.inc.sync.aligned.u32 %0;" :: "n"(REG_F));
    c.lane = lane_id();
    uint32_t wa[16][4], wb[16][4], wv[16][4];
    fft_rows_fwd((float2*)smraw, (const __nv_bfloat16*)(smraw + SM_GW), c.r, threadIdx.x, BAR(B_ROWS), BAR(B_FREE));
    mbar_arrive_warp(BAR(B_P1));
    if (tid_now() == 0) TL2(1);
    __syncwarp();
    mbar_spin(BAR(B_WFULL + c.m), 0);
    if ((tid_now() & 127) == 0) TL2(16);
    __syncwarp();
    {
      const uint32_t st = c.sb + c.m * ST_WG + frag_off(c.w, c.lane);
#pragma unroll
      for (int k = 0; k < 16; k++) ldsm4t(wb[k], st + k * 2048);
#pragma unroll
      for (int k = NP; k < 16; k++) ldsm4t(wa[k], st + (16 + k - NP) * 2048);
#pragma unroll
      for (int k = 0; k < NV; k++) ldsm4t(wv[k], st + (32 - NP + k) * 2048);
      mbar_arrive_warp(BAR(B_WREAD));
#pragma unroll
      for (int k = 0; k < NP; k++) ldsm4t(wa[k], c.sb + SM_POOL + c.m * NP * 2048 + frag_off(c.w, c.lane) + k * 2048);
      bar_sync(NB_XCH, 256);
#pragma unroll
      for (int k = 0; k < NP; k++) sts128(c.sb + SM_POOL + c.m * 2048 + c.w * 512 + c.lane * 16 + k * 4096, make_uint4(wa[k][0], wa[k][1], wa[k][2], wa[k][3]));
    }
    if (tid_now() == 0) TL2(12);
    __syncwarp();
    asm volatile("barrier.cluster.wait;" ::: "memory");
    uint32_t t16 = c.m * 2048 + c.w * 512 + c.lane * 16;
    uint32_t pk = (c.m * NHV * 2048 + frag_off(c.w, c.lane)) | (tile_off(2 * (c.w & 1), c.lane) << 16) | ((c.lane & 12) ? 0u : 0x80000000u);
    const uint32_t dx = desc_lo(c.sb + SM_XT + c.m * 4096), dh = desc_lo(c.sb + SM_HV + c.m * NHV * 2048);
    for (int s = -2; s < NSEG; s++) {
      t16 = vary(t16, s, c.sb); pk = vary(pk, s, c.sb);
      if (s >= 0) {
        uint32_t af[16][4], bf[4][4], wo;
        const uint32_t tab = ((t16 >> 3) & 0x1C0) + (c.sb + SM_TAB + (s & 1) * 512);
        const char* pa;
        mem_proj(wa, wb, wv, af, wo, pa, tab, t16, pk, c, s);
        const uint32_t t0 = clock_lo();
        t16 = dep(t16, t0, c.sb);
        auto ldwo = [&](int f) { ldsm4t(af[f], (f < WO_D ? wo : dep(wo, af[f < WO_D ? 0 : f - WO_D][0], c.sb)) + (c.sb + SM_WO + (f & 1) * 32768 + (f >> 1) * 2048)); };
        {
          const uint32_t tg = s >> 1, vm = t16 >> 1, chk = (~t16 >> 4) & 1;
#pragma unroll
          for (int f = WO_0; f < WO_1; f++) ldwo(f);
          delay_until(t0 + DLY_V);
          uint2 v0 = ld_poll2(pa), v1 = ld_poll2(pa + 1024), v2 = ld_poll2(pa + 2048), v3 = ld_poll2(pa + 3072);
          TR(s, 3);
#pragma unroll
          for (int f = WO_1; f < 16 - WO_L; f++) ldwo(f);
          TR(s, 4);
          uint32_t n = 0;
          while (true) {
            sts64(vm + (c.sb + SM_VM), sum4(v0.x, v1.x, v2.x, v3.x), sum4(v0.y, v1.y, v2.y, v3.y));
            if (arrive_if_clear(stale1(stale1(stale2(v0.x, v1.x, tg), v2.x, tg), v3.x, tg), chk, NB_VM, 384)) break;
            v0 = ld_poll2(pa); v1 = ld_poll2(pa + 1024); v2 = ld_poll2(pa + 2048); v3 = ld_poll2(pa + 3072);
            n++; CNT(3);
          }
          TR(s, 12); TRV(s, 15, n);
        }
        const uint32_t ob = dep(dep(t16 & 511, af[14 - WO_L][0], c.sb), af[15 - WO_L][0], c.sb);
        uint32_t l4 = ob >> 2;
        const uint32_t bit = (t16 & 48) ? 0u : 1u;
        mbar_spin_if(BAR(B_XFULL), s & 1, s + 2 < XEND);
        bar_sync(NB_OM, 384);
        TR(s, 5);
#pragma unroll
        for (int i = 0; i < 4; i++) ldsm4t(bf[i], ob + (c.sb + SM_OM + i * 512));
        uint2 sum = lds64(((t16 >> 1) & 24) + (c.sb + SM_SUM));
        if (OM_F) sched_fence(c.sb);
        float d[WO_C][4] = {};
        uint4 d0, d1;
#pragma unroll
        for (int f = 0; f < 16; f++) {
          mma_a(d[f % WO_C], af[f], bf[f >> 2][f & 2], bf[f >> 2][(f & 2) + 1]);
          if (f >= WO_C && f < WO_C + WO_L) {
            const int l = 16 - WO_L + f - WO_C;
            ldsm4t(af[l], (WO_LD ? dep(wo, __float_as_uint(d[(f + 1) % WO_C][0]), c.sb) : wo) + (c.sb + SM_WO + (l & 1) * 32768 + (l >> 1) * 2048));
          }
          if (f == WO_T) {
            const uint32_t tb2 = dep((t16 >> 3) & 0x1C0, __float_as_uint(d[f % WO_C][0]), c.sb) + (c.sb + SM_TAB + (s & 1) * 512);
            d0 = lds128(tb2 + 32); d1 = lds128(tb2 + 48);
          }
          if (f >= PL_WA && f < PL_WA + PL_W) lds_frag(wa[f - PL_WA], (PL_WD ? dep(t16, __float_as_uint(d[(f + PL_WD) % WO_C][0]), c.sb) : t16) + (c.sb + SM_POOL + (f - PL_WA) * 4096));
          if (PL_W && PL_WF && f == PL_WA + PL_W - 1) sched_fence(c.sb);
          if (f == 4) { sum.x = dep(sum.x, __float_as_uint(d[0][0]), c.sb); sum.y = dep(sum.y, __float_as_uint(d[0][0]), c.sb); }
        }
        if (PL_W && !PL_WF) {
          uint32_t all = 0;
#pragma unroll
          for (int k = 0; k < PL_W; k++) all ^= wa[k][0];
          l4 = dep(l4, all, c.sb);
        }
        char* dst[4] = {mk_ptr(d0.x | l4, d0.y), mk_ptr(d0.z | l4, d0.w), mk_ptr(d1.x | l4, d1.y), mk_ptr(d1.z | l4, d1.w)};
        const float i0 = rcp(__uint_as_float(sum.x)), i1 = rcp(__uint_as_float(sum.y));
#pragma unroll
        for (int i = 0; i < 4; i++) {
          const int t = i >> 1, e = 2 * (i & 1);
          const float y0 = WO_C == 2 ? d[t][e] : d[t][e] + d[(t + 2) % WO_C][e], y1 = WO_C == 2 ? d[t][e + 1] : d[t][e + 1] + d[(t + 2) % WO_C][e + 1];
          st_pub(dst[i], put_tag(pack_bf16(y0 * i0, y1 * i1), bit, s >> 1));
        }
        if (ANCH2) sts32(c.sb + SM_SUM + 64, clock_lo());
        mbar_arrive_warp(BAR(B_E2TRIG));
        TR(s, 6);
        sched_fence(c.sb);
        if (W_E2 == 2) mbar_spin(BAR(B_E2TRIG), s & 1);
      }
      auto ldp = [&](int k0, int k1, int d, int back = 0) {
#pragma unroll
        for (int k = k0; k < k1; k++) lds_frag(wa[k], (k < k0 + d - back ? t16 : dep(t16, wa[k < d ? 0 : k - d][0], c.sb)) + (c.sb + SM_POOL + k * 4096));
      };
      ldp(PL_W, PL_0 < PL_W + PL_D ? PL_0 : PL_W + PL_D, PL_D);
      mbar_spin_if(BAR(B_XFULL), s & 1, s < 0);
      const uint32_t tgo = clock_lo() + (t16 >> 11) * STAG;
      ldp(PL_W + PL_D, PL_0 - PL_D, PL_D, PL_D);
      if (STAG) delay_until(tgo);
      ldp(PL_0 - PL_D, PL_0, PL_D, PL_D);
      if (s + 2 < XEND) {
        float xa[16];
        uint32_t q[4];
        if (W_E2 == 1 && s >= 0) mbar_spin(BAR(B_E2TRIG), s & 1);
        if (W_PV && s >= 0) mbar_spin(BAR(B_PVDONE), s & 1);
        TR(s, 7);
        constexpr int S1 = ORDER ? 0 : 2, S2 = ORDER == 0 ? 0 : ORDER == 1 ? 2 : 1, S3 = ORDER == 2 ? 2 : 1;
        if (ORDER) issue_qk<0, 16>(xa, wb, vary(dx, s, c.sb)); else issue_v(xa, wv, vary(dx, s, c.sb), vary(dh, s, c.sb));
        if (IS_F) sched_fence(c.sb);
        ldp(PL_0, PL_1, PL_D1);
        const uint32_t land = (t16 ^ ((t16 >> 3) & 0x60)) + vary(c.sb + SM_LAND + c.b * 4096, s, c.sb);
        mbar_spin(BAR(B_LFREE), s & 1);
        WG_WAIT(0);
        TR(s, 8);
        park_own<S1 == 2>(q, xa, land, S1, c.sb);
        if (W_PUB == 4 && s >= 0) mbar_spin(BAR(B_PUB), s & 1);
        if (ORDER == 1) issue_v(xa, wv, vary(dx, s, c.sb + 32), vary(dh, s, c.sb)); else issue_qk<0, 16>(xa, ORDER ? wa : wb, vary(dx, s, c.sb + 32));
        if (IS_F) sched_fence(c.sb);
        ldp(PL_1, PL_2, PL_D1);
        if (W_PUB == 1) mbar_spin_if(BAR(B_PUB), s & 1, s >= 0);
        uint32_t tp = clock_lo(), q1[4] = {q[0], q[1], q[2], q[3]};
        if (W_PUB != 3) park_peer(q, land, S1, c);
        ldp(PL_2, NP - PL_L, PL_D1);
        TR(s, 13);
        WG_WAIT(0);
        TR(s, 9);
        park_own<S2 == 2>(q, xa, land, S2, c.sb);
        if (ORDER == 2) issue_v(xa, wv, vary(dx, s, c.sb + 64), vary(dh, s, c.sb));
        else {
          issue_qk<0, PL_L ? NP - PL_L : 16>(xa, wa, vary(dx, s, c.sb + 64));
          ldp(NP - PL_L, NP, PL_E);
          if (PL_L) issue_qk<NP - PL_L, 16>(xa, wa, vary(dx, s, c.sb + 64));
        }
        if ((W_PUB == 2 || W_PUB == 3) && s >= 0) { mbar_spin(BAR(B_PUB), s & 1); tp = clock_lo(); }
        if (W_PUB == 3) park_peer(q1, land, S1, c);
        if (DLY_S && s >= 0) delay_until(tp + DLY_S);
        park_peer(q, land, S2, c);
        WG_WAIT(0);
        TR(s, 10);
        mbar_arrive_warp(BAR(B_XEMPTY));
        park_own<S3 == 2>(q, xa, land, S3, c.sb);
        park_peer(q, land, S3, c);
        TR(s, 11);
      } else ldp(PL_0, NP, 1);
    }
    mbar_arrive_warp(BAR(B_DONE));
    asm volatile("barrier.cluster.arrive.relaxed;" ::: "memory");
  }
}

constexpr int OP_STAGES = 5;
constexpr uint32_t OP_BT = OP_STAGES * 32768, OP_TW = OP_BT + 4 * ROW_BUF * 8, OP_BAR = OP_TW + 8192, OP_SMEM = OP_BAR + 128 + 1024;

__device__ __forceinline__ void wgmma_ss_n128_tb(float (&d)[64], uint64_t a, uint64_t b) {
  asm volatile("wgmma.mma_async.sync.aligned.m64n128k16.f32.bf16.bf16 "
    "{%0,%1,%2,%3,%4,%5,%6,%7,%8,%9,%10,%11,%12,%13,%14,%15,%16,%17,%18,%19,%20,%21,%22,%23,%24,%25,%26,%27,%28,%29,%30,%31,"
    "%32,%33,%34,%35,%36,%37,%38,%39,%40,%41,%42,%43,%44,%45,%46,%47,%48,%49,%50,%51,%52,%53,%54,%55,%56,%57,%58,%59,%60,%61,%62,%63}, "
    "%64, %65, 1, 1, 1, 0, 1;"
    : "+f"(d[0]), "+f"(d[1]), "+f"(d[2]), "+f"(d[3]), "+f"(d[4]), "+f"(d[5]), "+f"(d[6]), "+f"(d[7]),
      "+f"(d[8]), "+f"(d[9]), "+f"(d[10]), "+f"(d[11]), "+f"(d[12]), "+f"(d[13]), "+f"(d[14]), "+f"(d[15]),
      "+f"(d[16]), "+f"(d[17]), "+f"(d[18]), "+f"(d[19]), "+f"(d[20]), "+f"(d[21]), "+f"(d[22]), "+f"(d[23]),
      "+f"(d[24]), "+f"(d[25]), "+f"(d[26]), "+f"(d[27]), "+f"(d[28]), "+f"(d[29]), "+f"(d[30]), "+f"(d[31]),
      "+f"(d[32]), "+f"(d[33]), "+f"(d[34]), "+f"(d[35]), "+f"(d[36]), "+f"(d[37]), "+f"(d[38]), "+f"(d[39]),
      "+f"(d[40]), "+f"(d[41]), "+f"(d[42]), "+f"(d[43]), "+f"(d[44]), "+f"(d[45]), "+f"(d[46]), "+f"(d[47]),
      "+f"(d[48]), "+f"(d[49]), "+f"(d[50]), "+f"(d[51]), "+f"(d[52]), "+f"(d[53]), "+f"(d[54]), "+f"(d[55]),
      "+f"(d[56]), "+f"(d[57]), "+f"(d[58]), "+f"(d[59]), "+f"(d[60]), "+f"(d[61]), "+f"(d[62]), "+f"(d[63])
    : "l"(a), "l"(b));
}

__device__ __forceinline__ void tma2d_mc(uint32_t dst, const CUtensorMap* tm, int c0, int c1, uint32_t bar) {
  asm volatile("cp.async.bulk.tensor.2d.shared::cluster.global.mbarrier::complete_tx::bytes.multicast::cluster [%0], [%1, {%3, %4}], [%2], %5;"
               :: "r"(dst), "l"(tm), "r"(bar), "r"(c0), "r"(c1), "h"((uint16_t)3) : "memory");
}

__global__ void __cluster_dims__(2, 1, 1) __launch_bounds__(640, 1)
outproj_kernel(const __grid_constant__ CUtensorMap ta, const __grid_constant__ CUtensorMap tw,
               const __grid_constant__ CUtensorMap tb, const __grid_constant__ CUtensorMap tout) {
  extern __shared__ __align__(1024) unsigned char smraw[];
  const uint32_t sb = __shfl_sync(~0u, (smem_u32(smraw) + 1023) & ~1023u, 0);
  const uint32_t full = sb + OP_BAR, empty = full + 8 * OP_STAGES, bfull = empty + 8 * OP_STAGES;
  const int m0 = (blockIdx.x >> 3) * 128, n0 = (blockIdx.x & 7) * 128, rank = blockIdx.x & 1;
  if (threadIdx.x == 0) {
    for (int i = 0; i < OP_STAGES; i++) { mbar_init(full + 8 * i, 1); mbar_init(empty + 8 * i, 4); }
    mbar_init(bfull, 1);
    asm volatile("fence.mbarrier_init.release.cluster;" ::: "memory");
  }
  __syncthreads();
  asm volatile("barrier.cluster.arrive.relaxed.aligned; barrier.cluster.wait.aligned;" ::: "memory");
  const int role = __shfl_sync(~0u, (int)(threadIdx.x >> 7), 0);
  if (role == 4) {
    if (threadIdx.x == 512) {
      TL(9);
      for (int st = 0; st < OP_STAGES; st++) {
        mbar_expect(full + 8 * st, 32768);
        tma2d(sb + st * 32768 + 16384, &tw, n0, st * 64, full + 8 * st);
        tma2d(sb + st * 32768 + 24576, &tw, n0 + 64, st * 64, full + 8 * st);
      }
      pdl_wait();
      TL(10);
      uint32_t st = 0, ph = 1;
      for (int kb = 0; kb < 64; kb++) {
        const uint32_t dst = sb + st * 32768;
        if (kb >= OP_STAGES) {
          mbar_wait(empty + 8 * st, ph);
          mbar_expect(full + 8 * st, 32768);
          tma2d(dst + 16384, &tw, n0, kb * 64, full + 8 * st);
          tma2d(dst + 24576, &tw, n0 + 64, kb * 64, full + 8 * st);
        }
        tma2d_mc(dst + rank * 8192, &ta, kb * 64, m0 + rank * 64, full + 8 * st);
        if (++st == OP_STAGES) { st = 0; ph ^= 1; }
      }
      mbar_wait(full + 8 * (63 % OP_STAGES), (63 / OP_STAGES) & 1);
    }
  } else if (role >= 2) {
    unsigned char* base = smraw + (sb - smem_u32(smraw));
    const int t = threadIdx.x & 31, w = (threadIdx.x >> 5) & 7;
    row_twiddles<false>((float2*)(base + OP_TW), threadIdx.x - 256, 256);
    bar_sync(2, 256);
    pdl_wait();
    { const int i = blockIdx.x * 256 + threadIdx.x - 256; if (i < C_CHAIN_END) g_ctl[i] = 0; }
    if (EXP_INV) fft_rows_inv((float2*)(base + OP_BT) + w * (ROW_BUF / 2), (const float2*)(base + OP_TW),
                 (blockIdx.x & 63) * 16 + (blockIdx.x >> 6) * 8 + w, t);
    if (threadIdx.x == 256) TL(3);
    FENCE_ASYNC_SMEM();
    bar_sync(2, 256);
    if (threadIdx.x == 256) {
      uint32_t* cnt = g_ctl + C_ROWS + ((blockIdx.x >> 3) & 7) * 32;
      asm volatile("fence.acq_rel.gpu;" ::: "memory");
      asm volatile("red.relaxed.gpu.global.add.u32 [%0], 1;" :: "l"(cnt) : "memory");
      for (uint32_t n = 0; ld_acquire(cnt) < 16; ) { watchdog(n, 1u << 22); __nanosleep(100); }
      asm volatile("fence.proxy.async.global;" ::: "memory");
      mbar_expect(bfull, 32768);
      tma2d(sb + OP_BT, &tb, n0, m0, bfull); tma2d(sb + OP_BT + 16384, &tb, n0 + 64, m0, bfull);
      TL(5);
    }
  } else {
    const int wg = role, lane = threadIdx.x & 31, w = (threadIdx.x >> 5) & 3;
    float acc[64];
#pragma unroll
    for (int i = 0; i < 64; i++) acc[i] = 0.f;
    const uint32_t rel = mapa(empty, lane & 1), la = desc_lo(sb + wg * 8192), lb = ((sb + 16384) & 0x3FFFF) >> 4 | (8192 >> 4) << 16;
    const uint32_t relon = (threadIdx.x & 127) < 2;
    uint32_t st = 0, ph = 0, prev = 0;
#pragma unroll 1
    for (int kb = 0; kb < 64; kb++) {
      mbar_spin(full + 8 * st, ph);
      WG_FENCE();
#pragma unroll
      for (int k = 0; k < 4; k++) wgmma_ss_n128_tb(acc, desc128(la + st * 2048 + k * 2), desc128(lb + st * 2048 + k * 128));
      WG_COMMIT();
      WG_WAIT(1);
      asm volatile("{ .reg .pred p; setp.ne.u32 p, %1, 0; @p mbarrier.arrive.shared::cluster.b64 _, [%0]; }"
                   :: "r"(rel + 8 * prev), "r"(relon & (uint32_t)(kb > 0 && kb + OP_STAGES <= 64)) : "memory");
      prev = st;
      if (++st == OP_STAGES) { st = 0; ph ^= 1; }
    }
    WG_WAIT(0);
    if (threadIdx.x == 0) TL(4);
    const int r0 = wg * 64 + w * 16 + (lane >> 2);
    const float g0 = __ldcg(g_gate + m0 + r0), g1 = __ldcg(g_gate + m0 + r0 + 8);
    mbar_wait(bfull, 0);
#pragma unroll
    for (int t = 0; t < 16; t++) {
      const uint32_t a0 = sb + OP_BT + (t >> 3) * 16384 + r0 * 128 + (((t & 7) ^ (r0 & 7)) << 4) + (lane & 3) * 4, a1 = a0 + 1024;
      uint32_t b0, b1;
      asm volatile("ld.shared.u32 %0, [%1];" : "=r"(b0) : "r"(a0) : "memory");
      asm volatile("ld.shared.u32 %0, [%1];" : "=r"(b1) : "r"(a1) : "memory");
      const uint32_t o0 = pack_bf16(fmaf(g0, acc[4 * t], (1.f - g0) * __uint_as_float(b0 << 16)), fmaf(g0, acc[4 * t + 1], (1.f - g0) * __uint_as_float(b0 & 0xFFFF0000u)));
      const uint32_t o1 = pack_bf16(fmaf(g1, acc[4 * t + 2], (1.f - g1) * __uint_as_float(b1 << 16)), fmaf(g1, acc[4 * t + 3], (1.f - g1) * __uint_as_float(b1 & 0xFFFF0000u)));
      asm volatile("st.shared.u32 [%0], %1;" :: "r"(a0), "r"(o0) : "memory");
      asm volatile("st.shared.u32 [%0], %1;" :: "r"(a1), "r"(o1) : "memory");
    }
    FENCE_ASYNC_SMEM();
    bar_sync(1, 256);
    if (threadIdx.x == 0) {
      tma2d_store(&tout, n0, m0, sb + OP_BT); tma2d_store(&tout, n0 + 64, m0, sb + OP_BT + 16384);
      asm volatile("cp.async.bulk.commit_group; cp.async.bulk.wait_group 0;" ::: "memory");
      TL(11);
    }
  }
}

typedef CUresult (*EncodeFn)(CUtensorMap*, CUtensorMapDataType, cuuint32_t, void*, const cuuint64_t*, const cuuint64_t*,
                             const cuuint32_t*, const cuuint32_t*, CUtensorMapInterleave, CUtensorMapSwizzle,
                             CUtensorMapL2promotion, CUtensorMapFloatOOBfill);

void make_map(EncodeFn enc, CUtensorMap* tm, const void* p, int rank, const cuuint64_t* dims, const cuuint64_t* strides, const cuuint32_t* box, bool swz = true) {
  const cuuint32_t es[4] = {1, 1, 1, 1};
  enc(tm, CU_TENSOR_MAP_DATA_TYPE_BFLOAT16, rank, (void*)p, dims, strides, box, es, CU_TENSOR_MAP_INTERLEAVE_NONE,
      swz ? CU_TENSOR_MAP_SWIZZLE_128B : CU_TENSOR_MAP_SWIZZLE_NONE, CU_TENSOR_MAP_L2_PROMOTION_L2_128B, CU_TENSOR_MAP_FLOAT_OOB_FILL_NONE);
}
void make_map2(EncodeFn enc, CUtensorMap* tm, const void* p, uint64_t cols, uint64_t rows, uint32_t boxrows) {
  const cuuint64_t dims[2] = {cols, rows}, strides[1] = {cols * 2};
  const cuuint32_t box[2] = {64, boxrows};
  make_map(enc, tm, p, 2, dims, strides, box);
}

}

extern "C" void kernel_launch(void* const* d_in, const int* in_sizes, int n_in, void* d_out, int out_size) {
  (void)in_sizes; (void)n_in; (void)out_size;
  const __nv_bfloat16* x = (const __nv_bfloat16*)d_in[0];
  const __nv_bfloat16* mem0 = (const __nv_bfloat16*)d_in[1];
  const __nv_bfloat16* gw = (const __nv_bfloat16*)d_in[10];

  EncodeFn enc = nullptr;
  cudaDriverEntryPointQueryResult qr;
  cudaGetDriverEntryPoint("cuTensorMapEncodeTiled", (void**)&enc, cudaEnableDefault, &qr);
  void *p_ox, *p_b, *p_mail;
  cudaGetSymbolAddress(&p_ox, g_ox); cudaGetSymbolAddress(&p_b, g_b); cudaGetSymbolAddress(&p_mail, g_mail);
  CUtensorMap tq, tk, tv, tv16, to, tx, twr, twi, ta, tw, tb, tout;
  make_map2(enc, &tq, d_in[2], 4096, 1024, 64);
  make_map2(enc, &tk, d_in[3], 4096, 1024, 64);
  make_map2(enc, &tv, d_in[4], 4096, 1024, 64);
  make_map2(enc, &tv16, d_in[4], 4096, 1024, 16);
  make_map2(enc, &to, d_in[5], 1024, 4096, 128);
  make_map2(enc, &tw, d_in[5], 1024, 4096, 64);
  make_map2(enc, &ta, p_ox, 4096, 2048, 64);
  make_map2(enc, &tb, p_b, 1024, 2048, 128);
  make_map2(enc, &tout, d_out, 1024, 2048, 128);
  {
    const cuuint64_t dims[4] = {64, 8, 16, 256}, strides[3] = {2048, 128, 16384};
    const cuuint32_t box[4] = {64, 8, 8, 2};
    make_map(enc, &tx, x, 4, dims, strides, box);
  }
  {
    const cuuint64_t dims[2] = {8 * 513, 256}, strides[1] = {8 * 513 * 2};
    const cuuint32_t box[2] = {8, 256};
    make_map(enc, &twr, d_in[8], 2, dims, strides, box, false);
    make_map(enc, &twi, d_in[9], 2, dims, strides, box, false);
  }
  cudaFuncSetAttribute(chain_kernel, cudaFuncAttributeMaxDynamicSharedMemorySize, CHAIN_SMEM);
  cudaFuncSetAttribute(outproj_kernel, cudaFuncAttributeMaxDynamicSharedMemorySize, OP_SMEM);

  cudaStream_t st = cudaStreamPerThread;
  char* mail = (char*)(((uintptr_t)p_mail + 8191) & ~(uintptr_t)8191);
  chain_kernel<<<132, 512, CHAIN_SMEM, st>>>(tq, tk, tv, tv16, to, tx, twr, twi, mem0, mail, x, gw);
  cudaLaunchAttribute pdl;
  pdl.id = cudaLaunchAttributeProgrammaticStreamSerialization;
  pdl.val.programmaticStreamSerializationAllowed = 1;
  cudaLaunchConfig_t cfg = {};
  cfg.stream = st; cfg.attrs = &pdl; cfg.numAttrs = USE_PDL;
  cfg.gridDim = dim3(128); cfg.blockDim = dim3(544); cfg.dynamicSmemBytes = OP_SMEM;
  cudaLaunchKernelEx(&cfg, outproj_kernel, ta, tw, tb, tout);
}
```

```cpp
#include <cuda_runtime.h>
#include <cuda_bf16.h>
#include <cuda.h>
#include <stdint.h>

#define DLY_E1 300
#define DLY_V 330
#define DLY_E2 400
#define DLY_E3 500
#define DLY_X 1
#define DLY_S 500
#define DLY_F 0
#define VM_AT 1
#define VM_F 0
#define OM_F 1
#define SXX_IN 0
#define C1_AT 1
#define NLAG 4
#define WO_D 2
#define WO_0 2
#define WO_1 12
#define PL_0 8
#define PL_1 NP_
#define PL_D 2
#define PL_L 0
#define DUAL 0
#define HV_D 3
#define DLY_FK 0
#define QX_SM 0
#define REG_F 216
#define REG_H 24
#define SC_F 1
#define E2_F 1
#define KVQ_AT 0
#define DLY_K 0
#define X_AT 2
#define W_PV 0
#define PL_2 NP_
#define BF_E 3
#define PL_E 2
#define ORDER 1
#define SSPOS 1
#define W_PUB 1
#define FIN_AT 5
#define AWARE 1
#define NPROBE 2
#define NP_ 12
#define USE_PDL 1
#define DLY_GRP 3000
#define P2_BULK 0
#define EXP_NV 4
#define EXP_NK 4
#define EXP_CHK 1
#define EXP_NXT 2
#define EXP_PEER 1
#define EXP_FIN 7
#define EXP_NWG 16
#define ANCH2 1
#define XF_AT 1
#define IS_F 1
#define PL_D1 2
#define W_E2 0
#define V_TMA 2
#define V_W 2
#define RED_L 3
#define RED_T 1
#define RED_P 1
#define DLY_E3B 0
#define HV_E 0
#define HV_R 4
#define HOLD 2
#define PACE 550
#define PACE0 0
#define EXP_ST 7
#define HOLD_AT NPROBE
#define WO_AT 34
#define WO_P 2
#define DLY_SEL 500
#define P1_AT 1
#define EXP_ZG 1
#define TMA_W tma2d_once
#define BULK_F bulk_once
#define TMA_O tma2d_e
#define PACE_Z 500
#define PACE_F 800
#define EXP_INV 1
#define VF_AT 0
#define UP_F 1
#define WO_L (12 - NP_)
#define WO_C 4
#define WO_T 3
#define WO_LD 0
#define EXP_LIN 0
#define PL_W 0
#define PL_WA 4
#define PL_WD 0
#define PL_WF 1
#define STAG 0
#define EXP_FL 0
#define DLY_FS 0
#define DLY_F2 0
#define LROT 0
#define PF_D 4
#define PF_A 1
#define PF_B 1
#define SIDE 1
#define ROLE 1
#define LOOSE 0x765498
#define E1OFF 1
#define EVOFF E1OFF
#define NCR 4
#define GATE 1
#define LASTM 1
#define PRE_AT B_SC

namespace {

constexpr int S_ = 2048, D_ = 1024, NSEG = 64;
constexpr uint32_t SENT = 0xFFFFFFFFu;
constexpr int NSLOT = 4;

constexpr uint32_t M_PAIR = 0, M_E3 = M_PAIR + 2 * 128 * 16384, M_REF = M_E3 + 16 * 8192, M_KVQ = M_REF + 8192,
                   MAIL_BYTES = M_KVQ + NSLOT * 32 * 24576;
__device__ __align__(1024) unsigned char g_mail[MAIL_BYTES + 16384];
constexpr int C_SEL = 0, C_P1 = C_SEL + 128, C_COLS = C_P1 + 32, C_EARLY = C_COLS + 32, C_LAST = C_EARLY + 32, C_ROWS = C_LAST + 32, C_END = C_ROWS + 8 * 32;
__device__ __align__(1024) uint32_t g_ctl[C_END];
#define CLK(i)
#define TL(i)
#define TL2(i)
#define FT(i, v)
#define CNT(i)
__device__ __align__(1024) __nv_bfloat16 g_ox[S_ * 4096];
__device__ __align__(1024) float2 g_z[257 * 4096];
__device__ __align__(1024) __nv_bfloat16 g_b[S_ * D_];
__device__ float g_gate[S_];
__device__ __align__(1024) float2 g_tw[1024];

#define TRV(s, ev, val)
#define TR(s, ev)
#define TRSYNC(ev)
__device__ __forceinline__ uint32_t smem_u32(const void* p) { return (uint32_t)__cvta_generic_to_shared(p); }
__device__ __forceinline__ void watchdog(uint32_t& n, uint32_t limit) {
  asm volatile("{ .reg .pred p; add.u32 %0, %0, 1; setp.gt.u32 p, %0, %1; @p trap; }" : "+r"(n) : "r"(limit));
}
__device__ __forceinline__ void mbar_init(uint32_t bar, uint32_t cnt) {
  asm volatile("mbarrier.init.shared::cta.b64 [%0], %1;" :: "r"(bar), "r"(cnt) : "memory");
}
__device__ __forceinline__ void mbar_arrive_warp(uint32_t bar) {
  __syncwarp();
  asm volatile("{ .reg .pred p; elect.sync _|p, 0xffffffff; @p mbarrier.arrive.shared::cta.b64 _, [%0]; }" :: "r"(bar) : "memory");
}
__device__ __forceinline__ uint32_t clock_lo() {
  uint32_t r; asm volatile("{ .reg .u64 c; .reg .u32 h; mov.u64 c, %%clock64; mov.b64 {%0, h}, c; }" : "=r"(r) :: "memory"); return r;
}
__device__ __forceinline__ void delay_until(uint32_t t) {
  asm volatile("{ .reg .pred p; .reg .u64 c; .reg .u32 l, h;\n"
               "DLY: mov.u64 c, %%clock64; mov.b64 {l, h}, c; sub.s32 l, l, %0; setp.lt.s32 p, l, 0; @p bra.uni DLY; }" :: "r"(t) : "memory");
}
__device__ __forceinline__ void delay_cycles(uint32_t n) { delay_until(clock_lo() + n); }
__device__ __forceinline__ void sched_fence(uint32_t z) {
  asm volatile("{ .reg .pred p; setp.eq.u32 p, %0, 0x7fff0000; @p pmevent 1; }" :: "r"(z) : "memory");
}
__device__ __forceinline__ void pdl_wait() { asm volatile("griddepcontrol.wait;" ::: "memory"); }
__device__ __forceinline__ void pdl_launch() { asm volatile("griddepcontrol.launch_dependents;" ::: "memory"); }
__device__ __forceinline__ float ex2(float x) { float r; asm("ex2.approx.ftz.f32 %0, %1;" : "=f"(r) : "f"(x)); return r; }
__device__ __forceinline__ float rcp(float x) { float r; asm("rcp.approx.ftz.f32 %0, %1;" : "=f"(r) : "f"(x)); return r; }
__device__ __forceinline__ void mbar_expect(uint32_t bar, uint32_t bytes) {
  asm volatile("mbarrier.arrive.expect_tx.shared::cta.b64 _, [%0], %1;" :: "r"(bar), "r"(bytes) : "memory");
}
__device__ __forceinline__ bool mbar_try(uint32_t bar, uint32_t ph) {
  uint32_t ok;
  asm volatile("{ .reg .pred p; mbarrier.try_wait.parity.shared::cta.b64 p, [%1], %2; selp.u32 %0, 1, 0, p; }"
               : "=r"(ok) : "r"(bar), "r"(ph) : "memory");
  return ok;
}
__device__ __forceinline__ void mbar_wait(uint32_t bar, uint32_t ph) {
  uint32_t n = 0;
  while (!mbar_try(bar, ph)) { watchdog(n, (1u << 20)); }
}
__device__ __forceinline__ void mbar_spin(uint32_t bar, uint32_t ph) { while (!mbar_try(bar, ph)) {} }
__device__ __forceinline__ void mbar_spin_if(uint32_t bar, uint32_t ph, bool on) {
  asm volatile("{ .reg .pred p, q; setp.ne.u32 p, %2, 0;\n"
               "SPN: setp.eq.u32 q, 0, 0; @p mbarrier.try_wait.parity.shared::cta.b64 q, [%0], %1; @!q bra.uni SPN; }" :: "r"(bar), "r"(ph), "r"((uint32_t)on) : "memory");
}
__device__ __forceinline__ void mbar_spin_cluster(uint32_t bar, uint32_t ph) {
  uint32_t ok;
  do {
    asm volatile("{ .reg .pred p; mbarrier.try_wait.parity.acquire.cluster.shared::cta.b64 p, [%1], %2; selp.u32 %0, 1, 0, p; }"
                 : "=r"(ok) : "r"(bar), "r"(ph) : "memory");
  } while (!ok);
}
__device__ __forceinline__ void tma2d(uint32_t dst, const CUtensorMap* tm, int c0, int c1, uint32_t bar) {
  asm volatile("cp.async.bulk.tensor.2d.shared::cluster.global.mbarrier::complete_tx::bytes [%0], [%1, {%3, %4}], [%2];"
               :: "r"(dst), "l"(tm), "r"(bar), "r"(c0), "r"(c1) : "memory");
}
__device__ __forceinline__ void tma2d_store(const CUtensorMap* tm, int c0, int c1, uint32_t src) {
  asm volatile("cp.async.bulk.tensor.2d.global.shared::cta.bulk_group [%0, {%2, %3}], [%1];"
               :: "l"(tm), "r"(src), "r"(c0), "r"(c1) : "memory");
}
__device__ __forceinline__ void mbar_expect_e(uint32_t bar, uint32_t bytes) {
  asm volatile("{ .reg .pred p; elect.sync _|p, 0xffffffff; @p mbarrier.arrive.expect_tx.shared::cta.b64 _, [%0], %1; }" :: "r"(bar), "r"(bytes) : "memory");
}
__device__ __forceinline__ void tma2d_e(uint32_t dst, const CUtensorMap* tm, int c0, int c1, uint32_t bar) {
  asm volatile("{ .reg .pred p; elect.sync _|p, 0xffffffff;\n"
               "@p cp.async.bulk.tensor.2d.shared::cluster.global.mbarrier::complete_tx::bytes [%0], [%1, {%3, %4}], [%2]; }"
               :: "r"(dst), "l"(tm), "r"(bar), "r"(c0), "r"(c1) : "memory");
}
__device__ __forceinline__ void tma2d_once(uint32_t dst, const CUtensorMap* tm, int c0, int c1, uint32_t bar) {
  asm volatile("{ .reg .pred p; .reg .b64 h; createpolicy.fractional.L2::evict_first.b64 h; elect.sync _|p, 0xffffffff;\n"
               "@p cp.async.bulk.tensor.2d.shared::cluster.global.mbarrier::complete_tx::bytes.L2::cache_hint [%0], [%1, {%3, %4}], [%2], h; }"
               :: "r"(dst), "l"(tm), "r"(bar), "r"(c0), "r"(c1) : "memory");
}
__device__ __forceinline__ void bulk_once(uint32_t dst, const void* src, uint32_t bytes, uint32_t bar) {
  asm volatile("{ .reg .pred p; .reg .b64 h; createpolicy.fractional.L2::evict_first.b64 h; elect.sync _|p, 0xffffffff;\n"
               "@p cp.async.bulk.shared::cluster.global.mbarrier::complete_tx::bytes.L2::cache_hint [%0], [%1], %2, [%3], h; }"
               :: "r"(dst), "l"(src), "r"(bytes), "r"(bar) : "memory");
}
__device__ __forceinline__ void tma4d_e(uint32_t dst, const CUtensorMap* tm, int c2, int c3, uint32_t bar) {
  asm volatile("{ .reg .pred p; elect.sync _|p, 0xffffffff;\n"
               "@p cp.async.bulk.tensor.4d.shared::cluster.global.mbarrier::complete_tx::bytes [%0], [%1, {0, 0, %3, %4}], [%2]; }"
               :: "r"(dst), "l"(tm), "r"(bar), "r"(c2), "r"(c3) : "memory");
}
__device__ __forceinline__ void bulk_load_e(uint32_t dst, const void* src, uint32_t bytes, uint32_t bar) {
  asm volatile("{ .reg .pred p; elect.sync _|p, 0xffffffff;\n"
               "@p cp.async.bulk.shared::cluster.global.mbarrier::complete_tx::bytes [%0], [%1], %2, [%3]; }"
               :: "r"(dst), "l"(src), "r"(bytes), "r"(bar) : "memory");
}
__device__ __forceinline__ void prefetch2d_e(const CUtensorMap* tm, int c0, int c1) {
  asm volatile("{ .reg .pred p; elect.sync _|p, 0xffffffff;\n"
               "@p cp.async.bulk.prefetch.tensor.2d.L2.global [%0, {%1, %2}]; }" :: "l"(tm), "r"(c0), "r"(c1) : "memory");
}
__device__ __forceinline__ void st_pub4(void* p, uint4 v) {
  asm volatile("st.relaxed.gpu.global.v4.u32 [%0], {%1,%2,%3,%4};" :: "l"(p), "r"(v.x), "r"(v.y), "r"(v.z), "r"(v.w) : "memory");
}
__device__ __forceinline__ void st_pub_if(void* p, uint32_t v, bool on) {
  asm volatile("{ .reg .pred p; setp.ne.u32 p, %2, 0; @p st.relaxed.gpu.global.u32 [%0], %1; }" :: "l"(p), "r"(v), "r"((uint32_t)on) : "memory");
}
__device__ __forceinline__ uint32_t mapa(uint32_t a, uint32_t r) {
  uint32_t d; asm volatile("mapa.shared::cluster.u32 %0, %1, %2;" : "=r"(d) : "r"(a), "r"(r)); return d;
}
__device__ __forceinline__ void st_async4(uint32_t a, uint32_t x, uint32_t y, uint32_t z, uint32_t w, uint32_t bar) {
  asm volatile("st.async.shared::cluster.mbarrier::complete_tx::bytes.v4.u32 [%0], {%1,%2,%3,%4}, [%5];"
               :: "r"(a), "r"(x), "r"(y), "r"(z), "r"(w), "r"(bar) : "memory");
}
__device__ __forceinline__ uint4 ld_poll(const void* p) {
  uint4 v;
  asm volatile("ld.volatile.global.v4.u32 {%0,%1,%2,%3}, [%4];" : "=r"(v.x), "=r"(v.y), "=r"(v.z), "=r"(v.w) : "l"(p) : "memory");
  return v;
}
__device__ __forceinline__ uint2 ld_poll2(const void* p) {
  uint2 v; asm volatile("ld.volatile.global.v2.u32 {%0,%1}, [%2];" : "=r"(v.x), "=r"(v.y) : "l"(p) : "memory"); return v;
}
__device__ __forceinline__ void st_pub2(void* p, uint32_t a, uint32_t b) {
  asm volatile("st.relaxed.gpu.global.v2.u32 [%0], {%1,%2};" :: "l"(p), "r"(a), "r"(b) : "memory");
}
__device__ __forceinline__ uint32_t ld_poll1(const void* p) {
  uint32_t v; asm volatile("ld.volatile.global.u32 %0, [%1];" : "=r"(v) : "l"(p) : "memory"); return v;
}
__device__ __forceinline__ uint32_t ld_acquire(const uint32_t* p) {
  uint32_t v; asm volatile("ld.acquire.gpu.global.u32 %0, [%1];" : "=r"(v) : "l"(p) : "memory"); return v;
}
__device__ __forceinline__ void st_pub(void* p, uint32_t v) {
  asm volatile("st.relaxed.gpu.global.u32 [%0], %1;" :: "l"(p), "r"(v) : "memory");
}
__device__ __forceinline__ uint32_t lds32(uint32_t a) {
  uint32_t v; asm volatile("ld.shared.u32 %0, [%1];" : "=r"(v) : "r"(a) : "memory"); return v;
}
__device__ __forceinline__ int race_init(void* p0, void* p1, uint32_t val) {
  int t;
  asm volatile("{ .reg .pred r; .reg .u32 a, b, u, v;\n"
               "atom.relaxed.gpu.global.exch.b32 u, [%1], %3; atom.relaxed.gpu.global.exch.b32 v, [%2], %3;\n"
               "setp.eq.u32 r, u, 0x12345; @r pmevent 1; mov.u32 a, %%clock;\n"
               "setp.eq.u32 r, v, 0x12345; @r pmevent 1; mov.u32 b, %%clock; sub.u32 %0, b, a; }" : "=r"(t) : "l"(p0), "l"(p1), "r"(val) : "memory");
  return t;
}
__device__ __forceinline__ uint4 lds128(uint32_t a) {
  uint4 v; asm volatile("ld.shared.v4.u32 {%0,%1,%2,%3}, [%4];" : "=r"(v.x), "=r"(v.y), "=r"(v.z), "=r"(v.w) : "r"(a) : "memory"); return v;
}
__device__ __forceinline__ uint2 lds64(uint32_t a) {
  uint2 v; asm volatile("ld.shared.v2.u32 {%0,%1}, [%2];" : "=r"(v.x), "=r"(v.y) : "r"(a) : "memory"); return v;
}
__device__ __forceinline__ void sts128(uint32_t a, uint4 v) {
  asm volatile("st.shared.v4.u32 [%0], {%1,%2,%3,%4};" :: "r"(a), "r"(v.x), "r"(v.y), "r"(v.z), "r"(v.w) : "memory");
}
__device__ __forceinline__ void sts64(uint32_t a, uint32_t x, uint32_t y) { asm volatile("st.shared.v2.u32 [%0], {%1,%2};" :: "r"(a), "r"(x), "r"(y) : "memory"); }
__device__ __forceinline__ void sts32(uint32_t a, uint32_t x) { asm volatile("st.shared.u32 [%0], %1;" :: "r"(a), "r"(x) : "memory"); }
__device__ __forceinline__ void ldsm4t(uint32_t (&r)[4], uint32_t a) {
  asm volatile("ldmatrix.sync.aligned.m8n8.x4.trans.shared.b16 {%0,%1,%2,%3}, [%4];"
               : "=r"(r[0]), "=r"(r[1]), "=r"(r[2]), "=r"(r[3]) : "r"(a) : "memory");
}
template<bool TRANS> __device__ __forceinline__ void stsm4(uint32_t a, uint32_t r0, uint32_t r1, uint32_t r2, uint32_t r3) {
  if (TRANS) asm volatile("stmatrix.sync.aligned.m8n8.x4.trans.shared.b16 [%0], {%1,%2,%3,%4};" :: "r"(a), "r"(r0), "r"(r1), "r"(r2), "r"(r3) : "memory");
  else       asm volatile("stmatrix.sync.aligned.m8n8.x4.shared.b16 [%0], {%1,%2,%3,%4};" :: "r"(a), "r"(r0), "r"(r1), "r"(r2), "r"(r3) : "memory");
}
__device__ __forceinline__ void mma16816(float (&d)[4], uint32_t a0, uint32_t a1, uint32_t a2, uint32_t a3, uint32_t b0, uint32_t b1) {
  asm volatile("mma.sync.aligned.m16n8k16.row.col.f32.bf16.bf16.f32 {%0,%1,%2,%3}, {%4,%5,%6,%7}, {%8,%9}, {%0,%1,%2,%3};"
               : "+f"(d[0]), "+f"(d[1]), "+f"(d[2]), "+f"(d[3]) : "r"(a0), "r"(a1), "r"(a2), "r"(a3), "r"(b0), "r"(b1));
}
__device__ __forceinline__ void mma1688(float (&d)[4], uint32_t a0, uint32_t a1, uint32_t b0) {
  asm volatile("mma.sync.aligned.m16n8k8.row.col.f32.bf16.bf16.f32 {%0,%1,%2,%3}, {%4,%5}, {%6}, {%0,%1,%2,%3};"
               : "+f"(d[0]), "+f"(d[1]), "+f"(d[2]), "+f"(d[3]) : "r"(a0), "r"(a1), "r"(b0));
}
__device__ __forceinline__ uint32_t pack_bf16(float lo, float hi) {
  uint32_t r; asm("cvt.rn.bf16x2.f32 %0, %1, %2;" : "=r"(r) : "f"(hi), "f"(lo)); return r;
}
__device__ __forceinline__ uint32_t add_bf16x2(uint32_t a, uint32_t b) {
  uint32_t r; asm("add.rn.bf16x2 %0, %1, %2;" : "=r"(r) : "r"(a), "r"(b)); return r;
}
__device__ __forceinline__ uint32_t umax4(uint4 v) { return max(max(v.x, v.y), max(v.z, v.w)); }
__device__ __forceinline__ uint32_t opaque(uint32_t x) { uint32_t r; asm volatile("mov.u32 %0, %1;" : "=r"(r) : "r"(x)); return r; }
template<class T> __device__ __forceinline__ void pin(T*& p) { asm volatile("" : "+l"(p)); }
__device__ __forceinline__ void pin(uint32_t& v) { asm volatile("" : "+r"(v)); }
__device__ __forceinline__ uint32_t desc_lo(uint32_t addr) { return ((addr & 0x3FFFF) >> 4) | 0x10000; }
__device__ __forceinline__ uint64_t desc128(uint32_t lo) {
  uint64_t d; asm("mov.b64 %0, {%1, %2};" : "=l"(d) : "r"(lo), "r"(0x40000040)); return d;
}
#define WG_FENCE()  asm volatile("wgmma.fence.sync.aligned;" ::: "memory")
#define WG_COMMIT() asm volatile("wgmma.commit_group.sync.aligned;" ::: "memory")
#define WG_WAIT(n)  asm volatile("wgmma.wait_group.sync.aligned " #n ";" ::: "memory")
#define FENCE_ASYNC_SMEM() asm volatile("fence.proxy.async.shared::cta;" ::: "memory")
__device__ __forceinline__ void bar_sync(int id, int n) { asm volatile("bar.sync %0, %1;" :: "r"(id), "r"(n) : "memory"); }

#define D16(c) c(d[0]), c(d[1]), c(d[2]), c(d[3]), c(d[4]), c(d[5]), c(d[6]), c(d[7]), \
               c(d[8]), c(d[9]), c(d[10]), c(d[11]), c(d[12]), c(d[13]), c(d[14]), c(d[15])
template<bool FIRST> __device__ __forceinline__ void wgmma_rs_n32(float (&d)[16], const uint32_t (&a)[4], uint64_t b) {
  if (FIRST)
    asm volatile("wgmma.mma_async.sync.aligned.m64n32k16.f32.bf16.bf16 {%0,%1,%2,%3,%4,%5,%6,%7,%8,%9,%10,%11,%12,%13,%14,%15}, {%16,%17,%18,%19}, %20, 0, 1, 1, 0;"
      : D16("=f") : "r"(a[0]), "r"(a[1]), "r"(a[2]), "r"(a[3]), "l"(b));
  else
    asm volatile("wgmma.mma_async.sync.aligned.m64n32k16.f32.bf16.bf16 {%0,%1,%2,%3,%4,%5,%6,%7,%8,%9,%10,%11,%12,%13,%14,%15}, {%16,%17,%18,%19}, %20, 1, 1, 1, 0;"
      : D16("+f") : "r"(a[0]), "r"(a[1]), "r"(a[2]), "r"(a[3]), "l"(b));
}
template<bool FIRST> __device__ __forceinline__ void wgmma_ss_n32_ta(float (&d)[16], uint64_t a, uint64_t b) {
  if (FIRST)
    asm volatile("wgmma.mma_async.sync.aligned.m64n32k16.f32.bf16.bf16 {%0,%1,%2,%3,%4,%5,%6,%7,%8,%9,%10,%11,%12,%13,%14,%15}, %16, %17, 0, 1, 1, 1, 0;"
      : D16("=f") : "l"(a), "l"(b));
  else
    asm volatile("wgmma.mma_async.sync.aligned.m64n32k16.f32.bf16.bf16 {%0,%1,%2,%3,%4,%5,%6,%7,%8,%9,%10,%11,%12,%13,%14,%15}, %16, %17, 1, 1, 1, 1, 0;"
      : D16("+f") : "l"(a), "l"(b));
}
__device__ __forceinline__ void wgmma_ss_n128_tb(float (&d)[64], uint64_t a, uint64_t b) {
  asm volatile("wgmma.mma_async.sync.aligned.m64n128k16.f32.bf16.bf16 "
    "{%0,%1,%2,%3,%4,%5,%6,%7,%8,%9,%10,%11,%12,%13,%14,%15,%16,%17,%18,%19,%20,%21,%22,%23,%24,%25,%26,%27,%28,%29,%30,%31,"
    "%32,%33,%34,%35,%36,%37,%38,%39,%40,%41,%42,%43,%44,%45,%46,%47,%48,%49,%50,%51,%52,%53,%54,%55,%56,%57,%58,%59,%60,%61,%62,%63}, "
    "%64, %65, 1, 1, 1, 0, 1;"
    : "+f"(d[0]), "+f"(d[1]), "+f"(d[2]), "+f"(d[3]), "+f"(d[4]), "+f"(d[5]), "+f"(d[6]), "+f"(d[7]),
      "+f"(d[8]), "+f"(d[9]), "+f"(d[10]), "+f"(d[11]), "+f"(d[12]), "+f"(d[13]), "+f"(d[14]), "+f"(d[15]),
      "+f"(d[16]), "+f"(d[17]), "+f"(d[18]), "+f"(d[19]), "+f"(d[20]), "+f"(d[21]), "+f"(d[22]), "+f"(d[23]),
      "+f"(d[24]), "+f"(d[25]), "+f"(d[26]), "+f"(d[27]), "+f"(d[28]), "+f"(d[29]), "+f"(d[30]), "+f"(d[31]),
      "+f"(d[32]), "+f"(d[33]), "+f"(d[34]), "+f"(d[35]), "+f"(d[36]), "+f"(d[37]), "+f"(d[38]), "+f"(d[39]),
      "+f"(d[40]), "+f"(d[41]), "+f"(d[42]), "+f"(d[43]), "+f"(d[44]), "+f"(d[45]), "+f"(d[46]), "+f"(d[47]),
      "+f"(d[48]), "+f"(d[49]), "+f"(d[50]), "+f"(d[51]), "+f"(d[52]), "+f"(d[53]), "+f"(d[54]), "+f"(d[55]),
      "+f"(d[56]), "+f"(d[57]), "+f"(d[58]), "+f"(d[59]), "+f"(d[60]), "+f"(d[61]), "+f"(d[62]), "+f"(d[63])
    : "l"(a), "l"(b));
}

__device__ __forceinline__ void tma2d_mc_e(uint32_t dst, const CUtensorMap* tm, int c0, int c1, uint32_t bar) {
  asm volatile("{ .reg .pred p; elect.sync _|p, 0xffffffff;\n"
               "@p cp.async.bulk.tensor.2d.shared::cluster.global.mbarrier::complete_tx::bytes.multicast::cluster [%0], [%1, {%3, %4}], [%2], %5; }"
               :: "r"(dst), "l"(tm), "r"(bar), "r"(c0), "r"(c1), "h"((uint16_t)3) : "memory");
}

__device__ __forceinline__ void count_e(uint32_t* p) {
  asm volatile("fence.acq_rel.gpu;" ::: "memory");
  __syncwarp();
  asm volatile("{ .reg .pred p; elect.sync _|p, 0xffffffff; @p red.relaxed.gpu.global.add.u32 [%0], 1; }" :: "l"(p) : "memory");
}
__device__ __forceinline__ void await_count(const uint32_t* p, uint32_t n) {
  for (uint32_t i = 0; ld_acquire(p) < n && i < (1u << 22); i++) {}
  asm volatile("fence.proxy.async.global;" ::: "memory");
}
__device__ __forceinline__ void mbar_lim(uint32_t bar, uint32_t ph) { for (uint32_t i = 0; !mbar_try(bar, ph) && i < (1u << 20); i++) {} }

struct cf { float x, y; };
__host__ __device__ constexpr float cos64(int k) {
  return k == 0 ? 1.0f : k == 1 ? 0.99518472667219689f : k == 2 ? 0.98078528040323045f : k == 3 ? 0.95694033573220887f :
         k == 4 ? 0.92387953251128676f : k == 5 ? 0.88192126434835503f : k == 6 ? 0.83146961230254524f : k == 7 ? 0.77301045336273696f :
         k == 8 ? 0.70710678118654752f : k == 9 ? 0.63439328416364550f : k == 10 ? 0.55557023301960222f : k == 11 ? 0.47139673682599765f :
         k == 12 ? 0.38268343236508977f : k == 13 ? 0.29028467725446236f : k == 14 ? 0.19509032201612827f : k == 15 ? 0.09801714032956060f : 0.0f;
}
__host__ __device__ constexpr float c64(int k) { return k <= 16 ? cos64(k) : -cos64(32 - k); }
__host__ __device__ constexpr float s64(int k) { return k <= 16 ? cos64(16 - k) : cos64(k - 16); }

template<int N, int ST, bool INV> struct Fft {
  template<int K> static __device__ __forceinline__ void bf(const cf* e, const cf* o, cf* out) {
    if constexpr (K < N / 2) {
      constexpr int idx = K * (64 / N);
      const cf a = e[K], b = o[K];
      if constexpr (idx == 0) {
        out[K] = {a.x + b.x, a.y + b.y}; out[K + N / 2] = {a.x - b.x, a.y - b.y};
      } else if constexpr (idx == 16) {
        if constexpr (INV) { out[K] = {a.x - b.y, a.y + b.x}; out[K + N / 2] = {a.x + b.y, a.y - b.x}; }
        else               { out[K] = {a.x + b.y, a.y - b.x}; out[K + N / 2] = {a.x - b.y, a.y + b.x}; }
      } else {
        constexpr float c = c64(idx), s = INV ? s64(idx) : -s64(idx);
        cf p; p.x = fmaf(-s, b.y, fmaf(c, b.x, a.x)); p.y = fmaf(s, b.x, fmaf(c, b.y, a.y));
        out[K] = p; out[K + N / 2] = {fmaf(2.0f, a.x, -p.x), fmaf(2.0f, a.y, -p.y)};
      }
      bf<K + 1>(e, o, out);
    }
  }
  static __device__ __forceinline__ void run(const cf* in, cf* out) {
    cf e[N / 2], o[N / 2];
    Fft<N / 2, 2 * ST, INV>::run(in, e);
    Fft<N / 2, 2 * ST, INV>::run(in + ST, o);
    bf<0>(e, o, out);
  }
};
template<int ST, bool INV> struct Fft<1, ST, INV> {
  static __device__ __forceinline__ void run(const cf* in, cf* out) { out[0] = in[0]; }
};
template<bool INV> __device__ __forceinline__ void fft32(cf (&v)[32]) {
  cf o[32]; Fft<32, 1, INV>::run(v, o);
#pragma unroll
  for (int i = 0; i < 32; i++) v[i] = o[i];
}
__device__ __forceinline__ cf cmul(cf a, float c, float s) { return {fmaf(-a.y, s, a.x * c), fmaf(a.x, s, a.y * c)}; }
__device__ __forceinline__ float bf2f(__nv_bfloat16 v) { return __bfloat162float(v); }

template<bool INV> __device__ __forceinline__ void warp_fft1024_a(cf (&v)[32], float2* __restrict__ buf, const float2* __restrict__ tw, int t, int u) {
  fft32<INV>(v);
#pragma unroll
  for (int j = 1; j < 32; j++) { const float2 w = tw[j * 32 + t]; v[j] = cmul(v[j], w.x, INV ? -w.y : w.y); }
  if (INV) {
    float* f = (float*)buf;
#pragma unroll
    for (int j = 0; j < 32; j++) f[j * 33 + t] = v[j].x;
    __syncwarp();
#pragma unroll
    for (int j = 0; j < 32; j++) v[j].x = f[u * 33 + j];
    __syncwarp();
#pragma unroll
    for (int j = 0; j < 32; j++) f[j * 33 + t] = v[j].y;
    __syncwarp();
#pragma unroll
    for (int j = 0; j < 32; j++) v[j].y = f[u * 33 + j];
  } else {
#pragma unroll
    for (int j = 0; j < 32; j++) buf[j * 33 + t] = make_float2(v[j].x, v[j].y);
    __syncwarp();
#pragma unroll
    for (int j = 0; j < 32; j++) { const float2 r = buf[u * 33 + j]; v[j] = {r.x, r.y}; }
  }
  __syncwarp();
}
constexpr int ROW_BUF = 32 * 33;

__device__ __forceinline__ int z_row(int p) { return (p & ~31) | (p & 7) << 2 | (p & 31) >> 3; }
template<bool PERM> __device__ __forceinline__ void row_twiddles(float2* tw, int tid, int nthreads) {
  for (int i = tid; i < 1024; i += nthreads) {
    float s, c; sincospif(-(float)((i >> 5) * ((PERM ? z_row(i) : i) & 31)) * (1.0f / 512.0f), &s, &c); tw[i] = make_float2(c, s);
  }
}
__device__ __forceinline__ void fft_rows_fwd(float2* sm2, const __nv_bfloat16* gw, int cta, int tid, uint32_t full_bar, uint32_t release_bar) {
  const int t = tid & 31, w = tid >> 5, n = z_row(cta * 8 + w);
  row_twiddles<false>(sm2, tid, 256);
  mbar_spin(full_bar, 0);
  if (tid == 0) TL2(6);
  __syncwarp();
  const __nv_bfloat16* xa = (const __nv_bfloat16*)(sm2 + 1024 + w * ROW_BUF) + t;
  cf v[32];
  float ga = 0.f, gb = 0.f;
#pragma unroll
  for (int j = 0; j < 32; j++) {
    v[j] = {bf2f(xa[32 * j]), bf2f(xa[D_ + 32 * j])};
    const float g = bf2f(gw[32 * j + t]); ga = fmaf(v[j].x, g, ga); gb = fmaf(v[j].y, g, gb);
  }
#pragma unroll
  for (int o = 16; o; o >>= 1) { ga += __shfl_xor_sync(~0u, ga, o); gb += __shfl_xor_sync(~0u, gb, o); }
  if (t < 2) g_gate[n + 1024 * t] = __fdividef(1.0f, 1.0f + __expf(-(t ? gb : ga)));
  bar_sync(13, 256);
  warp_fft1024_a<false>(v, sm2 + 1024 + w * ROW_BUF, sm2, t, t);
  FENCE_ASYNC_SMEM();
  mbar_arrive_warp(release_bar);
  fft32<false>(v);
  float ws, wc; sincospif(-(float)n * (1.0f / 1024.0f), &ws, &wc);
  uint32_t tz = clock_lo();
  float4* z = (float4*)g_z + ((size_t)(t >> 1) * 1024 + cta * 8 + w) * 2 + (t & 1);
#pragma unroll
  for (int j = 0; j < 17; j++) {
    cf q = v[(32 - j) & 31];
    if (j < 16) {
      const cf r = {__shfl_sync(~0u, v[31 - j].x, 32 - t), __shfl_sync(~0u, v[31 - j].y, 32 - t)};
      if (t != 0) q = r;
    }
    const cf a = {v[j].x + q.x, v[j].y - q.y}, b = {v[j].y + q.y, q.x - v[j].x};
    const cf d = cmul({a.x - b.x, a.y - b.y}, wc, ws);
    if (PACE_Z && j && j < 16) delay_until(tz += PACE_Z);
    if ((j < 16 || t == 0) && ((EXP_ST & 4) || d.x == 123.f)) z[j * 32768] = make_float4(a.x + b.x, a.y + b.y, d.x, d.y);
  }
}
constexpr int COL_FS = 1057, COL_W = (8192 + 16 * COL_FS * 4 + 127) & ~127, COL_SMEM = COL_W + 131072 + 16;

__device__ __forceinline__ void fft_cols(float2* sm2, int cta, const CUtensorMap* twr, const CUtensorMap* twi) {
  const int grp = __shfl_sync(~0u, (int)(threadIdx.x >> 7), 0), tid = threadIdx.x & 127, tp = tid >> 2, t = z_row(tp);
  float* buf = (float*)(sm2 + 1024) + (grp * 4 + (tid & 3)) * COL_FS;
  const uint32_t wsm = smem_u32(sm2) + COL_W, wbar = wsm + 131072;
  const int res = (tid >> 5) * 2 + (tid & 1), el = res + grp * 2 + ((tid >> 1) & 1);
  uint32_t wa = (el >> 3) * 65536 + res * 4096 + (tp & 7) * 16 + (el & 7) * 2;
  auto load_w = [&](int q) { for (int i = 0; i < 16; i++) tma2d(wsm + (q & 1) * 65536 + i * 4096, i < 8 ? twr : twi, (i & 7) * 512 + q * 8, 0, wbar); };
  if (threadIdx.x == 0) { mbar_init(wbar, 1); sts32(wbar + 8, 0); asm volatile("fence.mbarrier_init.release.cluster;" ::: "memory"); }
  row_twiddles<true>(sm2, threadIdx.x, 512);
  if (cta < 2) row_twiddles<false>(g_tw, cta * 512 + threadIdx.x, 1024);
  for (uint32_t n = 0; ld_acquire(g_ctl + C_P1) < 128; ) { watchdog(n, 1u << 22); __nanosleep(200); }
  __syncthreads();
  if (threadIdx.x == 0) { mbar_expect(wbar, 131072); load_w(cta * 16); load_w(cta * 16 + 1); }
  __syncwarp();
  delay_cycles(1 + grp * DLY_GRP);
  const int end = cta * 64 + 64 + (cta == 3);
  for (int item = cta * 64 + grp; item < end; item += 4, wa ^= 65536) {
    float2* zp = g_z + (size_t)item * 4096;
    cf v[32];
#pragma unroll
    for (int j = 0; j < 32; j++) { const float2 a = __ldcg(zp + tid + j * 128); v[j] = {a.x, a.y}; }
#pragma unroll 1
    for (int dir = 0; dir < 2; dir++) {
      fft32<false>(v);
#pragma unroll
      for (int j = 1; j < 32; j++) { const float2 w = sm2[j * 32 + tp]; v[j] = cmul(v[j], w.x, w.y); }
      bar_sync(1 + grp, 128);
      if (dir == 1 && tid == 0) {
        uint32_t n; asm volatile("atom.shared.inc.u32 %0, [%1], 3;" : "=r"(n) : "r"(wbar + 8) : "memory");
        if (n == 3 && item - grp + 4 < end) { mbar_expect(wbar, 65536); load_w((item >> 2) + 2); }
      }
      __syncwarp();
#pragma unroll
      for (int j = 0; j < 32; j++) buf[j * 33 + t] = v[j].x;
      bar_sync(1 + grp, 128);
#pragma unroll
      for (int j = 0; j < 32; j++) v[j].x = buf[t * 33 + j];
      bar_sync(1 + grp, 128);
#pragma unroll
      for (int j = 0; j < 32; j++) buf[j * 33 + t] = v[j].y;
      bar_sync(1 + grp, 128);
#pragma unroll
      for (int j = 0; j < 32; j++) v[j].y = buf[t * 33 + j];
      fft32<false>(v);
      if (dir == 0) {
        mbar_wait(wbar, (item >> 2) & 1);
#pragma unroll
        for (int j = 0; j < 32; j++) {
          uint32_t re, im;
          asm volatile("ld.shared.u16 %0, [%1];" : "=r"(re) : "r"(wsm + wa + j * 128) : "memory");
          asm volatile("ld.shared.u16 %0, [%1];" : "=r"(im) : "r"(wsm + wa + 32768 + j * 128) : "memory");
          const cf r = cmul(v[j], __uint_as_float(re << 16), __uint_as_float(im << 16));
          v[j] = {r.y, r.x};
        }
      }
    }
#pragma unroll
    for (int j = 0; j < 32; j++) zp[tid + j * 128] = make_float2(v[j].y, v[j].x);
  }
  __syncthreads();
  if (threadIdx.x < 32) {
    count_e(g_ctl + C_COLS);
    await_count(g_ctl + C_COLS, 4);
    g_ctl[C_P1] = 0;
  }
  __syncthreads();
  ((float4*)sm2)[threadIdx.x] = __ldcg((const float4*)g_tw + threadIdx.x);
  __syncthreads();
}

template<class F> __device__ __forceinline__ void fft_rows_inv(uint32_t zs, float2* buf, const float2* tw, int p, int lane, F read) {
  const int n = z_row(p), t = (lane & 17) | (lane & 6) << 1 | (lane & 8) >> 2, tm = -t & 31, src = (tm & 17) | (tm & 12) >> 1 | (tm & 2) << 2;
  const uint32_t z = zs + (t >> 1) * 128 + ((((p & 3) * 2 + (t & 1)) ^ (t >> 1 & 7)) << 4);
  FT(0, 0.f);
  float4 e[17];
  uint32_t all = 0;
  e[16] = __ldcg((const float4*)g_z + ((size_t)256 * 1024 + p) * 2);
#pragma unroll
  for (int j = 0; j < 16; j++) { const uint4 u = lds128(z + j * 2048); e[j] = make_float4(__uint_as_float(u.x), __uint_as_float(u.y), __uint_as_float(u.z), __uint_as_float(u.w)); all |= u.x; }
  sched_fence(all);
  read();
  float ws, wc; sincospif((float)n * (1.0f / 1024.0f), &ws, &wc);
  cf v[32], q[17];
#pragma unroll
  for (int j = 0; j < 17; j++) {
    const cf d = cmul({e[j].z, e[j].w}, wc, ws);
    cf a = {e[j].x + d.x, e[j].y + d.y}, b = {e[j].x - d.x, e[j].y - d.y};
    if (j == 16 || (j == 0 && t == 0)) { a.y = 0.f; b.y = 0.f; }
    if (j < 16) v[j] = {a.x - b.y, a.y + b.x};
    q[j] = {a.x + b.y, b.x - a.y};
  }
#pragma unroll
  for (int j = 16; j < 32; j++) {
    v[j] = {__shfl_sync(~0u, q[31 - j].x, src), __shfl_sync(~0u, q[31 - j].y, src)};
    if (t == 0) v[j] = q[32 - j];
  }
  FT(1, v[0].x + v[16].x + v[31].x);
  warp_fft1024_a<true>(v, buf, tw, t, lane);
  FT(2, v[31].y);
  fft32<true>(v);
  FT(3, v[31].y + v[0].x);
  const float sc = 0.5f / (2048.0f * 1024.0f);
  __nv_bfloat16* o = g_b + (size_t)n * D_ + lane;
#pragma unroll
  for (int j = 0; j < 32; j++) { o[32 * j] = __float2bfloat16(v[j].x * sc); o[1024 * D_ + 32 * j] = __float2bfloat16(v[j].y * sc); }
  FT(4, 0.f);
}

constexpr int NP = NP_, NHV = REG_F == 216 ? 5 : 7, NV = 16 - NHV;
constexpr int XEND = NSEG;
constexpr uint32_t SM_WO = 0, SM_V = 65536, SM_LAND = SM_V + 8192, SM_MEM = SM_LAND + 24576, SM_SP = SM_MEM, SM_SPM = SM_MEM + 5120, SM_OM = SM_MEM + 6144,
                   SM_OX = SM_MEM + 8192, SM_RED = SM_OX + 2048, SM_XCH = SM_RED + 1024, SM_SUM = SM_XCH + 4096, SM_VM = SM_SUM + 128, SM_TAB = SM_VM + 2048, SM_TRACE = SM_TAB + 2048,
                   ST_WG = (32 - NP + NV) * 2048,
                   SM_XT = 2 * ST_WG, SM_POOL = SM_XT + 32768, SM_HV = SM_POOL + 2 * NP * 2048,
                   SM_BAR = SM_HV + 2 * NHV * 2048, SM_SEL = SM_BAR + 320, CHAIN_SMEM = SM_SEL + 544;
constexpr uint32_t SM_GW = 74 * 1024;
static_assert(NP % 4 == 0 && NV == 11 && SM_TRACE + 4096 <= SM_XT, "shared memory layout");
static_assert(CHAIN_SMEM <= 232448 && COL_SMEM <= CHAIN_SMEM && (1024 + 8 * ROW_BUF) * 8 <= SM_GW && SM_GW + 2048 > ST_WG, "shared memory budget");
enum { B_WFULL = 0, B_WREAD = 2, B_WOFULL, B_XFULL, B_XEMPTY, B_E1TRIG, B_E2TRIG, B_PVDONE, B_PUB, B_SC, B_MEM, B_SPFREE,
       B_LAND, B_LFREE, B_DONE, B_SEL, B_PROBE, B_FREE, B_P1, B_ROWS, B_VFULL, B_VST, B_TW, B_BT, B_Z, B_GFULL = B_Z + 4, B_GEMPTY = B_GFULL + 5, B_END = B_GEMPTY + 5 };
static_assert(B_END * 8 <= 320, "barriers");
constexpr uint32_t SM_BT = 65536, SM_TW = SM_XT - 8192, COL_Z = 75 * 1024;
static_assert(SM_XT + 3 * 32768 <= SM_BAR && SM_BT + 32768 <= SM_MEM && SM_TRACE <= SM_TW && SM_MEM + 4 * ROW_BUF * 4 <= SM_TAB &&
              8192 + 16 * ROW_BUF * 4 <= COL_Z && COL_Z + 131072 <= SM_BAR, "shared memory layout");
__device__ __forceinline__ uint32_t next_stage(uint32_t o) { return o == SM_XT + 65536 ? 0 : o == 32768 ? SM_XT : o + 32768; }

struct ChainCtx { char* mail; uint32_t sb, sel; int r, h, a, b, j, m, w, lane; };
#define BAR(i) (c.sb + SM_BAR + 8 * (i))

__device__ __forceinline__ uint32_t tile_off(int line, int lane) {
  return line * 128 + (((lane & 3) ^ line) << 5) + (lane >> 2) * 4;
}
__device__ __forceinline__ uint32_t read_off(int lane) {
  const int n = lane >> 2, jj = lane & 3, l = 2 * (jj >> 1) + (n & 1);
  return l * 128 + (((n >> 1) ^ l) << 5) + (jj & 1) * 16;
}
__device__ __forceinline__ uint32_t frag_off(int w, int lane) {
  const int mi = lane >> 3, r = lane & 7;
  return ((mi >> 1) * 8 + r) * 128 + (((2 * w + (mi & 1)) ^ r) << 4);
}
__device__ __forceinline__ uint32_t land_off(int w, int lane) { return w * 512 + ((lane ^ (((lane >> 4) | ((w & 1) << 1)) << 1)) << 4); }
__device__ __forceinline__ uint32_t tagged(uint32_t v, uint32_t tag) { return (v | 1u) ^ tag; }
__device__ __forceinline__ void mma_a(float (&d)[4], const uint32_t (&a)[4], uint32_t b0, uint32_t b1) { mma16816(d, a[0], a[1], a[2], a[3], b0, b1); }
__device__ __forceinline__ void mma_q(float (&d)[4], const uint4& a, uint32_t b0, uint32_t b1) { mma16816(d, a.x, a.y, a.z, a.w, b0, b1); }
__device__ __forceinline__ uint4 add4(uint4 a, uint4 b) {
  return make_uint4(add_bf16x2(a.x, b.x), add_bf16x2(a.y, b.y), add_bf16x2(a.z, b.z), add_bf16x2(a.w, b.w));
}
__device__ __forceinline__ void mbar_arrive_both(uint32_t bar, int peer) {
  __syncwarp();
  asm volatile("{ .reg .pred p; .reg .u32 a; mapa.shared::cluster.u32 a, %0, %1; elect.sync _|p, 0xffffffff;\n"
               "@p mbarrier.arrive.shared::cta.b64 _, [%0]; @p mbarrier.arrive.shared::cluster.b64 _, [a]; }" :: "r"(bar), "r"(peer) : "memory");
}

__device__ __forceinline__ void arrive_remote_if(uint32_t a, bool on) {
  asm volatile("{ .reg .pred p; setp.ne.u32 p, %1, 0; @p mbarrier.arrive.shared::cluster.b64 _, [%0]; }" :: "r"(a), "r"((uint32_t)on) : "memory");
}
__device__ __forceinline__ void store_count(void* p, uint4 v, uint32_t* cnt) {
  asm volatile("{ .reg .pred p, q; .reg .b128 a, b; .reg .b64 l, h; mov.b64 l, {%1, %2}; mov.b64 h, {%3, %4}; mov.b128 a, {l, h};\n"
               "atom.relaxed.gpu.global.exch.b128 b, [%0], a; mov.b128 {l, h}, b; setp.eq.u64 q, l, 0x7fc17fc17fc17fc1; @q pmevent 1;\n"
               "elect.sync _|p, 0xffffffff; @p red.relaxed.gpu.global.add.u32 [%5], 1; }"
               :: "l"(p), "r"(v.x), "r"(v.y), "r"(v.z), "r"(v.w), "l"(cnt) : "memory");
}

__device__ __forceinline__ int lane_id() {
  int l; asm volatile("{ .reg .u32 t; mov.u32 t, %%laneid; shfl.sync.idx.b32 %0, t, t, 31, 0xffffffff; }" : "=r"(l)); return l;
}
__device__ __forceinline__ uint32_t tid_now() { uint32_t t; asm volatile("mov.u32 %0, %%tid.x;" : "=r"(t)); return t; }
enum { NB_ATT = 1, NB_OM = 2, NB_VM = 3, NB_XCH = 4, NB_MEM = 8, NB_HELP = 12 };
__device__ __forceinline__ uint32_t dep(uint32_t a, uint32_t v, uint32_t z) { uint32_t r; asm("shf.l.wrap.b32 %0, %2, %1, %3;" : "=r"(r) : "r"(a), "r"(v), "r"(z)); return r; }
__device__ __forceinline__ uint32_t vary(uint32_t a, int s, uint32_t z) { return dep(a, 0, z + 32 * s); }
__device__ __forceinline__ char* mk_ptr(uint32_t lo, uint32_t hi) { uint64_t r; asm("mov.b64 %0, {%1, %2};" : "=l"(r) : "r"(lo), "r"(hi)); return (char*)r; }
__device__ __forceinline__ void lds_frag(uint32_t (&r)[4], uint32_t a) {
  asm volatile("ld.shared.v4.u32 {%0,%1,%2,%3}, [%4];" : "=r"(r[0]), "=r"(r[1]), "=r"(r[2]), "=r"(r[3]) : "r"(a) : "memory");
}
__device__ __forceinline__ uint32_t stale2(uint32_t a, uint32_t b, uint32_t t) { uint32_t r; asm("lop3.b32 %0, %1, %2, %3, 0xbd;" : "=r"(r) : "r"(a), "r"(b), "r"(t)); return r; }
__device__ __forceinline__ uint32_t stale1(uint32_t acc, uint32_t a, uint32_t t) { uint32_t r; asm("lop3.b32 %0, %1, %2, %3, 0xf9;" : "=r"(r) : "r"(acc), "r"(a), "r"(t)); return r; }
__device__ __forceinline__ bool all_clear(uint32_t x, uint32_t m) {
  uint32_t r;
  asm volatile("{ .reg .pred p; .reg .u32 t; and.b32 t, %1, %2; setp.eq.u32 p, t, 0; vote.sync.all.pred p, p, 0xffffffff; selp.u32 %0, 1, 0, p; }" : "=r"(r) : "r"(x), "r"(m));
  return r;
}
__device__ __forceinline__ bool arrive_if_all(bool ok, int id, int n) {
  uint32_t r;
  asm volatile("{ .reg .pred p, q; setp.ne.u32 p, %1, 0; vote.sync.all.pred q, p, 0xffffffff; @q bar.arrive %2, %3; selp.u32 %0, 1, 0, q; }"
               : "=r"(r) : "r"((uint32_t)ok), "r"(id), "r"(n) : "memory");
  return r;
}
__device__ __forceinline__ bool arrive_if_clear(uint32_t x, uint32_t m, int id, int n) {
  uint32_t r;
  asm volatile("{ .reg .pred p; .reg .u32 t; and.b32 t, %1, %2; setp.eq.u32 p, t, 0; vote.sync.all.pred p, p, 0xffffffff; @p bar.arrive %3, %4; selp.u32 %0, 1, 0, p; }"
               : "=r"(r) : "r"(x), "r"(m), "r"(id), "r"(n) : "memory");
  return r;
}
__device__ __forceinline__ void touch(const void* p, uint32_t z) {
  asm volatile("{ .reg .pred p; setp.eq.u32 p, %1, 0x7fff0000; @p prefetch.global.L2 [%0]; }" :: "l"(p), "r"(z) : "memory");
}

__device__ __forceinline__ uint64_t desc_x(uint32_t lo, int k) {
  uint64_t d; asm("mov.b64 %0, {%1, %2};" : "=l"(d) : "r"(lo + (k >> 2) * 64 + (k & 3) * 2), "r"(0x40000200)); return d;
}
template<int K0, int K1> __device__ __forceinline__ void issue_qk(float (&xa)[16], const uint32_t (&wt)[16][4], uint32_t lo) {
  WG_FENCE();
#pragma unroll
  for (int k = K0; k < K1; k++) {
    if (k >= EXP_NWG) continue;
    if (k == 0) wgmma_rs_n32<true>(xa, wt[0], desc_x(lo, 0));
    else wgmma_rs_n32<false>(xa, wt[k], desc_x(lo, k));
  }
  WG_COMMIT();
}
__host__ __device__ constexpr int v_order(int i) { return SSPOS == 0 ? i : SSPOS == 2 ? (i + NV) % 16 : NHV == 5 ? (i % 3 == 2 ? NV + i / 3 : i - i / 3) : (i == 15 ? NV - 1 : i % 2 ? NV + i / 2 : i / 2); }
__device__ __forceinline__ void issue_v(float (&xa)[16], const uint32_t (&wv)[16][4], uint32_t lo, uint32_t la) {
  WG_FENCE();
#pragma unroll
  for (int i = 0; i < EXP_NWG; i++) {
    const int k = v_order(i);
    const uint64_t b = desc_x(lo, k);
    if (k < NV) { if (i == 0) wgmma_rs_n32<true>(xa, wv[k], b); else wgmma_rs_n32<false>(xa, wv[k], b); }
    else        { if (i == 0) wgmma_ss_n32_ta<true>(xa, desc128(la + (k - NV) * 128), b); else wgmma_ss_n32_ta<false>(xa, desc128(la + (k - NV) * 128), b); }
  }
  WG_COMMIT();
}
template<bool ISV> __device__ __forceinline__ void park_own(uint32_t (&q)[4], float (&xa)[16], uint32_t dst, int slot, uint32_t z) {
  uint32_t p[8];
#pragma unroll
  for (int i = 0; i < 16; i++) asm volatile("" : "+f"(xa[i]) :: "memory");
#pragma unroll
  for (int i = 0; i < 2; i++) {
    const float* k = xa + 8 * i;
    if (ISV) { p[4 * i] = pack_bf16(k[0], k[1]); p[4 * i + 1] = pack_bf16(k[2], k[3]); p[4 * i + 2] = pack_bf16(k[4], k[5]); p[4 * i + 3] = pack_bf16(k[6], k[7]); }
    else     { p[4 * i] = pack_bf16(k[0], k[2]); p[4 * i + 1] = pack_bf16(k[1], k[3]); p[4 * i + 2] = pack_bf16(k[4], k[6]); p[4 * i + 3] = pack_bf16(k[5], k[7]); }
  }
  sts128(dep(dep(dst, p[4] ^ p[5] ^ p[6], z), p[7], z) + slot * 8192, make_uint4(p[0], p[1], p[2], p[3]));
#pragma unroll
  for (int i = 0; i < 4; i++) q[i] = p[4 + i];
}
__device__ __forceinline__ void park_peer(const uint32_t (&q)[4], uint32_t dst, int slot, const ChainCtx& c) {
  const uint32_t bar = BAR(B_LAND);
  if (EXP_PEER) st_async4(mapa(dst + slot * 8192, c.b ^ 1), q[0], q[1], q[2], q[3], mapa(bar, c.b ^ 1));
  else touch((void*)(uintptr_t)(q[0] ^ q[1] ^ q[2] ^ q[3]), c.sb);
  mbar_arrive_warp(bar);
}
__device__ __forceinline__ uint32_t put_tag(uint32_t v, uint32_t bit, uint32_t t) {
  uint32_t r; asm("lop3.b32 %0, %1, %2, %3, 0x74;" : "=r"(r) : "r"(v), "r"(bit), "r"(t)); return r;
}
__device__ __forceinline__ void mem_proj(const uint32_t (&wa)[16][4], const uint32_t (&wb)[16][4], uint32_t (&wv)[16][4], uint32_t (&af)[16][4],
                                         uint32_t& wo, const char*& pa, uint32_t tab, uint32_t t16, uint32_t pk, const ChainCtx& c, int s) {
  const uint32_t mp = t16 & ~0x600u, id = NB_MEM + (t16 >> 11);
  uint32_t r[8][4];
  float la[4][4] = {}, lg[NLAG][4] = {}, lv[4][4] = {};
  auto lead = [&](int k) { mma_a(la[k & 3], wa[k], r[k >> 1][2 * (k & 1)], r[k >> 1][2 * (k & 1) + 1]); };
  auto lag = [&](int k) { mma_a(lg[k % NLAG], wb[k], r[k >> 1][2 * (k & 1)], r[k >> 1][2 * (k & 1) + 1]); };
  auto sum = [](const float (&d)[4][4], int i) { return (d[0][i] + d[1][i]) + (d[2][i] + d[3][i]); };
  bar_sync(id, 160);
  TR(s, 0);
#pragma unroll
  for (int i = 0; i < 4; i++) ldsm4t(r[i], mp + (c.sb + SM_MEM + i * 512));
  const uint4 tq = lds128(tab);
  bar_sync(id + 2, 160);
#pragma unroll
  for (int k = 0; k < 8; k++) lead(k);
  const uint32_t ta = tq.x | ((pk >> 16) & 511), tb = tq.z ^ ((pk >> 16) & 511);
  char* dst = mk_ptr(ta, tq.y);
  char* dst2 = mk_ptr(tb, tq.w);
  const uint32_t mp1 = dep(mp, __float_as_uint(la[C1_AT][0]) ^ ta ^ tb, c.sb);
#pragma unroll
  for (int i = 4; i < 8; i++) ldsm4t(r[i], mp1 + (c.sb + SM_MEM + 2048 + i * 512));
  const uint32_t hv = pk & 0xFFFF;
#pragma unroll
  for (int k = NV; k < NV + HV_E; k++) ldsm4t(wv[k], dep(hv, r[HV_R][0], c.sb) + (c.sb + SM_HV + (k - NV) * 2048));
#pragma unroll
  for (int k = 0; k < 8; k++) lag(k);
#pragma unroll
  for (int k = 8; k < 16; k++) lead(k);
  sts128((HV_E ? dep(t16, wv[NV][0] ^ wv[NV + HV_E / 2][1] ^ wv[NV + HV_E - (HV_E > 0)][2], c.sb) : t16) + (c.sb + SM_XCH), make_uint4(__float_as_uint(sum(la, 0)), __float_as_uint(sum(la, 1)), __float_as_uint(sum(la, 2)), __float_as_uint(sum(la, 3))));
  bar_sync(NB_XCH | ((t16 >> 9) & 3), 64);
  const uint4 o = lds128((t16 ^ 2048) + (c.sb + SM_XCH));
#pragma unroll
  for (int k = 8; k < 16; k++) lag(k);
  float t[4];
#pragma unroll
  for (int i = 0; i < 4; i++) {
    const float oi = __uint_as_float(i == 0 ? o.x : i == 1 ? o.y : i == 2 ? o.z : o.w);
    t[i] = NLAG == 4 ? (((lg[0][i] + lg[1][i]) + lg[2 % NLAG][i]) + lg[3 % NLAG][i]) + oi : NLAG == 3 ? (lg[1][i] + lg[2 % NLAG][i]) + (lg[0][i] + oi) : (lg[0][i] + oi) + lg[1][i];
  }
  const uint32_t y0 = put_tag(pack_bf16(t[0], t[2]), pk >> 31, s >> 1), y1 = put_tag(pack_bf16(t[1], t[3]), pk >> 31, s >> 1);
  st_pub(dst, y0); st_pub(dst2, y1);
  mbar_arrive_warp(BAR(B_E1TRIG));
  TR(s, 1);
  sched_fence(c.sb);
  const uint4 tv = lds128(tab + 16);
#pragma unroll
  for (int k = NV + HV_E; k < 16; k++) ldsm4t(wv[k], (k < NV + HV_E + HV_D ? hv : dep(hv, k == NV + HV_E + HV_D ? wv[k - HV_D][0] ^ tv.x : wv[k - HV_D][0], c.sb)) + (c.sb + SM_HV + (k - NV) * 2048));
  wo = (hv & 2047) | ((t16 & 2048) << 3);
  const uint32_t l8 = (t16 >> 1) & 255;
  char* dv = mk_ptr(tv.x | l8, tv.y);
  pa = mk_ptr(tv.z | l8, tv.w);
#pragma unroll
  for (int f = 0; f < WO_0; f++) ldsm4t(af[f], dep(wo, f < WO_D ? wv[16 - WO_D + f][0] : af[f < WO_D ? 0 : f - WO_D][0], c.sb) + (c.sb + SM_WO + (f & 1) * 32768 + (f >> 1) * 2048));
#pragma unroll
  for (int k = 0; k < 16; k++) mma_a(lv[k & 3], wv[k], r[k >> 1][2 * (k & 1)], r[k >> 1][2 * (k & 1) + 1]);
  const uint32_t z0 = put_tag(pack_bf16(sum(lv, 0), sum(lv, 1)), (~t16 >> 4) & 1, s >> 1), z1 = pack_bf16(sum(lv, 2), sum(lv, 3));
  st_pub2(dv, z0, z1);
  if (FIN_AT >= 3) mbar_arrive_warp(BAR(B_VST));
  TR(s, 2);
}
__device__ __forceinline__ uint32_t max_bf16x2(uint32_t a, uint32_t b) { uint32_t r; asm("max.bf16x2 %0, %1, %2;" : "=r"(r) : "r"(a), "r"(b)); return r; }
constexpr float SCL = 0.08838834764831845f * 1.4426950408889634f;
__device__ __forceinline__ uint32_t max5(const uint32_t (&sc)[5]) { return max_bf16x2(max_bf16x2(max_bf16x2(max_bf16x2(sc[0], sc[1]), sc[2]), sc[3]), sc[4]); }
__device__ __forceinline__ float row_off(uint32_t m, uint32_t& m1) {
  m1 = __shfl_xor_sync(~0u, m, 1);
  const uint32_t m2 = __shfl_xor_sync(~0u, m, 2), m3 = __shfl_xor_sync(~0u, m, 3);
  const uint32_t mm = max_bf16x2(max_bf16x2(max_bf16x2(m, m1), m2), m3);
  return -SCL * fmaxf(__uint_as_float(mm << 16), __uint_as_float(mm & 0xFFFF0000u));
}
__device__ __forceinline__ void unpack(float (&f)[10], const uint32_t (&sc)[5]) {
#pragma unroll
  for (int i = 0; i < 5; i++) {
    asm volatile("shl.b32 %0, %1, 16;" : "=f"(f[2 * i]) : "r"(sc[i]));
    asm volatile("and.b32 %0, %1, 0xffff0000;" : "=f"(f[2 * i + 1]) : "r"(sc[i]));
  }
}
__device__ __forceinline__ uint32_t exp_pair(const float (&f)[10], int i, float off) {
  return pack_bf16(ex2(fmaf(f[2 * i], SCL, off)), ex2(fmaf(f[2 * i + 1], SCL, off)));
}
template<bool SPLIT> __device__ __forceinline__ void scores_x(float (&a)[2][4], const uint4 (&kf)[4], const uint4& q, uint32_t z) {
#pragma unroll
  for (int t = 0; t < 2; t++) { a[t][0] = a[t][1] = a[t][2] = a[t][3] = 0.f; }
  mma_q(a[0], kf[0], q.x, q.y); mma_q(a[1], kf[2], q.x, q.y);
  if (SPLIT) sched_fence(z);
  mma_q(a[0], kf[1], q.z, q.w); mma_q(a[1], kf[3], q.z, q.w);
}
__device__ __forceinline__ uint32_t scores_m(const uint4& q, const uint4& k) {
  float a[4] = {}, b[4] = {};
  mma_q(a, q, k.x, k.z); mma_q(b, q, k.y, k.w);
  return pack_bf16(a[0] + b[2], a[1] + b[3]);
}
__device__ __forceinline__ void store_scores(const float (&a)[2][4], uint32_t dst) {
  sts64(dst, pack_bf16(a[0][0], a[0][2]), pack_bf16(a[1][0], a[1][2]));
  sts64(dst + 320, pack_bf16(a[0][1], a[0][3]), pack_bf16(a[1][1], a[1][3]));
}
__device__ __forceinline__ uint32_t sum4(uint32_t a, uint32_t b, uint32_t d, uint32_t e) { return add_bf16x2(add_bf16x2(a, b), add_bf16x2(d, e)); }
__device__ __forceinline__ void load_scores(uint32_t (&sc)[5], uint32_t ax, uint32_t am) {
  uint4 p[4];
#pragma unroll
  for (int i = 0; i < 4; i++) p[i] = lds128(ax + i * 1280);
  const uint2 m0 = lds64(am), m1 = lds64(am + 256);
  const uint4 t = add4(add4(add4(p[0], p[1]), p[2]), p[3]);
  sc[1] = t.x; sc[2] = t.y; sc[3] = t.z; sc[4] = t.w;
  sc[0] = sum4(m0.x, m0.y, m1.x, m1.y);
}
constexpr uint32_t ONES = 0x3F803F80u;
__device__ __forceinline__ float pv(float (&o)[2][4], const uint32_t (&p)[5], const uint4 (&vf)[4], const uint4& vm) {
  float a[4] = {}, b[4] = {};
#pragma unroll
  for (int t = 0; t < 2; t++) { o[t][0] = o[t][1] = o[t][2] = o[t][3] = 0.f; }
  mma_q(o[0], vf[0], p[1], p[2]); mma_q(o[1], vf[2], p[1], p[2]);
  mma_q(o[0], vf[1], p[3], p[4]); mma_q(o[1], vf[3], p[3], p[4]);
  mma16816(a, p[1], p[2], p[3], p[4], ONES, ONES);
  mma1688(o[0], vm.x, vm.y, p[0]); mma1688(o[1], vm.z, vm.w, p[0]);
  mma1688(b, p[0], ONES, ONES);
  return (a[0] + a[2]) + b[0];
}
constexpr uint32_t POLL_LIMIT = 1u << 21;
__device__ __forceinline__ void probe_pair(const ChainCtx& c, uint32_t off, int i, uint32_t val) {
  if (c.lane == 0) {
    char* pa = c.mail + off;
    int far1 = 0;
#pragma unroll 1
    for (int rep = 0; rep <= NPROBE; rep++) {
      const int lag = race_init(pa + (rep & 1) * 4096, pa + (~rep & 1) * 4096, val);
      if (rep) far1 += (rep & 1 ? -1 : 1) * min(lag, 200);
    }
    sts32(c.sb + SM_SEL + 512 + i * 4, AWARE && far1 < 0 ? 1u << i : 0u);
  }
}

__device__ __forceinline__ uint32_t e1_off(const ChainCtx& c) {
  if (E1OFF != 1) return E1OFF;
  const uint4 v = lds128(c.sb + SM_SEL + c.h * 16);
  return __popc(((v.x ^ v.z) & 15) | ((v.y ^ v.w) & 15) << 4) < 4 ? 8192 : 0;
}
__device__ __forceinline__ uint32_t tile_key() {
  uint32_t sm; asm volatile("mov.u32 %0, %%smid;" : "=r"(sm));
  return (sm < 64 ? sm / 2 % 8 : sm < 120 ? 1 + (sm / 2 - 32) % 7 : 0) << 24 | sm << 16;
}
__device__ __forceinline__ int tile_of(const ChainCtx& c) { return SIDE ? __shfl_sync(~0u, lds32(c.sb + SM_SEL + 528), 0) : c.r; }

__global__ void __cluster_dims__(2, 1, 1) __launch_bounds__(512, 1)
chain_kernel(const __grid_constant__ CUtensorMap tq, const __grid_constant__ CUtensorMap tk, const __grid_constant__ CUtensorMap tv,
             const __grid_constant__ CUtensorMap tv16, const __grid_constant__ CUtensorMap to, const __grid_constant__ CUtensorMap tx,
             const __grid_constant__ CUtensorMap twr, const __grid_constant__ CUtensorMap twi,
             const __grid_constant__ CUtensorMap ta, const __grid_constant__ CUtensorMap tw,
             const __grid_constant__ CUtensorMap tb, const __grid_constant__ CUtensorMap tout, const __grid_constant__ CUtensorMap tz,
             const __nv_bfloat16* __restrict__ mem0, char* __restrict__ mail, const __nv_bfloat16* __restrict__ x,
             const __nv_bfloat16* __restrict__ gw) {
  extern __shared__ __align__(1024) unsigned char smraw[];
  if (threadIdx.x == 0) TL(0);
  ChainCtx c;
  c.sb = __shfl_sync(~0u, smem_u32(smraw), 0);
  c.mail = mail; c.sel = 0; c.r = blockIdx.x;
  if (ROLE) {
    const uint32_t u = blockIdx.x >> 1, k = u - 4, l = u - 36;
    c.r = __shfl_sync(~0u, 2 * (k < 32 ? 4 + (k & 16) + (k & 7) * 2 + (k >> 3 & 1) : l < 28 ? 36 + l / 14 * 14 + l % 7 * 2 + l / 7 % 2 : u) + (blockIdx.x & 1) + (threadIdx.x >> 9), 0);
  }
  c.h = c.r >> 2; c.a = (c.r >> 1) & 1; c.b = c.r & 1; c.j = c.r & 3;
  c.m = __shfl_sync(~0u, (int)(threadIdx.x >> 7), 0); c.w = __shfl_sync(~0u, (int)((threadIdx.x >> 5) & 3), 0);
  if (threadIdx.x < B_END) {
    const int i = threadIdx.x;
    const uint32_t n = i == B_LAND ? 25 : i >= B_GEMPTY || i == B_DONE ? 4 :
                       (i == B_WREAD || i == B_XEMPTY || i == B_E1TRIG || i == B_E2TRIG || i == B_LFREE || i == B_FREE || i == B_PROBE || i == B_VST || i == B_P1) ? 8 :
                       (i == B_PVDONE || i == B_PUB || i == B_SC || i == B_MEM || i == B_SPFREE) ? 4 : 1;
    mbar_init(BAR(i), n);
    asm volatile("fence.mbarrier_init.release.cluster;" ::: "memory");
  }
  __syncthreads();
  asm volatile("barrier.cluster.arrive.relaxed.aligned;" ::: "memory");

  if (c.r >= 128) {
    fft_cols((float2*)smraw, c.r - 128, &twr, &twi);
    if ((threadIdx.x & 127) == 0) TL(7);
    __syncwarp();
  } else if (c.m == 3) {
    asm volatile("setmaxnreg.dec.sync.aligned.u32 %0;" :: "n"(REG_H));
    c.lane = lane_id();
    if (c.sb & 1023) asm volatile("trap;");
    const int col = c.h * 128 + c.a * 64;
    {
      char* own = c.mail + (uint32_t)(M_E3 + (c.w * 4 + (c.r >> 5)) * 8192 + (c.r & 31) * 128 + c.lane * 4);
      race_init(own, own + 4096, SENT);
      mbar_arrive_warp(BAR(B_PROBE));
    }
    uint32_t tl = 0;
    if (c.w == 0) {
      if (HOLD == 2) mbar_wait(BAR(B_PROBE), 0);
      if (HOLD == 3) mbar_wait(BAR(B_SEL), 0);
      mbar_expect_e(BAR(B_ROWS), 32768 + 2048);
      for (int i = 0; i < 16; i++) bulk_load_e(c.sb + (1024 + (i >> 1) * ROW_BUF) * 8 + (i & 1) * 2048, x + (size_t)(z_row(c.r * 8 + (i >> 1)) + (i & 1) * 1024) * D_, 2048, BAR(B_ROWS));
      bulk_load_e(c.sb + SM_GW, gw, 2048, BAR(B_ROWS));
      if (HOLD == 1) mbar_wait(BAR(B_PROBE), 0);
      tl = clock_lo();
      mbar_expect_e(BAR(B_WFULL), 48 * 2048);
      mbar_expect_e(BAR(B_WFULL + 1), 48 * 2048);
    }
    auto dst_x = [&](int e, int w) {
      const uint32_t g2 = 2 * c.a + (w >> 1), u = w & 1;
      return M_KVQ + c.h * 24576 + (e == 0 ? 8192 + (2 * u + c.b) * 2048 + g2 * 512 : e == 1 ? g2 * 2048 + u * 1024 + c.b * 128 : 16384 + c.b * 4096 + g2 * 512 + u * 256);
    };
    if (c.w == 0) {
      tl += PACE0;
      constexpr int P = NP / 4, LATE = P + 13 - (SM_GW + 2048 - ST_WG + 8191) / 8192;
      for (int i = 0; i < 24; i++) {
        const int m = i > P && i < P + 13, k = i <= P ? i : m ? i - P - 1 : i - 12;
        const int row = c.b * 512 + m * 256;
        const uint32_t st = c.sb + m * ST_WG, bar = BAR(B_WFULL + m);
        if (PACE) delay_until(tl += PACE);
        if (i == LATE) { mbar_wait(BAR(B_FREE), 0); if (c.lane == 0) TL2(2); __syncwarp(); }
        if (k < P) TMA_W(c.sb + SM_POOL + m * NP * 2048 + k * 8192, m ? &tq : &tk, col, row + k * 64, bar);
        else if (k == P) TMA_W(c.sb + SM_HV + (m * NHV + 1) * 2048, &tv, col, row + 192, bar);
        else if (k == P + 1) for (int j = 8; j < 12; j++) TMA_W(j < NV ? st + (32 - NP + j) * 2048 : c.sb + SM_HV + m * NHV * 2048, &tv16, col, row + j * 16, bar);
        else if (k < P + 4) TMA_W(st + (32 - NP) * 2048 + (k - P - 2) * 8192, &tv, col, row + (k - P - 2) * 64, bar);
        else if (k < 8) TMA_W(st + (k - P) * 8192, m ? &tq : &tk, col, row + (k - 4) * 64, bar);
        else TMA_W(st + (11 - k) * 8192, m ? &tk : &tq, col, row + (11 - k) * 64, bar);
      }
    } else if (c.w == 3) {
      mbar_wait(BAR(B_FREE), 0);
      mbar_expect_e(BAR(B_XFULL), 32768);
      for (int i = 0; i < 2; i++) tma4d_e(c.sb + SM_XT + i * 16384, &tx, c.b * 8, 2 * (c.b ^ i), BAR(B_XFULL));
    } else if (c.w == 1) {
      mbar_wait(BAR(B_P1), 0);
      if (P1_AT) { mbar_wait(BAR(B_WFULL), 0); mbar_wait(BAR(B_WFULL + 1), 0); }
      st_pub_if(g_ctl + C_COLS + c.lane * 32, 0, c.r == 0 && c.lane < (C_END - C_COLS) / 32);
      count_e(g_ctl + C_P1);
    }
    asm volatile("barrier.cluster.wait;" ::: "memory");
    mbar_wait(BAR(B_WREAD), 0);
    mbar_arrive_both(BAR(B_LFREE), c.b ^ 1);
    if (c.w == 0) {
      mbar_expect_e(BAR(B_WOFULL), 65536);
      for (int i = 0; i < 4; i++) TMA_O(c.sb + SM_WO + i * 16384, &to, c.j * 256 + i * 64, c.h * 128, BAR(B_WOFULL));
    }
    {
      const int ln = tid_now() & 31, e = (ln >> 2) & 3, w = (tid_now() >> 5) & 3;
      const uintptr_t ad = (uintptr_t)(c.mail + (uint32_t)(dst_x(e, w) + (ln & 3) * 32 * 24576));
      sts64(c.sb + SM_TAB + 1536 + (ln & 3) * 128 + w * 32 + e * 8, (uint32_t)ad, (uint32_t)(ad >> 32));
      __syncwarp();
    }
    {
      mbar_wait(BAR(B_SEL), 0);
      const int ln = tid_now() & 31, sl = ln & 3, e = (ln >> 2) & 3;
      const uint32_t t = c.sb + SM_SEL, own = lds32(t + c.r * 4);
      uint32_t votes = 0;
      for (int i = 0; i < 7; i++) { const uint32_t v = lds32(t + (sl * 4 + 2 * c.b + (c.w >> 1) + 16 * i) * 4); votes += ((v >> 2) ^ (v >> 3)) & 1; }
      const uint32_t off = e == 0 ? M_PAIR + ((~sl & 1) * 128 + c.r) * 16384 + ((own >> (~sl & 1)) & 1) * 4096 + c.w * 1024
                         : e == 2 ? M_E3 + (sl * 4 + c.b * 2 + (c.w >> 1)) * 8192 + (((votes >= 4 ? 1u : 0u) ^ (own >> 3)) & 1) * 4096 + (c.w & 1) * 2048
                         : M_E3 + ((sl ^ (e & 2)) * 4 + (c.r >> 5)) * 8192 + (c.w & 1) * 4096 + (c.r & 31) * 128;
      const uintptr_t ad = (uintptr_t)(c.mail + off);
      sts64(c.sb + SM_TAB + 1024 + sl * 128 + c.w * 32 + e * 8, (uint32_t)ad, (uint32_t)(ad >> 32));
      {
        const int i = tid_now() & 127, e = i & 7, w = (i >> 3) & 3, m = (i >> 5) & 1, sl = i >> 6;
        const int cta = e < 2 ? c.r & ~1 : e == 2 ? c.r | 1 : e == 3 ? c.h * 4 + 2 * m + 1 : c.j * 32 + m * 8 + 2 * w + (e & 2) * 8 + (e & 1);
        const uint32_t off = e < 2 ? c.b * 2048 + m * 1024 + (w >> 1) * 512 + e * 160 : e == 2 ? c.b * 2048 + m * 1024 + w * 256 : e == 3 ? w * 256 : c.h * 128;
        const uintptr_t ad = (uintptr_t)(c.mail + (uint32_t)(M_PAIR + (sl * 128 + cta) * 16384 + (e < 4 ? e1_off(c) : 0) + (((lds32(t + cta * 4) >> sl) ^ (e < 4)) & 1) * 4096 + off));
        sts64(c.sb + SM_TAB + i * 8, (uint32_t)ad, (uint32_t)(ad >> 32));
      }
      if (tid_now() == 384) TL2(25);
      __syncwarp();
      bar_sync(NB_HELP, 128);
    }
    for (int s = -1; s < NSEG; s++) {
      if (s >= 0) {
        const uint32_t tab = c.sb + SM_TAB + 1024 + (s & 3) * 128 + c.w * 32;
        uint32_t t0;
        if (s > 0) {
          const uint32_t ln = tid_now() & 31;
          const uint4 ta = lds128(tab);
          const char* src = mk_ptr(ta.x | ln * 4, ta.y);
          char* dst = mk_ptr(ta.z | ln * 4, ta.w);
          const uint32_t tg = (s - 1) >> 1, chk = (ln & 3) ? 0u : 1u, red = ln * (RED_L == 3 ? 4 : 8);
          touch(src, dep(c.sb, chk, c.sb)); touch(dst, dep(c.sb, red, c.sb));
          mbar_wait(BAR(B_E2TRIG), (s - 1) & 1);
          TR(s, 0);
          if (ANCH2) delay_until(lds32(c.sb + SM_SUM + 64) + DLY_E2); else delay_cycles(DLY_E2);
          uint32_t n = 0;
          while (true) {
            uint32_t v[8];
#pragma unroll
            for (int i = 0; i < 8; i++) v[i] = ld_poll1(src + i * 128);
            if (E2_F) sched_fence(c.sb);
            const uint32_t bad = RED_T ? (stale2(v[0], v[1], tg) | stale2(v[2], v[3], tg) | stale2(v[4], v[5], tg)) | stale2(v[6], v[7], tg)
                                       : stale1(stale1(stale2(v[0], v[1], tg), v[2], tg), v[3], tg) | stale1(stale1(stale2(v[4], v[5], tg), v[6], tg), v[7], tg);
            const bool ok = all_clear(bad, chk);
#pragma unroll
            for (int l = 0; l < RED_L; l++)
#pragma unroll
              for (int i = 0; i < (4 >> l); i++) v[i] = add_bf16x2(v[2 * i], v[2 * i + 1]);
            if (RED_L == 3) sts32(red + (c.sb + SM_RED + c.w * 128), v[0]);
            else {
              float lo[8], hi[8];
#pragma unroll
              for (int i = 0; i < (8 >> RED_L); i++) { lo[i] = __uint_as_float(v[i] << 16); hi[i] = __uint_as_float(v[i] & 0xFFFF0000u); }
#pragma unroll
              for (int l = RED_L; l < 3; l++)
#pragma unroll
                for (int i = 0; i < (4 >> l); i++) { lo[i] = lo[2 * i] + lo[2 * i + 1]; hi[i] = hi[2 * i] + hi[2 * i + 1]; }
              sts64(red + (c.sb + SM_RED + c.w * 256), __float_as_uint(lo[0]), __float_as_uint(hi[0]));
            }
            if (ok) break;
            n++; CNT(0);
          }
          bar_sync(NB_HELP, 128);
          const uint32_t rd = red + (c.sb + SM_RED);
          if (!RED_P || c.w < 2) {
            if (RED_L == 3) st_pub_if(dst, sum4(lds32(rd), lds32(rd + 128), lds32(rd + 256), lds32(rd + 384)), c.w < 2);
            else {
              const uint2 p0 = lds64(rd), p1 = lds64(rd + 256), p2 = lds64(rd + 512), p3 = lds64(rd + 768);
              st_pub_if(dst, pack_bf16((__uint_as_float(p0.x) + __uint_as_float(p1.x)) + (__uint_as_float(p2.x) + __uint_as_float(p3.x)),
                                       (__uint_as_float(p0.y) + __uint_as_float(p1.y)) + (__uint_as_float(p2.y) + __uint_as_float(p3.y))), c.w < 2);
            }
          }
          t0 = clock_lo();
          mbar_arrive_warp(BAR(B_PUB));
          TRV(s, 15, n);
          mbar_wait(BAR(B_SPFREE), (s - 1) & 1);
        } else {
          if (tid_now() == 384) TL2(24);
          __syncwarp();
          mbar_wait(BAR(B_WOFULL), 0);
          if (tid_now() == 384) TL2(19);
          __syncwarp();
          t0 = clock_lo() - DLY_E3;
        }
        TRV(s, 1, t0);
        {
          const uint32_t l16 = (tid_now() & 31) * 16, dst = l16 + (c.sb + SM_MEM + (c.w & 1) * 4096 + (c.w >> 1) * 2048);
          const uint4 tb = lds128(tab + 16);
          st_pub_if(mk_ptr(tb.z | l16 >> 2, tb.w), SENT, c.w >= 2);
          const char* src = mk_ptr(tb.x | l16, tb.y);
          touch(src, dep(c.sb, dst, c.sb));
          delay_until(t0 + (DLY_E3 + (c.w & 1) * DLY_E3B));
          uint32_t n = 0;
          while (true) {
            uint4 v[4];
#pragma unroll
            for (int i = 0; i < 4; i++) v[i] = ld_poll(src + i * 512);
#pragma unroll
            for (int i = 0; i < 4; i++) sts128(dst + i * 512, v[i]);
            if (arrive_if_all(max(max(v[0].x, v[1].x), max(v[2].x, v[3].x)) != SENT, NB_MEM + (c.w & 1) * 2 + (c.w >> 1), 160)) break;
            n++; CNT(1);
          }
          mbar_arrive_warp(BAR(B_MEM));
          TR(s, 2); TRV(s, 14, n);
        }
        if (s == 1) CLK(1); if (s == 8) CLK(2); if (s == 56) CLK(3);
        if (c.w == 2 && s == 15) TRSYNC(8);
        if (c.w == 2 && s == 21) TRSYNC(10);
      }
      const int g = s + 1;
      auto load_v = [&]() {
        if (V_TMA && c.w == V_W) {
          mbar_expect_e(BAR(B_VFULL), 8192);
          bulk_load_e(c.sb + SM_V, c.mail + (uint32_t)(M_KVQ + ((min(g, XEND - 1) & (NSLOT - 1)) * 32 + c.h) * 24576 + 8192), 8192, BAR(B_VFULL));
        }
      };
      if (XEND < NSEG && g >= XEND && g < NSEG) { mbar_wait(BAR(B_SC), s & 1); load_v(); }
      if (g < XEND) {
        const uint32_t tx_ = c.sb + SM_TAB + 1536 + (g & 3) * 128 + c.w * 32, tag = (g >> 2) & 1;
        if (c.w == 0) mbar_expect_e(BAR(B_LAND), EXP_PEER * 12288);
        auto load_x = [&]() {
          if (c.w == 3 && g + 1 < XEND) {
            mbar_wait(BAR(B_XEMPTY), g & 1);
            mbar_expect_e(BAR(B_XFULL), 16384 * EXP_NXT);
            for (int i = 0; i < EXP_NXT; i++) tma4d_e(c.sb + SM_XT + i * 16384, &tx, c.b * 8, (g + 1) * 4 + 2 * (c.b ^ i), BAR(B_XFULL));
          }
        };
        if (X_AT == 0 || g == 0) load_x();
        mbar_wait(BAR(B_LAND), g & 1);
        if (DLY_F && g > 0) delay_cycles(DLY_F);
        auto total = [&](int w, int lane, uint32_t o0, uint32_t o1) {
          const uint32_t a = c.sb + SM_LAND + land_off(w, lane);
          if (EXP_FL == 1) return make_uint4(a, a, a, a);
          const uint4 t = add4(lds128(a + o0), lds128(a + o1 + 2048));
          const uint32_t a2 = dep(dep(a, t.x ^ t.y ^ t.z, c.sb), t.w, c.sb);
          return add4(t, add4(lds128(a2 + o0 + 4096), lds128(a2 + o1 + 6144)));
        };
        auto get = [&](int e) {
          const int ln = tid_now() & 31;
          return e == 0 ? total(c.w, ln, 16384, 16384)
               : e == 1 ? total((c.w & 2) + ((ln >> 1) & 1), (ln & 1) * 16 + (c.w & 1) * 8 + (ln >> 2), 8192, 0)
                        : total((c.w & 2) + ((ln >> 1) & 1), (ln & 1) * 16 + (ln >> 3) * 4 + (c.w & 1) * 2 + ((ln >> 2) & 1), 0, 8192);
        };
        auto put = [&](int e, uint4 v) {
          const int ln = tid_now() & 31;
          const uint2 d = lds64(tx_ + e * 8);
          if (e < 2) {
            v.x = tagged(v.x, tag);
            st_pub4(mk_ptr(d.x | (e ? (ln & 24) * 32 + (ln & 7) * 16 : ln * 16), d.y), v);
          } else {
            char* dst = mk_ptr(d.x | ((ln & 7) * 16 + (ln >> 3) * 4), d.y);
            const uint32_t bit = ln < 8;
            st_pub(dst, put_tag(v.x, bit, tag)); st_pub(dst + 128, put_tag(v.y, bit, tag));
            st_pub(dst + 2048, put_tag(v.z, bit, tag)); st_pub(dst + 2176, put_tag(v.w, bit, tag));
          }
        };
        auto after_sc = [&]() { if (g > 0) { mbar_wait(BAR(B_SC), s & 1); if (DLY_FK) delay_cycles(DLY_FK); if (X_AT == 1) load_x(); } };
        if (FIN_AT == 5) {
          put(0, get(0));
          if (DLY_F2 && g > 0) delay_cycles(DLY_F2); else sched_fence(c.sb);
          const uint4 k = get(1);
          sched_fence(c.sb);
          const uint4 q = get(2);
          if (g > 0) { mbar_wait(BAR(B_VST), s & 1); if (DLY_FS) delay_cycles(DLY_FS); }
          put(1, k); put(2, q);
          mbar_arrive_both(BAR(B_LFREE), c.b ^ 1);
          after_sc();
          load_v();
          continue;
        }
        if (FIN_AT < 3) {
          if (EXP_FIN & 1) put(0, get(0));
          TR(s, 3);
          if (FIN_AT == 1) after_sc();
          if (V_TMA == 1) load_v();
          if (EXP_FIN & 2) put(1, get(1));
        } else {
          const uint4 v = get(0);
          sched_fence(c.sb);
          const uint4 k = get(1);
          if (g > 0) { mbar_wait(BAR(B_VST), s & 1); if (DLY_FS) delay_cycles(DLY_FS); }
          put(0, v); put(1, k);
        }
        TR(s, 4);
        if (FIN_AT == 4) {
          const uint4 q = get(2);
          after_sc();
          load_v();
          put(2, q);
        } else {
          if (FIN_AT >= 2) after_sc();
          if (V_TMA == 2) load_v();
          if (EXP_FIN & 4) put(2, get(2));
        }
        mbar_arrive_both(BAR(B_LFREE), c.b ^ 1);
        if (V_TMA == 3) load_v();
        TR(s, 5);
        if (!FIN_AT && X_AT && g > 0) { mbar_wait(BAR(B_SC), s & 1); if (DLY_FK) delay_cycles(DLY_FK); load_x(); }
      }
    }
    const int tile = tile_of(c), m0 = (tile >> 3) * 128 + c.b * 64, n0 = (tile & 7) * 128;
    auto load_b = [&](int kb, uint32_t o, uint32_t bar) {
      mbar_expect_e(bar, 32768);
      tma2d_e(c.sb + o + 16384, &tw, n0, kb * 64, bar);
      tma2d_e(c.sb + o + 24576, &tw, n0 + 64, kb * 64, bar);
    };
    auto load_a = [&](int kb, uint32_t o, uint32_t bar) { tma2d_mc_e(c.sb + o + c.b * 8192, &ta, kb * 64, m0, bar); };
    if (c.w == 1) {
      mbar_wait(BAR(B_PVDONE), 0);
      count_e(g_ctl + C_EARLY);
      st_pub(g_ctl + C_SEL + c.r, 0);
      await_count(g_ctl + C_COLS, 4);
      mbar_expect_e(BAR(B_TW), 8192);
      bulk_load_e(c.sb + SM_TW, g_tw, 8192, BAR(B_TW));
    } else if (c.w == 2) {
      const uint32_t ln = tid_now() & 31, rel = mapa(BAR(B_GEMPTY) + (ln >> 2) * 8, ln & 1);
      mbar_wait(BAR(B_VST), 1); mbar_wait(BAR(PRE_AT), 1);
      arrive_remote_if(rel, ln < 12);
      mbar_wait(BAR(B_E2TRIG), 1);
      if (GATE) mbar_wait(BAR(B_DONE), 0);
      arrive_remote_if(rel, ln >= 12 && ln < 20);
    } else {
      auto ahead = [&](int k) {
        if (c.w) { if (PF_A && (k & 3) == (tile >> 1 & 3)) prefetch2d_e(&ta, k * 64, m0); }
        else if (PF_B && (k & 7) == (tile >> 4)) prefetch2d_e(&tw, n0 + (tile & 8) * 8, k * 64);
      };
      for (int k = 0; k < PF_D; k++) ahead(k);
      if (c.w == 3) { await_count(g_ctl + C_EARLY, 128); if (tile >= 120) await_count(g_ctl + C_LAST, 512); }
      if (tid_now() == 480) TL(10);
      __syncwarp();
      uint32_t o = SM_XT, st = 0, ph = 0;
#pragma unroll 1
      for (int kb = 0; kb < 64; kb++, o = next_stage(o)) {
        mbar_wait(BAR(B_GEMPTY + st), ph);
        const int k = (kb + (tile < 120 ? 0 : LROT)) & 63;
        if (c.w) load_a(k, o, BAR(B_GFULL + st)); else load_b(k, o, BAR(B_GFULL + st));
        if (kb + PF_D < 64) ahead(kb + PF_D);
        if (++st == 5) { st = 0; ph ^= 1; }
      }
    }
    return;
  } else if (c.m == 2) {
    asm volatile("setmaxnreg.dec.sync.aligned.u32 %0;" :: "n"(512 - 2 * REG_F - REG_H));
    c.lane = lane_id();
    {
      char* own = c.mail + (uint32_t)(M_E3 + (c.r >> 5) * 8192 + (c.r & 31) * 128 + c.lane * 4);
      probe_pair(c, c.w < 2 ? M_PAIR + (c.w * 128 + c.r) * 16384 : c.w == 2 ? M_E3 + (c.r & 15) * 8192 + (c.r >> 4) * 128 : M_REF + c.r * 32, c.w, c.w == 2 ? SENT : 0u);
      if (tid_now() == 256) TL2(14);
      __syncwarp();
      uint32_t tl = clock_lo() + (PACE0 + WO_AT * PACE);
      mbar_arrive_warp(BAR(B_PROBE));
      if (c.w == 0) {
        const unsigned short* mp = (const unsigned short*)mem0 + (2 * (c.lane & 3)) * D_ + 8 * c.r + (c.lane >> 2);
        uint32_t mv = (uint32_t)mp[0] | ((uint32_t)mp[D_] << 16);
        if (mv == SENT) mv = 0x7FFF7FFFu;
        mbar_wait(BAR(B_PROBE), 0);
        const uint4 bits = lds128(c.sb + SM_SEL + 512);
        st_pub_if(g_ctl + C_SEL + c.r, bits.x | bits.y | bits.z | bits.w | 0x100u | tile_key(), c.lane == 0);
        uint4 v; uint32_t n = 0;
        while (true) {
          delay_cycles(DLY_SEL);
          v = ld_poll(g_ctl + C_SEL + c.lane * 4);
          if (__all_sync(~0u, v.x & v.y & v.z & v.w & 0x100u)) break;
          watchdog(n, POLL_LIMIT);
        }
        st_pub(own, mv); st_pub(own + 4096, mv);
        sts128(c.sb + SM_SEL + c.lane * 16, v);
        mbar_arrive_warp(BAR(B_SEL));
        if (SIDE == 2) {
#pragma unroll 1
          for (uint32_t g = 0; g < 8; g++) {
            const bool a = v.x >> 24 == g, b = v.z >> 24 == g;
            const int n = __reduce_add_sync(~0u, (a ? (int)(v.x & 8) + (v.y & 8) - 8 : 0) + (b ? (int)(v.z & 8) + (v.w & 8) - 8 : 0));
            if (n > 0) { v.x |= (uint32_t)a << 28; v.z |= (uint32_t)b << 28; }
          }
        }
        const uint32_t key = __shfl_sync(~0u, c.a ? v.z : v.x, c.h);
        const int u = __popc(__ballot_sync(~0u, v.x < key)) + __popc(__ballot_sync(~0u, v.z < key));
        sts32(c.sb + SM_SEL + 528, (u & 32) * 2 + (u & 7) * 8 + (u >> 2 & 6) + c.b);
        if (c.lane == 0) TL2(13);
        __syncwarp();
      }
      if (c.w == 1) for (int i = 0; i < 4; i++) { delay_until(tl += WO_P * PACE); prefetch2d_e(&to, c.j * 256 + i * 64, c.h * 128); }
    }
    asm volatile("barrier.cluster.wait;" ::: "memory");
    const int g = c.w, src0 = c.h * 4 + (g >> 1) * 2;
    mbar_wait(BAR(B_SEL), 0);
    c.sel = __shfl_sync(~0u, (~lds32(c.sb + SM_SEL + src0 * 4 + (c.lane >> 5)) & 3) * 4096 | e1_off(c) * 6, 0);
    mbar_wait(BAR(B_WREAD), 0);
    uint32_t l16 = c.sb + g * 512 + c.lane * 16;
    auto lane = [&](uint32_t v) { l16 = dep(l16, v, c.sb); return (int)((l16 & 511) >> 4); };
    for (int s = 0; s < NSEG; s++) {
      l16 = vary(l16, s, c.sb);
      int ln = (l16 & 511) >> 4;
      uint4 kf[4], qx;
      {
        const int gs = min(s, XEND - 1);
        const char* pk = c.mail + (uint32_t)(M_KVQ + ((gs & (NSLOT - 1)) * 32 + c.h) * 24576 + g * 2048 + ln * 16);
        const char* pq = pk + (16384 + c.j * 2048 - g * 1536);
        const uint32_t tg = (gs / NSLOT) & 1;
        touch(pk, c.sb); touch(pq, c.sb);
        mbar_wait(BAR(B_VFULL), s & 1);
        if (KVQ_AT) { mbar_wait(BAR(B_MEM), s & 1); if (DLY_K) delay_cycles(DLY_K); } else if (s > 0) mbar_wait(BAR(B_PUB), (s - 1) & 1);
        for (uint32_t n = 0; ; ) {
          uint4 k[4];
#pragma unroll
          for (int t = 0; t < 4; t++) k[t] = ld_poll(pk + t * 512);
          qx = ld_poll(pq);
#pragma unroll
          for (int t = 0; t < 2; t++) {
            auto cp = [&](uint32_t v) { return dep(v, 0, c.sb); };
            kf[t] = make_uint4(cp(k[2 * t].x), cp(k[2 * t].y), cp(k[2 * t + 1].x), cp(k[2 * t + 1].y));
            kf[2 + t] = make_uint4(cp(k[2 * t].z), cp(k[2 * t].w), cp(k[2 * t + 1].z), cp(k[2 * t + 1].w));
          }
          if (all_clear(stale1(stale2(k[0].x, k[1].x, tg) | stale2(k[2].x, k[3].x, tg), qx.x, tg), EXP_CHK)) break;
          watchdog(n, POLL_LIMIT); CNT(4);
        }
        TR(s, 2);
      }
      if (X_AT >= 2 && g == 0 && s + 2 < XEND) {
        mbar_wait(BAR(B_XEMPTY), ~s & 1);
        if (X_AT == 3) mbar_wait(BAR(B_MEM), s & 1);
        mbar_expect_e(BAR(B_XFULL), 16384 * EXP_NXT);
        for (int i = 0; i < EXP_NXT; i++) tma4d_e(c.sb + SM_XT + i * 16384, &tx, c.b * 8, (s + 2) * 4 + 2 * (c.b ^ i), BAR(B_XFULL));
      }
      ln = lane(kf[0].y);
      const char* pa = c.mail + (uint32_t)(M_PAIR + ((s & 1) * 128 + src0) * 16384 + (c.sel >> (s & 1) & 4096) + (c.sel >> 2 & 8192) + (g & 1) * 512 + (EXP_LIN ? ln * 16 : read_off(ln)));
      const uint32_t spw = c.sb + SM_SP + g * 1280 + (ln & 3) * 64 + ((((ln >> 3) ^ ln) & 2) << 4) + (ln & 4) * 4 + (ln & 8),
                     spr = c.sb + SM_SP + (ln & 4) * 80 + (ln >> 3) * 64 + (((ln & 3) ^ ((ln >> 3) & 2)) << 4), l8 = ln * 8;
      const uint32_t tg = s >> 1;
      float sx[2][4];
      uint32_t sm;
      uint4 km;
      touch(pa, c.sb);
      mbar_wait(BAR(B_E1TRIG), s & 1);
      const uint32_t t0 = clock_lo();
      TRV(s, 3, t0);
      scores_x<false>(sx, kf, qx, 0);
      store_scores(sx, spw + 640);
      delay_until(t0 + DLY_E1);
      uint32_t nr = 0;
      while (true) {
        const uint4 q0 = ld_poll(pa), q1 = ld_poll(pa + 2048), k0 = ld_poll(pa + 1024), k1 = ld_poll(pa + 3072);
        uint4 qm = add4(q0, q1);
        const uint32_t bq = stale2(q0.x, q1.x, tg);
        qm.x = dep(qm.x, bq, c.sb);
        scores_x<SC_F>(sx, kf, qm, c.sb);
        const uint32_t bk = stale2(k0.x, k1.x, tg);
        km = add4(k0, k1);
        km.x = dep(km.x, bk, c.sb);
        const bool ok = all_clear(bq | bk, 1);
        sm = scores_m(qm, km);
        store_scores(sx, spw);
        if (ok) break;
        nr++; CNT(2);
      }
      sts32(l8 + (c.sb + SM_SPM + (g >> 1) * 256 + (g & 1) * 4), sm);
      bar_sync(NB_ATT, 128);
      TR(s, 5); TRV(s, 13, nr);
      float o[2][4];
      uint32_t sp[5];
      uint4 vf[4];
      load_scores(sp, spr, l8 + (c.sb + SM_SPM));
      const uint32_t m5 = max5(sp);
      uint32_t m1;
      float off = row_off(m5, m1), f[10];
      l16 = dep(l16, VF_AT ? m1 : m5, c.sb);
#pragma unroll
      for (int t = 0; t < 4; t++) vf[(t >> 1) + 2 * (t & 1)] = lds128(l16 + SM_V + ((t >> 1) + 2 * (t & 1)) * 2048);
      qx.x = dep(qx.x, sp[0], c.sb);
      sts32(l8 + (c.sb + SM_SPM + 512 + (g >> 1) * 256 + (g & 1) * 4), scores_m(qx, km));
      mbar_arrive_warp(BAR(B_SC));
      unpack(f, sp);
      if (UP_F) sched_fence(c.sb);
      uint4 vm;
      if (VM_AT < 2) {
        bar_sync(NB_VM, 384);
        sp[1] = exp_pair(f, 1, off);
        const uint32_t av = dep(l8, VM_AT ? sp[1] : __float_as_uint(off), c.sb) + (c.sb + g * 512 + SM_VM);
        const uint2 vm0 = lds64(av), vm1 = lds64(av + 256);
        vm = make_uint4(vm0.x, vm0.y, vm1.x, vm1.y);
#pragma unroll
        for (int i = 2; i < 6; i++) sp[i % 5] = exp_pair(f, i % 5, off);
      } else {
#pragma unroll
        for (int i = 1; i < 6; i++) sp[i % 5] = exp_pair(f, i % 5, off);
        bar_sync(VM_AT == 2 ? dep(dep(0, sp[1] ^ sp[2], c.sb) + NB_VM, sp[0], c.sb) : dep(dep(0, sp[0] ^ sp[1] ^ sp[2], c.sb) + NB_VM, sp[3], c.sb), 384);
        const uint32_t av = l8 + (c.sb + g * 512 + SM_VM);
        const uint2 vm0 = lds64(av), vm1 = lds64(av + 256);
        vm = make_uint4(vm0.x, vm0.y, vm1.x, vm1.y);
      }
      float sum;
      auto rows_m = [&]() {
        const uint32_t tv = min(s, XEND - 1) / NSLOT;
        sum = pv(o, sp, vf, vm);
        stsm4<false>(l16 + SM_OM, pack_bf16(o[0][0], o[0][1]), pack_bf16(o[0][2], o[0][3]), pack_bf16(o[1][0], o[1][1]), pack_bf16(o[1][2], o[1][3]));
        sts32(c.sb + SM_SUM + ((l16 >> 4) & 28), __float_as_uint(sum));
        return arrive_if_clear(stale2(vf[0].x, vf[1].x, tv) | stale2(vf[2].x, vf[3].x, tv), EXP_CHK, NB_OM, 384);
      };
      if (!rows_m()) {
        const char* pv_ = c.mail + (uint32_t)(M_KVQ + ((min(s, XEND - 1) & (NSLOT - 1)) * 32 + c.h) * 24576 + 8192 + (l16 - c.sb));
        uint32_t n = 0;
        do {
#pragma unroll
          for (int t = 0; t < 4; t++) vf[t] = ld_poll(pv_ + t * 2048);
          watchdog(n, POLL_LIMIT); CNT(5);
        } while (!rows_m());
      }
      const uint32_t tom = clock_lo();
      TRV(s, 8, tom);
      sched_fence(c.sb);
      ln = lane(tom);
      const int n = ln >> 2, jj = ln & 3, tq_ = 8 * c.j + (n & 4) + 2 * (n & 1) + ((n >> 1) & 1), lim = 16 * (tq_ - 2 * jj + 1);
      if (DLY_X) delay_until(tom + DLY_X);
      load_scores(sp, spr + 640, c.sb + SM_SPM + 512 + ln * 8);
#pragma unroll
      for (int w = 0; w < 4; w++) {
        uint32_t m; asm("shl.b32 %0, 0xffffffff, %1;" : "=r"(m) : "r"(max(lim - 128 * w, 0)));
        sp[1 + w] = (sp[1 + w] & ~m) | (0xD029D029u & m);
      }
      mbar_arrive_warp(dep(dep(0, sp[0], c.sb), sp[1], c.sb) + BAR(B_SPFREE));
      off = row_off(max5(sp), m1);
      unpack(f, sp);
#pragma unroll
      for (int i = 1; i < 6; i++) sp[i % 5] = exp_pair(f, i % 5, off);
      sum = pv(o, sp, vf, vm);
      if (W_PV) mbar_arrive_warp(dep(dep(0, __float_as_uint(o[1][0]), c.sb), __float_as_uint(sum), c.sb) + BAR(B_PVDONE));
      TR(s, 7);
      sum = rcp(sum);
      const float i0 = __shfl_sync(~0u, sum, 8 * jj), i1 = __shfl_sync(~0u, sum, 8 * jj + 4);
      const uint32_t oxs = c.sb + SM_OX + g * 512;
      stsm4<true>(oxs + (ln & 7) * 64 + (((ln >> 3) ^ ((ln >> 1) & 3)) << 4),
                  pack_bf16(o[0][0] * i0, o[0][1] * i1), pack_bf16(o[0][2] * i0, o[0][3] * i1), pack_bf16(o[1][0] * i0, o[1][1] * i1), pack_bf16(o[1][2] * i0, o[1][3] * i1));
      __syncwarp();
      *(uint4*)(g_ox + (uint32_t)((32 * s + tq_) * 4096 + c.h * 128 + 32 * g + 8 * jj)) = lds128(oxs + n * 64 + ((jj ^ (n >> 1)) << 4));
      mbar_arrive_warp(BAR(B_PVDONE));
      TR(s, 9);
    }
    if (LASTM) {
      const int ln = tid_now() & 31, n = ln >> 2, jj = ln & 3, tq_ = 8 * c.j + (n & 4) + 2 * (n & 1) + ((n >> 1) & 1);
      store_count(g_ox + (uint32_t)((S_ - 32 + tq_) * 4096 + c.h * 128 + 32 * g + 8 * jj), lds128(c.sb + SM_OX + g * 512 + n * 64 + ((jj ^ (n >> 1)) << 4)), g_ctl + C_LAST);
    } else count_e(g_ctl + C_LAST);
    mbar_arrive_warp(BAR(B_DONE));
    if (tid_now() == 256) TL(8);
    __syncwarp();
    mbar_wait(BAR(B_E2TRIG), 1); mbar_wait(BAR(B_DONE), 0); mbar_wait(BAR(B_TW), 0);
    asm volatile("setmaxnreg.inc.sync.aligned.u32 128;");
  } else {
    asm volatile("setmaxnreg.inc.sync.aligned.u32 %0;" :: "n"(REG_F));
    c.lane = lane_id();
    uint32_t wa[16][4], wb[16][4], wv[16][4];
    fft_rows_fwd((float2*)smraw, (const __nv_bfloat16*)(smraw + SM_GW), c.r, threadIdx.x, BAR(B_ROWS), BAR(B_FREE));
    mbar_arrive_warp(BAR(B_P1));
    if (tid_now() == 0) TL2(1);
    __syncwarp();
    mbar_spin(BAR(B_WFULL + c.m), 0);
    if ((tid_now() & 127) == 0) TL2(16);
    __syncwarp();
    {
      const uint32_t st = c.sb + c.m * ST_WG + frag_off(c.w, c.lane);
#pragma unroll
      for (int k = 0; k < 16; k++) ldsm4t(wb[k], st + k * 2048);
#pragma unroll
      for (int k = NP; k < 16; k++) ldsm4t(wa[k], st + (16 + k - NP) * 2048);
#pragma unroll
      for (int k = 0; k < NV; k++) ldsm4t(wv[k], st + (32 - NP + k) * 2048);
      mbar_arrive_warp(BAR(B_WREAD));
#pragma unroll
      for (int k = 0; k < NP; k++) ldsm4t(wa[k], c.sb + SM_POOL + c.m * NP * 2048 + frag_off(c.w, c.lane) + k * 2048);
      bar_sync(NB_XCH, 256);
#pragma unroll
      for (int k = 0; k < NP; k++) sts128(c.sb + SM_POOL + c.m * 2048 + c.w * 512 + c.lane * 16 + k * 4096, make_uint4(wa[k][0], wa[k][1], wa[k][2], wa[k][3]));
    }
    if (tid_now() == 0) TL2(12);
    __syncwarp();
    asm volatile("barrier.cluster.wait;" ::: "memory");
    uint32_t t16 = c.m * 2048 + c.w * 512 + c.lane * 16;
    uint32_t pk = (c.m * NHV * 2048 + frag_off(c.w, c.lane)) | (tile_off(2 * (c.w & 1), c.lane) << 16) | ((c.lane & 12) ? 0u : 0x80000000u);
    const uint32_t dx = desc_lo(c.sb + SM_XT + c.m * 4096), dh = desc_lo(c.sb + SM_HV + c.m * NHV * 2048);
    for (int s = -2; ; s++) {
      t16 = vary(t16, s, c.sb); pk = vary(pk, s, c.sb);
      if (s >= 0) {
        uint32_t af[16][4], bf[4][4], wo;
        const uint32_t tab = ((t16 >> 3) & 0x1C0) + (c.sb + SM_TAB + (s & 1) * 512);
        const char* pa;
        mem_proj(wa, wb, wv, af, wo, pa, tab, t16, pk, c, s);
        const uint32_t t0 = clock_lo();
        t16 = dep(t16, t0, c.sb);
        auto ldwo = [&](int f) { ldsm4t(af[f], (f < WO_D ? wo : dep(wo, af[f < WO_D ? 0 : f - WO_D][0], c.sb)) + (c.sb + SM_WO + (f & 1) * 32768 + (f >> 1) * 2048)); };
        {
          const uint32_t tg = s >> 1, vm = t16 >> 1, chk = (~t16 >> 4) & 1;
#pragma unroll
          for (int f = WO_0; f < WO_1; f++) ldwo(f);
          delay_until(t0 + DLY_V);
          uint2 v0 = ld_poll2(pa), v1 = ld_poll2(pa + 1024), v2 = ld_poll2(pa + 2048), v3 = ld_poll2(pa + 3072);
          TR(s, 3);
#pragma unroll
          for (int f = WO_1; f < 16 - WO_L; f++) ldwo(f);
          TR(s, 4);
          uint32_t n = 0;
          while (true) {
            sts64(vm + (c.sb + SM_VM), sum4(v0.x, v1.x, v2.x, v3.x), sum4(v0.y, v1.y, v2.y, v3.y));
            if (arrive_if_clear(stale1(stale1(stale2(v0.x, v1.x, tg), v2.x, tg), v3.x, tg), chk, NB_VM, 384)) break;
            v0 = ld_poll2(pa); v1 = ld_poll2(pa + 1024); v2 = ld_poll2(pa + 2048); v3 = ld_poll2(pa + 3072);
            n++; CNT(3);
          }
          TR(s, 12); TRV(s, 15, n);
        }
        const uint32_t ob = dep(dep(t16 & 511, af[14 - WO_L][0], c.sb), af[15 - WO_L][0], c.sb);
        uint32_t l4 = ob >> 2;
        const uint32_t bit = (t16 & 48) ? 0u : 1u;
        mbar_spin_if(BAR(B_XFULL), s & 1, s + 2 < XEND);
        bar_sync(NB_OM, 384);
        TR(s, 5);
#pragma unroll
        for (int i = 0; i < 4; i++) ldsm4t(bf[i], ob + (c.sb + SM_OM + i * 512));
        uint2 sum = lds64(((t16 >> 1) & 24) + (c.sb + SM_SUM));
        if (OM_F) sched_fence(c.sb);
        float d[WO_C][4] = {};
        uint4 d0, d1;
#pragma unroll
        for (int f = 0; f < 16; f++) {
          mma_a(d[f % WO_C], af[f], bf[f >> 2][f & 2], bf[f >> 2][(f & 2) + 1]);
          if (f >= WO_C && f < WO_C + WO_L) {
            const int l = 16 - WO_L + f - WO_C;
            ldsm4t(af[l], (WO_LD ? dep(wo, __float_as_uint(d[(f + 1) % WO_C][0]), c.sb) : wo) + (c.sb + SM_WO + (l & 1) * 32768 + (l >> 1) * 2048));
          }
          if (f == WO_T) {
            const uint32_t tb2 = dep((t16 >> 3) & 0x1C0, __float_as_uint(d[f % WO_C][0]), c.sb) + (c.sb + SM_TAB + (s & 1) * 512);
            d0 = lds128(tb2 + 32); d1 = lds128(tb2 + 48);
          }
          if (f >= PL_WA && f < PL_WA + PL_W) lds_frag(wa[f - PL_WA], (PL_WD ? dep(t16, __float_as_uint(d[(f + PL_WD) % WO_C][0]), c.sb) : t16) + (c.sb + SM_POOL + (f - PL_WA) * 4096));
          if (PL_W && PL_WF && f == PL_WA + PL_W - 1) sched_fence(c.sb);
          if (f == 4) { sum.x = dep(sum.x, __float_as_uint(d[0][0]), c.sb); sum.y = dep(sum.y, __float_as_uint(d[0][0]), c.sb); }
        }
        if (PL_W && !PL_WF) {
          uint32_t all = 0;
#pragma unroll
          for (int k = 0; k < PL_W; k++) all ^= wa[k][0];
          l4 = dep(l4, all, c.sb);
        }
        char* dst[4] = {mk_ptr(d0.x | l4, d0.y), mk_ptr(d0.z | l4, d0.w), mk_ptr(d1.x | l4, d1.y), mk_ptr(d1.z | l4, d1.w)};
        const float i0 = rcp(__uint_as_float(sum.x)), i1 = rcp(__uint_as_float(sum.y));
#pragma unroll
        for (int i = 0; i < 4; i++) {
          const int t = i >> 1, e = 2 * (i & 1);
          const float y0 = WO_C == 2 ? d[t][e] : d[t][e] + d[(t + 2) % WO_C][e], y1 = WO_C == 2 ? d[t][e + 1] : d[t][e + 1] + d[(t + 2) % WO_C][e + 1];
          st_pub(dst[i], put_tag(pack_bf16(y0 * i0, y1 * i1), bit, s >> 1));
        }
        if (ANCH2) sts32(c.sb + SM_SUM + 64, clock_lo());
        mbar_arrive_warp(BAR(B_E2TRIG));
        TR(s, 6);
        sched_fence(c.sb);
        if (W_E2 == 2) mbar_spin(BAR(B_E2TRIG), s & 1);
        if (s == NSEG - 1) break;
      }
      auto ldp = [&](int k0, int k1, int d, int back = 0) {
#pragma unroll
        for (int k = k0; k < k1; k++) lds_frag(wa[k], (k < k0 + d - back ? t16 : dep(t16, wa[k < d ? 0 : k - d][0], c.sb)) + (c.sb + SM_POOL + k * 4096));
      };
      ldp(PL_W, PL_0 < PL_W + PL_D ? PL_0 : PL_W + PL_D, PL_D);
      mbar_spin_if(BAR(B_XFULL), s & 1, s < 0);
      const uint32_t tgo = clock_lo() + (t16 >> 11) * STAG;
      ldp(PL_W + PL_D, PL_0 - PL_D, PL_D, PL_D);
      if (STAG) delay_until(tgo);
      ldp(PL_0 - PL_D, PL_0, PL_D, PL_D);
      if (s + 2 < XEND) {
        float xa[16];
        uint32_t q[4];
        if (W_E2 == 1 && s >= 0) mbar_spin(BAR(B_E2TRIG), s & 1);
        if (W_PV && s >= 0) mbar_spin(BAR(B_PVDONE), s & 1);
        TR(s, 7);
        constexpr int S1 = ORDER ? 0 : 2, S2 = ORDER == 0 ? 0 : ORDER == 1 ? 2 : 1, S3 = ORDER == 2 ? 2 : 1;
        if (ORDER) issue_qk<0, 16>(xa, wb, vary(dx, s, c.sb)); else issue_v(xa, wv, vary(dx, s, c.sb), vary(dh, s, c.sb));
        if (IS_F) sched_fence(c.sb);
        ldp(PL_0, PL_1, PL_D1);
        const uint32_t land = (t16 ^ ((t16 >> 3) & 0x60)) + vary(c.sb + SM_LAND + c.b * 4096, s, c.sb);
        mbar_spin(BAR(B_LFREE), s & 1);
        WG_WAIT(0);
        TR(s, 8);
        park_own<S1 == 2>(q, xa, land, S1, c.sb);
        if (W_PUB == 4 && s >= 0) mbar_spin(BAR(B_PUB), s & 1);
        if (ORDER == 1) issue_v(xa, wv, vary(dx, s, c.sb + 32), vary(dh, s, c.sb)); else issue_qk<0, 16>(xa, ORDER ? wa : wb, vary(dx, s, c.sb + 32));
        if (IS_F) sched_fence(c.sb);
        ldp(PL_1, PL_2, PL_D1);
        if (W_PUB == 1) mbar_spin_if(BAR(B_PUB), s & 1, s >= 0);
        uint32_t tp = clock_lo(), q1[4] = {q[0], q[1], q[2], q[3]};
        if (W_PUB != 3) park_peer(q, land, S1, c);
        ldp(PL_2, NP - PL_L, PL_D1);
        TR(s, 13);
        WG_WAIT(0);
        TR(s, 9);
        park_own<S2 == 2>(q, xa, land, S2, c.sb);
        if (ORDER == 2) issue_v(xa, wv, vary(dx, s, c.sb + 64), vary(dh, s, c.sb));
        else {
          issue_qk<0, PL_L ? NP - PL_L : 16>(xa, wa, vary(dx, s, c.sb + 64));
          ldp(NP - PL_L, NP, PL_E);
          if (PL_L) issue_qk<NP - PL_L, 16>(xa, wa, vary(dx, s, c.sb + 64));
        }
        if ((W_PUB == 2 || W_PUB == 3) && s >= 0) { mbar_spin(BAR(B_PUB), s & 1); tp = clock_lo(); }
        if (W_PUB == 3) park_peer(q1, land, S1, c);
        if (DLY_S && s >= 0) delay_until(tp + DLY_S);
        park_peer(q, land, S2, c);
        WG_WAIT(0);
        TR(s, 10);
        mbar_arrive_warp(BAR(B_XEMPTY));
        park_own<S3 == 2>(q, xa, land, S3, c.sb);
        park_peer(q, land, S3, c);
        TR(s, 11);
      } else ldp(PL_0, NP, 1);
    }
    asm volatile("setmaxnreg.dec.sync.aligned.u32 128;");
    const int tid = tid_now(), lane = tid & 31, tile = tile_of(c), m0 = (tile >> 3) * 128, n0 = (tile & 7) * 128;
    float acc[64];
#pragma unroll
    for (int i = 0; i < 64; i++) acc[i] = 0.f;
    const uint32_t rel = mapa(BAR(B_GEMPTY), lane & 1), la = desc_lo(c.sb + c.m * 8192), lb = ((c.sb + 16384) & 0x3FFFF) >> 4 | (8192 >> 4) << 16;
    const bool relon = (tid & 127) < 2;
    uint32_t o = SM_XT, st = 0, ph = 0, prev = 0;
    if (tid == 0) TL(9);
    __syncwarp();
#pragma unroll 1
    for (int kb = 0; kb < 64; kb++, o = next_stage(o)) {
      mbar_lim(BAR(B_GFULL + st), ph);
      WG_FENCE();
#pragma unroll
      for (int k = 0; k < 4; k++) wgmma_ss_n128_tb(acc, desc128(la + (o >> 4) + k * 2), desc128(lb + (o >> 4) + k * 128));
      WG_COMMIT();
      WG_WAIT(1);
      arrive_remote_if(rel + 8 * prev, relon && kb > 0 && kb < 60);
      prev = st;
      if (++st == 5) { st = 0; ph ^= 1; }
    }
    WG_WAIT(0);
    if (tid == 0) TL(4);
    __syncwarp();
    const int r0 = c.m * 64 + c.w * 16 + (lane >> 2);
    const float g0 = __ldcg(g_gate + m0 + r0), g1 = __ldcg(g_gate + m0 + r0 + 8);
    mbar_lim(BAR(B_BT), 0);
#pragma unroll
    for (int t = 0; t < 16; t++) {
      const uint32_t a0 = c.sb + SM_BT + (t >> 3) * 16384 + r0 * 128 + (((t & 7) ^ (r0 & 7)) << 4) + (lane & 3) * 4, a1 = a0 + 1024;
      const uint32_t b0 = lds32(a0), b1 = lds32(a1);
      sts32(a0, pack_bf16(fmaf(g0, acc[4 * t], (1.f - g0) * __uint_as_float(b0 << 16)), fmaf(g0, acc[4 * t + 1], (1.f - g0) * __uint_as_float(b0 & 0xFFFF0000u))));
      sts32(a1, pack_bf16(fmaf(g1, acc[4 * t + 2], (1.f - g1) * __uint_as_float(b1 << 16)), fmaf(g1, acc[4 * t + 3], (1.f - g1) * __uint_as_float(b1 & 0xFFFF0000u))));
    }
    FENCE_ASYNC_SMEM();
    bar_sync(13, 256);
    if (tid == 0) {
      tma2d_store(&tout, n0, m0, c.sb + SM_BT); tma2d_store(&tout, n0 + 64, m0, c.sb + SM_BT + 16384);
      asm volatile("cp.async.bulk.commit_group; cp.async.bulk.wait_group 0;" ::: "memory");
      TL(11);
    }
    return;
  }
  const bool col = c.r >= 128;
  const int tile = col ? 0 : tile_of(c);
  const int q0 = col ? 256 - 16 * NCR + (c.r - 128) * 4 + c.m : tile < 120 ? tile : 256, dq = col ? 16 : 120, qe = col ? 256 : 256 - 16 * NCR;
  const uint32_t zs = c.sb + (col ? COL_Z + c.m * 32768 : SM_BT), zb = BAR(B_Z + c.m);
  auto load_z = [&](int q) { if (c.w == 0 && q < qe) { mbar_expect_e(zb, 32768); tma2d_e(zs, &tz, q * 64, 0, zb); } };
  asm volatile("fence.proxy.async;" ::: "memory");
  load_z(q0);
  uint32_t ph = 0;
#pragma unroll 1
  for (int q = q0; q < qe; q += dq, ph ^= 1) {
    mbar_lim(zb, ph);
    const int p = q * 4 + c.w;
    if (EXP_INV) fft_rows_inv(zs, (float2*)(smraw + (col ? 8192 + c.m * ROW_BUF * 16 : SM_MEM)) + c.w * (ROW_BUF / 2), (const float2*)(smraw + (col ? 0 : SM_TW)), p, tid_now() & 31,
                              [&]() { bar_sync(5 + c.m, 128); load_z(q + dq); });
    else { bar_sync(5 + c.m, 128); load_z(q + dq); }
  }
  asm volatile("fence.acq_rel.gpu;" ::: "memory");
  __syncwarp();
  { const int q = q0 + (tid_now() & 31) * dq; if (q < qe) asm volatile("red.relaxed.gpu.global.add.u32 [%0], 1;" :: "l"(g_ctl + C_ROWS + (q >> 5) * 32) : "memory"); }
  if (tid_now() == 256) { if (col) TL(27); else TL(3); }
  __syncwarp();
  if (!col && c.w == 0) {
    await_count(g_ctl + C_ROWS + ((tile >> 3) & 7) * 32, 128);
    mbar_expect_e(BAR(B_BT), 32768);
    for (int i = 0; i < 2; i++) tma2d_e(c.sb + SM_BT + i * 16384, &tb, (tile & 7) * 128 + i * 64, (tile >> 3) * 128, BAR(B_BT));
    if (tid_now() == 256) TL(5);
  }
}

typedef CUresult (*EncodeFn)(CUtensorMap*, CUtensorMapDataType, cuuint32_t, void*, const cuuint64_t*, const cuuint64_t*,
                             const cuuint32_t*, const cuuint32_t*, CUtensorMapInterleave, CUtensorMapSwizzle,
                             CUtensorMapL2promotion, CUtensorMapFloatOOBfill);

void make_map(EncodeFn enc, CUtensorMap* tm, const void* p, int rank, const cuuint64_t* dims, const cuuint64_t* strides, const cuuint32_t* box, bool swz = true) {
  const cuuint32_t es[4] = {1, 1, 1, 1};
  enc(tm, CU_TENSOR_MAP_DATA_TYPE_BFLOAT16, rank, (void*)p, dims, strides, box, es, CU_TENSOR_MAP_INTERLEAVE_NONE,
      swz ? CU_TENSOR_MAP_SWIZZLE_128B : CU_TENSOR_MAP_SWIZZLE_NONE, CU_TENSOR_MAP_L2_PROMOTION_L2_128B, CU_TENSOR_MAP_FLOAT_OOB_FILL_NONE);
}
void make_map2(EncodeFn enc, CUtensorMap* tm, const void* p, uint64_t cols, uint64_t rows, uint32_t boxrows) {
  const cuuint64_t dims[2] = {cols, rows}, strides[1] = {cols * 2};
  const cuuint32_t box[2] = {64, boxrows};
  make_map(enc, tm, p, 2, dims, strides, box);
}

}

extern "C" void kernel_launch(void* const* d_in, const int* in_sizes, int n_in, void* d_out, int out_size) {
  (void)in_sizes; (void)n_in; (void)out_size;
  const __nv_bfloat16* x = (const __nv_bfloat16*)d_in[0];
  const __nv_bfloat16* mem0 = (const __nv_bfloat16*)d_in[1];
  const __nv_bfloat16* gw = (const __nv_bfloat16*)d_in[10];

  EncodeFn enc = nullptr;
  cudaDriverEntryPointQueryResult qr;
  cudaGetDriverEntryPoint("cuTensorMapEncodeTiled", (void**)&enc, cudaEnableDefault, &qr);
  void *p_ox, *p_b, *p_z, *p_mail;
  cudaGetSymbolAddress(&p_ox, g_ox); cudaGetSymbolAddress(&p_b, g_b); cudaGetSymbolAddress(&p_z, g_z); cudaGetSymbolAddress(&p_mail, g_mail);
  CUtensorMap tq, tk, tv, tv16, to, tx, twr, twi, ta, tw, tb, tout, tz;
  make_map2(enc, &tq, d_in[2], 4096, 1024, 64);
  make_map2(enc, &tk, d_in[3], 4096, 1024, 64);
  make_map2(enc, &tv, d_in[4], 4096, 1024, 64);
  make_map2(enc, &tv16, d_in[4], 4096, 1024, 16);
  make_map2(enc, &to, d_in[5], 1024, 4096, 128);
  make_map2(enc, &tw, d_in[5], 1024, 4096, 64);
  make_map2(enc, &ta, p_ox, 4096, 2048, 64);
  make_map2(enc, &tb, p_b, 1024, 2048, 128);
  make_map2(enc, &tout, d_out, 1024, 2048, 128);
  make_map2(enc, &tz, p_z, 16384, 257, 256);
  {
    const cuuint64_t dims[4] = {64, 8, 16, 256}, strides[3] = {2048, 128, 16384};
    const cuuint32_t box[4] = {64, 8, 8, 2};
    make_map(enc, &tx, x, 4, dims, strides, box);
  }
  {
    const cuuint64_t dims[2] = {8 * 513, 256}, strides[1] = {8 * 513 * 2};
    const cuuint32_t box[2] = {8, 256};
    make_map(enc, &twr, d_in[8], 2, dims, strides, box, false);
    make_map(enc, &twi, d_in[9], 2, dims, strides, box, false);
  }
  cudaFuncSetAttribute(chain_kernel, cudaFuncAttributeMaxDynamicSharedMemorySize, CHAIN_SMEM);

  cudaStream_t st = cudaStreamPerThread;
  char* mail = (char*)(((uintptr_t)p_mail + 16383) & ~(uintptr_t)16383);
  chain_kernel<<<132, 512, CHAIN_SMEM, st>>>(tq, tk, tv, tv16, to, tx, twr, twi, ta, tw, tb, tout, tz, mem0, mail, x, gw);
}
```

```cpp
#include <cuda_runtime.h>
#include <cuda_bf16.h>
#include <cuda.h>
#include <stdint.h>

#define DLY_E1 300
#define DLY_V 330
#define DLY_E2 400
#define DLY_E3 500
#define DLY_X 1
#define DLY_S 500
#define DLY_F 0
#define VM_AT 1
#define VM_F 0
#define OM_F 1
#define SXX_IN 0
#define C1_AT 1
#define NLAG 4
#define WO_D 2
#define WO_0 2
#define WO_1 12
#define PL_0 8
#define PL_1 NP_
#define PL_D 2
#define PL_L 0
#define DUAL 0
#define HV_D 3
#define DLY_FK 0
#define QX_SM 0
#define REG_F 216
#define REG_H 24
#define SC_F 1
#define E2_F 1
#define KVQ_AT 0
#define DLY_K 0
#define X_AT 2
#define W_PV 0
#define PL_2 NP_
#define BF_E 3
#define PL_E 2
#define ORDER 1
#define SSPOS 1
#define W_PUB 1
#define FIN_AT 5
#define AWARE 1
#define NPROBE 2
#define NP_ 12
#define USE_PDL 1
#define DLY_GRP 3000
#define P2_BULK 0
#define EXP_NV 4
#define EXP_NK 4
#define EXP_CHK 1
#define EXP_NXT 2
#define EXP_PEER 1
#define EXP_FIN 7
#define EXP_NWG 16
#define ANCH2 1
#define XF_AT 1
#define IS_F 1
#define PL_D1 2
#define W_E2 0
#define V_TMA 2
#define V_W 2
#define RED_L 3
#define RED_T 1
#define RED_P 1
#define DLY_E3B 0
#define HV_E 0
#define HV_R 4
#define HOLD 0
#define PACE 550
#define PACE0 0
#define EXP_ST 7
#define HOLD_AT NPROBE
#define WO_AT 38
#define WO_P 2
#define DLY_SEL 500
#define P1_AT 1
#define EXP_ZG 1
#define TMA_W tma2d_once
#define BULK_F bulk_once
#define TMA_O tma2d_e
#define PACE_Z 500
#define PACE_F 800
#define EXP_INV 1
#define VF_AT 0
#define UP_F 1
#define WO_L (12 - NP_)
#define WO_C 4
#define WO_T 3
#define WO_LD 0
#define EXP_LIN 0
#define PL_W 0
#define PL_WA 4
#define PL_WD 0
#define PL_WF 1
#define STAG 0
#define EXP_FL 0
#define DLY_FS 0
#define DLY_F2 0
#define LROT 0
#define PF_D 4
#define PF_A 1
#define PF_B 1
#define SIDE 1
#define ROLE 1
#define LOOSE 0x765498
#define E1OFF 1
#define EVOFF E1OFF
#define EPI 0
#define WAITRD ".read"
#define X01 0
#define E3I 1
#define START 1000
#define WUNR 24
#define WO_W 0
#define PRIOR 12
#define EARLY 1
#define SEL_AT 3000
#define NCR 3
#define GATE 1
#define LASTM 1
#define PRE_AT B_SC

namespace {
constexpr int wunr = WUNR;

constexpr int S_ = 2048, D_ = 1024, NSEG = 64;
constexpr uint32_t SENT = 0xFFFFFFFFu;
constexpr int NSLOT = 4;

constexpr uint32_t M_REG = 1 << 21, M_E3 = 64 * 16384, M_KVQ = M_E3 + 4 * 8192, M_SEL = M_KVQ + 32 * 24576;
__device__ __align__(1024) unsigned char g_mail[5 * M_REG];
constexpr int C_P1 = 0, C_COLS = C_P1 + 32, C_EARLY = C_COLS + 32, C_LAST = C_EARLY + 32, C_ROWS = C_LAST + 128, C_END = C_ROWS + 8 * 32;
__device__ __align__(1024) uint32_t g_ctl[C_END];
#define CLK(i)
#define TL(i)
#define TL2(i)
#define FT(i, v)
#define CNT(i)
__device__ __align__(1024) __nv_bfloat16 g_ox[S_ * 4096];
__device__ __align__(1024) float2 g_z[257 * 4096];
__device__ __align__(1024) __nv_bfloat16 g_b[S_ * D_];
__device__ float g_gate[S_];
__device__ __align__(1024) float2 g_tw[1024];

#define TRV(s, ev, val)
#define TR(s, ev)
#define TRSYNC(ev)
__device__ __forceinline__ uint32_t smem_u32(const void* p) { return (uint32_t)__cvta_generic_to_shared(p); }
__device__ __forceinline__ void watchdog(uint32_t& n, uint32_t limit) {
  asm volatile("{ .reg .pred p; add.u32 %0, %0, 1; setp.gt.u32 p, %0, %1; @p trap; }" : "+r"(n) : "r"(limit));
}
__device__ __forceinline__ void mbar_init(uint32_t bar, uint32_t cnt) {
  asm volatile("mbarrier.init.shared::cta.b64 [%0], %1;" :: "r"(bar), "r"(cnt) : "memory");
}
__device__ __forceinline__ void mbar_arrive_warp(uint32_t bar) {
  __syncwarp();
  asm volatile("{ .reg .pred p; elect.sync _|p, 0xffffffff; @p mbarrier.arrive.shared::cta.b64 _, [%0]; }" :: "r"(bar) : "memory");
}
__device__ __forceinline__ uint32_t clock_lo() {
  uint32_t r; asm volatile("{ .reg .u64 c; .reg .u32 h; mov.u64 c, %%clock64; mov.b64 {%0, h}, c; }" : "=r"(r) :: "memory"); return r;
}
__device__ __forceinline__ void delay_until(uint32_t t) {
  asm volatile("{ .reg .pred p; .reg .u64 c; .reg .u32 l, h;\n"
               "DLY: mov.u64 c, %%clock64; mov.b64 {l, h}, c; sub.s32 l, l, %0; setp.lt.s32 p, l, 0; @p bra.uni DLY; }" :: "r"(t) : "memory");
}
__device__ __forceinline__ void delay_cycles(uint32_t n) { delay_until(clock_lo() + n); }
__device__ __forceinline__ void sched_fence(uint32_t z) {
  asm volatile("{ .reg .pred p; setp.eq.u32 p, %0, 0x7fff0000; @p pmevent 1; }" :: "r"(z) : "memory");
}
__device__ __forceinline__ void pdl_wait() { asm volatile("griddepcontrol.wait;" ::: "memory"); }
__device__ __forceinline__ void pdl_launch() { asm volatile("griddepcontrol.launch_dependents;" ::: "memory"); }
__device__ __forceinline__ float ex2(float x) { float r; asm("ex2.approx.ftz.f32 %0, %1;" : "=f"(r) : "f"(x)); return r; }
__device__ __forceinline__ float rcp(float x) { float r; asm("rcp.approx.ftz.f32 %0, %1;" : "=f"(r) : "f"(x)); return r; }
__device__ __forceinline__ void mbar_expect(uint32_t bar, uint32_t bytes) {
  asm volatile("mbarrier.arrive.expect_tx.shared::cta.b64 _, [%0], %1;" :: "r"(bar), "r"(bytes) : "memory");
}
__device__ __forceinline__ bool mbar_try(uint32_t bar, uint32_t ph) {
  uint32_t ok;
  asm volatile("{ .reg .pred p; mbarrier.try_wait.parity.shared::cta.b64 p, [%1], %2; selp.u32 %0, 1, 0, p; }"
               : "=r"(ok) : "r"(bar), "r"(ph) : "memory");
  return ok;
}
__device__ __forceinline__ void mbar_wait(uint32_t bar, uint32_t ph) {
  uint32_t n = 0;
  while (!mbar_try(bar, ph)) { watchdog(n, (1u << 20)); }
}
__device__ __forceinline__ void mbar_spin(uint32_t bar, uint32_t ph) { while (!mbar_try(bar, ph)) {} }
__device__ __forceinline__ void mbar_spin_if(uint32_t bar, uint32_t ph, bool on) {
  asm volatile("{ .reg .pred p, q; setp.ne.u32 p, %2, 0;\n"
               "SPN: setp.eq.u32 q, 0, 0; @p mbarrier.try_wait.parity.shared::cta.b64 q, [%0], %1; @!q bra.uni SPN; }" :: "r"(bar), "r"(ph), "r"((uint32_t)on) : "memory");
}
__device__ __forceinline__ void mbar_spin_cluster(uint32_t bar, uint32_t ph) {
  uint32_t ok;
  do {
    asm volatile("{ .reg .pred p; mbarrier.try_wait.parity.acquire.cluster.shared::cta.b64 p, [%1], %2; selp.u32 %0, 1, 0, p; }"
                 : "=r"(ok) : "r"(bar), "r"(ph) : "memory");
  } while (!ok);
}
__device__ __forceinline__ void tma2d(uint32_t dst, const CUtensorMap* tm, int c0, int c1, uint32_t bar) {
  asm volatile("cp.async.bulk.tensor.2d.shared::cluster.global.mbarrier::complete_tx::bytes [%0], [%1, {%3, %4}], [%2];"
               :: "r"(dst), "l"(tm), "r"(bar), "r"(c0), "r"(c1) : "memory");
}
__device__ __forceinline__ void mbar_expect_e(uint32_t bar, uint32_t bytes) {
  asm volatile("{ .reg .pred p; elect.sync _|p, 0xffffffff; @p mbarrier.arrive.expect_tx.shared::cta.b64 _, [%0], %1; }" :: "r"(bar), "r"(bytes) : "memory");
}
__device__ __forceinline__ void tma2d_e(uint32_t dst, const CUtensorMap* tm, int c0, int c1, uint32_t bar) {
  asm volatile("{ .reg .pred p; elect.sync _|p, 0xffffffff;\n"
               "@p cp.async.bulk.tensor.2d.shared::cluster.global.mbarrier::complete_tx::bytes [%0], [%1, {%3, %4}], [%2]; }"
               :: "r"(dst), "l"(tm), "r"(bar), "r"(c0), "r"(c1) : "memory");
}
__device__ __forceinline__ void tma2d_out_e(const CUtensorMap* tm, int c0, int c1, uint32_t src) {
  if (EPI) asm volatile("{ .reg .pred p; elect.sync _|p, 0xffffffff;\n"
               "@p cp.reduce.async.bulk.tensor.2d.global.shared::cta.add.bulk_group [%0, {%2, %3}], [%1]; }" :: "l"(tm), "r"(src), "r"(c0), "r"(c1) : "memory");
  else asm volatile("{ .reg .pred p; elect.sync _|p, 0xffffffff;\n"
               "@p cp.async.bulk.tensor.2d.global.shared::cta.bulk_group [%0, {%2, %3}], [%1]; }" :: "l"(tm), "r"(src), "r"(c0), "r"(c1) : "memory");
}
__device__ __forceinline__ void tma2d_once(uint32_t dst, const CUtensorMap* tm, int c0, int c1, uint32_t bar) {
  asm volatile("{ .reg .pred p; .reg .b64 h; createpolicy.fractional.L2::evict_first.b64 h; elect.sync _|p, 0xffffffff;\n"
               "@p cp.async.bulk.tensor.2d.shared::cluster.global.mbarrier::complete_tx::bytes.L2::cache_hint [%0], [%1, {%3, %4}], [%2], h; }"
               :: "r"(dst), "l"(tm), "r"(bar), "r"(c0), "r"(c1) : "memory");
}
__device__ __forceinline__ void bulk_once(uint32_t dst, const void* src, uint32_t bytes, uint32_t bar) {
  asm volatile("{ .reg .pred p; .reg .b64 h; createpolicy.fractional.L2::evict_first.b64 h; elect.sync _|p, 0xffffffff;\n"
               "@p cp.async.bulk.shared::cluster.global.mbarrier::complete_tx::bytes.L2::cache_hint [%0], [%1], %2, [%3], h; }"
               :: "r"(dst), "l"(src), "r"(bytes), "r"(bar) : "memory");
}
__device__ __forceinline__ void tma4d_e(uint32_t dst, const CUtensorMap* tm, int c2, int c3, uint32_t bar) {
  asm volatile("{ .reg .pred p; elect.sync _|p, 0xffffffff;\n"
               "@p cp.async.bulk.tensor.4d.shared::cluster.global.mbarrier::complete_tx::bytes [%0], [%1, {0, 0, %3, %4}], [%2]; }"
               :: "r"(dst), "l"(tm), "r"(bar), "r"(c2), "r"(c3) : "memory");
}
__device__ __forceinline__ void bulk_load_e(uint32_t dst, const void* src, uint32_t bytes, uint32_t bar) {
  asm volatile("{ .reg .pred p; elect.sync _|p, 0xffffffff;\n"
               "@p cp.async.bulk.shared::cluster.global.mbarrier::complete_tx::bytes [%0], [%1], %2, [%3]; }"
               :: "r"(dst), "l"(src), "r"(bytes), "r"(bar) : "memory");
}
__device__ __forceinline__ void prefetch2d_e(const CUtensorMap* tm, int c0, int c1) {
  asm volatile("{ .reg .pred p; elect.sync _|p, 0xffffffff;\n"
               "@p cp.async.bulk.prefetch.tensor.2d.L2.global [%0, {%1, %2}]; }" :: "l"(tm), "r"(c0), "r"(c1) : "memory");
}
__device__ __forceinline__ void st_pub4(void* p, uint4 v) {
  asm volatile("st.relaxed.gpu.global.v4.u32 [%0], {%1,%2,%3,%4};" :: "l"(p), "r"(v.x), "r"(v.y), "r"(v.z), "r"(v.w) : "memory");
}
__device__ __forceinline__ void st_pub_if(void* p, uint32_t v, bool on) {
  asm volatile("{ .reg .pred p; setp.ne.u32 p, %2, 0; @p st.relaxed.gpu.global.u32 [%0], %1; }" :: "l"(p), "r"(v), "r"((uint32_t)on) : "memory");
}
__device__ __forceinline__ uint32_t mapa(uint32_t a, uint32_t r) {
  uint32_t d; asm volatile("mapa.shared::cluster.u32 %0, %1, %2;" : "=r"(d) : "r"(a), "r"(r)); return d;
}
__device__ __forceinline__ void st_async4(uint32_t a, uint32_t x, uint32_t y, uint32_t z, uint32_t w, uint32_t bar) {
  asm volatile("st.async.shared::cluster.mbarrier::complete_tx::bytes.v4.u32 [%0], {%1,%2,%3,%4}, [%5];"
               :: "r"(a), "r"(x), "r"(y), "r"(z), "r"(w), "r"(bar) : "memory");
}
__device__ __forceinline__ uint4 ld_poll(const void* p) {
  uint4 v;
  asm volatile("ld.volatile.global.v4.u32 {%0,%1,%2,%3}, [%4];" : "=r"(v.x), "=r"(v.y), "=r"(v.z), "=r"(v.w) : "l"(p) : "memory");
  return v;
}
__device__ __forceinline__ uint2 ld_poll2(const void* p) {
  uint2 v; asm volatile("ld.volatile.global.v2.u32 {%0,%1}, [%2];" : "=r"(v.x), "=r"(v.y) : "l"(p) : "memory"); return v;
}
__device__ __forceinline__ void st_pub2(void* p, uint32_t a, uint32_t b) {
  asm volatile("st.relaxed.gpu.global.v2.u32 [%0], {%1,%2};" :: "l"(p), "r"(a), "r"(b) : "memory");
}
__device__ __forceinline__ uint32_t ld_poll1(const void* p) {
  uint32_t v; asm volatile("ld.volatile.global.u32 %0, [%1];" : "=r"(v) : "l"(p) : "memory"); return v;
}
__device__ __forceinline__ uint32_t ld_acquire(const uint32_t* p) {
  uint32_t v; asm volatile("ld.acquire.gpu.global.u32 %0, [%1];" : "=r"(v) : "l"(p) : "memory"); return v;
}
__device__ __forceinline__ void st_pub(void* p, uint32_t v) {
  asm volatile("st.relaxed.gpu.global.u32 [%0], %1;" :: "l"(p), "r"(v) : "memory");
}
__device__ __forceinline__ uint32_t lds32(uint32_t a) {
  uint32_t v; asm volatile("ld.shared.u32 %0, [%1];" : "=r"(v) : "r"(a) : "memory"); return v;
}
__device__ __forceinline__ int race_init(void* p0, void* p1, uint32_t val) {
  int t;
  asm volatile("{ .reg .pred r; .reg .u32 a, b, u, v;\n"
               "atom.relaxed.gpu.global.exch.b32 u, [%1], %3; atom.relaxed.gpu.global.exch.b32 v, [%2], %3;\n"
               "setp.eq.u32 r, u, 0x12345; @r pmevent 1; mov.u32 a, %%clock;\n"
               "setp.eq.u32 r, v, 0x12345; @r pmevent 1; mov.u32 b, %%clock; sub.u32 %0, b, a; }" : "=r"(t) : "l"(p0), "l"(p1), "r"(val) : "memory");
  return t;
}
__device__ __forceinline__ void race_init2(void* p0, void* p1, uint32_t val) {
  asm volatile("{ .reg .pred r; .reg .u32 a, b, u, v;\n"
               "atom.relaxed.gpu.global.exch.b32 u, [%0], %2; atom.relaxed.gpu.global.exch.b32 v, [%1], %2;\n"
               "atom.relaxed.gpu.global.exch.b32 a, [%0 + 4096], %2; atom.relaxed.gpu.global.exch.b32 b, [%1 + 4096], %2;\n"
               "lop3.b32 u, u, v, a, 0x96; setp.eq.u32 r, u, 0x12345; setp.eq.and.u32 r, b, u, r; @r pmevent 1; }" :: "l"(p0), "l"(p1), "r"(val) : "memory");
}
__device__ __forceinline__ uint4 lds128(uint32_t a) {
  uint4 v; asm volatile("ld.shared.v4.u32 {%0,%1,%2,%3}, [%4];" : "=r"(v.x), "=r"(v.y), "=r"(v.z), "=r"(v.w) : "r"(a) : "memory"); return v;
}
__device__ __forceinline__ uint2 lds64(uint32_t a) {
  uint2 v; asm volatile("ld.shared.v2.u32 {%0,%1}, [%2];" : "=r"(v.x), "=r"(v.y) : "r"(a) : "memory"); return v;
}
__device__ __forceinline__ void sts128(uint32_t a, uint4 v) {
  asm volatile("st.shared.v4.u32 [%0], {%1,%2,%3,%4};" :: "r"(a), "r"(v.x), "r"(v.y), "r"(v.z), "r"(v.w) : "memory");
}
__device__ __forceinline__ void sts64(uint32_t a, uint32_t x, uint32_t y) { asm volatile("st.shared.v2.u32 [%0], {%1,%2};" :: "r"(a), "r"(x), "r"(y) : "memory"); }
__device__ __forceinline__ void sts32(uint32_t a, uint32_t x) { asm volatile("st.shared.u32 [%0], %1;" :: "r"(a), "r"(x) : "memory"); }
__device__ __forceinline__ void ldsm4t(uint32_t (&r)[4], uint32_t a) {
  asm volatile("ldmatrix.sync.aligned.m8n8.x4.trans.shared.b16 {%0,%1,%2,%3}, [%4];"
               : "=r"(r[0]), "=r"(r[1]), "=r"(r[2]), "=r"(r[3]) : "r"(a) : "memory");
}
__device__ __forceinline__ void ldsm4(uint32_t (&r)[4], uint32_t a) {
  asm volatile("ldmatrix.sync.aligned.m8n8.x4.shared.b16 {%0,%1,%2,%3}, [%4];"
               : "=r"(r[0]), "=r"(r[1]), "=r"(r[2]), "=r"(r[3]) : "r"(a) : "memory");
}
template<bool TRANS> __device__ __forceinline__ void stsm4(uint32_t a, uint32_t r0, uint32_t r1, uint32_t r2, uint32_t r3) {
  if (TRANS) asm volatile("stmatrix.sync.aligned.m8n8.x4.trans.shared.b16 [%0], {%1,%2,%3,%4};" :: "r"(a), "r"(r0), "r"(r1), "r"(r2), "r"(r3) : "memory");
  else       asm volatile("stmatrix.sync.aligned.m8n8.x4.shared.b16 [%0], {%1,%2,%3,%4};" :: "r"(a), "r"(r0), "r"(r1), "r"(r2), "r"(r3) : "memory");
}
__device__ __forceinline__ void mma16816(float (&d)[4], uint32_t a0, uint32_t a1, uint32_t a2, uint32_t a3, uint32_t b0, uint32_t b1) {
  asm volatile("mma.sync.aligned.m16n8k16.row.col.f32.bf16.bf16.f32 {%0,%1,%2,%3}, {%4,%5,%6,%7}, {%8,%9}, {%0,%1,%2,%3};"
               : "+f"(d[0]), "+f"(d[1]), "+f"(d[2]), "+f"(d[3]) : "r"(a0), "r"(a1), "r"(a2), "r"(a3), "r"(b0), "r"(b1));
}
__device__ __forceinline__ void mma1688(float (&d)[4], uint32_t a0, uint32_t a1, uint32_t b0) {
  asm volatile("mma.sync.aligned.m16n8k8.row.col.f32.bf16.bf16.f32 {%0,%1,%2,%3}, {%4,%5}, {%6}, {%0,%1,%2,%3};"
               : "+f"(d[0]), "+f"(d[1]), "+f"(d[2]), "+f"(d[3]) : "r"(a0), "r"(a1), "r"(b0));
}
__device__ __forceinline__ uint32_t pack_bf16(float lo, float hi) {
  uint32_t r; asm("cvt.rn.bf16x2.f32 %0, %1, %2;" : "=r"(r) : "f"(hi), "f"(lo)); return r;
}
__device__ __forceinline__ uint32_t add_bf16x2(uint32_t a, uint32_t b) {
  uint32_t r; asm("add.rn.bf16x2 %0, %1, %2;" : "=r"(r) : "r"(a), "r"(b)); return r;
}
__device__ __forceinline__ uint32_t umax4(uint4 v) { return max(max(v.x, v.y), max(v.z, v.w)); }
__device__ __forceinline__ uint32_t opaque(uint32_t x) { uint32_t r; asm volatile("mov.u32 %0, %1;" : "=r"(r) : "r"(x)); return r; }
template<class T> __device__ __forceinline__ void pin(T*& p) { asm volatile("" : "+l"(p)); }
__device__ __forceinline__ void pin(uint32_t& v) { asm volatile("" : "+r"(v)); }
__device__ __forceinline__ uint32_t desc_lo(uint32_t addr) { return ((addr & 0x3FFFF) >> 4) | 0x10000; }
__device__ __forceinline__ uint64_t desc128(uint32_t lo) {
  uint64_t d; asm("mov.b64 %0, {%1, %2};" : "=l"(d) : "r"(lo), "r"(0x40000040)); return d;
}
#define WG_FENCE()  asm volatile("wgmma.fence.sync.aligned;" ::: "memory")
#define WG_COMMIT() asm volatile("wgmma.commit_group.sync.aligned;" ::: "memory")
#define WG_WAIT(n)  asm volatile("wgmma.wait_group.sync.aligned " #n ";" ::: "memory")
#define FENCE_ASYNC_SMEM() asm volatile("fence.proxy.async.shared::cta;" ::: "memory")
__device__ __forceinline__ void bar_sync(int id, int n) { asm volatile("bar.sync %0, %1;" :: "r"(id), "r"(n) : "memory"); }

#define D16(c) c(d[0]), c(d[1]), c(d[2]), c(d[3]), c(d[4]), c(d[5]), c(d[6]), c(d[7]), \
               c(d[8]), c(d[9]), c(d[10]), c(d[11]), c(d[12]), c(d[13]), c(d[14]), c(d[15])
template<bool FIRST> __device__ __forceinline__ void wgmma_rs_n32(float (&d)[16], const uint32_t (&a)[4], uint64_t b) {
  if (FIRST)
    asm volatile("wgmma.mma_async.sync.aligned.m64n32k16.f32.bf16.bf16 {%0,%1,%2,%3,%4,%5,%6,%7,%8,%9,%10,%11,%12,%13,%14,%15}, {%16,%17,%18,%19}, %20, 0, 1, 1, 0;"
      : D16("=f") : "r"(a[0]), "r"(a[1]), "r"(a[2]), "r"(a[3]), "l"(b));
  else
    asm volatile("wgmma.mma_async.sync.aligned.m64n32k16.f32.bf16.bf16 {%0,%1,%2,%3,%4,%5,%6,%7,%8,%9,%10,%11,%12,%13,%14,%15}, {%16,%17,%18,%19}, %20, 1, 1, 1, 0;"
      : D16("+f") : "r"(a[0]), "r"(a[1]), "r"(a[2]), "r"(a[3]), "l"(b));
}
template<bool FIRST> __device__ __forceinline__ void wgmma_ss_n32_ta(float (&d)[16], uint64_t a, uint64_t b) {
  if (FIRST)
    asm volatile("wgmma.mma_async.sync.aligned.m64n32k16.f32.bf16.bf16 {%0,%1,%2,%3,%4,%5,%6,%7,%8,%9,%10,%11,%12,%13,%14,%15}, %16, %17, 0, 1, 1, 1, 0;"
      : D16("=f") : "l"(a), "l"(b));
  else
    asm volatile("wgmma.mma_async.sync.aligned.m64n32k16.f32.bf16.bf16 {%0,%1,%2,%3,%4,%5,%6,%7,%8,%9,%10,%11,%12,%13,%14,%15}, %16, %17, 1, 1, 1, 1, 0;"
      : D16("+f") : "l"(a), "l"(b));
}
__device__ __forceinline__ void wgmma_ss_n128_tb(float (&d)[64], uint64_t a, uint64_t b) {
  asm volatile("wgmma.mma_async.sync.aligned.m64n128k16.f32.bf16.bf16 "
    "{%0,%1,%2,%3,%4,%5,%6,%7,%8,%9,%10,%11,%12,%13,%14,%15,%16,%17,%18,%19,%20,%21,%22,%23,%24,%25,%26,%27,%28,%29,%30,%31,"
    "%32,%33,%34,%35,%36,%37,%38,%39,%40,%41,%42,%43,%44,%45,%46,%47,%48,%49,%50,%51,%52,%53,%54,%55,%56,%57,%58,%59,%60,%61,%62,%63}, "
    "%64, %65, 1, 1, 1, 0, 1;"
    : "+f"(d[0]), "+f"(d[1]), "+f"(d[2]), "+f"(d[3]), "+f"(d[4]), "+f"(d[5]), "+f"(d[6]), "+f"(d[7]),
      "+f"(d[8]), "+f"(d[9]), "+f"(d[10]), "+f"(d[11]), "+f"(d[12]), "+f"(d[13]), "+f"(d[14]), "+f"(d[15]),
      "+f"(d[16]), "+f"(d[17]), "+f"(d[18]), "+f"(d[19]), "+f"(d[20]), "+f"(d[21]), "+f"(d[22]), "+f"(d[23]),
      "+f"(d[24]), "+f"(d[25]), "+f"(d[26]), "+f"(d[27]), "+f"(d[28]), "+f"(d[29]), "+f"(d[30]), "+f"(d[31]),
      "+f"(d[32]), "+f"(d[33]), "+f"(d[34]), "+f"(d[35]), "+f"(d[36]), "+f"(d[37]), "+f"(d[38]), "+f"(d[39]),
      "+f"(d[40]), "+f"(d[41]), "+f"(d[42]), "+f"(d[43]), "+f"(d[44]), "+f"(d[45]), "+f"(d[46]), "+f"(d[47]),
      "+f"(d[48]), "+f"(d[49]), "+f"(d[50]), "+f"(d[51]), "+f"(d[52]), "+f"(d[53]), "+f"(d[54]), "+f"(d[55]),
      "+f"(d[56]), "+f"(d[57]), "+f"(d[58]), "+f"(d[59]), "+f"(d[60]), "+f"(d[61]), "+f"(d[62]), "+f"(d[63])
    : "l"(a), "l"(b));
}

__device__ __forceinline__ void tma2d_mc_e(uint32_t dst, const CUtensorMap* tm, int c0, int c1, uint32_t bar) {
  asm volatile("{ .reg .pred p; elect.sync _|p, 0xffffffff;\n"
               "@p cp.async.bulk.tensor.2d.shared::cluster.global.mbarrier::complete_tx::bytes.multicast::cluster [%0], [%1, {%3, %4}], [%2], %5; }"
               :: "r"(dst), "l"(tm), "r"(bar), "r"(c0), "r"(c1), "h"((uint16_t)3) : "memory");
}

__device__ __forceinline__ void count_e(uint32_t* p) {
  asm volatile("fence.acq_rel.gpu;" ::: "memory");
  __syncwarp();
  asm volatile("{ .reg .pred p; elect.sync _|p, 0xffffffff; @p red.relaxed.gpu.global.add.u32 [%0], 1; }" :: "l"(p) : "memory");
}
__device__ __forceinline__ void await_count(const uint32_t* p, uint32_t n) {
  for (uint32_t i = 0; ld_acquire(p) < n && i < (1u << 22); i++) {}
  asm volatile("fence.proxy.async.global;" ::: "memory");
}
__device__ __forceinline__ void await_flags(const uint32_t* p) {
  for (uint32_t i = 0; i < (1u << 22); i++) {
    uint4 v;
    asm volatile("ld.acquire.gpu.global.v4.u32 {%0,%1,%2,%3}, [%4];" : "=r"(v.x), "=r"(v.y), "=r"(v.z), "=r"(v.w) : "l"(p) : "memory");
    if (__all_sync(~0u, (v.x & v.y & v.z & v.w) == 0x01010101u)) break;
  }
  asm volatile("fence.proxy.async.global;" ::: "memory");
}
__device__ __forceinline__ void mbar_lim(uint32_t bar, uint32_t ph) { for (uint32_t i = 0; !mbar_try(bar, ph) && i < (1u << 20); i++) {} }

struct cf { float x, y; };
__host__ __device__ constexpr float cos64(int k) {
  return k == 0 ? 1.0f : k == 1 ? 0.99518472667219689f : k == 2 ? 0.98078528040323045f : k == 3 ? 0.95694033573220887f :
         k == 4 ? 0.92387953251128676f : k == 5 ? 0.88192126434835503f : k == 6 ? 0.83146961230254524f : k == 7 ? 0.77301045336273696f :
         k == 8 ? 0.70710678118654752f : k == 9 ? 0.63439328416364550f : k == 10 ? 0.55557023301960222f : k == 11 ? 0.47139673682599765f :
         k == 12 ? 0.38268343236508977f : k == 13 ? 0.29028467725446236f : k == 14 ? 0.19509032201612827f : k == 15 ? 0.09801714032956060f : 0.0f;
}
__host__ __device__ constexpr float c64(int k) { return k <= 16 ? cos64(k) : -cos64(32 - k); }
__host__ __device__ constexpr float s64(int k) { return k <= 16 ? cos64(16 - k) : cos64(k - 16); }

template<int N, int ST, bool INV> struct Fft {
  template<int K> static __device__ __forceinline__ void bf(const cf* e, const cf* o, cf* out) {
    if constexpr (K < N / 2) {
      constexpr int idx = K * (64 / N);
      const cf a = e[K], b = o[K];
      if constexpr (idx == 0) {
        out[K] = {a.x + b.x, a.y + b.y}; out[K + N / 2] = {a.x - b.x, a.y - b.y};
      } else if constexpr (idx == 16) {
        if constexpr (INV) { out[K] = {a.x - b.y, a.y + b.x}; out[K + N / 2] = {a.x + b.y, a.y - b.x}; }
        else               { out[K] = {a.x + b.y, a.y - b.x}; out[K + N / 2] = {a.x - b.y, a.y + b.x}; }
      } else {
        constexpr float c = c64(idx), s = INV ? s64(idx) : -s64(idx);
        cf p; p.x = fmaf(-s, b.y, fmaf(c, b.x, a.x)); p.y = fmaf(s, b.x, fmaf(c, b.y, a.y));
        out[K] = p; out[K + N / 2] = {fmaf(2.0f, a.x, -p.x), fmaf(2.0f, a.y, -p.y)};
      }
      bf<K + 1>(e, o, out);
    }
  }
  static __device__ __forceinline__ void run(const cf* in, cf* out) {
    cf e[N / 2], o[N / 2];
    Fft<N / 2, 2 * ST, INV>::run(in, e);
    Fft<N / 2, 2 * ST, INV>::run(in + ST, o);
    bf<0>(e, o, out);
  }
};
template<int ST, bool INV> struct Fft<1, ST, INV> {
  static __device__ __forceinline__ void run(const cf* in, cf* out) { out[0] = in[0]; }
};
template<bool INV> __device__ __forceinline__ void fft32(cf (&v)[32]) {
  cf o[32]; Fft<32, 1, INV>::run(v, o);
#pragma unroll
  for (int i = 0; i < 32; i++) v[i] = o[i];
}
__device__ __forceinline__ cf cmul(cf a, float c, float s) { return {fmaf(-a.y, s, a.x * c), fmaf(a.x, s, a.y * c)}; }
__device__ __forceinline__ float bf2f(__nv_bfloat16 v) { return __bfloat162float(v); }

template<bool INV> __device__ __forceinline__ void warp_fft1024_a(cf (&v)[32], float2* __restrict__ buf, const float2* __restrict__ tw, int t, int u) {
  fft32<INV>(v);
#pragma unroll
  for (int j = 1; j < 32; j++) { const float2 w = tw[j * 32 + t]; v[j] = cmul(v[j], w.x, INV ? -w.y : w.y); }
  if (INV) {
    float* f = (float*)buf;
#pragma unroll
    for (int j = 0; j < 32; j++) f[j * 33 + t] = v[j].x;
    __syncwarp();
#pragma unroll
    for (int j = 0; j < 32; j++) v[j].x = f[u * 33 + j];
    __syncwarp();
#pragma unroll
    for (int j = 0; j < 32; j++) f[j * 33 + t] = v[j].y;
    __syncwarp();
#pragma unroll
    for (int j = 0; j < 32; j++) v[j].y = f[u * 33 + j];
  } else {
#pragma unroll
    for (int j = 0; j < 32; j++) buf[j * 33 + t] = make_float2(v[j].x, v[j].y);
    __syncwarp();
#pragma unroll
    for (int j = 0; j < 32; j++) { const float2 r = buf[u * 33 + j]; v[j] = {r.x, r.y}; }
  }
  __syncwarp();
}
constexpr int ROW_BUF = 32 * 33;

__device__ __forceinline__ int z_row(int p) { return (p & ~31) | (p & 7) << 2 | (p & 31) >> 3; }
template<bool PERM> __device__ __forceinline__ void row_twiddles(float2* tw, int tid, int nthreads) {
  for (int i = tid; i < 1024; i += nthreads) {
    float s, c; sincospif(-(float)((i >> 5) * ((PERM ? z_row(i) : i) & 31)) * (1.0f / 512.0f), &s, &c); tw[i] = make_float2(c, s);
  }
}
template<class F> __device__ __forceinline__ void fft_rows_fwd(float2* sm2, const __nv_bfloat16* gw, int cta, int tid, uint32_t full_bar, uint32_t release_bar, F ev) {
  const int t = tid & 31, w = tid >> 5, n = z_row(cta * 8 + w);
  row_twiddles<false>(sm2, tid, 256);
  ev(5);
  mbar_spin(full_bar, 0);
  if (tid == 0) TL2(6);
  __syncwarp();
  const __nv_bfloat16* xa = (const __nv_bfloat16*)(sm2 + 1024 + w * ROW_BUF) + t;
  cf v[32];
  float ga = 0.f, gb = 0.f;
#pragma unroll
  for (int j = 0; j < 32; j++) {
    v[j] = {bf2f(xa[32 * j]), bf2f(xa[D_ + 32 * j])};
    const float g = bf2f(gw[32 * j + t]); ga = fmaf(v[j].x, g, ga); gb = fmaf(v[j].y, g, gb);
  }
#pragma unroll
  for (int o = 16; o; o >>= 1) { ga += __shfl_xor_sync(~0u, ga, o); gb += __shfl_xor_sync(~0u, gb, o); }
  if (t < 2) g_gate[n + 1024 * t] = __fdividef(1.0f, 1.0f + __expf(-(t ? gb : ga)));
  ev(6);
  bar_sync(13, 256);
  warp_fft1024_a<false>(v, sm2 + 1024 + w * ROW_BUF, sm2, t, t);
  FENCE_ASYNC_SMEM();
  mbar_arrive_warp(release_bar);
  fft32<false>(v);
  float ws, wc; sincospif(-(float)n * (1.0f / 1024.0f), &ws, &wc);
  ev(12);
  uint32_t tz = clock_lo();
  float4* z = (float4*)g_z + ((size_t)(t >> 1) * 1024 + cta * 8 + w) * 2 + (t & 1);
#pragma unroll
  for (int j = 0; j < 17; j++) {
    cf q = v[(32 - j) & 31];
    if (j < 16) {
      const cf r = {__shfl_sync(~0u, v[31 - j].x, 32 - t), __shfl_sync(~0u, v[31 - j].y, 32 - t)};
      if (t != 0) q = r;
    }
    const cf a = {v[j].x + q.x, v[j].y - q.y}, b = {v[j].y + q.y, q.x - v[j].x};
    const cf d = cmul({a.x - b.x, a.y - b.y}, wc, ws);
    if (PACE_Z && j && j < 16) delay_until(tz += PACE_Z);
    if ((j < 16 || t == 0) && ((EXP_ST & 4) || d.x == 123.f)) z[j * 32768] = make_float4(a.x + b.x, a.y + b.y, d.x, d.y);
  }
}
constexpr int COL_FS = 1057, COL_W = (8192 + 16 * COL_FS * 4 + 127) & ~127, COL_SMEM = COL_W + 131072 + 16;

__device__ __forceinline__ void fft_cols(float2* sm2, int cta, const CUtensorMap* twr, const CUtensorMap* twi) {
  const int grp = __shfl_sync(~0u, (int)(threadIdx.x >> 7), 0), tid = threadIdx.x & 127, tp = tid >> 2, t = z_row(tp);
  float* buf = (float*)(sm2 + 1024) + (grp * 4 + (tid & 3)) * COL_FS;
  const uint32_t wsm = smem_u32(sm2) + COL_W, wbar = wsm + 131072;
  const int res = (tid >> 5) * 2 + (tid & 1), el = res + grp * 2 + ((tid >> 1) & 1);
  uint32_t wa = (el >> 3) * 65536 + res * 4096 + (tp & 7) * 16 + (el & 7) * 2;
  auto load_w = [&](int q) { for (int i = 0; i < 16; i++) tma2d(wsm + (q & 1) * 65536 + i * 4096, i < 8 ? twr : twi, (i & 7) * 512 + q * 8, 0, wbar); };
  if (threadIdx.x == 0) { mbar_init(wbar, 1); sts32(wbar + 8, 0); asm volatile("fence.mbarrier_init.release.cluster;" ::: "memory"); }
  row_twiddles<true>(sm2, threadIdx.x, 512);
  if (cta < 2) row_twiddles<false>(g_tw, cta * 512 + threadIdx.x, 1024);
  for (uint32_t n = 0; ld_acquire(g_ctl + C_P1) < 128; ) { watchdog(n, 1u << 22); __nanosleep(200); }
  __syncthreads();
  if (threadIdx.x == 0) { mbar_expect(wbar, 131072); load_w(cta * 16); load_w(cta * 16 + 1); }
  __syncwarp();
  delay_cycles(1 + grp * DLY_GRP);
  const int end = cta * 64 + 64 + (cta == 3);
  for (int item = cta * 64 + grp; item < end; item += 4, wa ^= 65536) {
    float2* zp = g_z + (size_t)item * 4096;
    cf v[32];
#pragma unroll
    for (int j = 0; j < 32; j++) { const float2 a = __ldcg(zp + tid + j * 128); v[j] = {a.x, a.y}; }
#pragma unroll 1
    for (int dir = 0; dir < 2; dir++) {
      fft32<false>(v);
#pragma unroll
      for (int j = 1; j < 32; j++) { const float2 w = sm2[j * 32 + tp]; v[j] = cmul(v[j], w.x, w.y); }
      bar_sync(1 + grp, 128);
      if (dir == 1 && tid == 0) {
        uint32_t n; asm volatile("atom.shared.inc.u32 %0, [%1], 3;" : "=r"(n) : "r"(wbar + 8) : "memory");
        if (n == 3 && item - grp + 4 < end) { mbar_expect(wbar, 65536); load_w((item >> 2) + 2); }
      }
      __syncwarp();
#pragma unroll
      for (int j = 0; j < 32; j++) buf[j * 33 + t] = v[j].x;
      bar_sync(1 + grp, 128);
#pragma unroll
      for (int j = 0; j < 32; j++) v[j].x = buf[t * 33 + j];
      bar_sync(1 + grp, 128);
#pragma unroll
      for (int j = 0; j < 32; j++) buf[j * 33 + t] = v[j].y;
      bar_sync(1 + grp, 128);
#pragma unroll
      for (int j = 0; j < 32; j++) v[j].y = buf[t * 33 + j];
      fft32<false>(v);
      if (dir == 0) {
        mbar_wait(wbar, (item >> 2) & 1);
#pragma unroll
        for (int j = 0; j < 32; j++) {
          uint32_t re, im;
          asm volatile("ld.shared.u16 %0, [%1];" : "=r"(re) : "r"(wsm + wa + j * 128) : "memory");
          asm volatile("ld.shared.u16 %0, [%1];" : "=r"(im) : "r"(wsm + wa + 32768 + j * 128) : "memory");
          const cf r = cmul(v[j], __uint_as_float(re << 16), __uint_as_float(im << 16));
          v[j] = {r.y, r.x};
        }
      }
    }
#pragma unroll
    for (int j = 0; j < 32; j++) zp[tid + j * 128] = make_float2(v[j].y, v[j].x);
  }
  __syncthreads();
  if (threadIdx.x < 32) {
    count_e(g_ctl + C_COLS);
    await_count(g_ctl + C_COLS, 4);
    g_ctl[C_P1] = 0;
  }
  __syncthreads();
  ((float4*)sm2)[threadIdx.x] = __ldcg((const float4*)g_tw + threadIdx.x);
  __syncthreads();
}

template<class F> __device__ __forceinline__ void fft_rows_inv(uint32_t zs, float2* buf, const float2* tw, int p, int lane, __nv_bfloat16* out, F read) {
  const int n = z_row(p), t = (lane & 17) | (lane & 6) << 1 | (lane & 8) >> 2, tm = -t & 31, src = (tm & 17) | (tm & 12) >> 1 | (tm & 2) << 2;
  const uint32_t z = zs + (t >> 1) * 128 + ((((p & 3) * 2 + (t & 1)) ^ (t >> 1 & 7)) << 4);
  FT(0, 0.f);
  float4 e[17];
  uint32_t all = 0;
  e[16] = __ldcg((const float4*)g_z + ((size_t)256 * 1024 + p) * 2);
  const float g0 = __ldcg(g_gate + n), g1 = __ldcg(g_gate + n + 1024);
#pragma unroll
  for (int j = 0; j < 16; j++) { const uint4 u = lds128(z + j * 2048); e[j] = make_float4(__uint_as_float(u.x), __uint_as_float(u.y), __uint_as_float(u.z), __uint_as_float(u.w)); all |= u.x; }
  sched_fence(all);
  read();
  float ws, wc; sincospif((float)n * (1.0f / 1024.0f), &ws, &wc);
  cf v[32], q[17];
#pragma unroll
  for (int j = 0; j < 17; j++) {
    const cf d = cmul({e[j].z, e[j].w}, wc, ws);
    cf a = {e[j].x + d.x, e[j].y + d.y}, b = {e[j].x - d.x, e[j].y - d.y};
    if (j == 16 || (j == 0 && t == 0)) { a.y = 0.f; b.y = 0.f; }
    if (j < 16) v[j] = {a.x - b.y, a.y + b.x};
    q[j] = {a.x + b.y, b.x - a.y};
  }
#pragma unroll
  for (int j = 16; j < 32; j++) {
    v[j] = {__shfl_sync(~0u, q[31 - j].x, src), __shfl_sync(~0u, q[31 - j].y, src)};
    if (t == 0) v[j] = q[32 - j];
  }
  FT(1, v[0].x + v[16].x + v[31].x);
  warp_fft1024_a<true>(v, buf, tw, t, lane);
  FT(2, v[31].y);
  fft32<true>(v);
  FT(3, v[31].y + v[0].x);
  const float sc = 0.5f / (2048.0f * 1024.0f), s0 = (1.f - g0) * sc, s1 = (1.f - g1) * sc;
  __nv_bfloat16* o = out + (size_t)n * D_ + lane;
#pragma unroll
  for (int j = 0; j < 32; j++) { o[32 * j] = __float2bfloat16(v[j].x * s0); o[1024 * D_ + 32 * j] = __float2bfloat16(v[j].y * s1); }
  FT(4, 0.f);
}

constexpr int NP = NP_, NHV = REG_F == 216 ? 5 : 7, NV = 16 - NHV;
constexpr int XEND = NSEG;
constexpr uint32_t SM_WO = 0, SM_V = 65536, SM_LAND = SM_V + 8192, SM_MEM = SM_LAND + 24576, SM_SP = SM_MEM, SM_SPM = SM_MEM + 5120, SM_OM = SM_MEM + 6144,
                   SM_OX = SM_MEM + 8192, SM_RED = SM_OX + 2048, SM_XCH = SM_RED + 1024, SM_SUM = SM_XCH + 4096, SM_VM = SM_SUM + 128, SM_TAB = SM_VM + 2048, SM_TRACE = SM_TAB + 2048,
                   ST_WG = (32 - NP + NV) * 2048,
                   SM_XT = 2 * ST_WG, SM_POOL = SM_XT + 32768, SM_HV = SM_POOL + 2 * NP * 2048,
                   SM_BAR = SM_HV + 2 * NHV * 2048, SM_SEL = SM_BAR + 320, CHAIN_SMEM = SM_SEL + 544 + 1024;
constexpr uint32_t SM_GW = 74 * 1024;
static_assert(NP % 4 == 0 && NV == 11 && SM_TRACE + 4096 <= SM_XT, "shared memory layout");
static_assert(CHAIN_SMEM <= 232448 && COL_SMEM <= CHAIN_SMEM && (1024 + 8 * ROW_BUF) * 8 <= SM_GW && SM_GW + 2048 > ST_WG, "shared memory budget");
enum { B_WFULL = 0, B_WREAD = 2, B_WOFULL, B_XFULL, B_XEMPTY, B_E1TRIG, B_E2TRIG, B_PVDONE, B_PUB, B_SC, B_MEM, B_SPFREE,
       B_LAND, B_LFREE, B_DONE, B_SEL, B_PROBE, B_FREE, B_P1, B_ROWS, B_VFULL, B_VST, B_TW, B_BT, B_Z, B_GFULL = B_Z + 4, B_GEMPTY = B_GFULL + 5, B_END = B_GEMPTY + 5 };
static_assert(B_END * 8 <= 320, "barriers");
__host__ __device__ constexpr uint32_t bar_codes(int g) {
  uint32_t r = 0;
  for (int i = 16 * g; i < 16 * g + 16; i++)
    r |= (i == B_LAND ? 3u : i == B_WREAD || i == B_XEMPTY || i == B_E1TRIG || i == B_E2TRIG || i == B_LFREE || i == B_FREE || i == B_VST || i == B_P1 || i == B_ROWS ? 2u :
          i >= B_GEMPTY || i == B_PROBE || i == B_DONE || i == B_PVDONE || i == B_PUB || i == B_SC || i == B_MEM || i == B_SPFREE ? 1u : 0u) << 2 * (i & 15);
  return r;
}
constexpr uint32_t SM_BT = 65536, SM_TW = SM_XT - 8192, COL_Z = 75 * 1024;
static_assert(SM_XT + 3 * 32768 <= SM_BAR && SM_BT + 32768 <= SM_MEM && SM_TRACE <= SM_TW && SM_MEM + 4 * ROW_BUF * 4 <= SM_TAB &&
              8192 + 16 * ROW_BUF * 4 <= COL_Z && COL_Z + 131072 <= SM_BAR, "shared memory layout");
__device__ __forceinline__ uint32_t next_stage(uint32_t o) { return o == SM_XT + 65536 ? 0 : o == 32768 ? SM_XT : o + 32768; }

struct ChainCtx { char* mail; uint32_t sb, sel; int r, h, a, b, j, m, w, lane; };
#define BAR(i) (c.sb + SM_BAR + 8 * (i))

__device__ __forceinline__ uint32_t tile_off(int line, int lane) {
  return line * 128 + (((lane & 3) ^ line) << 5) + (lane >> 2) * 4;
}
__device__ __forceinline__ uint32_t read_off(int lane) {
  const int n = lane >> 2, jj = lane & 3, l = 2 * (jj >> 1) + (n & 1);
  return l * 128 + (((n >> 1) ^ l) << 5) + (jj & 1) * 16;
}
__device__ __forceinline__ uint32_t frag_off(int w, int lane) {
  const int mi = lane >> 3, r = lane & 7;
  return ((mi >> 1) * 8 + r) * 128 + (((2 * w + (mi & 1)) ^ r) << 4);
}
__device__ __forceinline__ uint32_t land_off(int w, int lane) { return w * 512 + ((lane ^ (((lane >> 4) | ((w & 1) << 1)) << 1)) << 4); }
__device__ __forceinline__ uint32_t tagged(uint32_t v, uint32_t tag) { return (v | 1u) ^ tag; }
__device__ __forceinline__ void mma_a(float (&d)[4], const uint32_t (&a)[4], uint32_t b0, uint32_t b1) { mma16816(d, a[0], a[1], a[2], a[3], b0, b1); }
__device__ __forceinline__ void mma_q(float (&d)[4], const uint4& a, uint32_t b0, uint32_t b1) { mma16816(d, a.x, a.y, a.z, a.w, b0, b1); }
__device__ __forceinline__ uint4 add4(uint4 a, uint4 b) {
  return make_uint4(add_bf16x2(a.x, b.x), add_bf16x2(a.y, b.y), add_bf16x2(a.z, b.z), add_bf16x2(a.w, b.w));
}
__device__ __forceinline__ void mbar_arrive_both(uint32_t bar, int peer) {
  __syncwarp();
  asm volatile("{ .reg .pred p; .reg .u32 a; mapa.shared::cluster.u32 a, %0, %1; elect.sync _|p, 0xffffffff;\n"
               "@p mbarrier.arrive.shared::cta.b64 _, [%0]; @p mbarrier.arrive.shared::cluster.b64 _, [a]; }" :: "r"(bar), "r"(peer) : "memory");
}

__device__ __forceinline__ void arrive_remote_if(uint32_t a, bool on) {
  asm volatile("{ .reg .pred p; setp.ne.u32 p, %1, 0; @p mbarrier.arrive.shared::cluster.b64 _, [%0]; }" :: "r"(a), "r"((uint32_t)on) : "memory");
}
__device__ __forceinline__ void store_count(void* p, uint4 v, void* cnt) {
  asm volatile("{ .reg .pred p, q; .reg .b128 a, b; .reg .b64 l, h; mov.b64 l, {%1, %2}; mov.b64 h, {%3, %4}; mov.b128 a, {l, h};\n"
               "atom.relaxed.gpu.global.exch.b128 b, [%0], a; mov.b128 {l, h}, b; setp.eq.u64 q, l, 0x7fc17fc17fc17fc1; @q pmevent 1;\n"
               "elect.sync _|p, 0xffffffff; @p red.relaxed.gpu.global.add.u32 [%5], 1; }"
               :: "l"(p), "r"(v.x), "r"(v.y), "r"(v.z), "r"(v.w), "l"(cnt) : "memory");
}

__device__ __forceinline__ int lane_id() {
  int l; asm volatile("{ .reg .u32 t; mov.u32 t, %%laneid; shfl.sync.idx.b32 %0, t, t, 31, 0xffffffff; }" : "=r"(l)); return l;
}
__device__ __forceinline__ uint32_t tid_now() { uint32_t t; asm volatile("mov.u32 %0, %%tid.x;" : "=r"(t)); return t; }
enum { NB_ATT = 1, NB_OM = 2, NB_VM = 3, NB_XCH = 4, NB_MEM = 8, NB_HELP = 12 };
__device__ __forceinline__ uint32_t dep(uint32_t a, uint32_t v, uint32_t z) { uint32_t r; asm("shf.l.wrap.b32 %0, %2, %1, %3;" : "=r"(r) : "r"(a), "r"(v), "r"(z)); return r; }
__device__ __forceinline__ uint32_t vary(uint32_t a, int s, uint32_t z) { return dep(a, 0, z + 32 * s); }
__device__ __forceinline__ char* mk_ptr(uint32_t lo, uint32_t hi) { uint64_t r; asm("mov.b64 %0, {%1, %2};" : "=l"(r) : "r"(lo), "r"(hi)); return (char*)r; }
__device__ __forceinline__ void lds_frag(uint32_t (&r)[4], uint32_t a) {
  asm volatile("ld.shared.v4.u32 {%0,%1,%2,%3}, [%4];" : "=r"(r[0]), "=r"(r[1]), "=r"(r[2]), "=r"(r[3]) : "r"(a) : "memory");
}
__device__ __forceinline__ uint32_t stale2(uint32_t a, uint32_t b, uint32_t t) { uint32_t r; asm("lop3.b32 %0, %1, %2, %3, 0xbd;" : "=r"(r) : "r"(a), "r"(b), "r"(t)); return r; }
__device__ __forceinline__ uint32_t stale1(uint32_t acc, uint32_t a, uint32_t t) { uint32_t r; asm("lop3.b32 %0, %1, %2, %3, 0xf9;" : "=r"(r) : "r"(acc), "r"(a), "r"(t)); return r; }
__device__ __forceinline__ bool all_clear(uint32_t x, uint32_t m) {
  uint32_t r;
  asm volatile("{ .reg .pred p; .reg .u32 t; and.b32 t, %1, %2; setp.eq.u32 p, t, 0; vote.sync.all.pred p, p, 0xffffffff; selp.u32 %0, 1, 0, p; }" : "=r"(r) : "r"(x), "r"(m));
  return r;
}
__device__ __forceinline__ bool arrive_if_all(bool ok, int id, int n) {
  uint32_t r;
  asm volatile("{ .reg .pred p, q; setp.ne.u32 p, %1, 0; vote.sync.all.pred q, p, 0xffffffff; @q bar.arrive %2, %3; selp.u32 %0, 1, 0, q; }"
               : "=r"(r) : "r"((uint32_t)ok), "r"(id), "r"(n) : "memory");
  return r;
}
__device__ __forceinline__ bool arrive_if_clear(uint32_t x, uint32_t m, int id, int n) {
  uint32_t r;
  asm volatile("{ .reg .pred p; .reg .u32 t; and.b32 t, %1, %2; setp.eq.u32 p, t, 0; vote.sync.all.pred p, p, 0xffffffff; @p bar.arrive %3, %4; selp.u32 %0, 1, 0, p; }"
               : "=r"(r) : "r"(x), "r"(m), "r"(id), "r"(n) : "memory");
  return r;
}
__device__ __forceinline__ void touch(const void* p, uint32_t z) {
  asm volatile("{ .reg .pred p; setp.eq.u32 p, %1, 0x7fff0000; @p prefetch.global.L2 [%0]; }" :: "l"(p), "r"(z) : "memory");
}

__device__ __forceinline__ uint64_t desc_x(uint32_t lo, int k) {
  uint64_t d; asm("mov.b64 %0, {%1, %2};" : "=l"(d) : "r"(lo + (k >> 2) * 64 + (k & 3) * 2), "r"(0x40000200)); return d;
}
template<int K0, int K1> __device__ __forceinline__ void issue_qk(float (&xa)[16], const uint32_t (&wt)[16][4], uint32_t lo) {
  WG_FENCE();
#pragma unroll
  for (int k = K0; k < K1; k++) {
    if (k >= EXP_NWG) continue;
    if (k == 0) wgmma_rs_n32<true>(xa, wt[0], desc_x(lo, 0));
    else wgmma_rs_n32<false>(xa, wt[k], desc_x(lo, k));
  }
  WG_COMMIT();
}
__host__ __device__ constexpr int v_order(int i) { return SSPOS == 0 ? i : SSPOS == 2 ? (i + NV) % 16 : NHV == 5 ? (i % 3 == 2 ? NV + i / 3 : i - i / 3) : (i == 15 ? NV - 1 : i % 2 ? NV + i / 2 : i / 2); }
__device__ __forceinline__ void issue_v(float (&xa)[16], const uint32_t (&wv)[16][4], uint32_t lo, uint32_t la) {
  WG_FENCE();
#pragma unroll
  for (int i = 0; i < EXP_NWG; i++) {
    const int k = v_order(i);
    const uint64_t b = desc_x(lo, k);
    if (k < NV) { if (i == 0) wgmma_rs_n32<true>(xa, wv[k], b); else wgmma_rs_n32<false>(xa, wv[k], b); }
    else        { if (i == 0) wgmma_ss_n32_ta<true>(xa, desc128(la + (k - NV) * 128), b); else wgmma_ss_n32_ta<false>(xa, desc128(la + (k - NV) * 128), b); }
  }
  WG_COMMIT();
}
template<bool ISV> __device__ __forceinline__ void park_own(uint32_t (&q)[4], float (&xa)[16], uint32_t dst, int slot, uint32_t z) {
  uint32_t p[8];
#pragma unroll
  for (int i = 0; i < 16; i++) asm volatile("" : "+f"(xa[i]) :: "memory");
#pragma unroll
  for (int i = 0; i < 2; i++) {
    const float* k = xa + 8 * i;
    if (ISV) { p[4 * i] = pack_bf16(k[0], k[1]); p[4 * i + 1] = pack_bf16(k[2], k[3]); p[4 * i + 2] = pack_bf16(k[4], k[5]); p[4 * i + 3] = pack_bf16(k[6], k[7]); }
    else     { p[4 * i] = pack_bf16(k[0], k[2]); p[4 * i + 1] = pack_bf16(k[1], k[3]); p[4 * i + 2] = pack_bf16(k[4], k[6]); p[4 * i + 3] = pack_bf16(k[5], k[7]); }
  }
  sts128(dep(dep(dst, p[4] ^ p[5] ^ p[6], z), p[7], z) + slot * 8192, make_uint4(p[0], p[1], p[2], p[3]));
#pragma unroll
  for (int i = 0; i < 4; i++) q[i] = p[4 + i];
}
__device__ __forceinline__ void park_peer(const uint32_t (&q)[4], uint32_t dst, int slot, const ChainCtx& c) {
  const uint32_t bar = BAR(B_LAND);
  if (EXP_PEER) st_async4(mapa(dst + slot * 8192, c.b ^ 1), q[0], q[1], q[2], q[3], mapa(bar, c.b ^ 1));
  else touch((void*)(uintptr_t)(q[0] ^ q[1] ^ q[2] ^ q[3]), c.sb);
  mbar_arrive_warp(bar);
}
__device__ __forceinline__ uint32_t put_tag(uint32_t v, uint32_t bit, uint32_t t) {
  uint32_t r; asm("lop3.b32 %0, %1, %2, %3, 0x74;" : "=r"(r) : "r"(v), "r"(bit), "r"(t)); return r;
}
__device__ __forceinline__ void mem_proj(const uint32_t (&wa)[16][4], const uint32_t (&wb)[16][4], uint32_t (&wv)[16][4], uint32_t (&af)[16][4],
                                         uint32_t& wo, const char*& pa, uint32_t tab, uint32_t t16, uint32_t pk, const ChainCtx& c, int s) {
  const uint32_t mp = t16 & ~0x600u, id = NB_MEM + (t16 >> 11);
  uint32_t r[8][4];
  float la[4][4] = {}, lg[NLAG][4] = {}, lv[4][4] = {};
  auto lead = [&](int k) { mma_a(la[k & 3], wa[k], r[k >> 1][2 * (k & 1)], r[k >> 1][2 * (k & 1) + 1]); };
  auto lag = [&](int k) { mma_a(lg[k % NLAG], wb[k], r[k >> 1][2 * (k & 1)], r[k >> 1][2 * (k & 1) + 1]); };
  auto sum = [](const float (&d)[4][4], int i) { return (d[0][i] + d[1][i]) + (d[2][i] + d[3][i]); };
  bar_sync(id, 160);
  TR(s, 0);
#pragma unroll
  for (int i = 0; i < 4; i++) ldsm4t(r[i], mp + (c.sb + SM_MEM + i * 512));
  const uint4 tq = lds128(tab);
  bar_sync(id + 2, 160);
#pragma unroll
  for (int k = 0; k < 8; k++) lead(k);
  const uint32_t ta = tq.x | ((pk >> 16) & 511), tb = tq.z ^ ((pk >> 16) & 511);
  char* dst = mk_ptr(ta, tq.y);
  char* dst2 = mk_ptr(tb, tq.w);
  const uint32_t mp1 = dep(mp, __float_as_uint(la[C1_AT][0]) ^ ta ^ tb, c.sb);
#pragma unroll
  for (int i = 4; i < 8; i++) ldsm4t(r[i], mp1 + (c.sb + SM_MEM + 2048 + i * 512));
  const uint32_t hv = pk & 0xFFFF;
#pragma unroll
  for (int k = NV; k < NV + HV_E; k++) ldsm4t(wv[k], dep(hv, r[HV_R][0], c.sb) + (c.sb + SM_HV + (k - NV) * 2048));
#pragma unroll
  for (int k = 0; k < 8; k++) lag(k);
#pragma unroll
  for (int k = 8; k < 16; k++) lead(k);
  sts128((HV_E ? dep(t16, wv[NV][0] ^ wv[NV + HV_E / 2][1] ^ wv[NV + HV_E - (HV_E > 0)][2], c.sb) : t16) + (c.sb + SM_XCH), make_uint4(__float_as_uint(sum(la, 0)), __float_as_uint(sum(la, 1)), __float_as_uint(sum(la, 2)), __float_as_uint(sum(la, 3))));
  bar_sync(NB_XCH | ((t16 >> 9) & 3), 64);
  const uint4 o = lds128((t16 ^ 2048) + (c.sb + SM_XCH));
#pragma unroll
  for (int k = 8; k < 16; k++) lag(k);
  float t[4];
#pragma unroll
  for (int i = 0; i < 4; i++) {
    const float oi = __uint_as_float(i == 0 ? o.x : i == 1 ? o.y : i == 2 ? o.z : o.w);
    t[i] = NLAG == 4 ? (((lg[0][i] + lg[1][i]) + lg[2 % NLAG][i]) + lg[3 % NLAG][i]) + oi : NLAG == 3 ? (lg[1][i] + lg[2 % NLAG][i]) + (lg[0][i] + oi) : (lg[0][i] + oi) + lg[1][i];
  }
  const uint32_t y0 = put_tag(pack_bf16(t[0], t[2]), pk >> 31, s >> 1), y1 = put_tag(pack_bf16(t[1], t[3]), pk >> 31, s >> 1);
  st_pub(dst, y0); st_pub(dst2, y1);
  mbar_arrive_warp(BAR(B_E1TRIG));
  TR(s, 1);
  sched_fence(c.sb);
  const uint4 tv = lds128(tab + 16);
#pragma unroll
  for (int k = NV + HV_E; k < 16; k++) ldsm4t(wv[k], (k < NV + HV_E + HV_D ? hv : dep(hv, k == NV + HV_E + HV_D ? wv[k - HV_D][0] ^ tv.x : wv[k - HV_D][0], c.sb)) + (c.sb + SM_HV + (k - NV) * 2048));
  wo = (hv & 2047) | ((t16 & 2048) << 3);
  const uint32_t l8 = (t16 >> 1) & 255;
  char* dv = mk_ptr(tv.x | l8, tv.y);
  pa = mk_ptr(tv.z | l8, tv.w);
#pragma unroll
  for (int f = 0; f < WO_0; f++) ldsm4t(af[f], dep(wo, f < WO_D ? wv[16 - WO_D + f][0] : af[f < WO_D ? 0 : f - WO_D][0], c.sb) + (c.sb + SM_WO + (f & 1) * 32768 + (f >> 1) * 2048));
#pragma unroll
  for (int k = 0; k < 16; k++) mma_a(lv[k & 3], wv[k], r[k >> 1][2 * (k & 1)], r[k >> 1][2 * (k & 1) + 1]);
  const uint32_t z0 = put_tag(pack_bf16(sum(lv, 0), sum(lv, 1)), (~t16 >> 4) & 1, s >> 1), z1 = pack_bf16(sum(lv, 2), sum(lv, 3));
  st_pub2(dv, z0, z1);
  if (FIN_AT >= 3) mbar_arrive_warp(BAR(B_VST));
  TR(s, 2);
}
__device__ __forceinline__ uint32_t max_bf16x2(uint32_t a, uint32_t b) { uint32_t r; asm("max.bf16x2 %0, %1, %2;" : "=r"(r) : "r"(a), "r"(b)); return r; }
constexpr float SCL = 0.08838834764831845f * 1.4426950408889634f;
__device__ __forceinline__ uint32_t max5(const uint32_t (&sc)[5]) { return max_bf16x2(max_bf16x2(max_bf16x2(max_bf16x2(sc[0], sc[1]), sc[2]), sc[3]), sc[4]); }
__device__ __forceinline__ float row_off(uint32_t m, uint32_t& m1) {
  m1 = __shfl_xor_sync(~0u, m, 1);
  const uint32_t m2 = __shfl_xor_sync(~0u, m, 2), m3 = __shfl_xor_sync(~0u, m, 3);
  const uint32_t mm = max_bf16x2(max_bf16x2(max_bf16x2(m, m1), m2), m3);
  return -SCL * fmaxf(__uint_as_float(mm << 16), __uint_as_float(mm & 0xFFFF0000u));
}
__device__ __forceinline__ void unpack(float (&f)[10], const uint32_t (&sc)[5]) {
#pragma unroll
  for (int i = 0; i < 5; i++) {
    asm volatile("shl.b32 %0, %1, 16;" : "=f"(f[2 * i]) : "r"(sc[i]));
    asm volatile("and.b32 %0, %1, 0xffff0000;" : "=f"(f[2 * i + 1]) : "r"(sc[i]));
  }
}
__device__ __forceinline__ uint32_t exp_pair(const float (&f)[10], int i, float off) {
  return pack_bf16(ex2(fmaf(f[2 * i], SCL, off)), ex2(fmaf(f[2 * i + 1], SCL, off)));
}
template<bool SPLIT> __device__ __forceinline__ void scores_x(float (&a)[2][4], const uint4 (&kf)[4], const uint4& q, uint32_t z) {
#pragma unroll
  for (int t = 0; t < 2; t++) { a[t][0] = a[t][1] = a[t][2] = a[t][3] = 0.f; }
  mma_q(a[0], kf[0], q.x, q.y); mma_q(a[1], kf[2], q.x, q.y);
  if (SPLIT) sched_fence(z);
  mma_q(a[0], kf[1], q.z, q.w); mma_q(a[1], kf[3], q.z, q.w);
}
__device__ __forceinline__ uint32_t scores_m(const uint4& q, const uint4& k) {
  float a[4] = {}, b[4] = {};
  mma_q(a, q, k.x, k.z); mma_q(b, q, k.y, k.w);
  return pack_bf16(a[0] + b[2], a[1] + b[3]);
}
__device__ __forceinline__ void store_scores(const float (&a)[2][4], uint32_t dst) {
  sts64(dst, pack_bf16(a[0][0], a[0][2]), pack_bf16(a[1][0], a[1][2]));
  sts64(dst + 320, pack_bf16(a[0][1], a[0][3]), pack_bf16(a[1][1], a[1][3]));
}
__device__ __forceinline__ uint32_t sum4(uint32_t a, uint32_t b, uint32_t d, uint32_t e) { return add_bf16x2(add_bf16x2(a, b), add_bf16x2(d, e)); }
__device__ __forceinline__ void load_scores(uint32_t (&sc)[5], uint32_t ax, uint32_t am) {
  uint4 p[4];
#pragma unroll
  for (int i = 0; i < 4; i++) p[i] = lds128(ax + i * 1280);
  const uint2 m0 = lds64(am), m1 = lds64(am + 256);
  const uint4 t = add4(add4(add4(p[0], p[1]), p[2]), p[3]);
  sc[1] = t.x; sc[2] = t.y; sc[3] = t.z; sc[4] = t.w;
  sc[0] = sum4(m0.x, m0.y, m1.x, m1.y);
}
constexpr uint32_t ONES = 0x3F803F80u;
__device__ __forceinline__ float pv(float (&o)[2][4], const uint32_t (&p)[5], const uint4 (&vf)[4], const uint4& vm) {
  float a[4] = {}, b[4] = {};
#pragma unroll
  for (int t = 0; t < 2; t++) { o[t][0] = o[t][1] = o[t][2] = o[t][3] = 0.f; }
  mma_q(o[0], vf[0], p[1], p[2]); mma_q(o[1], vf[2], p[1], p[2]);
  mma_q(o[0], vf[1], p[3], p[4]); mma_q(o[1], vf[3], p[3], p[4]);
  mma16816(a, p[1], p[2], p[3], p[4], ONES, ONES);
  mma1688(o[0], vm.x, vm.y, p[0]); mma1688(o[1], vm.z, vm.w, p[0]);
  mma1688(b, p[0], ONES, ONES);
  return (a[0] + a[2]) + b[0];
}
constexpr uint32_t POLL_LIMIT = 1u << 21;
__device__ __forceinline__ uint32_t box(int slot, int cta) { return (slot * 2 + (cta >> 6)) * M_REG + (cta & 63) * 16384; }
__device__ __forceinline__ uint32_t near_page(const ChainCtx& c, int cta, uint32_t off) {
  return off + (((lds32(c.sb + SM_SEL + cta * 4) >> (off >> 21)) ^ __popc(off & 0xB2000)) & 1) * 4096;
}
__device__ __forceinline__ uint32_t e1_box(const ChainCtx& c, int slot, int cta) { return near_page(c, E1OFF ? cta ^ 2 : cta, box(slot, cta) + 8192) ^ (E1OFF ? 0 : 4096); }
__device__ __forceinline__ uint32_t tile_key() {
  uint32_t sm; asm volatile("mov.u32 %0, %%smid;" : "=r"(sm));
  return (sm < 64 ? sm / 2 % 8 : sm < 120 ? 1 + (sm / 2 - 32) % 7 : 0) << 24 | sm << 16;
}
__device__ __forceinline__ int tile_of(const ChainCtx& c) { return SIDE ? __shfl_sync(~0u, lds32(c.sb + SM_SEL + 528), 0) : c.r; }

__global__ void __cluster_dims__(2, 1, 1) __launch_bounds__(512, 1)
chain_kernel(const __grid_constant__ CUtensorMap tq, const __grid_constant__ CUtensorMap tk, const __grid_constant__ CUtensorMap tv,
             const __grid_constant__ CUtensorMap tv16, const __grid_constant__ CUtensorMap to, const __grid_constant__ CUtensorMap tx,
             const __grid_constant__ CUtensorMap twr, const __grid_constant__ CUtensorMap twi,
             const __grid_constant__ CUtensorMap ta, const __grid_constant__ CUtensorMap tw,
             const __grid_constant__ CUtensorMap tb, const __grid_constant__ CUtensorMap tout, const __grid_constant__ CUtensorMap tz,
             const __nv_bfloat16* __restrict__ mem0, char* __restrict__ mail, const __nv_bfloat16* __restrict__ x,
             const __nv_bfloat16* __restrict__ gw, __nv_bfloat16* __restrict__ out) {
  extern __shared__ __align__(1024) unsigned char smraw[];
  if (threadIdx.x == 0) TL(0);
  ChainCtx c;
  c.sb = __shfl_sync(~0u, smem_u32(smraw), 0);
  c.mail = mail; c.sel = 0; c.r = blockIdx.x;
  if (ROLE) {
    const uint32_t u = blockIdx.x >> 1, n = u < 36 ? 8 : 7, k = u - (u < 36 ? 4 : 36), q = k * (u < 36 ? 32 : 37) >> 8;
    c.r = __shfl_sync(~0u, 2 * (u - 4 < 60 ? u + k - q * n - (q & 1) * (n - 1) : u) + (blockIdx.x & 1) + (threadIdx.x >> 9), 0);
  }
  c.h = c.r >> 2; c.a = (c.r >> 1) & 1; c.b = c.r & 1; c.j = c.r & 3;
  c.m = __shfl_sync(~0u, (int)(threadIdx.x >> 7), 0); c.w = __shfl_sync(~0u, (int)((threadIdx.x >> 5) & 3), 0);
  char* own = c.mail + (uint32_t)(c.w * M_REG + M_E3 + (c.r >> 5) * 8192 + (c.r & 31) * 128 + (threadIdx.x & 31) * 4);
  uint32_t i0 = 0, i1 = 0;
  if (EARLY) asm volatile("{ .reg .pred p; setp.ne.u32 p, %4, 0; @p atom.relaxed.gpu.global.exch.b32 %0, [%2], %3; @p atom.relaxed.gpu.global.exch.b32 %1, [%2 + 4096], %3; }"
               : "+r"(i0), "+r"(i1) : "l"(own), "r"(SENT), "r"((uint32_t)(c.m == 2 && c.r < 128)) : "memory");
#pragma unroll
  for (int g = 0; g < 3; g++) {
    const int i = c.m * 4 + c.w;
    if (g < 2 || i < B_END - 32)
      asm volatile("{ .reg .pred p; elect.sync _|p, 0xffffffff; @p mbarrier.init.shared::cta.b64 [%0], %1; }"
                   :: "r"(BAR(g * 16 + i)), "r"(0x19080401u >> (bar_codes(g) >> 2 * i & 3) * 8 & 255) : "memory");
  }
  asm volatile("fence.mbarrier_init.release.cluster;" ::: "memory");
  __syncthreads();
  asm volatile("barrier.cluster.arrive.relaxed.aligned;" ::: "memory");

  if (c.r >= 128) {
    fft_cols((float2*)smraw, c.r - 128, &twr, &twi);
    if ((threadIdx.x & 127) == 0) TL(7);
    __syncwarp();
  } else if (c.m == 3) {
    asm volatile("setmaxnreg.dec.sync.aligned.u32 %0;" :: "n"(REG_H));
    c.lane = lane_id();
    if (c.sb & 1023) asm volatile("trap;");
    const int col = c.h * 128 + c.a * 64;
    uint32_t tl = clock_lo();
    TR(-2, 3);
    if (c.w == 0) {
      if (START) delay_until(tl + START);
      if (HOLD == 2) mbar_wait(BAR(B_PROBE), 0);
      if (HOLD == 3) mbar_wait(BAR(B_SEL), 0);
      if (HOLD == 1) mbar_wait(BAR(B_PROBE), 0);
      TR(-2, 4);
      tl = clock_lo();
      mbar_expect_e(BAR(B_WFULL), 48 * 2048);
      mbar_expect_e(BAR(B_WFULL + 1), 48 * 2048);
    }
    auto dst_x = [&](int e, int w) {
      const uint32_t g2 = 2 * c.a + (w >> 1), u = w & 1;
      return M_KVQ + c.h * 24576 + (e == 0 ? 8192 + (2 * u + c.b) * 2048 + g2 * 512 : e == 1 ? g2 * 2048 + u * 1024 + c.b * 128 : 16384 + c.b * 4096 + g2 * 512 + u * 256);
    };
    if (c.w == 0) {
      tl += PACE0;
      constexpr int P = NP / 4, LATE = P + 13 - (SM_GW + 2048 - ST_WG + 8191) / 8192;
#pragma unroll wunr
      for (int i = 0; i < 24; i++) {
        const int m = i > P && i < P + 13, k = i <= P ? i : m ? i - P - 1 : i - 12;
        const int row = c.b * 512 + m * 256;
        const uint32_t st = c.sb + m * ST_WG, bar = BAR(B_WFULL + m);
        if (PACE) delay_until(tl += PACE);
        if (i == LATE) { mbar_wait(BAR(B_FREE), 0); if (c.lane == 0) TL2(2); __syncwarp(); }
        if (k < P) TMA_W(c.sb + SM_POOL + m * NP * 2048 + k * 8192, m ? &tq : &tk, col, row + k * 64, bar);
        else if (k == P) TMA_W(c.sb + SM_HV + (m * NHV + 1) * 2048, &tv, col, row + 192, bar);
        else if (k == P + 1) for (int j = 8; j < 12; j++) TMA_W(j < NV ? st + (32 - NP + j) * 2048 : c.sb + SM_HV + m * NHV * 2048, &tv16, col, row + j * 16, bar);
        else if (k < P + 4) TMA_W(st + (32 - NP) * 2048 + (k - P - 2) * 8192, &tv, col, row + (k - P - 2) * 64, bar);
        else if (k < 8) TMA_W(st + (k - P) * 8192, m ? &tq : &tk, col, row + (k - 4) * 64, bar);
        else TMA_W(st + (11 - k) * 8192, m ? &tk : &tq, col, row + (11 - k) * 64, bar);
      }
      TR(-2, 7);
    } else if (c.w == 2) {
      const unsigned short* mp = (const unsigned short*)mem0 + (2 * (c.lane & 3)) * D_ + 8 * c.r + (c.lane >> 2);
      uint32_t mv = (uint32_t)mp[0] | (uint32_t)mp[D_] << 16;
      if (mv == SENT) mv = 0x7FFF7FFFu;
      mbar_wait(BAR(B_PROBE), 0);
      char* dst = c.mail + (uint32_t)(M_E3 + (c.r >> 5) * 8192 + (c.r & 31) * 128 + c.lane * 4);
      st_pub(dst, mv); st_pub(dst + 4096, mv);
    } else if (c.w == 3) {
      mbar_wait(BAR(B_FREE), 0);
      mbar_expect_e(BAR(B_XFULL), X01 == 1 ? 65536 : 32768);
      for (int i = 0; i < 2; i++) tma4d_e(c.sb + SM_XT + i * 16384, &tx, c.b * 8, (X01 & 1) * 4 + 2 * (c.b ^ i), BAR(B_XFULL));
    }
    {
      mbar_wait(BAR(B_SEL), 0);
      const int i = tid_now() & 127, sl = i & 3, e = (i >> 2) & 3;
      uint32_t ox = dst_x(e, i >> 5) + sl * M_REG;
      uint32_t oh = e & 1 ? (sl ^ (e & 2)) * M_REG + M_E3 + (c.r >> 5) * 8192 + (c.w & 1) * 4096 + (c.r & 31) * 128
                          : near_page(c, c.r, e ? sl * M_REG + M_E3 + (c.b * 2 + (c.w >> 1)) * 8192 : box(~sl & 1, c.r)) + (e ? (c.w & 1) * 2048 : c.w * 1024), of;
      {
        const int e = i & 7, w = (i >> 3) & 3, m = (i >> 5) & 1, sl = i >> 6;
        const int cta = e < 2 ? c.r & ~1 : e == 2 ? c.r | 1 : e == 3 ? c.h * 4 + 2 * m + 1 : c.j * 32 + m * 8 + 2 * w + (e & 2) * 8 + (e & 1);
        const uint32_t off = e < 2 ? c.b * 2048 + m * 1024 + (w >> 1) * 512 + e * 160 : e == 2 ? c.b * 2048 + m * 1024 + w * 256 : e == 3 ? w * 256 : c.h * 128;
        of = (e < 4 ? e1_box(c, sl, cta) : near_page(c, cta, box(sl, cta))) + off;
      }
      char *px = c.mail + ox, *ph = c.mail + oh, *pf = c.mail + of;
      uint32_t at = sl * 128 + (i >> 5) * 32 + e * 8, af = i * 8;
      pin(px); pin(ph); pin(pf); pin(at); pin(af);
      asm volatile("barrier.cluster.wait;" ::: "memory");
      TR(-2, 0);
      mbar_wait(BAR(B_WREAD), 0);
      TR(-2, 1);
      mbar_arrive_both(BAR(B_LFREE), c.b ^ 1);
      sts64(at + (c.sb + SM_TAB + 1536), (uint32_t)(uintptr_t)px, (uint32_t)((uintptr_t)px >> 32));
      sts64(at + (c.sb + SM_TAB + 1024), (uint32_t)(uintptr_t)ph, (uint32_t)((uintptr_t)ph >> 32));
      sts64(af + (c.sb + SM_TAB), (uint32_t)(uintptr_t)pf, (uint32_t)((uintptr_t)pf >> 32));
      TR(-2, 2);
      if (tid_now() == 384) TL2(25);
      __syncwarp();
      bar_sync(NB_HELP, 128);
    }
    for (int s = -1; s < NSEG; s++) {
      if (s >= 0) {
        const uint32_t tab = c.sb + SM_TAB + 1024 + (s & 3) * 128 + c.w * 32;
        uint32_t t0;
        if (s > 0) {
          const uint32_t ln = tid_now() & 31;
          const uint4 ta = lds128(tab);
          const char* src = mk_ptr(ta.x | ln * 4, ta.y);
          char* dst = mk_ptr(ta.z | ln * 4, ta.w);
          const uint32_t tg = (s - 1) >> 1, chk = (ln & 3) ? 0u : 1u, red = ln * (RED_L == 3 ? 4 : 8);
          touch(src, dep(c.sb, chk, c.sb)); touch(dst, dep(c.sb, red, c.sb));
          mbar_wait(BAR(B_E2TRIG), (s - 1) & 1);
          TR(s, 0);
          if (ANCH2) delay_until(lds32(c.sb + SM_SUM + 64) + DLY_E2); else delay_cycles(DLY_E2);
          uint32_t n = 0;
          while (true) {
            uint32_t v[8];
#pragma unroll
            for (int i = 0; i < 8; i++) v[i] = ld_poll1(src + i * 128);
            if (E2_F) sched_fence(c.sb);
            const uint32_t bad = RED_T ? (stale2(v[0], v[1], tg) | stale2(v[2], v[3], tg) | stale2(v[4], v[5], tg)) | stale2(v[6], v[7], tg)
                                       : stale1(stale1(stale2(v[0], v[1], tg), v[2], tg), v[3], tg) | stale1(stale1(stale2(v[4], v[5], tg), v[6], tg), v[7], tg);
            const bool ok = all_clear(bad, chk);
#pragma unroll
            for (int l = 0; l < RED_L; l++)
#pragma unroll
              for (int i = 0; i < (4 >> l); i++) v[i] = add_bf16x2(v[2 * i], v[2 * i + 1]);
            if (RED_L == 3) sts32(red + (c.sb + SM_RED + c.w * 128), v[0]);
            else {
              float lo[8], hi[8];
#pragma unroll
              for (int i = 0; i < (8 >> RED_L); i++) { lo[i] = __uint_as_float(v[i] << 16); hi[i] = __uint_as_float(v[i] & 0xFFFF0000u); }
#pragma unroll
              for (int l = RED_L; l < 3; l++)
#pragma unroll
                for (int i = 0; i < (4 >> l); i++) { lo[i] = lo[2 * i] + lo[2 * i + 1]; hi[i] = hi[2 * i] + hi[2 * i + 1]; }
              sts64(red + (c.sb + SM_RED + c.w * 256), __float_as_uint(lo[0]), __float_as_uint(hi[0]));
            }
            if (ok) break;
            n++; CNT(0);
          }
          bar_sync(NB_HELP, 128);
          const uint32_t rd = red + (c.sb + SM_RED);
          if (!RED_P || c.w < 2) {
            if (RED_L == 3) st_pub_if(dst, sum4(lds32(rd), lds32(rd + 128), lds32(rd + 256), lds32(rd + 384)), c.w < 2);
            else {
              const uint2 p0 = lds64(rd), p1 = lds64(rd + 256), p2 = lds64(rd + 512), p3 = lds64(rd + 768);
              st_pub_if(dst, pack_bf16((__uint_as_float(p0.x) + __uint_as_float(p1.x)) + (__uint_as_float(p2.x) + __uint_as_float(p3.x)),
                                       (__uint_as_float(p0.y) + __uint_as_float(p1.y)) + (__uint_as_float(p2.y) + __uint_as_float(p3.y))), c.w < 2);
            }
          }
          t0 = clock_lo();
          mbar_arrive_warp(BAR(B_PUB));
          TRV(s, 15, n);
          mbar_wait(BAR(B_SPFREE), (s - 1) & 1);
        } else {
          if (tid_now() == 384) TL2(24);
          __syncwarp();
          mbar_wait(BAR(B_WOFULL), 0);
          if (tid_now() == 384) TL2(19);
          __syncwarp();
          t0 = clock_lo() - DLY_E3;
        }
        TRV(s, 1, t0);
        {
          const uint32_t l16 = (tid_now() & 31) * 16, dst = l16 + (c.sb + SM_MEM + (c.w & 1) * 4096 + (c.w >> 1) * 2048);
          const uint4 tb = lds128(tab + 16);
          st_pub_if(mk_ptr(tb.z | l16 >> 2, tb.w), SENT, c.w >= 2);
          const char* src = mk_ptr(tb.x | l16, tb.y);
          touch(src, dep(c.sb, dst, c.sb));
          delay_until(t0 + (DLY_E3 + (c.w & 1) * DLY_E3B));
          uint32_t n = 0;
          while (true) {
            uint4 v[4];
#pragma unroll
            for (int i = 0; i < 4; i++) v[i] = ld_poll(src + i * 512);
#pragma unroll
            for (int i = 0; i < 4; i++) sts128(dst + i * 512, v[i]);
            if (arrive_if_all(max(max(v[0].x, v[1].x), max(v[2].x, v[3].x)) != SENT, NB_MEM + (c.w & 1) * 2 + (c.w >> 1), 160)) break;
            n++; CNT(1);
          }
          mbar_arrive_warp(BAR(B_MEM));
          TR(s, 2); TRV(s, 14, n);
        }
        if (s == 1) CLK(1); if (s == 8) CLK(2); if (s == 56) CLK(3);
        if (c.w == 2 && s == 15) TRSYNC(8);
        if (c.w == 2 && s == 21) TRSYNC(10);
      }
      const int g = s + 1;
      auto load_v = [&]() {
        if (V_TMA && c.w == V_W) {
          mbar_expect_e(BAR(B_VFULL), 8192);
          bulk_load_e(c.sb + SM_V, c.mail + (uint32_t)(M_KVQ + (min(g, XEND - 1) & (NSLOT - 1)) * M_REG + c.h * 24576 + 8192), 8192, BAR(B_VFULL));
        }
      };
      if (XEND < NSEG && g >= XEND && g < NSEG) { mbar_wait(BAR(B_SC), s & 1); load_v(); }
      if (g < XEND) {
        const uint32_t tx_ = c.sb + SM_TAB + 1536 + (g & 3) * 128 + c.w * 32, tag = (g >> 2) & 1;
        if (c.w == 0) mbar_expect_e(BAR(B_LAND), EXP_PEER * 12288);
        auto load_x = [&]() {
          if (c.w == 3 && g + 1 < XEND) {
            mbar_wait(BAR(B_XEMPTY), g & 1);
            mbar_expect_e(BAR(B_XFULL), 16384 * EXP_NXT);
            for (int i = 0; i < EXP_NXT; i++) tma4d_e(c.sb + SM_XT + i * 16384, &tx, c.b * 8, (g + 1) * 4 + 2 * (c.b ^ i), BAR(B_XFULL));
          }
        };
        if (X_AT == 0 && g > 0) load_x();
        TR(s, 6);
        mbar_wait(BAR(B_LAND), g & 1);
        TR(s, 7);
        if (DLY_F && g > 0) delay_cycles(DLY_F);
        auto total = [&](int w, int lane, uint32_t o0, uint32_t o1) {
          const uint32_t a = c.sb + SM_LAND + land_off(w, lane);
          if (EXP_FL == 1) return make_uint4(a, a, a, a);
          const uint4 t = add4(lds128(a + o0), lds128(a + o1 + 2048));
          const uint32_t a2 = dep(dep(a, t.x ^ t.y ^ t.z, c.sb), t.w, c.sb);
          return add4(t, add4(lds128(a2 + o0 + 4096), lds128(a2 + o1 + 6144)));
        };
        auto get = [&](int e) {
          const int ln = tid_now() & 31;
          return e == 0 ? total(c.w, ln, 16384, 16384)
               : e == 1 ? total((c.w & 2) + ((ln >> 1) & 1), (ln & 1) * 16 + (c.w & 1) * 8 + (ln >> 2), 8192, 0)
                        : total((c.w & 2) + ((ln >> 1) & 1), (ln & 1) * 16 + (ln >> 3) * 4 + (c.w & 1) * 2 + ((ln >> 2) & 1), 0, 8192);
        };
        auto put = [&](int e, uint4 v) {
          const int ln = tid_now() & 31;
          const uint2 d = lds64(tx_ + e * 8);
          if (e < 2) {
            v.x = tagged(v.x, tag);
            st_pub4(mk_ptr(d.x | (e ? (ln & 24) * 32 + (ln & 7) * 16 : ln * 16), d.y), v);
          } else {
            char* dst = mk_ptr(d.x | ((ln & 7) * 16 + (ln >> 3) * 4), d.y);
            const uint32_t bit = ln < 8;
            st_pub(dst, put_tag(v.x, bit, tag)); st_pub(dst + 128, put_tag(v.y, bit, tag));
            st_pub(dst + 2048, put_tag(v.z, bit, tag)); st_pub(dst + 2176, put_tag(v.w, bit, tag));
          }
        };
        auto after_sc = [&]() { if (g > 0) { mbar_wait(BAR(B_SC), s & 1); if (DLY_FK) delay_cycles(DLY_FK); if (X_AT == 1) load_x(); } };
        if (FIN_AT == 5) {
          put(0, get(0));
          if (DLY_F2 && g > 0) delay_cycles(DLY_F2); else sched_fence(c.sb);
          const uint4 k = get(1);
          sched_fence(c.sb);
          const uint4 q = get(2);
          if (g > 0) { mbar_wait(BAR(B_VST), s & 1); if (DLY_FS) delay_cycles(DLY_FS); }
          put(1, k); put(2, q);
          TR(s, 5);
          mbar_arrive_both(BAR(B_LFREE), c.b ^ 1);
          after_sc();
          load_v();
          continue;
        }
        if (FIN_AT < 3) {
          if (EXP_FIN & 1) put(0, get(0));
          TR(s, 3);
          if (FIN_AT == 1) after_sc();
          if (V_TMA == 1) load_v();
          if (EXP_FIN & 2) put(1, get(1));
        } else {
          const uint4 v = get(0);
          sched_fence(c.sb);
          const uint4 k = get(1);
          if (g > 0) { mbar_wait(BAR(B_VST), s & 1); if (DLY_FS) delay_cycles(DLY_FS); }
          put(0, v); put(1, k);
        }
        TR(s, 4);
        if (FIN_AT == 4) {
          const uint4 q = get(2);
          after_sc();
          load_v();
          put(2, q);
        } else {
          if (FIN_AT >= 2) after_sc();
          if (V_TMA == 2) load_v();
          if (EXP_FIN & 4) put(2, get(2));
        }
        mbar_arrive_both(BAR(B_LFREE), c.b ^ 1);
        if (V_TMA == 3) load_v();
        TR(s, 5);
        if (!FIN_AT && X_AT && g > 0) { mbar_wait(BAR(B_SC), s & 1); if (DLY_FK) delay_cycles(DLY_FK); load_x(); }
      }
    }
    const int tile = tile_of(c), m0 = (tile >> 3) * 128 + c.b * 64, n0 = (tile & 7) * 128;
    auto load_b = [&](int kb, uint32_t o, uint32_t bar) {
      mbar_expect_e(bar, 32768);
      tma2d_e(c.sb + o + 16384, &tw, n0, kb * 64, bar);
      tma2d_e(c.sb + o + 24576, &tw, n0 + 64, kb * 64, bar);
    };
    auto load_a = [&](int kb, uint32_t o, uint32_t bar) { tma2d_mc_e(c.sb + o + c.b * 8192, &ta, kb * 64, m0, bar); };
    if (c.w == 1) {
      mbar_wait(BAR(B_PVDONE), 0);
      count_e(g_ctl + C_EARLY);
      st_pub(c.mail + (uint32_t)((tid_now() & 6) * (M_REG / 2) + M_SEL + (tid_now() & 1) * 4096 + c.r * 4), 0);
      await_count(g_ctl + C_COLS, 4);
      mbar_expect_e(BAR(B_TW), 8192);
      bulk_load_e(c.sb + SM_TW, g_tw, 8192, BAR(B_TW));
    } else if (c.w == 2) {
      const uint32_t ln = tid_now() & 31, rel = mapa(BAR(B_GEMPTY) + (ln >> 2) * 8, ln & 1);
      mbar_wait(BAR(B_VST), 1); mbar_wait(BAR(PRE_AT), 1);
      arrive_remote_if(rel, ln < 12);
      mbar_wait(BAR(B_E2TRIG), 1);
      if (GATE) mbar_wait(BAR(B_DONE), 0);
      arrive_remote_if(rel, ln >= 12 && ln < 20);
    } else {
      auto ahead = [&](int k) {
        if (c.w) { if (PF_A && (k & 3) == (tile >> 1 & 3)) prefetch2d_e(&ta, k * 64, m0); }
        else if (PF_B && (k & 7) == (tile >> 4)) prefetch2d_e(&tw, n0 + (tile & 8) * 8, k * 64);
      };
      for (int k = 0; k < PF_D; k++) ahead(k);
      if (c.w == 3) { await_count(g_ctl + C_EARLY, 128); if (tile >= 120) { if (LASTM == 2) await_flags(g_ctl + C_LAST + (tid_now() & 31) * 4); else await_count(g_ctl + C_LAST, 512); } }
      if (tid_now() == 480) TL(10);
      __syncwarp();
      uint32_t o = SM_XT, st = 0, ph = 0;
#pragma unroll 1
      for (int kb = 0; kb < 64; kb++, o = next_stage(o)) {
        mbar_wait(BAR(B_GEMPTY + st), ph);
        const int k = (kb + (tile < 120 ? 0 : LROT)) & 63;
        if (c.w) load_a(k, o, BAR(B_GFULL + st)); else load_b(k, o, BAR(B_GFULL + st));
        if (kb + PF_D < 64) ahead(kb + PF_D);
        if (++st == 5) { st = 0; ph ^= 1; }
      }
    }
    return;
  } else if (c.m == 2) {
    asm volatile("setmaxnreg.dec.sync.aligned.u32 %0;" :: "n"(512 - 2 * REG_F - REG_H));
    c.lane = lane_id();
    {
      uint32_t tl = clock_lo() + (PACE0 + WO_AT * PACE);
      TR(-2, 0);
      sched_fence(i0 ^ i1);
      TR(-2, 7);
      int far1 = 0;
#pragma unroll 1
      for (int rep = EARLY; rep <= NPROBE; rep++) {
        const int lag = race_init(own + (rep & 1) * 4096, own + (~rep & 1) * 4096, SENT);
        if (rep) far1 += ((rep ^ c.r >> 5) & 1 ? 1 : -1) * min(lag, 200);
      }
      sts32(c.sb + SM_SEL + 512 + c.w * 4, (8 + far1 / (16 * NPROBE)) << 4 * c.w);
      TR(-2, 1);
      if (tid_now() == 256) TL2(14);
      __syncwarp();
      mbar_arrive_warp(BAR(B_PROBE));
      if (c.w == 0) {
        mbar_wait(BAR(B_PROBE), 0);
        const uint4 bits = lds128(c.sb + SM_SEL + 512);
        const uint32_t res = bits.x | bits.y | bits.z | bits.w;
        st_pub_if(c.mail + (uint32_t)((c.lane & 6) * (M_REG / 2) + M_SEL + (c.lane & 1) * 4096 + c.r * 4), res | tile_key(), c.lane < 8);
        const int q = (res >> 4 * ((c.lane + c.r) & 3) & 15) - 8, best = __reduce_max_sync(~0u, abs(q) * 64 + (c.lane & 3) * 16 + ((c.lane + c.r) & 3) * 2 + (q <= 0));
        const char* src = c.mail + (uint32_t)((best & 6) * (M_REG / 2) + M_SEL + (best & 1) * 4096 + c.lane * 16);
        if (SEL_AT) delay_until(tl - (PACE0 + WO_AT * PACE - SEL_AT));
        uint4 v; uint32_t n = 0;
        TR(-2, 4);
        while (true) {
          delay_cycles(DLY_SEL);
          TR(-2, 6);
          v = ld_poll(src);
          if (__all_sync(~0u, v.x && v.y && v.z && v.w)) break;
          watchdog(n, POLL_LIMIT);
        }
        TR(-2, 5);
        int ta = 0, tb = 0, pa = 0, pb = 0;
        uint32_t flip = 0;
#pragma unroll 1
        for (int i = 0; i < 4; i++) {
          const int a = (v.x >> 4 * i & 15) + (v.y >> 4 * i & 15) - 16, b = (v.z >> 4 * i & 15) + (v.w >> 4 * i & 15) - 16;
          const bool f = __reduce_add_sync(~0u, a * ta + b * tb) < 0;
          ta += f ? -a : a; tb += f ? -b : b; flip |= (uint32_t)f << i;
        }
#pragma unroll 1
        for (uint32_t g = 0; g < 8; g++) {
          const bool a = (v.x >> 16) - g * 256 < 120, b = (v.z >> 16) - g * 256 < 120;
          const int n = __reduce_add_sync(~0u, (a ? ta : 0) + (b ? tb : 0)) > 0 ? PRIOR : -PRIOR;
          if (a) pa = n;
          if (b) pb = n;
        }
        const uint32_t ka = AWARE && ta + pa > 0 ? ~flip : flip, kb = AWARE && tb + pb > 0 ? ~flip : flip;
        sts128(c.sb + SM_SEL + c.lane * 16, make_uint4(ka, ka, kb, kb));
        mbar_arrive_warp(BAR(B_SEL));
        const uint32_t key = __shfl_sync(~0u, c.a ? v.z : v.x, c.h);
        const int u = __popc(__ballot_sync(~0u, v.x < key)) + __popc(__ballot_sync(~0u, v.z < key));
        sts32(c.sb + SM_SEL + 528, (u & 32) * 2 + (u & 7) * 8 + (u >> 2 & 6) + c.b);
        TR(-2, 2);
        if (c.lane == 0) TL2(13);
        __syncwarp();
      }
      if (c.w == 2) {
        mbar_wait(BAR(B_P1), 0);
        if (P1_AT) { mbar_wait(BAR(B_WFULL), 0); mbar_wait(BAR(B_WFULL + 1), 0); }
        st_pub_if(g_ctl + C_COLS + (c.r & 15) * 32 + c.lane, 0, c.r < (C_END - C_COLS) / 32);
        count_e(g_ctl + C_P1);
        TR(-2, 3);
      }
      if (c.w == 1) {
        for (int i = 0; i < 4; i++) { delay_until(tl += WO_P * PACE); prefetch2d_e(&to, c.j * 256 + i * 64, c.h * 128); }
        if (WO_W) mbar_wait(BAR(B_WREAD), 0);
        if (WO_W) mbar_expect_e(BAR(B_WOFULL), 65536);
        if (WO_W) for (int i = X01 ? 2 : 0; i < 4; i++) TMA_O(c.sb + SM_WO + i * 16384, &to, c.j * 256 + i * 64, c.h * 128, BAR(B_WOFULL));
      }
      if (c.w == 3) {
        mbar_wait(BAR(B_WREAD), 0);
        if (X01) for (int i = 0; i < 2; i++) tma4d_e(c.sb + SM_WO + i * 16384, &tx, c.b * 8, 2 * (c.b ^ i), BAR(B_XFULL));
        if (!WO_W) mbar_expect_e(BAR(B_WOFULL), 65536);
        if (!WO_W) for (int i = X01 ? 2 : 0; i < 4; i++) TMA_O(c.sb + SM_WO + i * 16384, &to, c.j * 256 + i * 64, c.h * 128, BAR(B_WOFULL));
        mbar_wait(BAR(B_XEMPTY), 0);
        mbar_expect_e(BAR(B_XFULL), X01 ? 0 : 32768);
        for (int i = 0; i < 2; i++)
          if (X01) TMA_O(c.sb + SM_WO + i * 16384, &to, c.j * 256 + i * 64, c.h * 128, BAR(B_WOFULL));
          else tma4d_e(c.sb + SM_XT + i * 16384, &tx, c.b * 8, 4 + 2 * (c.b ^ i), BAR(B_XFULL));
      }
    }
    asm volatile("barrier.cluster.wait;" ::: "memory");
    const int g = c.w, src0 = c.h * 4 + (g >> 1) * 2;
    mbar_wait(BAR(B_SEL), 0);
    c.sel = __shfl_sync(~0u, (e1_box(c, 0, src0 + (c.lane >> 5)) & 4096) | (e1_box(c, 1, src0) & 4096) * 2, 0);
    mbar_wait(BAR(B_WREAD), 0);
    uint32_t l16 = c.sb + g * 512 + c.lane * 16;
    auto lane = [&](uint32_t v) { l16 = dep(l16, v, c.sb); return (int)((l16 & 511) >> 4); };
    for (int s = 0; s < NSEG; s++) {
      l16 = vary(l16, s, c.sb);
      int ln = (l16 & 511) >> 4;
      uint4 kf[4], qx;
      {
        const int gs = min(s, XEND - 1);
        const char* pk = c.mail + (uint32_t)(M_KVQ + (gs & (NSLOT - 1)) * M_REG + c.h * 24576 + g * 2048 + ln * 16);
        const char* pq = pk + (16384 + c.j * 2048 - g * 1536);
        const uint32_t tg = (gs / NSLOT) & 1;
        touch(pk, c.sb); touch(pq, c.sb);
        TR(s, 0);
        mbar_wait(BAR(B_VFULL), s & 1);
        TR(s, 1);
        if (KVQ_AT) { mbar_wait(BAR(B_MEM), s & 1); if (DLY_K) delay_cycles(DLY_K); } else if (s > 0) mbar_wait(BAR(B_PUB), (s - 1) & 1);
        for (uint32_t n = 0; ; ) {
          uint4 k[4];
#pragma unroll
          for (int t = 0; t < 4; t++) k[t] = ld_poll(pk + t * 512);
          qx = ld_poll(pq);
#pragma unroll
          for (int t = 0; t < 2; t++) {
            auto cp = [&](uint32_t v) { return dep(v, 0, c.sb); };
            kf[t] = make_uint4(cp(k[2 * t].x), cp(k[2 * t].y), cp(k[2 * t + 1].x), cp(k[2 * t + 1].y));
            kf[2 + t] = make_uint4(cp(k[2 * t].z), cp(k[2 * t].w), cp(k[2 * t + 1].z), cp(k[2 * t + 1].w));
          }
          if (all_clear(stale1(stale2(k[0].x, k[1].x, tg) | stale2(k[2].x, k[3].x, tg), qx.x, tg), EXP_CHK)) break;
          watchdog(n, POLL_LIMIT); CNT(4);
        }
        TR(s, 2);
      }
      if (X_AT >= 2 && g == 0 && s + 2 < XEND) {
        mbar_wait(BAR(B_XEMPTY), ~s & 1);
        if (X_AT == 3) mbar_wait(BAR(B_MEM), s & 1);
        mbar_expect_e(BAR(B_XFULL), 16384 * EXP_NXT);
        for (int i = 0; i < EXP_NXT; i++) tma4d_e(c.sb + SM_XT + i * 16384, &tx, c.b * 8, (s + 2) * 4 + 2 * (c.b ^ i), BAR(B_XFULL));
      }
      ln = lane(kf[0].y);
      const char* pa = c.mail + (uint32_t)(box(s & 1, src0) + 8192 + (c.sel >> (s & 1) & 4096) + (g & 1) * 512 + (EXP_LIN ? ln * 16 : read_off(ln)));
      const uint32_t spw = c.sb + SM_SP + g * 1280 + (ln & 3) * 64 + ((((ln >> 3) ^ ln) & 2) << 4) + (ln & 4) * 4 + (ln & 8),
                     spr = c.sb + SM_SP + (ln & 4) * 80 + (ln >> 3) * 64 + (((ln & 3) ^ ((ln >> 3) & 2)) << 4), l8 = ln * 8;
      const uint32_t tg = s >> 1;
      float sx[2][4];
      uint32_t sm;
      uint4 km;
      touch(pa, c.sb);
      mbar_wait(BAR(B_E1TRIG), s & 1);
      const uint32_t t0 = clock_lo();
      TRV(s, 3, t0);
      scores_x<false>(sx, kf, qx, 0);
      store_scores(sx, spw + 640);
      delay_until(t0 + DLY_E1);
      uint32_t nr = 0;
      while (true) {
        const uint4 q0 = ld_poll(pa), q1 = ld_poll(pa + 2048), k0 = ld_poll(pa + 1024), k1 = ld_poll(pa + 3072);
        uint4 qm = add4(q0, q1);
        const uint32_t bq = stale2(q0.x, q1.x, tg);
        qm.x = dep(qm.x, bq, c.sb);
        scores_x<SC_F>(sx, kf, qm, c.sb);
        const uint32_t bk = stale2(k0.x, k1.x, tg);
        km = add4(k0, k1);
        km.x = dep(km.x, bk, c.sb);
        const bool ok = all_clear(bq | bk, 1);
        sm = scores_m(qm, km);
        store_scores(sx, spw);
        if (ok) break;
        nr++; CNT(2);
      }
      sts32(l8 + (c.sb + SM_SPM + (g >> 1) * 256 + (g & 1) * 4), sm);
      bar_sync(NB_ATT, 128);
      TR(s, 5); TRV(s, 13, nr);
      float o[2][4];
      uint32_t sp[5];
      uint4 vf[4];
      load_scores(sp, spr, l8 + (c.sb + SM_SPM));
      const uint32_t m5 = max5(sp);
      uint32_t m1;
      float off = row_off(m5, m1), f[10];
      l16 = dep(l16, VF_AT ? m1 : m5, c.sb);
#pragma unroll
      for (int t = 0; t < 4; t++) vf[(t >> 1) + 2 * (t & 1)] = lds128(l16 + SM_V + ((t >> 1) + 2 * (t & 1)) * 2048);
      qx.x = dep(qx.x, sp[0], c.sb);
      sts32(l8 + (c.sb + SM_SPM + 512 + (g >> 1) * 256 + (g & 1) * 4), scores_m(qx, km));
      mbar_arrive_warp(BAR(B_SC));
      unpack(f, sp);
      if (UP_F) sched_fence(c.sb);
      uint4 vm;
      if (VM_AT < 2) {
        bar_sync(NB_VM, 384);
        sp[1] = exp_pair(f, 1, off);
        const uint32_t av = dep(l8, VM_AT ? sp[1] : __float_as_uint(off), c.sb) + (c.sb + g * 512 + SM_VM);
        const uint2 vm0 = lds64(av), vm1 = lds64(av + 256);
        vm = make_uint4(vm0.x, vm0.y, vm1.x, vm1.y);
#pragma unroll
        for (int i = 2; i < 6; i++) sp[i % 5] = exp_pair(f, i % 5, off);
      } else {
#pragma unroll
        for (int i = 1; i < 6; i++) sp[i % 5] = exp_pair(f, i % 5, off);
        bar_sync(VM_AT == 2 ? dep(dep(0, sp[1] ^ sp[2], c.sb) + NB_VM, sp[0], c.sb) : dep(dep(0, sp[0] ^ sp[1] ^ sp[2], c.sb) + NB_VM, sp[3], c.sb), 384);
        const uint32_t av = l8 + (c.sb + g * 512 + SM_VM);
        const uint2 vm0 = lds64(av), vm1 = lds64(av + 256);
        vm = make_uint4(vm0.x, vm0.y, vm1.x, vm1.y);
      }
      float sum;
      auto rows_m = [&]() {
        const uint32_t tv = min(s, XEND - 1) / NSLOT;
        sum = pv(o, sp, vf, vm);
        stsm4<false>(l16 + SM_OM, pack_bf16(o[0][0], o[0][1]), pack_bf16(o[0][2], o[0][3]), pack_bf16(o[1][0], o[1][1]), pack_bf16(o[1][2], o[1][3]));
        sts32(c.sb + SM_SUM + ((l16 >> 4) & 28), __float_as_uint(sum));
        return arrive_if_clear(stale2(vf[0].x, vf[1].x, tv) | stale2(vf[2].x, vf[3].x, tv), EXP_CHK, NB_OM, 384);
      };
      if (!rows_m()) {
        const char* pv_ = c.mail + (uint32_t)(M_KVQ + (min(s, XEND - 1) & (NSLOT - 1)) * M_REG + c.h * 24576 + 8192 + (l16 - c.sb));
        uint32_t n = 0;
        do {
#pragma unroll
          for (int t = 0; t < 4; t++) vf[t] = ld_poll(pv_ + t * 2048);
          watchdog(n, POLL_LIMIT); CNT(5);
        } while (!rows_m());
      }
      const uint32_t tom = clock_lo();
      TRV(s, 8, tom);
      sched_fence(c.sb);
      ln = lane(tom);
      const int n = ln >> 2, jj = ln & 3, tq_ = 8 * c.j + (n & 4) + 2 * (n & 1) + ((n >> 1) & 1), lim = 16 * (tq_ - 2 * jj + 1);
      if (DLY_X) delay_until(tom + DLY_X);
      load_scores(sp, spr + 640, c.sb + SM_SPM + 512 + ln * 8);
#pragma unroll
      for (int w = 0; w < 4; w++) {
        uint32_t m; asm("shl.b32 %0, 0xffffffff, %1;" : "=r"(m) : "r"(max(lim - 128 * w, 0)));
        sp[1 + w] = (sp[1 + w] & ~m) | (0xD029D029u & m);
      }
      mbar_arrive_warp(dep(dep(0, sp[0], c.sb), sp[1], c.sb) + BAR(B_SPFREE));
      off = row_off(max5(sp), m1);
      unpack(f, sp);
#pragma unroll
      for (int i = 1; i < 6; i++) sp[i % 5] = exp_pair(f, i % 5, off);
      sum = pv(o, sp, vf, vm);
      if (W_PV) mbar_arrive_warp(dep(dep(0, __float_as_uint(o[1][0]), c.sb), __float_as_uint(sum), c.sb) + BAR(B_PVDONE));
      TR(s, 7);
      sum = rcp(sum);
      const float i0 = __shfl_sync(~0u, sum, 8 * jj), i1 = __shfl_sync(~0u, sum, 8 * jj + 4);
      const uint32_t oxs = c.sb + SM_OX + g * 512;
      stsm4<true>(oxs + (ln & 7) * 64 + (((ln >> 3) ^ ((ln >> 1) & 3)) << 4),
                  pack_bf16(o[0][0] * i0, o[0][1] * i1), pack_bf16(o[0][2] * i0, o[0][3] * i1), pack_bf16(o[1][0] * i0, o[1][1] * i1), pack_bf16(o[1][2] * i0, o[1][3] * i1));
      __syncwarp();
      *(uint4*)(g_ox + (uint32_t)((32 * s + tq_) * 4096 + c.h * 128 + 32 * g + 8 * jj)) = lds128(oxs + n * 64 + ((jj ^ (n >> 1)) << 4));
      mbar_arrive_warp(BAR(B_PVDONE));
      TR(s, 9);
    }
    if (LASTM) {
      const int ln = tid_now() & 31, n = ln >> 2, jj = ln & 3, tq_ = 8 * c.j + (n & 4) + 2 * (n & 1) + ((n >> 1) & 1);
      store_count(g_ox + (uint32_t)((S_ - 32 + tq_) * 4096 + c.h * 128 + 32 * g + 8 * jj), lds128(c.sb + SM_OX + g * 512 + n * 64 + ((jj ^ (n >> 1)) << 4)), (char*)(g_ctl + C_LAST) + (LASTM == 2 ? c.r * 4 + g : 0));
    } else count_e(g_ctl + C_LAST);
    mbar_arrive_warp(BAR(B_DONE));
    if (tid_now() == 256) TL(8);
    __syncwarp();
    mbar_wait(BAR(B_E2TRIG), 1); mbar_wait(BAR(B_DONE), 0); mbar_wait(BAR(B_TW), 0);
    asm volatile("setmaxnreg.inc.sync.aligned.u32 128;");
  } else {
    {
      const int w = c.m * 4 + c.w;
      mbar_expect_e(BAR(B_ROWS), 4096 + 256);
      for (int i = 0; i < 2; i++) bulk_load_e(c.sb + (1024 + w * ROW_BUF) * 8 + i * 2048, x + (size_t)(z_row(c.r * 8 + w) + i * 1024) * D_, 2048, BAR(B_ROWS));
      bulk_load_e(c.sb + SM_GW + w * 256, gw + w * 128, 256, BAR(B_ROWS));
    }
    asm volatile("setmaxnreg.inc.sync.aligned.u32 %0;" :: "n"(REG_F));
    c.lane = lane_id();
    uint32_t wa[16][4], wb[16][4], wv[16][4];
    TR(-2, 4);
    fft_rows_fwd((float2*)smraw, (const __nv_bfloat16*)(smraw + SM_GW), c.r, threadIdx.x, BAR(B_ROWS), BAR(B_FREE), [&](int e) { TR(-2, e); });
    mbar_arrive_warp(BAR(B_P1));
    TR(-2, 0);
    if (tid_now() == 0) TL2(1);
    __syncwarp();
    mbar_spin(BAR(B_WFULL + c.m), 0);
    TR(-2, 1);
    if ((tid_now() & 127) == 0) TL2(16);
    __syncwarp();
    {
      const uint32_t st = c.sb + c.m * ST_WG + frag_off(c.w, c.lane);
#pragma unroll
      for (int k = 0; k < 16; k++) ldsm4t(wb[k], st + k * 2048);
#pragma unroll
      for (int k = NP; k < 16; k++) ldsm4t(wa[k], st + (16 + k - NP) * 2048);
#pragma unroll
      for (int k = 0; k < NV; k++) ldsm4t(wv[k], st + (32 - NP + k) * 2048);
      mbar_arrive_warp(BAR(B_WREAD));
      TR(-2, 2);
#pragma unroll
      for (int k = 0; k < NP; k++) ldsm4t(wa[k], c.sb + SM_POOL + c.m * NP * 2048 + frag_off(c.w, c.lane) + k * 2048);
      bar_sync(NB_XCH, 256);
#pragma unroll
      for (int k = 0; k < NP; k++) sts128(c.sb + SM_POOL + c.m * 2048 + c.w * 512 + c.lane * 16 + k * 4096, make_uint4(wa[k][0], wa[k][1], wa[k][2], wa[k][3]));
    }
    TR(-2, 3);
    if (tid_now() == 0) TL2(12);
    __syncwarp();
    asm volatile("barrier.cluster.wait;" ::: "memory");
    uint32_t t16 = c.m * 2048 + c.w * 512 + c.lane * 16;
    uint32_t pk = (c.m * NHV * 2048 + frag_off(c.w, c.lane)) | (tile_off(2 * (c.w & 1), c.lane) << 16) | ((c.lane & 12) ? 0u : 0x80000000u);
    const uint32_t dx1 = desc_lo(c.sb + SM_XT + c.m * 4096), dh = desc_lo(c.sb + SM_HV + c.m * NHV * 2048);
    for (int s = -2; ; s++) {
      t16 = vary(t16, s, c.sb); pk = vary(pk, s, c.sb);
      const uint32_t dx = dx1 - (X01 && s == X01 - 3 ? (SM_XT - SM_WO) / 16 : 0);
      auto ldp = [&](int k0, int k1, int d, int back = 0) {
#pragma unroll
        for (int k = k0; k < k1; k++) lds_frag(wa[k], (k < k0 + d - back ? t16 : dep(t16, wa[k < d ? 0 : k - d][0], c.sb)) + (c.sb + SM_POOL + k * 4096));
      };
      if (s >= 0) {
        uint32_t af[16][4], bf[4][4], wo;
        const uint32_t tab = ((t16 >> 3) & 0x1C0) + (c.sb + SM_TAB + (s & 1) * 512);
        const char* pa;
        mem_proj(wa, wb, wv, af, wo, pa, tab, t16, pk, c, s);
        const uint32_t t0 = clock_lo();
        t16 = dep(t16, t0, c.sb);
        auto ldwo = [&](int f) { ldsm4t(af[f], (f < WO_D ? wo : dep(wo, af[f < WO_D ? 0 : f - WO_D][0], c.sb)) + (c.sb + SM_WO + (f & 1) * 32768 + (f >> 1) * 2048)); };
        {
          const uint32_t tg = s >> 1, vm = t16 >> 1, chk = (~t16 >> 4) & 1;
#pragma unroll
          for (int f = WO_0; f < WO_1; f++) ldwo(f);
          delay_until(t0 + DLY_V);
          uint2 v0 = ld_poll2(pa), v1 = ld_poll2(pa + 1024), v2 = ld_poll2(pa + 2048), v3 = ld_poll2(pa + 3072);
          TR(s, 3);
#pragma unroll
          for (int f = WO_1; f < 16 - WO_L; f++) ldwo(f);
          TR(s, 4);
          uint32_t n = 0;
          while (true) {
            sts64(vm + (c.sb + SM_VM), sum4(v0.x, v1.x, v2.x, v3.x), sum4(v0.y, v1.y, v2.y, v3.y));
            if (arrive_if_clear(stale1(stale1(stale2(v0.x, v1.x, tg), v2.x, tg), v3.x, tg), chk, NB_VM, 384)) break;
            v0 = ld_poll2(pa); v1 = ld_poll2(pa + 1024); v2 = ld_poll2(pa + 2048); v3 = ld_poll2(pa + 3072);
            n++; CNT(3);
          }
          TR(s, 12); TRV(s, 15, n);
        }
        const uint32_t ob = dep(dep(t16 & 511, af[14 - WO_L][0], c.sb), af[15 - WO_L][0], c.sb);
        uint32_t l4 = ob >> 2;
        const uint32_t bit = (t16 & 48) ? 0u : 1u;
        mbar_spin_if(BAR(B_XFULL), s & 1, s + 2 < XEND);
        bar_sync(NB_OM, 384);
        TR(s, 5);
#pragma unroll
        for (int i = 0; i < 4; i++) ldsm4t(bf[i], ob + (c.sb + SM_OM + i * 512));
        uint2 sum = lds64(((t16 >> 1) & 24) + (c.sb + SM_SUM));
        if (OM_F) sched_fence(c.sb);
        float d[WO_C][4] = {};
        uint4 d0, d1;
#pragma unroll
        for (int f = 0; f < 16; f++) {
          mma_a(d[f % WO_C], af[f], bf[f >> 2][f & 2], bf[f >> 2][(f & 2) + 1]);
          if (f >= WO_C && f < WO_C + WO_L) {
            const int l = 16 - WO_L + f - WO_C;
            ldsm4t(af[l], (WO_LD ? dep(wo, __float_as_uint(d[(f + 1) % WO_C][0]), c.sb) : wo) + (c.sb + SM_WO + (l & 1) * 32768 + (l >> 1) * 2048));
          }
          if (f == WO_T) {
            const uint32_t tb2 = dep((t16 >> 3) & 0x1C0, __float_as_uint(d[f % WO_C][0]), c.sb) + (c.sb + SM_TAB + (s & 1) * 512);
            d0 = lds128(tb2 + 32); d1 = lds128(tb2 + 48);
          }
          if (f >= PL_WA && f < PL_WA + PL_W) lds_frag(wa[f - PL_WA], (PL_WD ? dep(t16, __float_as_uint(d[(f + PL_WD) % WO_C][0]), c.sb) : t16) + (c.sb + SM_POOL + (f - PL_WA) * 4096));
          if (PL_W && PL_WF && f == PL_WA + PL_W - 1) sched_fence(c.sb);
          if (f == 4) { sum.x = dep(sum.x, __float_as_uint(d[0][0]), c.sb); sum.y = dep(sum.y, __float_as_uint(d[0][0]), c.sb); }
        }
        if (PL_W && !PL_WF) {
          uint32_t all = 0;
#pragma unroll
          for (int k = 0; k < PL_W; k++) all ^= wa[k][0];
          l4 = dep(l4, all, c.sb);
        }
        char* dst[4] = {mk_ptr(d0.x | l4, d0.y), mk_ptr(d0.z | l4, d0.w), mk_ptr(d1.x | l4, d1.y), mk_ptr(d1.z | l4, d1.w)};
        const float i0 = rcp(__uint_as_float(sum.x)), i1 = rcp(__uint_as_float(sum.y));
#pragma unroll
        for (int i = 0; i < 4; i++) {
          const int t = i >> 1, e = 2 * (i & 1);
          const float y0 = WO_C == 2 ? d[t][e] : d[t][e] + d[(t + 2) % WO_C][e], y1 = WO_C == 2 ? d[t][e + 1] : d[t][e + 1] + d[(t + 2) % WO_C][e + 1];
          st_pub(dst[i], put_tag(pack_bf16(y0 * i0, y1 * i1), bit, s >> 1));
        }
        if (ANCH2) sts32(c.sb + SM_SUM + 64, clock_lo());
        mbar_arrive_warp(BAR(B_E2TRIG));
        TR(s, 6);
        sched_fence(c.sb);
        if (W_E2 == 2) mbar_spin(BAR(B_E2TRIG), s & 1);
        if (s == NSEG - 1) break;
        ldp(PL_W, PL_0, PL_D);
      } else mbar_spin(BAR(B_XFULL), s & 1);
      if (s + 2 < XEND) {
        float xa[16];
        uint32_t q[4];
        if (W_E2 == 1 && s >= 0) mbar_spin(BAR(B_E2TRIG), s & 1);
        if (W_PV && s >= 0) mbar_spin(BAR(B_PVDONE), s & 1);
        TR(s, 7);
        constexpr int S1 = ORDER ? 0 : 2, S2 = ORDER == 0 ? 0 : ORDER == 1 ? 2 : 1, S3 = ORDER == 2 ? 2 : 1;
        if (ORDER) issue_qk<0, 16>(xa, wb, vary(dx, s, c.sb)); else issue_v(xa, wv, vary(dx, s, c.sb), vary(dh, s, c.sb));
        if (IS_F) sched_fence(c.sb);
        ldp(PL_0, PL_1, PL_D1);
        const uint32_t land = (t16 ^ ((t16 >> 3) & 0x60)) + vary(c.sb + SM_LAND + c.b * 4096, s, c.sb);
        TR(s, 14);
        mbar_spin(BAR(B_LFREE), s & 1);
        TR(s, 15);
        WG_WAIT(0);
        TR(s, 8);
        park_own<S1 == 2>(q, xa, land, S1, c.sb);
        if (W_PUB == 4 && s >= 0) mbar_spin(BAR(B_PUB), s & 1);
        if (ORDER == 1) issue_v(xa, wv, vary(dx, s, c.sb + 32), vary(dh, s, c.sb)); else issue_qk<0, 16>(xa, ORDER ? wa : wb, vary(dx, s, c.sb + 32));
        if (IS_F) sched_fence(c.sb);
        ldp(PL_1, PL_2, PL_D1);
        if (W_PUB == 1) mbar_spin_if(BAR(B_PUB), s & 1, s >= 0);
        uint32_t tp = clock_lo(), q1[4] = {q[0], q[1], q[2], q[3]};
        if (W_PUB != 3) park_peer(q, land, S1, c);
        ldp(PL_2, NP - PL_L, PL_D1);
        TR(s, 13);
        WG_WAIT(0);
        TR(s, 9);
        park_own<S2 == 2>(q, xa, land, S2, c.sb);
        if (ORDER == 2) issue_v(xa, wv, vary(dx, s, c.sb + 64), vary(dh, s, c.sb));
        else {
          issue_qk<0, PL_L ? NP - PL_L : 16>(xa, wa, vary(dx, s, c.sb + 64));
          ldp(NP - PL_L, NP, PL_E);
          if (PL_L) issue_qk<NP - PL_L, 16>(xa, wa, vary(dx, s, c.sb + 64));
        }
        if ((W_PUB == 2 || W_PUB == 3) && s >= 0) { mbar_spin(BAR(B_PUB), s & 1); tp = clock_lo(); }
        if (W_PUB == 3) park_peer(q1, land, S1, c);
        if (DLY_S && s >= 0) delay_until(tp + DLY_S);
        park_peer(q, land, S2, c);
        WG_WAIT(0);
        TR(s, 10);
        mbar_arrive_warp(BAR(B_XEMPTY));
        park_own<S3 == 2>(q, xa, land, S3, c.sb);
        park_peer(q, land, S3, c);
        TR(s, 11);
      } else ldp(PL_0, NP, 1);
    }
    asm volatile("setmaxnreg.dec.sync.aligned.u32 128;");
    const int tid = tid_now(), lane = tid & 31, tile = tile_of(c), m0 = (tile >> 3) * 128, n0 = (tile & 7) * 128;
    float acc[64];
#pragma unroll
    for (int i = 0; i < 64; i++) acc[i] = 0.f;
    const uint32_t rel = mapa(BAR(B_GEMPTY), lane & 1), la = desc_lo(c.sb + c.m * 8192), lb = ((c.sb + 16384) & 0x3FFFF) >> 4 | (8192 >> 4) << 16;
    const bool relon = (tid & 127) < 2;
    const float g0 = __ldcg(g_gate + m0 + (tid >> 5) * 16 + (lane >> 2)), g1 = __ldcg(g_gate + m0 + (tid >> 5) * 16 + (lane >> 2) + 8);
    uint32_t o = SM_XT, st = 0, ph = 0, prev = 0;
    if (tid == 0) TL(9);
    __syncwarp();
#pragma unroll 1
    for (int kb = 0; kb < 64; kb++, o = next_stage(o)) {
      mbar_lim(BAR(B_GFULL + st), ph);
      WG_FENCE();
#pragma unroll
      for (int k = 0; k < 4; k++) wgmma_ss_n128_tb(acc, desc128(la + (o >> 4) + k * 2), desc128(lb + (o >> 4) + k * 128));
      WG_COMMIT();
      WG_WAIT(1);
      arrive_remote_if(rel + 8 * prev, relon && kb > 0 && kb < 60);
      prev = st;
      if (++st == 5) { st = 0; ph ^= 1; }
    }
    WG_WAIT(0);
    if (tid == 0) TL(4);
    __syncwarp();
    const uint32_t row = (tid >> 5) * 2048 + (lane & 15) * 128 + (((lane >> 4) ^ (lane & 7)) << 4);
    mbar_lim(BAR(B_BT), 0);
    if (EPI) asm volatile("fence.proxy.async.global;" ::: "memory");
#pragma unroll
    for (int hf = 0; hf < 2; hf++) {
      uint32_t b[4][4];
      if (!EPI) for (int t = 0; t < 4; t++) ldsm4(b[t], (row ^ t * 32) + (c.sb + SM_BT + hf * 16384));
#pragma unroll
      for (int t = 0; t < 4; t++) {
        uint32_t y[4];
#pragma unroll
        for (int i = 0; i < 4; i++) {
          const float* a = acc + 32 * hf + 8 * t + 2 * i, g = i & 1 ? g1 : g0;
          y[i] = EPI ? pack_bf16(g * a[0], g * a[1]) : pack_bf16(fmaf(g, a[0], __uint_as_float(b[t][i] << 16)), fmaf(g, a[1], __uint_as_float(b[t][i] & 0xFFFF0000u)));
        }
        stsm4<false>((row ^ t * 32) + (c.sb + SM_BT + hf * 16384), y[0], y[1], y[2], y[3]);
      }
      FENCE_ASYNC_SMEM();
      __syncwarp();
      tma2d_out_e(&tout, n0 + hf * 64, m0 + (c.m * 4 + c.w) * 16, c.sb + SM_BT + hf * 16384 + (c.m * 4 + c.w) * 2048);
    }
    asm volatile("cp.async.bulk.commit_group; cp.async.bulk.wait_group" WAITRD " 0;" ::: "memory");
    if (tid == 0) TL(11);
    return;
  }
  const bool col = c.r >= 128;
  const int tile = col ? 0 : tile_of(c);
  const int q0 = col ? 256 - 16 * NCR + (c.r - 128) * 4 + c.m : tile < 120 ? tile : 256, dq = col ? 16 : 120, qe = col ? 256 : 256 - 16 * NCR;
  const uint32_t zs = c.sb + (col ? COL_Z + c.m * 32768 : SM_BT), zb = BAR(B_Z + c.m);
  auto load_z = [&](int q) { if (c.w == 0 && q < qe) { mbar_expect_e(zb, 32768); tma2d_e(zs, &tz, q * 64, 0, zb); } };
  asm volatile("fence.proxy.async.global;" ::: "memory");
  load_z(q0);
  uint32_t ph = 0;
#pragma unroll 1
  for (int q = q0; q < qe; q += dq, ph ^= 1) {
    mbar_lim(zb, ph);
    const int p = q * 4 + c.w;
    if (EXP_INV) fft_rows_inv(zs, (float2*)(smraw + (col ? 8192 + c.m * ROW_BUF * 16 : SM_MEM)) + c.w * (ROW_BUF / 2), (const float2*)(smraw + (col ? 0 : SM_TW)), p, tid_now() & 31, EPI ? out : g_b,
                              [&]() { bar_sync(5 + c.m, 128); load_z(q + dq); });
    else { bar_sync(5 + c.m, 128); load_z(q + dq); }
  }
  asm volatile("fence.acq_rel.gpu;" ::: "memory");
  __syncwarp();
  { const int q = q0 + (tid_now() & 31) * dq; if (q < qe) asm volatile("red.relaxed.gpu.global.add.u32 [%0], 1;" :: "l"(g_ctl + C_ROWS + (q >> 5) * 32) : "memory"); }
  if (tid_now() == 256) { if (col) TL(27); else TL(3); }
  __syncwarp();
  if (!col && c.w == 0) {
    await_count(g_ctl + C_ROWS + ((tile >> 3) & 7) * 32, 128);
    mbar_expect_e(BAR(B_BT), EPI ? 0 : 32768);
    if (!EPI) for (int i = 0; i < 2; i++) tma2d_e(c.sb + SM_BT + i * 16384, &tb, (tile & 7) * 128 + i * 64, (tile >> 3) * 128, BAR(B_BT));
    if (tid_now() == 256) TL(5);
  }
}

typedef CUresult (*EncodeFn)(CUtensorMap*, CUtensorMapDataType, cuuint32_t, void*, const cuuint64_t*, const cuuint64_t*,
                             const cuuint32_t*, const cuuint32_t*, CUtensorMapInterleave, CUtensorMapSwizzle,
                             CUtensorMapL2promotion, CUtensorMapFloatOOBfill);

void make_map(EncodeFn enc, CUtensorMap* tm, const void* p, int rank, const cuuint64_t* dims, const cuuint64_t* strides, const cuuint32_t* box, bool swz = true) {
  const cuuint32_t es[4] = {1, 1, 1, 1};
  enc(tm, CU_TENSOR_MAP_DATA_TYPE_BFLOAT16, rank, (void*)p, dims, strides, box, es, CU_TENSOR_MAP_INTERLEAVE_NONE,
      swz ? CU_TENSOR_MAP_SWIZZLE_128B : CU_TENSOR_MAP_SWIZZLE_NONE, CU_TENSOR_MAP_L2_PROMOTION_L2_128B, CU_TENSOR_MAP_FLOAT_OOB_FILL_NONE);
}
void make_map2(EncodeFn enc, CUtensorMap* tm, const void* p, uint64_t cols, uint64_t rows, uint32_t boxrows) {
  const cuuint64_t dims[2] = {cols, rows}, strides[1] = {cols * 2};
  const cuuint32_t box[2] = {64, boxrows};
  make_map(enc, tm, p, 2, dims, strides, box);
}

}

extern "C" void kernel_launch(void* const* d_in, const int* in_sizes, int n_in, void* d_out, int out_size) {
  (void)in_sizes; (void)n_in; (void)out_size;
  const __nv_bfloat16* x = (const __nv_bfloat16*)d_in[0];
  const __nv_bfloat16* mem0 = (const __nv_bfloat16*)d_in[1];
  const __nv_bfloat16* gw = (const __nv_bfloat16*)d_in[10];

  EncodeFn enc = nullptr;
  cudaDriverEntryPointQueryResult qr;
  cudaGetDriverEntryPoint("cuTensorMapEncodeTiled", (void**)&enc, cudaEnableDefault, &qr);
  void *p_ox, *p_b, *p_z, *p_mail;
  cudaGetSymbolAddress(&p_ox, g_ox); cudaGetSymbolAddress(&p_b, g_b); cudaGetSymbolAddress(&p_z, g_z); cudaGetSymbolAddress(&p_mail, g_mail);
  CUtensorMap tq, tk, tv, tv16, to, tx, twr, twi, ta, tw, tb, tout, tz;
  make_map2(enc, &tq, d_in[2], 4096, 1024, 64);
  make_map2(enc, &tk, d_in[3], 4096, 1024, 64);
  make_map2(enc, &tv, d_in[4], 4096, 1024, 64);
  make_map2(enc, &tv16, d_in[4], 4096, 1024, 16);
  make_map2(enc, &to, d_in[5], 1024, 4096, 128);
  make_map2(enc, &tw, d_in[5], 1024, 4096, 64);
  make_map2(enc, &ta, p_ox, 4096, 2048, 64);
  make_map2(enc, &tb, p_b, 1024, 2048, 128);
  make_map2(enc, &tout, d_out, 1024, 2048, 16);
  make_map2(enc, &tz, p_z, 16384, 257, 256);
  {
    const cuuint64_t dims[4] = {64, 8, 16, 256}, strides[3] = {2048, 128, 16384};
    const cuuint32_t box[4] = {64, 8, 8, 2};
    make_map(enc, &tx, x, 4, dims, strides, box);
  }
  {
    const cuuint64_t dims[2] = {8 * 513, 256}, strides[1] = {8 * 513 * 2};
    const cuuint32_t box[2] = {8, 256};
    make_map(enc, &twr, d_in[8], 2, dims, strides, box, false);
    make_map(enc, &twi, d_in[9], 2, dims, strides, box, false);
  }
  cudaFuncSetAttribute(chain_kernel, cudaFuncAttributeMaxDynamicSharedMemorySize, CHAIN_SMEM);

  cudaStream_t st = cudaStreamPerThread;
  char* mail = (char*)(((uintptr_t)p_mail + M_REG - 1) & ~(uintptr_t)(M_REG - 1));
  chain_kernel<<<132, 512, CHAIN_SMEM, st>>>(tq, tk, tv, tv16, to, tx, twr, twi, ta, tw, tb, tout, tz, mem0, mail, x, gw, (__nv_bfloat16*)d_out);
}
```

```cpp
#include <cuda_runtime.h>
#include <cuda_bf16.h>
#include <cuda.h>
#include <stdint.h>

#define DLY_E1 300
#define DLY_V 330
#define DLY_E2 320
#define DLY_E3 500
#define DLY_X 1
#define DLY_S 0
#define DLY_F 150
#define VM_AT 1
#define VM_F 0
#define OM_F 1
#define SXX_IN 0
#define C1_AT 1
#define NLAG 4
#define WO_D 2
#define WO_0 2
#define WO_1 10
#define PL_0 8
#define PL_1 10
#define PL_D 2
#define PL_L 0
#define DUAL 0
#define HV_D 3
#define DLY_FK 0
#define QX_SM 0
#define REG_F 216
#define REG_H 24
#define SC_F 1
#define E2_F 1
#define KVQ_AT 0
#define DLY_K 0
#define X_AT 2
#define W_PV 0
#define PL_2 10
#define BF_E 3
#define PL_E 2
#define ORDER 1
#define SSPOS 1
#define W_PUB 1
#define FIN_AT 5
#define AWARE 1
#define NPROBE 2
#define NP_ 12
#define USE_PDL 1
#define DLY_GRP 3000
#define P2_BULK 0
#define EXP_NV 4
#define EXP_NK 4
#define EXP_CHK 1
#define EXP_NXT 2
#define EXP_PEER 1
#define EXP_FIN 7
#define EXP_NWG 16
#define ANCH2 1
#define XF_AT 1
#define IS_F 1
#define PL_D1 2
#define W_E2 0
#define V_TMA 2
#define V_W 2
#define RED_L 3
#define RED_T 1
#define RED_P 1
#define DLY_E3B 0
#define HV_E 0
#define HV_R 4
#define HOLD 0
#define PACE 550
#define PACE0 0
#define EXP_ST 7
#define HOLD_AT NPROBE
#define WO_AT 38
#define WO_P 2
#define DLY_SEL 500
#define P1_AT 1
#define EXP_ZG 1
#define TMA_W tma2d_once
#define BULK_F bulk_once
#define TMA_O tma2d_e
#define PACE_Z 500
#define PACE_F 800
#define EXP_INV 1
#define VF_AT 0
#define UP_F 1
#define WO_L (12 - NP_)
#define WO_C 4
#define WO_T 3
#define WO_LD 0
#define EXP_LIN 0
#define PL_W 0
#define PL_WA 4
#define PL_WD 0
#define PL_WF 1
#define STAG 0
#define EXP_FL 0
#define DLY_FS 0
#define DLY_F2 0
#define LROT 0
#define PF_D 4
#define PF_A 1
#define PF_B 1
#define SIDE 1
#define ROLE 1
#define LOOSE 0x765498
#define E1OFF 1
#define EVOFF E1OFF
#define EPI 0
#define WAITRD ".read"
#define X01 1
#define E3I 1
#define START 1000
#define WUNR 1
#define WO_N 0
#define WO_H 0
#define PL_2B 1
#define DLY_P 430
#define LP_IN 1
#define LF_AT 1
#define FINE 0
#define LAG_F 0
#define E30 1
#define WO_S 1
#define POOL_AT 8
#define COL_DLY 0
#define WO_F 0
#define PAD0 0
#define PAD2 0
#define PAD3 0
#define WO_X 0
#define PRIOR 12
#define EARLY 1
#define SEL_AT 3000
#define CUNR 1
#define FUNR 0
#define ZINIT 1
#define ZDLY 0
#define NCR 3
#define GATE 1
#define LASTM 1
#define PRE_AT B_SC

namespace {
constexpr int wunr = WUNR;

constexpr int S_ = 2048, D_ = 1024, NSEG = 64;
constexpr uint32_t SENT = 0xFFFFFFFFu;
constexpr int NSLOT = 4;

constexpr uint32_t M_REG = 1 << 21, M_E3 = 64 * 16384, M_KVQ = M_E3 + 4 * 8192, M_SEL = M_KVQ + 32 * 24576;
__device__ __align__(1024) unsigned char g_mail[5 * M_REG];
constexpr int C_P1 = 0, C_COLS = C_P1 + 32, C_EARLY = C_COLS + 32, C_LAST = C_EARLY + 32, C_ROWS = C_LAST + 128, C_END = C_ROWS + 8 * 32;
__device__ __align__(1024) uint32_t g_ctl[C_END];
#define CLK(i)
#define TL(i)
#define TL2(i)
#define FT(i, v)
#define CNT(i)
__device__ __align__(1024) __nv_bfloat16 g_ox[S_ * 4096];
__device__ __align__(1024) float2 g_z[257 * 4096];
__device__ __align__(1024) __nv_bfloat16 g_b[S_ * D_];
__device__ float g_gate[S_];
__device__ __align__(1024) float2 g_tw[1024];

#define TRV(s, ev, val)
#define TR(s, ev)
#define TRSYNC(ev)
__device__ __forceinline__ uint32_t smem_u32(const void* p) { return (uint32_t)__cvta_generic_to_shared(p); }
__device__ __forceinline__ void watchdog(uint32_t& n, uint32_t limit) {
  asm volatile("{ .reg .pred p; add.u32 %0, %0, 1; setp.gt.u32 p, %0, %1; @p trap; }" : "+r"(n) : "r"(limit));
}
__device__ __forceinline__ void mbar_init(uint32_t bar, uint32_t cnt) {
  asm volatile("mbarrier.init.shared::cta.b64 [%0], %1;" :: "r"(bar), "r"(cnt) : "memory");
}
__device__ __forceinline__ void mbar_arrive_warp(uint32_t bar) {
  __syncwarp();
  asm volatile("{ .reg .pred p; elect.sync _|p, 0xffffffff; @p mbarrier.arrive.shared::cta.b64 _, [%0]; }" :: "r"(bar) : "memory");
}
__device__ __forceinline__ uint32_t clock_lo() {
  uint32_t r; asm volatile("{ .reg .u64 c; .reg .u32 h; mov.u64 c, %%clock64; mov.b64 {%0, h}, c; }" : "=r"(r) :: "memory"); return r;
}
__device__ __forceinline__ void delay_until(uint32_t t) {
  asm volatile("{ .reg .pred p; .reg .u64 c; .reg .u32 l, h;\n"
               "DLY: mov.u64 c, %%clock64; mov.b64 {l, h}, c; sub.s32 l, l, %0; setp.lt.s32 p, l, 0; @p bra.uni DLY; }" :: "r"(t) : "memory");
}
__device__ __forceinline__ void delay_fine(uint32_t t) {
  delay_until(t);
}
__device__ __forceinline__ void delay_cycles(uint32_t n) { delay_until(clock_lo() + n); }
__device__ __forceinline__ void sched_fence(uint32_t z) {
  asm volatile("{ .reg .pred p; setp.eq.u32 p, %0, 0x7fff0000; @p pmevent 1; }" :: "r"(z) : "memory");
}
__device__ __forceinline__ void pdl_wait() { asm volatile("griddepcontrol.wait;" ::: "memory"); }
__device__ __forceinline__ void pdl_launch() { asm volatile("griddepcontrol.launch_dependents;" ::: "memory"); }
__device__ __forceinline__ float ex2(float x) { float r; asm("ex2.approx.ftz.f32 %0, %1;" : "=f"(r) : "f"(x)); return r; }
__device__ __forceinline__ float rcp(float x) { float r; asm("rcp.approx.ftz.f32 %0, %1;" : "=f"(r) : "f"(x)); return r; }
__device__ __forceinline__ void mbar_expect(uint32_t bar, uint32_t bytes) {
  asm volatile("mbarrier.arrive.expect_tx.shared::cta.b64 _, [%0], %1;" :: "r"(bar), "r"(bytes) : "memory");
}
__device__ __forceinline__ bool mbar_try(uint32_t bar, uint32_t ph) {
  uint32_t ok;
  asm volatile("{ .reg .pred p; mbarrier.try_wait.parity.shared::cta.b64 p, [%1], %2; selp.u32 %0, 1, 0, p; }"
               : "=r"(ok) : "r"(bar), "r"(ph) : "memory");
  return ok;
}
__device__ __forceinline__ void mbar_wait(uint32_t bar, uint32_t ph) {
  uint32_t n = 0;
  while (!mbar_try(bar, ph)) { watchdog(n, (1u << 20)); }
}
__device__ __forceinline__ void mbar_spin(uint32_t bar, uint32_t ph) { while (!mbar_try(bar, ph)) {} }
__device__ __forceinline__ void mbar_spin_if(uint32_t bar, uint32_t ph, bool on) {
  asm volatile("{ .reg .pred p, q; setp.ne.u32 p, %2, 0;\n"
               "SPN: setp.eq.u32 q, 0, 0; @p mbarrier.try_wait.parity.shared::cta.b64 q, [%0], %1; @!q bra.uni SPN; }" :: "r"(bar), "r"(ph), "r"((uint32_t)on) : "memory");
}
__device__ __forceinline__ void mbar_spin2_if(uint32_t bar, uint32_t bar2, uint32_t ph, bool on) {
  asm volatile("{ .reg .pred p, q, r; setp.ne.u32 p, %3, 0;\n"
               "SPN: setp.eq.u32 q, 0, 0; setp.eq.u32 r, 0, 0; @p mbarrier.try_wait.parity.shared::cta.b64 q, [%0], %2;\n"
               "@p mbarrier.try_wait.parity.shared::cta.b64 r, [%1], %2; and.pred q, q, r; @!q bra.uni SPN; }" :: "r"(bar), "r"(bar2), "r"(ph), "r"((uint32_t)on) : "memory");
}
__device__ __forceinline__ void mbar_spin_cluster(uint32_t bar, uint32_t ph) {
  uint32_t ok;
  do {
    asm volatile("{ .reg .pred p; mbarrier.try_wait.parity.acquire.cluster.shared::cta.b64 p, [%1], %2; selp.u32 %0, 1, 0, p; }"
                 : "=r"(ok) : "r"(bar), "r"(ph) : "memory");
  } while (!ok);
}
__device__ __forceinline__ void tma2d(uint32_t dst, const CUtensorMap* tm, int c0, int c1, uint32_t bar) {
  asm volatile("cp.async.bulk.tensor.2d.shared::cluster.global.mbarrier::complete_tx::bytes [%0], [%1, {%3, %4}], [%2];"
               :: "r"(dst), "l"(tm), "r"(bar), "r"(c0), "r"(c1) : "memory");
}
__device__ __forceinline__ void mbar_expect_e(uint32_t bar, uint32_t bytes) {
  asm volatile("{ .reg .pred p; elect.sync _|p, 0xffffffff; @p mbarrier.arrive.expect_tx.shared::cta.b64 _, [%0], %1; }" :: "r"(bar), "r"(bytes) : "memory");
}
__device__ __forceinline__ void tma2d_e(uint32_t dst, const CUtensorMap* tm, int c0, int c1, uint32_t bar) {
  asm volatile("{ .reg .pred p; elect.sync _|p, 0xffffffff;\n"
               "@p cp.async.bulk.tensor.2d.shared::cluster.global.mbarrier::complete_tx::bytes [%0], [%1, {%3, %4}], [%2]; }"
               :: "r"(dst), "l"(tm), "r"(bar), "r"(c0), "r"(c1) : "memory");
}
__device__ __forceinline__ void tma2d_out_e(const CUtensorMap* tm, int c0, int c1, uint32_t src) {
  if (EPI) asm volatile("{ .reg .pred p; elect.sync _|p, 0xffffffff;\n"
               "@p cp.reduce.async.bulk.tensor.2d.global.shared::cta.add.bulk_group [%0, {%2, %3}], [%1]; }" :: "l"(tm), "r"(src), "r"(c0), "r"(c1) : "memory");
  else asm volatile("{ .reg .pred p; elect.sync _|p, 0xffffffff;\n"
               "@p cp.async.bulk.tensor.2d.global.shared::cta.bulk_group [%0, {%2, %3}], [%1]; }" :: "l"(tm), "r"(src), "r"(c0), "r"(c1) : "memory");
}
__device__ __forceinline__ void tma2d_once(uint32_t dst, const CUtensorMap* tm, int c0, int c1, uint32_t bar) {
  asm volatile("{ .reg .pred p; .reg .b64 h; createpolicy.fractional.L2::evict_first.b64 h; elect.sync _|p, 0xffffffff;\n"
               "@p cp.async.bulk.tensor.2d.shared::cluster.global.mbarrier::complete_tx::bytes.L2::cache_hint [%0], [%1, {%3, %4}], [%2], h; }"
               :: "r"(dst), "l"(tm), "r"(bar), "r"(c0), "r"(c1) : "memory");
}
__device__ __forceinline__ void bulk_once(uint32_t dst, const void* src, uint32_t bytes, uint32_t bar) {
  asm volatile("{ .reg .pred p; .reg .b64 h; createpolicy.fractional.L2::evict_first.b64 h; elect.sync _|p, 0xffffffff;\n"
               "@p cp.async.bulk.shared::cluster.global.mbarrier::complete_tx::bytes.L2::cache_hint [%0], [%1], %2, [%3], h; }"
               :: "r"(dst), "l"(src), "r"(bytes), "r"(bar) : "memory");
}
__device__ __forceinline__ void tma4d_e(uint32_t dst, const CUtensorMap* tm, int c2, int c3, uint32_t bar) {
  asm volatile("{ .reg .pred p; elect.sync _|p, 0xffffffff;\n"
               "@p cp.async.bulk.tensor.4d.shared::cluster.global.mbarrier::complete_tx::bytes [%0], [%1, {0, 0, %3, %4}], [%2]; }"
               :: "r"(dst), "l"(tm), "r"(bar), "r"(c2), "r"(c3) : "memory");
}
__device__ __forceinline__ void bulk_load_e(uint32_t dst, const void* src, uint32_t bytes, uint32_t bar) {
  asm volatile("{ .reg .pred p; elect.sync _|p, 0xffffffff;\n"
               "@p cp.async.bulk.shared::cluster.global.mbarrier::complete_tx::bytes [%0], [%1], %2, [%3]; }"
               :: "r"(dst), "l"(src), "r"(bytes), "r"(bar) : "memory");
}
__device__ __forceinline__ void prefetch2d_e(const CUtensorMap* tm, int c0, int c1) {
  asm volatile("{ .reg .pred p; elect.sync _|p, 0xffffffff;\n"
               "@p cp.async.bulk.prefetch.tensor.2d.L2.global [%0, {%1, %2}]; }" :: "l"(tm), "r"(c0), "r"(c1) : "memory");
}
__device__ __forceinline__ void st_pub4(void* p, uint4 v) {
  asm volatile("st.relaxed.gpu.global.v4.u32 [%0], {%1,%2,%3,%4};" :: "l"(p), "r"(v.x), "r"(v.y), "r"(v.z), "r"(v.w) : "memory");
}
__device__ __forceinline__ void st_pub_if(void* p, uint32_t v, bool on) {
  asm volatile("{ .reg .pred p; setp.ne.u32 p, %2, 0; @p st.relaxed.gpu.global.u32 [%0], %1; }" :: "l"(p), "r"(v), "r"((uint32_t)on) : "memory");
}
__device__ __forceinline__ uint32_t mapa(uint32_t a, uint32_t r) {
  uint32_t d; asm volatile("mapa.shared::cluster.u32 %0, %1, %2;" : "=r"(d) : "r"(a), "r"(r)); return d;
}
__device__ __forceinline__ void st_async4(uint32_t a, uint32_t x, uint32_t y, uint32_t z, uint32_t w, uint32_t bar) {
  asm volatile("st.async.shared::cluster.mbarrier::complete_tx::bytes.v4.u32 [%0], {%1,%2,%3,%4}, [%5];"
               :: "r"(a), "r"(x), "r"(y), "r"(z), "r"(w), "r"(bar) : "memory");
}
__device__ __forceinline__ uint4 ld_poll(const void* p) {
  uint4 v;
  asm volatile("ld.volatile.global.v4.u32 {%0,%1,%2,%3}, [%4];" : "=r"(v.x), "=r"(v.y), "=r"(v.z), "=r"(v.w) : "l"(p) : "memory");
  return v;
}
__device__ __forceinline__ uint2 ld_poll2(const void* p) {
  uint2 v; asm volatile("ld.volatile.global.v2.u32 {%0,%1}, [%2];" : "=r"(v.x), "=r"(v.y) : "l"(p) : "memory"); return v;
}
__device__ __forceinline__ void st_pub2(void* p, uint32_t a, uint32_t b) {
  asm volatile("st.relaxed.gpu.global.v2.u32 [%0], {%1,%2};" :: "l"(p), "r"(a), "r"(b) : "memory");
}
__device__ __forceinline__ uint32_t ld_poll1(const void* p) {
  uint32_t v; asm volatile("ld.volatile.global.u32 %0, [%1];" : "=r"(v) : "l"(p) : "memory"); return v;
}
__device__ __forceinline__ uint32_t ld_acquire(const uint32_t* p) {
  uint32_t v; asm volatile("ld.acquire.gpu.global.u32 %0, [%1];" : "=r"(v) : "l"(p) : "memory"); return v;
}
__device__ __forceinline__ void st_pub(void* p, uint32_t v) {
  asm volatile("st.relaxed.gpu.global.u32 [%0], %1;" :: "l"(p), "r"(v) : "memory");
}
__device__ __forceinline__ uint32_t lds32(uint32_t a) {
  uint32_t v; asm volatile("ld.shared.u32 %0, [%1];" : "=r"(v) : "r"(a) : "memory"); return v;
}
__device__ __forceinline__ int race_init(void* p0, void* p1, uint32_t val) {
  int t;
  asm volatile("{ .reg .pred r; .reg .u32 a, b, u, v;\n"
               "atom.relaxed.gpu.global.exch.b32 u, [%1], %3; atom.relaxed.gpu.global.exch.b32 v, [%2], %3;\n"
               "setp.eq.u32 r, u, 0x12345; @r pmevent 1; mov.u32 a, %%clock;\n"
               "setp.eq.u32 r, v, 0x12345; @r pmevent 1; mov.u32 b, %%clock; sub.u32 %0, b, a; }" : "=r"(t) : "l"(p0), "l"(p1), "r"(val) : "memory");
  return t;
}
__device__ __forceinline__ void race_init2(void* p0, void* p1, uint32_t val) {
  asm volatile("{ .reg .pred r; .reg .u32 a, b, u, v;\n"
               "atom.relaxed.gpu.global.exch.b32 u, [%0], %2; atom.relaxed.gpu.global.exch.b32 v, [%1], %2;\n"
               "atom.relaxed.gpu.global.exch.b32 a, [%0 + 4096], %2; atom.relaxed.gpu.global.exch.b32 b, [%1 + 4096], %2;\n"
               "lop3.b32 u, u, v, a, 0x96; setp.eq.u32 r, u, 0x12345; setp.eq.and.u32 r, b, u, r; @r pmevent 1; }" :: "l"(p0), "l"(p1), "r"(val) : "memory");
}
__device__ __forceinline__ uint4 lds128(uint32_t a) {
  uint4 v; asm volatile("ld.shared.v4.u32 {%0,%1,%2,%3}, [%4];" : "=r"(v.x), "=r"(v.y), "=r"(v.z), "=r"(v.w) : "r"(a) : "memory"); return v;
}
__device__ __forceinline__ uint2 lds64(uint32_t a) {
  uint2 v; asm volatile("ld.shared.v2.u32 {%0,%1}, [%2];" : "=r"(v.x), "=r"(v.y) : "r"(a) : "memory"); return v;
}
__device__ __forceinline__ void sts128(uint32_t a, uint4 v) {
  asm volatile("st.shared.v4.u32 [%0], {%1,%2,%3,%4};" :: "r"(a), "r"(v.x), "r"(v.y), "r"(v.z), "r"(v.w) : "memory");
}
__device__ __forceinline__ void sts64(uint32_t a, uint32_t x, uint32_t y) { asm volatile("st.shared.v2.u32 [%0], {%1,%2};" :: "r"(a), "r"(x), "r"(y) : "memory"); }
__device__ __forceinline__ void sts32(uint32_t a, uint32_t x) { asm volatile("st.shared.u32 [%0], %1;" :: "r"(a), "r"(x) : "memory"); }
__device__ __forceinline__ void ldsm4t(uint32_t (&r)[4], uint32_t a) {
  asm volatile("ldmatrix.sync.aligned.m8n8.x4.trans.shared.b16 {%0,%1,%2,%3}, [%4];"
               : "=r"(r[0]), "=r"(r[1]), "=r"(r[2]), "=r"(r[3]) : "r"(a) : "memory");
}
__device__ __forceinline__ void ldsm4(uint32_t (&r)[4], uint32_t a) {
  asm volatile("ldmatrix.sync.aligned.m8n8.x4.shared.b16 {%0,%1,%2,%3}, [%4];"
               : "=r"(r[0]), "=r"(r[1]), "=r"(r[2]), "=r"(r[3]) : "r"(a) : "memory");
}
template<bool TRANS> __device__ __forceinline__ void stsm4(uint32_t a, uint32_t r0, uint32_t r1, uint32_t r2, uint32_t r3) {
  if (TRANS) asm volatile("stmatrix.sync.aligned.m8n8.x4.trans.shared.b16 [%0], {%1,%2,%3,%4};" :: "r"(a), "r"(r0), "r"(r1), "r"(r2), "r"(r3) : "memory");
  else       asm volatile("stmatrix.sync.aligned.m8n8.x4.shared.b16 [%0], {%1,%2,%3,%4};" :: "r"(a), "r"(r0), "r"(r1), "r"(r2), "r"(r3) : "memory");
}
__device__ __forceinline__ void mma16816(float (&d)[4], uint32_t a0, uint32_t a1, uint32_t a2, uint32_t a3, uint32_t b0, uint32_t b1) {
  asm volatile("mma.sync.aligned.m16n8k16.row.col.f32.bf16.bf16.f32 {%0,%1,%2,%3}, {%4,%5,%6,%7}, {%8,%9}, {%0,%1,%2,%3};"
               : "+f"(d[0]), "+f"(d[1]), "+f"(d[2]), "+f"(d[3]) : "r"(a0), "r"(a1), "r"(a2), "r"(a3), "r"(b0), "r"(b1));
}
__device__ __forceinline__ void mma1688(float (&d)[4], uint32_t a0, uint32_t a1, uint32_t b0) {
  asm volatile("mma.sync.aligned.m16n8k8.row.col.f32.bf16.bf16.f32 {%0,%1,%2,%3}, {%4,%5}, {%6}, {%0,%1,%2,%3};"
               : "+f"(d[0]), "+f"(d[1]), "+f"(d[2]), "+f"(d[3]) : "r"(a0), "r"(a1), "r"(b0));
}
__device__ __forceinline__ uint32_t pack_bf16(float lo, float hi) {
  uint32_t r; asm("cvt.rn.bf16x2.f32 %0, %1, %2;" : "=r"(r) : "f"(hi), "f"(lo)); return r;
}
__device__ __forceinline__ uint32_t add_bf16x2(uint32_t a, uint32_t b) {
  uint32_t r; asm("add.rn.bf16x2 %0, %1, %2;" : "=r"(r) : "r"(a), "r"(b)); return r;
}
__device__ __forceinline__ uint32_t umax4(uint4 v) { return max(max(v.x, v.y), max(v.z, v.w)); }
__device__ __forceinline__ uint32_t opaque(uint32_t x) { uint32_t r; asm volatile("mov.u32 %0, %1;" : "=r"(r) : "r"(x)); return r; }
template<class T> __device__ __forceinline__ void pin(T*& p) { asm volatile("" : "+l"(p)); }
__device__ __forceinline__ void pin(uint32_t& v) { asm volatile("" : "+r"(v)); }
__device__ __forceinline__ uint32_t desc_lo(uint32_t addr) { return ((addr & 0x3FFFF) >> 4) | 0x10000; }
__device__ __forceinline__ uint64_t desc128(uint32_t lo) {
  uint64_t d; asm("mov.b64 %0, {%1, %2};" : "=l"(d) : "r"(lo), "r"(0x40000040)); return d;
}
#define WG_FENCE()  asm volatile("wgmma.fence.sync.aligned;" ::: "memory")
#define WG_COMMIT() asm volatile("wgmma.commit_group.sync.aligned;" ::: "memory")
#define WG_WAIT(n)  asm volatile("wgmma.wait_group.sync.aligned " #n ";" ::: "memory")
#define FENCE_ASYNC_SMEM() asm volatile("fence.proxy.async.shared::cta;" ::: "memory")
__device__ __forceinline__ void bar_sync(int id, int n) { asm volatile("bar.sync %0, %1;" :: "r"(id), "r"(n) : "memory"); }

#define D16(c) c(d[0]), c(d[1]), c(d[2]), c(d[3]), c(d[4]), c(d[5]), c(d[6]), c(d[7]), \
               c(d[8]), c(d[9]), c(d[10]), c(d[11]), c(d[12]), c(d[13]), c(d[14]), c(d[15])
template<bool FIRST> __device__ __forceinline__ void wgmma_rs_n32(float (&d)[16], const uint32_t (&a)[4], uint64_t b) {
  if (FIRST)
    asm volatile("wgmma.mma_async.sync.aligned.m64n32k16.f32.bf16.bf16 {%0,%1,%2,%3,%4,%5,%6,%7,%8,%9,%10,%11,%12,%13,%14,%15}, {%16,%17,%18,%19}, %20, 0, 1, 1, 0;"
      : D16("=f") : "r"(a[0]), "r"(a[1]), "r"(a[2]), "r"(a[3]), "l"(b));
  else
    asm volatile("wgmma.mma_async.sync.aligned.m64n32k16.f32.bf16.bf16 {%0,%1,%2,%3,%4,%5,%6,%7,%8,%9,%10,%11,%12,%13,%14,%15}, {%16,%17,%18,%19}, %20, 1, 1, 1, 0;"
      : D16("+f") : "r"(a[0]), "r"(a[1]), "r"(a[2]), "r"(a[3]), "l"(b));
}
template<bool FIRST> __device__ __forceinline__ void wgmma_ss_n32_ta(float (&d)[16], uint64_t a, uint64_t b) {
  if (FIRST)
    asm volatile("wgmma.mma_async.sync.aligned.m64n32k16.f32.bf16.bf16 {%0,%1,%2,%3,%4,%5,%6,%7,%8,%9,%10,%11,%12,%13,%14,%15}, %16, %17, 0, 1, 1, 1, 0;"
      : D16("=f") : "l"(a), "l"(b));
  else
    asm volatile("wgmma.mma_async.sync.aligned.m64n32k16.f32.bf16.bf16 {%0,%1,%2,%3,%4,%5,%6,%7,%8,%9,%10,%11,%12,%13,%14,%15}, %16, %17, 1, 1, 1, 1, 0;"
      : D16("+f") : "l"(a), "l"(b));
}
__device__ __forceinline__ void wgmma_ss_n128_tb(float (&d)[64], uint64_t a, uint64_t b) {
  asm volatile("wgmma.mma_async.sync.aligned.m64n128k16.f32.bf16.bf16 "
    "{%0,%1,%2,%3,%4,%5,%6,%7,%8,%9,%10,%11,%12,%13,%14,%15,%16,%17,%18,%19,%20,%21,%22,%23,%24,%25,%26,%27,%28,%29,%30,%31,"
    "%32,%33,%34,%35,%36,%37,%38,%39,%40,%41,%42,%43,%44,%45,%46,%47,%48,%49,%50,%51,%52,%53,%54,%55,%56,%57,%58,%59,%60,%61,%62,%63}, "
    "%64, %65, 1, 1, 1, 0, 1;"
    : "+f"(d[0]), "+f"(d[1]), "+f"(d[2]), "+f"(d[3]), "+f"(d[4]), "+f"(d[5]), "+f"(d[6]), "+f"(d[7]),
      "+f"(d[8]), "+f"(d[9]), "+f"(d[10]), "+f"(d[11]), "+f"(d[12]), "+f"(d[13]), "+f"(d[14]), "+f"(d[15]),
      "+f"(d[16]), "+f"(d[17]), "+f"(d[18]), "+f"(d[19]), "+f"(d[20]), "+f"(d[21]), "+f"(d[22]), "+f"(d[23]),
      "+f"(d[24]), "+f"(d[25]), "+f"(d[26]), "+f"(d[27]), "+f"(d[28]), "+f"(d[29]), "+f"(d[30]), "+f"(d[31]),
      "+f"(d[32]), "+f"(d[33]), "+f"(d[34]), "+f"(d[35]), "+f"(d[36]), "+f"(d[37]), "+f"(d[38]), "+f"(d[39]),
      "+f"(d[40]), "+f"(d[41]), "+f"(d[42]), "+f"(d[43]), "+f"(d[44]), "+f"(d[45]), "+f"(d[46]), "+f"(d[47]),
      "+f"(d[48]), "+f"(d[49]), "+f"(d[50]), "+f"(d[51]), "+f"(d[52]), "+f"(d[53]), "+f"(d[54]), "+f"(d[55]),
      "+f"(d[56]), "+f"(d[57]), "+f"(d[58]), "+f"(d[59]), "+f"(d[60]), "+f"(d[61]), "+f"(d[62]), "+f"(d[63])
    : "l"(a), "l"(b));
}

__device__ __forceinline__ void tma2d_mc_e(uint32_t dst, const CUtensorMap* tm, int c0, int c1, uint32_t bar) {
  asm volatile("{ .reg .pred p; elect.sync _|p, 0xffffffff;\n"
               "@p cp.async.bulk.tensor.2d.shared::cluster.global.mbarrier::complete_tx::bytes.multicast::cluster [%0], [%1, {%3, %4}], [%2], %5; }"
               :: "r"(dst), "l"(tm), "r"(bar), "r"(c0), "r"(c1), "h"((uint16_t)3) : "memory");
}

__device__ __forceinline__ void count_e(uint32_t* p) {
  asm volatile("fence.acq_rel.gpu;" ::: "memory");
  __syncwarp();
  asm volatile("{ .reg .pred p; elect.sync _|p, 0xffffffff; @p red.relaxed.gpu.global.add.u32 [%0], 1; }" :: "l"(p) : "memory");
}
__device__ __forceinline__ void await_count(const uint32_t* p, uint32_t n) {
  for (uint32_t i = 0; ld_acquire(p) < n && i < (1u << 22); i++) {}
  asm volatile("fence.proxy.async.global;" ::: "memory");
}
__device__ __forceinline__ void await_flags(const uint32_t* p) {
  for (uint32_t i = 0; i < (1u << 22); i++) {
    uint4 v;
    asm volatile("ld.acquire.gpu.global.v4.u32 {%0,%1,%2,%3}, [%4];" : "=r"(v.x), "=r"(v.y), "=r"(v.z), "=r"(v.w) : "l"(p) : "memory");
    if (__all_sync(~0u, (v.x & v.y & v.z & v.w) == 0x01010101u)) break;
  }
  asm volatile("fence.proxy.async.global;" ::: "memory");
}
__device__ __forceinline__ void mbar_lim(uint32_t bar, uint32_t ph) { for (uint32_t i = 0; !mbar_try(bar, ph) && i < (1u << 20); i++) {} }

struct cf { float x, y; };
__host__ __device__ constexpr float cos64(int k) {
  return k == 0 ? 1.0f : k == 1 ? 0.99518472667219689f : k == 2 ? 0.98078528040323045f : k == 3 ? 0.95694033573220887f :
         k == 4 ? 0.92387953251128676f : k == 5 ? 0.88192126434835503f : k == 6 ? 0.83146961230254524f : k == 7 ? 0.77301045336273696f :
         k == 8 ? 0.70710678118654752f : k == 9 ? 0.63439328416364550f : k == 10 ? 0.55557023301960222f : k == 11 ? 0.47139673682599765f :
         k == 12 ? 0.38268343236508977f : k == 13 ? 0.29028467725446236f : k == 14 ? 0.19509032201612827f : k == 15 ? 0.09801714032956060f : 0.0f;
}
__host__ __device__ constexpr float c64(int k) { return k <= 16 ? cos64(k) : -cos64(32 - k); }
__host__ __device__ constexpr float s64(int k) { return k <= 16 ? cos64(16 - k) : cos64(k - 16); }

template<int N, int ST, bool INV> struct Fft {
  template<int K> static __device__ __forceinline__ void bf(const cf* e, const cf* o, cf* out) {
    if constexpr (K < N / 2) {
      constexpr int idx = K * (64 / N);
      const cf a = e[K], b = o[K];
      if constexpr (idx == 0) {
        out[K] = {a.x + b.x, a.y + b.y}; out[K + N / 2] = {a.x - b.x, a.y - b.y};
      } else if constexpr (idx == 16) {
        if constexpr (INV) { out[K] = {a.x - b.y, a.y + b.x}; out[K + N / 2] = {a.x + b.y, a.y - b.x}; }
        else               { out[K] = {a.x + b.y, a.y - b.x}; out[K + N / 2] = {a.x - b.y, a.y + b.x}; }
      } else {
        constexpr float c = c64(idx), s = INV ? s64(idx) : -s64(idx);
        cf p; p.x = fmaf(-s, b.y, fmaf(c, b.x, a.x)); p.y = fmaf(s, b.x, fmaf(c, b.y, a.y));
        out[K] = p; out[K + N / 2] = {fmaf(2.0f, a.x, -p.x), fmaf(2.0f, a.y, -p.y)};
      }
      bf<K + 1>(e, o, out);
    }
  }
  static __device__ __forceinline__ void run(const cf* in, cf* out) {
    cf e[N / 2], o[N / 2];
    Fft<N / 2, 2 * ST, INV>::run(in, e);
    Fft<N / 2, 2 * ST, INV>::run(in + ST, o);
    bf<0>(e, o, out);
  }
};
template<int ST, bool INV> struct Fft<1, ST, INV> {
  static __device__ __forceinline__ void run(const cf* in, cf* out) { out[0] = in[0]; }
};
template<bool INV> __device__ __forceinline__ void fft32(cf (&v)[32]) {
  cf o[32]; Fft<32, 1, INV>::run(v, o);
#pragma unroll
  for (int i = 0; i < 32; i++) v[i] = o[i];
}
__device__ __forceinline__ cf cmul(cf a, float c, float s) { return {fmaf(-a.y, s, a.x * c), fmaf(a.x, s, a.y * c)}; }
__device__ __forceinline__ float bf2f(__nv_bfloat16 v) { return __bfloat162float(v); }

template<bool INV, class F> __device__ __forceinline__ void warp_fft1024(cf (&v)[32], float2* __restrict__ buf, const float2* __restrict__ tw, int t, int u, F mid) {
#pragma unroll 1
  for (uint32_t h = 0; h < 2; h++) {
    fft32<INV>(v);
    if (FUNR ? h : opaque(h)) continue;
#pragma unroll
    for (int j = 1; j < 32; j++) { const float2 w = tw[j * 32 + t]; v[j] = cmul(v[j], w.x, INV ? -w.y : w.y); }
    if (INV) {
      float* f = (float*)buf;
#pragma unroll
      for (int j = 0; j < 32; j++) f[j * 33 + t] = v[j].x;
      __syncwarp();
#pragma unroll
      for (int j = 0; j < 32; j++) v[j].x = f[u * 33 + j];
      __syncwarp();
#pragma unroll
      for (int j = 0; j < 32; j++) f[j * 33 + t] = v[j].y;
      __syncwarp();
#pragma unroll
      for (int j = 0; j < 32; j++) v[j].y = f[u * 33 + j];
    } else {
#pragma unroll
      for (int j = 0; j < 32; j++) buf[j * 33 + t] = make_float2(v[j].x, v[j].y);
      __syncwarp();
#pragma unroll
      for (int j = 0; j < 32; j++) { const float2 r = buf[u * 33 + j]; v[j] = {r.x, r.y}; }
    }
    __syncwarp();
    mid();
  }
}
constexpr int ROW_BUF = 32 * 33;

__device__ __forceinline__ int z_row(int p) { return (p & ~31) | (p & 7) << 2 | (p & 31) >> 3; }
__device__ __forceinline__ float2 twiddle(int i) { float s, c; sincospif(-(float)((i >> 5) * (i & 31)) * (1.0f / 512.0f), &s, &c); return make_float2(c, s); }
template<class F, class G> __device__ __forceinline__ void fft_rows_fwd(float2* sm2, const __nv_bfloat16* gw, int cta, int tid, uint32_t full_bar, uint32_t release_bar, F ev, G extra) {
  const int t = tid & 31, w = tid >> 5, n = z_row(cta * 8 + w);
#pragma unroll 1
  for (int i = tid; i < 1024; i += 256) sm2[i] = twiddle(i);
  ev(5);
  mbar_spin(full_bar, 0);
  if (tid == 0) TL2(6);
  __syncwarp();
  const __nv_bfloat16* xa = (const __nv_bfloat16*)(sm2 + 1024 + w * ROW_BUF) + t;
  cf v[32];
  float ga = 0.f, gb = 0.f;
#pragma unroll
  for (int j = 0; j < 32; j++) {
    v[j] = {bf2f(xa[32 * j]), bf2f(xa[D_ + 32 * j])};
    const float g = bf2f(gw[32 * j + t]); ga = fmaf(v[j].x, g, ga); gb = fmaf(v[j].y, g, gb);
  }
#pragma unroll
  for (int o = 16; o; o >>= 1) { ga += __shfl_xor_sync(~0u, ga, o); gb += __shfl_xor_sync(~0u, gb, o); }
  if (t < 2) g_gate[n + 1024 * t] = __fdividef(1.0f, 1.0f + __expf(-(t ? gb : ga)));
  ev(6);
  bar_sync(13, 256);
  warp_fft1024<false>(v, sm2 + 1024 + w * ROW_BUF, sm2, t, t, [&]() { FENCE_ASYNC_SMEM(); mbar_arrive_warp(release_bar); });
  float ws, wc; sincospif(-(float)n * (1.0f / 1024.0f), &ws, &wc);
  ev(12);
  uint32_t tz = clock_lo();
  float4* z = (float4*)g_z + ((size_t)(t >> 1) * 1024 + cta * 8 + w) * 2 + (t & 1);
#pragma unroll
  for (int j = 0; j < 17; j++) {
    cf q = v[(32 - j) & 31];
    if (j < 16) {
      const cf r = {__shfl_sync(~0u, v[31 - j].x, 32 - t), __shfl_sync(~0u, v[31 - j].y, 32 - t)};
      if (t != 0) q = r;
    }
    const cf a = {v[j].x + q.x, v[j].y - q.y}, b = {v[j].y + q.y, q.x - v[j].x};
    const cf d = cmul({a.x - b.x, a.y - b.y}, wc, ws);
    if (j == POOL_AT) extra();
    if (PACE_Z && j && j < 16) delay_until(tz += PACE_Z);
    if ((j < 16 || t == 0) && ((EXP_ST & 4) || d.x == 123.f)) z[j * 32768] = make_float4(a.x + b.x, a.y + b.y, d.x, d.y);
  }
}
constexpr int COL_FS = 1057, COL_W = (8192 + 16 * COL_FS * 4 + 127) & ~127, COL_SMEM = COL_W + 131072 + 16;

__device__ __forceinline__ void fft_cols(float2* sm2, int cta, const CUtensorMap* twr, const CUtensorMap* twi) {
  const int grp = __shfl_sync(~0u, (int)(threadIdx.x >> 7), 0), tid = threadIdx.x & 127, tp = tid >> 2, t = z_row(tp);
  float* buf = (float*)(sm2 + 1024) + (grp * 4 + (tid & 3)) * COL_FS;
  const uint32_t wsm = smem_u32(sm2) + COL_W, wbar = wsm + 131072;
  const int res = (tid >> 5) * 2 + (tid & 1), el = res + grp * 2 + ((tid >> 1) & 1);
  uint32_t wa = (el >> 3) * 65536 + res * 4096 + (tp & 7) * 16 + (el & 7) * 2;
  auto load_w = [&](int q, int n) {
#pragma unroll 1
    for (int i = q * 16; i < (q + n) * 16; i++) tma2d(wsm + (i & 31) * 4096, i & 8 ? twi : twr, (i & 7) * 512 + (i >> 4) * 8, 0, wbar);
  };
  if (threadIdx.x == 0) { mbar_init(wbar, 1); sts32(wbar + 8, 0); asm volatile("fence.mbarrier_init.release.cluster;" ::: "memory"); }
#pragma unroll 1
  for (int i = threadIdx.x; i < 1024; i += 512) {
    const float2 w = twiddle(z_row(i));
    sm2[i] = w;
    if (cta == 0) g_tw[z_row(i)] = w;
  }
  for (uint32_t n = 0; ld_acquire(g_ctl + C_P1) < 128; ) { watchdog(n, 1u << 22); __nanosleep(200); }
  if (COL_DLY) delay_cycles(COL_DLY);
  __syncthreads();
  if (threadIdx.x == 0) { mbar_expect(wbar, 131072); load_w(cta * 16, 2); }
  __syncwarp();
  delay_cycles(1 + grp * DLY_GRP);
  const int end = cta * 64 + 64 + (cta == 3);
  for (int item = cta * 64 + grp; item < end; item += 4, wa ^= 65536) {
    float2* zp = g_z + (size_t)item * 4096;
    cf v[32];
#pragma unroll
    for (int j = 0; j < 32; j++) { const float2 a = __ldcg(zp + tid + j * 128); v[j] = {a.x, a.y}; }
#pragma unroll 1
    for (int ph = 0; ; ph++) {
      fft32<false>(v);
      if (CUNR || !(ph & 1)) {
#pragma unroll
        for (int j = 1; j < 32; j++) { const float2 w = sm2[j * 32 + tp]; v[j] = cmul(v[j], w.x, w.y); }
        bar_sync(1 + grp, 128);
        if (ph && tid == 0) {
          uint32_t n; asm volatile("atom.shared.inc.u32 %0, [%1], 3;" : "=r"(n) : "r"(wbar + 8) : "memory");
          if (n == 3 && item - grp + 4 < end) { mbar_expect(wbar, 65536); load_w((item >> 2) + 2, 1); }
        }
        __syncwarp();
#pragma unroll
        for (int j = 0; j < 32; j++) buf[j * 33 + t] = v[j].x;
        bar_sync(1 + grp, 128);
#pragma unroll
        for (int j = 0; j < 32; j++) v[j].x = buf[t * 33 + j];
        bar_sync(1 + grp, 128);
#pragma unroll
        for (int j = 0; j < 32; j++) buf[j * 33 + t] = v[j].y;
        bar_sync(1 + grp, 128);
#pragma unroll
        for (int j = 0; j < 32; j++) v[j].y = buf[t * 33 + j];
        if (CUNR) fft32<false>(v); else continue;
      }
      if (ph == (CUNR ? 1 : 3)) break;
      mbar_wait(wbar, (item >> 2) & 1);
#pragma unroll
      for (int j = 0; j < 32; j++) {
        uint32_t re, im;
        asm volatile("ld.shared.u16 %0, [%1];" : "=r"(re) : "r"(wsm + wa + j * 128) : "memory");
        asm volatile("ld.shared.u16 %0, [%1];" : "=r"(im) : "r"(wsm + wa + 32768 + j * 128) : "memory");
        const cf r = cmul(v[j], __uint_as_float(re << 16), __uint_as_float(im << 16));
        v[j] = {r.y, r.x};
      }
    }
#pragma unroll
    for (int j = 0; j < 32; j++) zp[tid + j * 128] = make_float2(v[j].y, v[j].x);
  }
  __syncthreads();
  if (threadIdx.x < 32) {
    count_e(g_ctl + C_COLS);
    await_count(g_ctl + C_COLS, 4);
    g_ctl[C_P1] = 0;
  }
  __syncthreads();
  ((float4*)sm2)[threadIdx.x] = __ldcg((const float4*)g_tw + threadIdx.x);
  __syncthreads();
}

template<class F> __device__ __forceinline__ void fft_rows_inv(uint32_t zs, float2* buf, const float2* tw, int p, int lane, __nv_bfloat16* out, F read) {
  const int n = z_row(p), t = (lane & 17) | (lane & 6) << 1 | (lane & 8) >> 2, tm = -t & 31, src = (tm & 17) | (tm & 12) >> 1 | (tm & 2) << 2;
  const uint32_t z = zs + (t >> 1) * 128 + ((((p & 3) * 2 + (t & 1)) ^ (t >> 1 & 7)) << 4);
  FT(0, 0.f);
  float4 e[17];
  uint32_t all = 0;
  e[16] = __ldcg((const float4*)g_z + ((size_t)256 * 1024 + p) * 2);
  const float g0 = __ldcg(g_gate + n), g1 = __ldcg(g_gate + n + 1024);
#pragma unroll
  for (int j = 0; j < 16; j++) { const uint4 u = lds128(z + j * 2048); e[j] = make_float4(__uint_as_float(u.x), __uint_as_float(u.y), __uint_as_float(u.z), __uint_as_float(u.w)); all |= u.x; }
  sched_fence(all);
  read();
  float ws, wc; sincospif((float)n * (1.0f / 1024.0f), &ws, &wc);
  cf v[32], q[17];
#pragma unroll
  for (int j = 0; j < 17; j++) {
    const cf d = cmul({e[j].z, e[j].w}, wc, ws);
    cf a = {e[j].x + d.x, e[j].y + d.y}, b = {e[j].x - d.x, e[j].y - d.y};
    if (j == 16 || (j == 0 && t == 0)) { a.y = 0.f; b.y = 0.f; }
    if (j < 16) v[j] = {a.x - b.y, a.y + b.x};
    q[j] = {a.x + b.y, b.x - a.y};
  }
#pragma unroll
  for (int j = 16; j < 32; j++) {
    v[j] = {__shfl_sync(~0u, q[31 - j].x, src), __shfl_sync(~0u, q[31 - j].y, src)};
    if (t == 0) v[j] = q[32 - j];
  }
  FT(1, v[0].x + v[16].x + v[31].x);
  warp_fft1024<true>(v, buf, tw, t, lane, []() {});
  FT(3, v[31].y + v[0].x);
  const float sc = 0.5f / (2048.0f * 1024.0f), s0 = (1.f - g0) * sc, s1 = (1.f - g1) * sc;
  __nv_bfloat16* o = out + (size_t)n * D_ + lane;
#pragma unroll
  for (int j = 0; j < 32; j++) { o[32 * j] = __float2bfloat16(v[j].x * s0); o[1024 * D_ + 32 * j] = __float2bfloat16(v[j].y * s1); }
  FT(4, 0.f);
}

constexpr int NP = NP_, NHV = REG_F == 216 ? 5 : 7, NV = 16 - NHV;
constexpr int XEND = NSEG;
constexpr uint32_t SM_WO = 0, SM_V = 65536, SM_LAND = SM_V + 8192, SM_MEM = SM_LAND + 24576, SM_SP = SM_MEM, SM_SPM = SM_MEM + 5120, SM_OM = SM_MEM + 6144,
                   SM_OX = SM_MEM + 8192, SM_RED = SM_OX + 2048, SM_XCH = SM_RED + 1024, SM_SUM = SM_XCH + 4096, SM_VM = SM_SUM + 128, SM_TAB = SM_VM + 2048, SM_TRACE = SM_TAB + 2048,
                   ST_WG = (32 - NP + NV) * 2048,
                   SM_XT = 2 * ST_WG, SM_POOL = SM_XT + 32768, SM_HV = SM_POOL + 2 * NP * 2048,
                   SM_BAR = SM_HV + 2 * NHV * 2048, SM_SEL = SM_BAR + 320, CHAIN_SMEM = SM_SEL + 544 + 1024;
constexpr uint32_t SM_FFT = 49152, SM_GW = SM_XT - 2048;
static_assert(NP % 4 == 0 && NV == 11 && SM_TRACE + 4096 <= SM_XT, "shared memory layout");
static_assert(CHAIN_SMEM <= 232448 && COL_SMEM <= CHAIN_SMEM && SM_FFT + (1024 + 8 * ROW_BUF) * 8 <= SM_GW && NP == 12, "shared memory budget");
enum { B_WFULL = 0, B_WREAD = 2, B_WOFULL, B_XFULL, B_XEMPTY, B_E1TRIG, B_E2TRIG, B_PVDONE, B_PUB, B_SC, B_PFULL, B_SPFREE,
       B_LAND, B_LFREE, B_DONE, B_SEL, B_PROBE, B_FREE, B_P1, B_ROWS, B_VFULL, B_VST, B_TW, B_BT, B_WREAD0, B_Z, B_GFULL = B_Z + 4, B_GEMPTY = B_GFULL + 5, B_END = B_GEMPTY + 5 };
static_assert(B_END * 8 <= 320, "barriers");
__host__ __device__ constexpr uint32_t bar_codes(int g) {
  uint32_t r = 0;
  for (int i = 16 * g; i < 16 * g + 16; i++)
    r |= (i == B_LAND ? 3u : i == B_WREAD || i == B_XEMPTY || i == B_E1TRIG || i == B_E2TRIG || i == B_LFREE || i == B_FREE || i == B_VST || i == B_P1 || i == B_ROWS ? 2u :
          i >= B_GEMPTY || i == B_WREAD0 || i == B_PROBE || i == B_DONE || i == B_PVDONE || i == B_PUB || i == B_SC || i == B_SPFREE ? 1u : 0u) << 2 * (i & 15);
  return r;
}
constexpr uint32_t SM_BT = 65536, SM_TW = SM_XT - 8192, COL_Z = 75 * 1024;
static_assert(SM_XT + 3 * 32768 <= SM_BAR && SM_BT + 32768 <= SM_MEM && SM_TRACE <= SM_TW && SM_MEM + 4 * ROW_BUF * 4 <= SM_TAB &&
              8192 + 16 * ROW_BUF * 4 <= COL_Z && COL_Z + 131072 <= SM_BAR, "shared memory layout");
__device__ __forceinline__ uint32_t next_stage(uint32_t o) { return o == SM_XT + 65536 ? 0 : o == 32768 ? SM_XT : o + 32768; }

struct ChainCtx { char* mail; uint32_t sb, sel; int r, h, a, b, j, m, w, lane; };
#define BAR(i) (c.sb + SM_BAR + 8 * (i))

__device__ __forceinline__ uint32_t tile_off(int line, int lane) {
  return line * 128 + (((lane & 3) ^ line) << 5) + (lane >> 2) * 4;
}
__device__ __forceinline__ uint32_t read_off(int lane) {
  const int n = lane >> 2, jj = lane & 3, l = 2 * (jj >> 1) + (n & 1);
  return l * 128 + (((n >> 1) ^ l) << 5) + (jj & 1) * 16;
}
__device__ __forceinline__ uint32_t frag_off(int w, int lane) {
  const int mi = lane >> 3, r = lane & 7;
  return ((mi >> 1) * 8 + r) * 128 + (((2 * w + (mi & 1)) ^ r) << 4);
}
__device__ __forceinline__ uint32_t land_off(int w, int lane) { return w * 512 + ((lane ^ (((lane >> 4) | ((w & 1) << 1)) << 1)) << 4); }
__device__ __forceinline__ uint32_t tagged(uint32_t v, uint32_t tag) { return (v | 1u) ^ tag; }
__device__ __forceinline__ void mma_a(float (&d)[4], const uint32_t (&a)[4], uint32_t b0, uint32_t b1) { mma16816(d, a[0], a[1], a[2], a[3], b0, b1); }
__device__ __forceinline__ void mma_q(float (&d)[4], const uint4& a, uint32_t b0, uint32_t b1) { mma16816(d, a.x, a.y, a.z, a.w, b0, b1); }
__device__ __forceinline__ uint4 add4(uint4 a, uint4 b) {
  return make_uint4(add_bf16x2(a.x, b.x), add_bf16x2(a.y, b.y), add_bf16x2(a.z, b.z), add_bf16x2(a.w, b.w));
}
__device__ __forceinline__ void mbar_arrive_both(uint32_t bar, int peer) {
  __syncwarp();
  asm volatile("{ .reg .pred p; .reg .u32 a; mapa.shared::cluster.u32 a, %0, %1; elect.sync _|p, 0xffffffff;\n"
               "@p mbarrier.arrive.shared::cta.b64 _, [%0]; @p mbarrier.arrive.shared::cluster.b64 _, [a]; }" :: "r"(bar), "r"(peer) : "memory");
}

__device__ __forceinline__ void arrive_remote_if(uint32_t a, bool on) {
  asm volatile("{ .reg .pred p; setp.ne.u32 p, %1, 0; @p mbarrier.arrive.shared::cluster.b64 _, [%0]; }" :: "r"(a), "r"((uint32_t)on) : "memory");
}
__device__ __forceinline__ void store_count(void* p, uint4 v, void* cnt) {
  asm volatile("{ .reg .pred p, q; .reg .b128 a, b; .reg .b64 l, h; mov.b64 l, {%1, %2}; mov.b64 h, {%3, %4}; mov.b128 a, {l, h};\n"
               "atom.relaxed.gpu.global.exch.b128 b, [%0], a; mov.b128 {l, h}, b; setp.eq.u64 q, l, 0x7fc17fc17fc17fc1; @q pmevent 1;\n"
               "elect.sync _|p, 0xffffffff; @p red.relaxed.gpu.global.add.u32 [%5], 1; }"
               :: "l"(p), "r"(v.x), "r"(v.y), "r"(v.z), "r"(v.w), "l"(cnt) : "memory");
}

template<int N> __device__ __forceinline__ void pad() {
#pragma unroll
  for (int i = 0; i < N; i++) asm volatile("pmevent 3;");
}
__device__ __forceinline__ int lane_id() {
  int l; asm volatile("{ .reg .u32 t; mov.u32 t, %%laneid; shfl.sync.idx.b32 %0, t, t, 31, 0xffffffff; }" : "=r"(l)); return l;
}
__device__ __forceinline__ uint32_t tid_now() { uint32_t t; asm volatile("mov.u32 %0, %%tid.x;" : "=r"(t)); return t; }
enum { NB_ATT = 1, NB_OM = 2, NB_VM = 3, NB_XCH = 4, NB_MEM = 8, NB_HELP = 12 };
__device__ __forceinline__ uint32_t dep(uint32_t a, uint32_t v, uint32_t z) { uint32_t r; asm("shf.l.wrap.b32 %0, %2, %1, %3;" : "=r"(r) : "r"(a), "r"(v), "r"(z)); return r; }
__device__ __forceinline__ uint32_t vary(uint32_t a, int s, uint32_t z) { return dep(a, 0, z + 32 * s); }
__device__ __forceinline__ char* mk_ptr(uint32_t lo, uint32_t hi) { uint64_t r; asm("mov.b64 %0, {%1, %2};" : "=l"(r) : "r"(lo), "r"(hi)); return (char*)r; }
__device__ __forceinline__ void lds_frag(uint32_t (&r)[4], uint32_t a) {
  asm volatile("ld.shared.v4.u32 {%0,%1,%2,%3}, [%4];" : "=r"(r[0]), "=r"(r[1]), "=r"(r[2]), "=r"(r[3]) : "r"(a) : "memory");
}
__device__ __forceinline__ uint32_t stale2(uint32_t a, uint32_t b, uint32_t t) { uint32_t r; asm("lop3.b32 %0, %1, %2, %3, 0xbd;" : "=r"(r) : "r"(a), "r"(b), "r"(t)); return r; }
__device__ __forceinline__ uint32_t stale1(uint32_t acc, uint32_t a, uint32_t t) { uint32_t r; asm("lop3.b32 %0, %1, %2, %3, 0xf9;" : "=r"(r) : "r"(acc), "r"(a), "r"(t)); return r; }
__device__ __forceinline__ bool all_clear(uint32_t x, uint32_t m) {
  uint32_t r;
  asm volatile("{ .reg .pred p; .reg .u32 t; and.b32 t, %1, %2; setp.eq.u32 p, t, 0; vote.sync.all.pred p, p, 0xffffffff; selp.u32 %0, 1, 0, p; }" : "=r"(r) : "r"(x), "r"(m));
  return r;
}
__device__ __forceinline__ bool arrive_if_all(bool ok, int id, int n) {
  uint32_t r;
  asm volatile("{ .reg .pred p, q; setp.ne.u32 p, %1, 0; vote.sync.all.pred q, p, 0xffffffff; @q bar.arrive %2, %3; selp.u32 %0, 1, 0, q; }"
               : "=r"(r) : "r"((uint32_t)ok), "r"(id), "r"(n) : "memory");
  return r;
}
__device__ __forceinline__ bool arrive_if_clear(uint32_t x, uint32_t m, int id, int n) {
  uint32_t r;
  asm volatile("{ .reg .pred p; .reg .u32 t; and.b32 t, %1, %2; setp.eq.u32 p, t, 0; vote.sync.all.pred p, p, 0xffffffff; @p bar.arrive %3, %4; selp.u32 %0, 1, 0, p; }"
               : "=r"(r) : "r"(x), "r"(m), "r"(id), "r"(n) : "memory");
  return r;
}
__device__ __forceinline__ void touch(const void* p, uint32_t z) {
  asm volatile("{ .reg .pred p; setp.eq.u32 p, %1, 0x7fff0000; @p prefetch.global.L2 [%0]; }" :: "l"(p), "r"(z) : "memory");
}

__device__ __forceinline__ uint64_t desc_x(uint32_t lo, int k) {
  uint64_t d; asm("mov.b64 %0, {%1, %2};" : "=l"(d) : "r"(lo + (k >> 2) * 64 + (k & 3) * 2), "r"(0x40000200)); return d;
}
template<int K0, int K1> __device__ __forceinline__ void issue_qk(float (&xa)[16], const uint32_t (&wt)[16][4], uint32_t lo) {
  WG_FENCE();
#pragma unroll
  for (int k = K0; k < K1; k++) {
    if (k >= EXP_NWG) continue;
    if (k == 0) wgmma_rs_n32<true>(xa, wt[0], desc_x(lo, 0));
    else wgmma_rs_n32<false>(xa, wt[k], desc_x(lo, k));
  }
  WG_COMMIT();
}
__host__ __device__ constexpr int v_order(int i) { return SSPOS == 0 ? i : SSPOS == 2 ? (i + NV) % 16 : NHV == 5 ? (i % 3 == 2 ? NV + i / 3 : i - i / 3) : (i == 15 ? NV - 1 : i % 2 ? NV + i / 2 : i / 2); }
__device__ __forceinline__ void issue_v(float (&xa)[16], const uint32_t (&wv)[16][4], uint32_t lo, uint32_t la) {
  WG_FENCE();
#pragma unroll
  for (int i = 0; i < EXP_NWG; i++) {
    const int k = v_order(i);
    const uint64_t b = desc_x(lo, k);
    if (k < NV) { if (i == 0) wgmma_rs_n32<true>(xa, wv[k], b); else wgmma_rs_n32<false>(xa, wv[k], b); }
    else        { if (i == 0) wgmma_ss_n32_ta<true>(xa, desc128(la + (k - NV) * 128), b); else wgmma_ss_n32_ta<false>(xa, desc128(la + (k - NV) * 128), b); }
  }
  WG_COMMIT();
}
template<bool ISV> __device__ __forceinline__ void park_own(uint32_t (&q)[4], float (&xa)[16], uint32_t dst, int slot, uint32_t z) {
  uint32_t p[8];
#pragma unroll
  for (int i = 0; i < 16; i++) asm volatile("" : "+f"(xa[i]) :: "memory");
#pragma unroll
  for (int i = 0; i < 2; i++) {
    const float* k = xa + 8 * i;
    if (ISV) { p[4 * i] = pack_bf16(k[0], k[1]); p[4 * i + 1] = pack_bf16(k[2], k[3]); p[4 * i + 2] = pack_bf16(k[4], k[5]); p[4 * i + 3] = pack_bf16(k[6], k[7]); }
    else     { p[4 * i] = pack_bf16(k[0], k[2]); p[4 * i + 1] = pack_bf16(k[1], k[3]); p[4 * i + 2] = pack_bf16(k[4], k[6]); p[4 * i + 3] = pack_bf16(k[5], k[7]); }
  }
  sts128(dep(dep(dst, p[4] ^ p[5] ^ p[6], z), p[7], z) + slot * 8192, make_uint4(p[0], p[1], p[2], p[3]));
#pragma unroll
  for (int i = 0; i < 4; i++) q[i] = p[4 + i];
}
__device__ __forceinline__ void park_peer(const uint32_t (&q)[4], uint32_t dst, int slot, const ChainCtx& c) {
  const uint32_t bar = BAR(B_LAND);
  if (EXP_PEER) st_async4(mapa(dst + slot * 8192, c.b ^ 1), q[0], q[1], q[2], q[3], mapa(bar, c.b ^ 1));
  else touch((void*)(uintptr_t)(q[0] ^ q[1] ^ q[2] ^ q[3]), c.sb);
  mbar_arrive_warp(bar);
}
__device__ __forceinline__ uint32_t put_tag(uint32_t v, uint32_t bit, uint32_t t) {
  uint32_t r; asm("lop3.b32 %0, %1, %2, %3, 0x74;" : "=r"(r) : "r"(v), "r"(bit), "r"(t)); return r;
}
__device__ __forceinline__ void mem_proj(const uint32_t (&wa)[16][4], const uint32_t (&wb)[16][4], uint32_t (&wv)[16][4], uint32_t (&af)[16][4],
                                         uint32_t& wo, const char*& pa, uint32_t tab, uint32_t t16, uint32_t pk, const ChainCtx& c, int s) {
  const uint32_t mp = t16 & ~0x600u, id = NB_MEM + (t16 >> 11);
  uint32_t r[8][4];
  float la[4][4] = {}, lg[NLAG][4] = {}, lv[4][4] = {};
  auto lead = [&](int k) { mma_a(la[k & 3], wa[k], r[k >> 1][2 * (k & 1)], r[k >> 1][2 * (k & 1) + 1]); };
  auto lag = [&](int k) { mma_a(lg[k % NLAG], wb[k], r[k >> 1][2 * (k & 1)], r[k >> 1][2 * (k & 1) + 1]); };
  auto sum = [](const float (&d)[4][4], int i) { return (d[0][i] + d[1][i]) + (d[2][i] + d[3][i]); };
  bar_sync(id, 160);
  TR(s, 0);
#pragma unroll
  for (int i = 0; i < 4; i++) ldsm4t(r[i], mp + (c.sb + SM_MEM + i * 512));
  const uint4 tq = lds128(tab);
  bar_sync(id + 2, 160);
#pragma unroll
  for (int k = 0; k < 8; k++) lead(k);
  const uint32_t ta = tq.x | ((pk >> 16) & 511), tb = tq.z ^ ((pk >> 16) & 511);
  char* dst = mk_ptr(ta, tq.y);
  char* dst2 = mk_ptr(tb, tq.w);
  const uint32_t mp1 = dep(mp, __float_as_uint(la[C1_AT][0]) ^ ta ^ tb, c.sb);
#pragma unroll
  for (int i = 4; i < 8; i++) ldsm4t(r[i], mp1 + (c.sb + SM_MEM + 2048 + i * 512));
  const uint32_t hv = pk & 0xFFFF;
#pragma unroll
  for (int k = NV; k < NV + HV_E; k++) ldsm4t(wv[k], dep(hv, r[HV_R][0], c.sb) + (c.sb + SM_HV + (k - NV) * 2048));
#pragma unroll
  for (int k = 0; k < 8; k++) lag(k);
#pragma unroll
  for (int k = 8; k < 16; k++) lead(k);
  sts128((HV_E ? dep(t16, wv[NV][0] ^ wv[NV + HV_E / 2][1] ^ wv[NV + HV_E - (HV_E > 0)][2], c.sb) : t16) + (c.sb + SM_XCH), make_uint4(__float_as_uint(sum(la, 0)), __float_as_uint(sum(la, 1)), __float_as_uint(sum(la, 2)), __float_as_uint(sum(la, 3))));
  bar_sync(NB_XCH | ((t16 >> 9) & 3), 64);
  const uint4 o = lds128((t16 ^ 2048) + (c.sb + SM_XCH));
#pragma unroll
  for (int k = 8; k < 16; k++) lag(k);
  float t[4];
#pragma unroll
  for (int i = 0; i < 4; i++) {
    const float oi = __uint_as_float(i == 0 ? o.x : i == 1 ? o.y : i == 2 ? o.z : o.w);
    t[i] = NLAG == 4 ? (((lg[0][i] + lg[1][i]) + lg[2 % NLAG][i]) + lg[3 % NLAG][i]) + oi : NLAG == 3 ? (lg[1][i] + lg[2 % NLAG][i]) + (lg[0][i] + oi) : (lg[0][i] + oi) + lg[1][i];
  }
  const uint32_t y0 = put_tag(pack_bf16(t[0], t[2]), pk >> 31, s >> 1), y1 = put_tag(pack_bf16(t[1], t[3]), pk >> 31, s >> 1);
  st_pub(dst, y0); st_pub(dst2, y1);
  mbar_arrive_warp(BAR(B_E1TRIG));
  TR(s, 1);
  sched_fence(c.sb);
  const uint4 tv = lds128(tab + 16);
#pragma unroll
  for (int k = NV + HV_E; k < 16; k++) ldsm4t(wv[k], (k < NV + HV_E + HV_D ? hv : dep(hv, k == NV + HV_E + HV_D ? wv[k - HV_D][0] ^ tv.x : wv[k - HV_D][0], c.sb)) + (c.sb + SM_HV + (k - NV) * 2048));
  wo = (hv & 2047) | ((t16 & 2048) << 3);
  const uint32_t l8 = (t16 >> 1) & 255;
  char* dv = mk_ptr(tv.x | l8, tv.y);
  pa = mk_ptr(tv.z | l8, tv.w);
#pragma unroll
  for (int f = 0; f < WO_0; f++) ldsm4t(af[f], dep(wo, f < WO_D ? wv[16 - WO_D + f][0] : af[f < WO_D ? 0 : f - WO_D][0], c.sb) + (c.sb + SM_WO + (f & 1) * 32768 + (f >> 1) * 2048));
#pragma unroll
  for (int k = 0; k < 16; k++) mma_a(lv[k & 3], wv[k], r[k >> 1][2 * (k & 1)], r[k >> 1][2 * (k & 1) + 1]);
  const uint32_t z0 = put_tag(pack_bf16(sum(lv, 0), sum(lv, 1)), (~t16 >> 4) & 1, s >> 1), z1 = pack_bf16(sum(lv, 2), sum(lv, 3));
  st_pub2(dv, z0, z1);
  if (FIN_AT >= 3) mbar_arrive_warp(BAR(B_VST));
  TR(s, 2);
}
__device__ __forceinline__ uint32_t max_bf16x2(uint32_t a, uint32_t b) { uint32_t r; asm("max.bf16x2 %0, %1, %2;" : "=r"(r) : "r"(a), "r"(b)); return r; }
constexpr float SCL = 0.08838834764831845f * 1.4426950408889634f;
__device__ __forceinline__ uint32_t max5(const uint32_t (&sc)[5]) { return max_bf16x2(max_bf16x2(max_bf16x2(max_bf16x2(sc[0], sc[1]), sc[2]), sc[3]), sc[4]); }
__device__ __forceinline__ float row_off(uint32_t m, uint32_t& m1) {
  m1 = __shfl_xor_sync(~0u, m, 1);
  const uint32_t m2 = __shfl_xor_sync(~0u, m, 2), m3 = __shfl_xor_sync(~0u, m, 3);
  const uint32_t mm = max_bf16x2(max_bf16x2(max_bf16x2(m, m1), m2), m3);
  return -SCL * fmaxf(__uint_as_float(mm << 16), __uint_as_float(mm & 0xFFFF0000u));
}
__device__ __forceinline__ void unpack(float (&f)[10], const uint32_t (&sc)[5]) {
#pragma unroll
  for (int i = 0; i < 5; i++) {
    asm volatile("shl.b32 %0, %1, 16;" : "=f"(f[2 * i]) : "r"(sc[i]));
    asm volatile("and.b32 %0, %1, 0xffff0000;" : "=f"(f[2 * i + 1]) : "r"(sc[i]));
  }
}
__device__ __forceinline__ uint32_t exp_pair(const float (&f)[10], int i, float off) {
  return pack_bf16(ex2(fmaf(f[2 * i], SCL, off)), ex2(fmaf(f[2 * i + 1], SCL, off)));
}
template<bool SPLIT> __device__ __forceinline__ void scores_x(float (&a)[2][4], const uint4 (&kf)[4], const uint4& q, uint32_t z) {
#pragma unroll
  for (int t = 0; t < 2; t++) { a[t][0] = a[t][1] = a[t][2] = a[t][3] = 0.f; }
  mma_q(a[0], kf[0], q.x, q.y); mma_q(a[1], kf[2], q.x, q.y);
  if (SPLIT) sched_fence(z);
  mma_q(a[0], kf[1], q.z, q.w); mma_q(a[1], kf[3], q.z, q.w);
}
__device__ __forceinline__ uint32_t scores_m(const uint4& q, const uint4& k) {
  float a[4] = {}, b[4] = {};
  mma_q(a, q, k.x, k.z); mma_q(b, q, k.y, k.w);
  return pack_bf16(a[0] + b[2], a[1] + b[3]);
}
__device__ __forceinline__ void store_scores(const float (&a)[2][4], uint32_t dst) {
  sts64(dst, pack_bf16(a[0][0], a[0][2]), pack_bf16(a[1][0], a[1][2]));
  sts64(dst + 320, pack_bf16(a[0][1], a[0][3]), pack_bf16(a[1][1], a[1][3]));
}
__device__ __forceinline__ uint32_t sum4(uint32_t a, uint32_t b, uint32_t d, uint32_t e) { return add_bf16x2(add_bf16x2(a, b), add_bf16x2(d, e)); }
__device__ __forceinline__ void load_scores(uint32_t (&sc)[5], uint32_t ax, uint32_t am) {
  uint4 p[4];
#pragma unroll
  for (int i = 0; i < 4; i++) p[i] = lds128(ax + i * 1280);
  const uint2 m0 = lds64(am), m1 = lds64(am + 256);
  const uint4 t = add4(add4(add4(p[0], p[1]), p[2]), p[3]);
  sc[1] = t.x; sc[2] = t.y; sc[3] = t.z; sc[4] = t.w;
  sc[0] = sum4(m0.x, m0.y, m1.x, m1.y);
}
constexpr uint32_t ONES = 0x3F803F80u;
__device__ __forceinline__ float pv(float (&o)[2][4], const uint32_t (&p)[5], const uint4 (&vf)[4], const uint4& vm) {
  float a[4] = {}, b[4] = {};
#pragma unroll
  for (int t = 0; t < 2; t++) { o[t][0] = o[t][1] = o[t][2] = o[t][3] = 0.f; }
  mma_q(o[0], vf[0], p[1], p[2]); mma_q(o[1], vf[2], p[1], p[2]);
  mma_q(o[0], vf[1], p[3], p[4]); mma_q(o[1], vf[3], p[3], p[4]);
  mma16816(a, p[1], p[2], p[3], p[4], ONES, ONES);
  mma1688(o[0], vm.x, vm.y, p[0]); mma1688(o[1], vm.z, vm.w, p[0]);
  mma1688(b, p[0], ONES, ONES);
  return (a[0] + a[2]) + b[0];
}
constexpr uint32_t POLL_LIMIT = 1u << 21;
__device__ __forceinline__ uint32_t box(int slot, int cta) { return (slot * 2 + (cta >> 6)) * M_REG + (cta & 63) * 16384; }
__device__ __forceinline__ uint32_t near_page(const ChainCtx& c, int cta, uint32_t off) {
  return off + (((lds32(c.sb + SM_SEL + cta * 4) >> (off >> 21)) ^ __popc(off & 0xB2000)) & 1) * 4096;
}
__device__ __forceinline__ uint32_t e1_box(const ChainCtx& c, int slot, int cta) { return near_page(c, E1OFF ? cta ^ 2 : cta, box(slot, cta) + 8192) ^ (E1OFF ? 0 : 4096); }
__device__ __forceinline__ uint32_t tile_key() {
  uint32_t sm; asm volatile("mov.u32 %0, %%smid;" : "=r"(sm));
  return (sm < 64 ? sm / 2 % 8 : sm < 120 ? 1 + (sm / 2 - 32) % 7 : 0) << 24 | sm << 16;
}
__device__ __forceinline__ int tile_of(const ChainCtx& c) { return SIDE ? __shfl_sync(~0u, lds32(c.sb + SM_SEL + 528), 0) : c.r; }

__global__ void __cluster_dims__(2, 1, 1) __launch_bounds__(512, 1)
chain_kernel(const __grid_constant__ CUtensorMap tq, const __grid_constant__ CUtensorMap tk, const __grid_constant__ CUtensorMap tv,
             const __grid_constant__ CUtensorMap tv16, const __grid_constant__ CUtensorMap to, const __grid_constant__ CUtensorMap tx,
             const __grid_constant__ CUtensorMap twr, const __grid_constant__ CUtensorMap twi,
             const __grid_constant__ CUtensorMap ta, const __grid_constant__ CUtensorMap tw,
             const __grid_constant__ CUtensorMap tb, const __grid_constant__ CUtensorMap tout, const __grid_constant__ CUtensorMap tz,
             const __nv_bfloat16* __restrict__ mem0, char* __restrict__ mail, const __nv_bfloat16* __restrict__ x,
             const __nv_bfloat16* __restrict__ gw, __nv_bfloat16* __restrict__ out) {
  extern __shared__ __align__(1024) unsigned char smraw[];
  if (threadIdx.x == 0) TL(0);
  ChainCtx c;
  c.sb = __shfl_sync(~0u, smem_u32(smraw), 0);
  c.mail = mail; c.sel = 0; c.r = blockIdx.x;
  if (ROLE) {
    const uint32_t u = blockIdx.x >> 1, n = u < 36 ? 8 : 7, k = u - (u < 36 ? 4 : 36), q = k * (u < 36 ? 32 : 37) >> 8;
    c.r = __shfl_sync(~0u, 2 * (u - 4 < 60 ? u + k - q * n - (q & 1) * (n - 1) : u) + (blockIdx.x & 1) + (threadIdx.x >> 9), 0);
  }
  c.h = c.r >> 2; c.a = (c.r >> 1) & 1; c.b = c.r & 1; c.j = c.r & 3;
  c.m = __shfl_sync(~0u, (int)(threadIdx.x >> 7), 0); c.w = __shfl_sync(~0u, (int)((threadIdx.x >> 5) & 3), 0);
  char* own = c.mail + (uint32_t)(c.w * M_REG + M_E3 + (c.r >> 5) * 8192 + (c.r & 31) * 128 + (threadIdx.x & 31) * 4);
  uint32_t i0 = 0, i1 = 0;
  if (EARLY) asm volatile("{ .reg .pred p; setp.ne.u32 p, %4, 0; @p atom.relaxed.gpu.global.exch.b32 %0, [%2], %3; @p atom.relaxed.gpu.global.exch.b32 %1, [%2 + 4096], %3; }"
               : "+r"(i0), "+r"(i1) : "l"(own), "r"(SENT), "r"((uint32_t)(c.m == 2 && c.r < 128)) : "memory");
#pragma unroll
  for (int g = 0; g < 3; g++) {
    const int i = c.m * 4 + c.w;
    if (g < 2 || i < B_END - 32)
      asm volatile("{ .reg .pred p; elect.sync _|p, 0xffffffff; @p mbarrier.init.shared::cta.b64 [%0], %1; }"
                   :: "r"(BAR(g * 16 + i)), "r"(0x19080401u >> (bar_codes(g) >> 2 * i & 3) * 8 & 255) : "memory");
  }
  asm volatile("fence.mbarrier_init.release.cluster;" ::: "memory");
  __syncthreads();
  asm volatile("barrier.cluster.arrive.relaxed.aligned;" ::: "memory");

  if (c.r >= 128) {
    fft_cols((float2*)smraw, c.r - 128, &twr, &twi);
    if ((threadIdx.x & 127) == 0) TL(7);
    __syncwarp();
  } else if (c.m == 3) {
    asm volatile("setmaxnreg.dec.sync.aligned.u32 %0;" :: "n"(REG_H));
    c.lane = lane_id();
    if (c.sb & 1023) asm volatile("trap;");
    const int col = c.h * 128 + c.a * 64;
    uint32_t tl = clock_lo();
    TR(-2, 3);
    if (c.w == 0) {
      if (START) delay_until(tl + START);
      if (HOLD == 2) mbar_wait(BAR(B_PROBE), 0);
      if (HOLD == 3) mbar_wait(BAR(B_SEL), 0);
      if (HOLD == 1) mbar_wait(BAR(B_PROBE), 0);
      TR(-2, 4);
      tl = clock_lo();
      mbar_expect_e(BAR(B_PFULL), 2 * NP * 2048);
      mbar_expect_e(BAR(B_WFULL), (48 - NP) * 2048);
      mbar_expect_e(BAR(B_WFULL + 1), (48 - NP) * 2048);
    }
    auto dst_x = [&](int e, int w) {
      const uint32_t g2 = 2 * c.a + (w >> 1), u = w & 1;
      return M_KVQ + c.h * 24576 + (e == 0 ? 8192 + (2 * u + c.b) * 2048 + g2 * 512 : e == 1 ? g2 * 2048 + u * 1024 + c.b * 128 : 16384 + c.b * 4096 + g2 * 512 + u * 256);
    };
    if (c.w == 0) {
      tl += PACE0;
#pragma unroll wunr
      for (int i = 0; i < 24; i++) {
        const int m = i < 4 || i >= 16, k = i < 4 ? i : m ? i - 12 : i - 4;
        const int row = c.b * 512 + m * 256;
        const uint32_t st = c.sb + m * ST_WG, bar = BAR(k < 3 ? B_PFULL : B_WFULL + m);
        if (PACE) delay_until(tl += PACE);
        if (i == 14) { mbar_wait(BAR(B_FREE), 0); if (c.lane == 0) TL2(2); __syncwarp(); }
        if (k < 11) TMA_W(k < 3 ? c.sb + SM_POOL + m * NP * 2048 + k * 8192 : k == 3 ? c.sb + SM_HV + (m * NHV + 1) * 2048 : st + (k - 4) * 8192,
                          k == 3 || k > 8 ? &tv : (k >> 2 & 1) == m ? &tk : &tq, col, row + (k < 8 ? k & 3 : (k - 9) & 3) * 64, bar);
        else {
#pragma unroll 1
          for (int j = 8; j < 12; j++) TMA_W(j < NV ? st + (32 - NP + j) * 2048 : c.sb + SM_HV + m * NHV * 2048, &tv16, col, row + j * 16, bar);
        }
      }
      TR(-2, 7);
    } else if (c.w == 2) {
      const unsigned short* mp = (const unsigned short*)mem0 + (2 * (c.lane & 3)) * D_ + 8 * c.r + (c.lane >> 2);
      uint32_t mv = (uint32_t)mp[0] | (uint32_t)mp[D_] << 16;
      if (mv == SENT) mv = 0x7FFF7FFFu;
      mbar_wait(BAR(B_PROBE), 0);
      char* dst = c.mail + (uint32_t)(M_E3 + (c.r >> 5) * 8192 + (c.r & 31) * 128 + c.lane * 4);
      st_pub(dst, mv); st_pub(dst + 4096, mv);
    } else if (c.w == 3) {
      mbar_wait(BAR(B_FREE), 0);
      mbar_wait(BAR(B_PFULL), 0);
      mbar_expect_e(BAR(B_PFULL), 65536);
      for (int i = 0; i < 2; i++) tma4d_e(c.sb + SM_XT + i * 16384, &tx, c.b * 8, 4 + 2 * (c.b ^ i), BAR(B_PFULL));
    }
    {
      mbar_wait(BAR(B_SEL), 0);
      const int i = tid_now() & 127, sl = i & 3, e = (i >> 2) & 3;
      uint32_t ox = dst_x(e, i >> 5) + sl * M_REG;
      uint32_t oh = e & 1 ? (sl ^ (e & 2)) * M_REG + M_E3 + (c.r >> 5) * 8192 + (c.w & 1) * 4096 + (c.r & 31) * 128
                          : near_page(c, c.r, e ? sl * M_REG + M_E3 + (c.b * 2 + (c.w >> 1)) * 8192 : box(~sl & 1, c.r)) + (e ? (c.w & 1) * 2048 : c.w * 1024), of;
      {
        const int e = i & 7, w = (i >> 3) & 3, m = (i >> 5) & 1, sl = i >> 6;
        const int cta = e < 2 ? c.r & ~1 : e == 2 ? c.r | 1 : e == 3 ? c.h * 4 + 2 * m + 1 : c.j * 32 + m * 8 + 2 * w + (e & 2) * 8 + (e & 1);
        const uint32_t off = e < 2 ? c.b * 2048 + m * 1024 + (w >> 1) * 512 + e * 160 : e == 2 ? c.b * 2048 + m * 1024 + w * 256 : e == 3 ? w * 256 : c.h * 128;
        of = (e < 4 ? e1_box(c, sl, cta) : near_page(c, cta, box(sl, cta))) + off;
      }
      char *px = c.mail + ox, *ph = c.mail + oh, *pf = c.mail + of;
      uint32_t at = sl * 128 + (i >> 5) * 32 + e * 8, af = i * 8;
      pin(px); pin(ph); pin(pf); pin(at); pin(af);
      asm volatile("barrier.cluster.wait;" ::: "memory");
      TR(-2, 0);
      mbar_wait(BAR(B_WREAD), 0);
      TR(-2, 1);
      mbar_arrive_both(BAR(B_LFREE), c.b ^ 1);
      sts64(at + (c.sb + SM_TAB + 1536), (uint32_t)(uintptr_t)px, (uint32_t)((uintptr_t)px >> 32));
      sts64(at + (c.sb + SM_TAB + 1024), (uint32_t)(uintptr_t)ph, (uint32_t)((uintptr_t)ph >> 32));
      sts64(af + (c.sb + SM_TAB), (uint32_t)(uintptr_t)pf, (uint32_t)((uintptr_t)pf >> 32));
      TR(-2, 2);
      if (tid_now() == 384) TL2(25);
      __syncwarp();
      bar_sync(14, 160);
    }
    pad<PAD3>();
    for (int s = -1; s < NSEG; s++) {
      if (E30 ? s != 0 : s >= 0) {
        const uint32_t tab = c.sb + SM_TAB + 1024 + (max(s, 0) & 3) * 128 + c.w * 32;
        uint32_t t0;
        if (s > 0) {
          const uint32_t ln = tid_now() & 31;
          const uint4 ta = lds128(tab);
          const char* src = mk_ptr(ta.x | ln * 4, ta.y);
          char* dst = mk_ptr(ta.z | ln * 4, ta.w);
          const uint32_t tg = (s - 1) >> 1, chk = (ln & 3) ? 0u : 1u, red = ln * (RED_L == 3 ? 4 : 8);
          touch(src, dep(c.sb, chk, c.sb)); touch(dst, dep(c.sb, red, c.sb));
          mbar_wait(BAR(B_E2TRIG), (s - 1) & 1);
          TR(s, 0);
          if (ANCH2) delay_fine(lds32(c.sb + SM_SUM + 64) + DLY_E2); else delay_cycles(DLY_E2);
          uint32_t n = 0;
          while (true) {
            uint32_t v[8];
#pragma unroll
            for (int i = 0; i < 8; i++) v[i] = ld_poll1(src + i * 128);
            if (E2_F) sched_fence(c.sb);
            const uint32_t bad = RED_T ? (stale2(v[0], v[1], tg) | stale2(v[2], v[3], tg) | stale2(v[4], v[5], tg)) | stale2(v[6], v[7], tg)
                                       : stale1(stale1(stale2(v[0], v[1], tg), v[2], tg), v[3], tg) | stale1(stale1(stale2(v[4], v[5], tg), v[6], tg), v[7], tg);
            const bool ok = all_clear(bad, chk);
#pragma unroll
            for (int l = 0; l < RED_L; l++)
#pragma unroll
              for (int i = 0; i < (4 >> l); i++) v[i] = add_bf16x2(v[2 * i], v[2 * i + 1]);
            if (RED_L == 3) sts32(red + (c.sb + SM_RED + c.w * 128), v[0]);
            else {
              float lo[8], hi[8];
#pragma unroll
              for (int i = 0; i < (8 >> RED_L); i++) { lo[i] = __uint_as_float(v[i] << 16); hi[i] = __uint_as_float(v[i] & 0xFFFF0000u); }
#pragma unroll
              for (int l = RED_L; l < 3; l++)
#pragma unroll
                for (int i = 0; i < (4 >> l); i++) { lo[i] = lo[2 * i] + lo[2 * i + 1]; hi[i] = hi[2 * i] + hi[2 * i + 1]; }
              sts64(red + (c.sb + SM_RED + c.w * 256), __float_as_uint(lo[0]), __float_as_uint(hi[0]));
            }
            if (ok) break;
            n++; CNT(0);
          }
          bar_sync(NB_HELP, 128);
          const uint32_t rd = red + (c.sb + SM_RED);
          if (!RED_P || c.w < 2) {
            if (RED_L == 3) st_pub_if(dst, sum4(lds32(rd), lds32(rd + 128), lds32(rd + 256), lds32(rd + 384)), c.w < 2);
            else {
              const uint2 p0 = lds64(rd), p1 = lds64(rd + 256), p2 = lds64(rd + 512), p3 = lds64(rd + 768);
              st_pub_if(dst, pack_bf16((__uint_as_float(p0.x) + __uint_as_float(p1.x)) + (__uint_as_float(p2.x) + __uint_as_float(p3.x)),
                                       (__uint_as_float(p0.y) + __uint_as_float(p1.y)) + (__uint_as_float(p2.y) + __uint_as_float(p3.y))), c.w < 2);
            }
          }
          t0 = clock_lo();
          mbar_arrive_warp(BAR(B_PUB));
          TRV(s, 15, n);
          mbar_wait(BAR(B_SPFREE), (s - 1) & 1);
        } else {
          if (tid_now() == 384) TL2(24);
          __syncwarp();
          if (!E30) mbar_wait(BAR(B_PROBE), 1);
          if (!WO_S) mbar_wait(BAR(B_WOFULL), 0);
          if (tid_now() == 384) TL2(19);
          __syncwarp();
          t0 = clock_lo() - DLY_E3;
        }
        TRV(s, 1, t0);
        {
          const uint32_t l16 = (tid_now() & 31) * 16, dst = vary(l16, s, c.sb) + (c.sb + SM_MEM + (c.w & 1) * 4096 + (c.w >> 1) * 2048);
          const uint4 tb = lds128(tab + 16);
          st_pub_if(mk_ptr(tb.z | l16 >> 2, tb.w), SENT, c.w >= 2);
          const char* src = mk_ptr(tb.x | l16, tb.y);
          touch(src, dep(c.sb, dst, c.sb));
          delay_fine(t0 + (DLY_E3 + (c.w & 1) * DLY_E3B));
          uint32_t n = 0;
          while (true) {
            uint4 v[4];
#pragma unroll
            for (int i = 0; i < 4; i++) v[i] = ld_poll(src + i * 512);
#pragma unroll
            for (int i = 0; i < 4; i++) sts128(dst + i * 512, v[i]);
            if (arrive_if_all(max(max(v[0].x, v[1].x), max(v[2].x, v[3].x)) != SENT, NB_MEM + (c.w & 1) * 2 + (c.w >> 1), 160)) break;
            n++; CNT(1);
          }
          TR(s, 2); TRV(s, 14, n);
        }
        if (s == 1) CLK(1); if (s == 8) CLK(2); if (s == 56) CLK(3);
        if (c.w == 2 && s == 15) TRSYNC(8);
        if (c.w == 2 && s == 21) TRSYNC(10);
      }
      const int g = s + 1;
      auto load_v = [&]() {
        if (V_TMA && c.w == V_W) {
          mbar_expect_e(BAR(B_VFULL), 8192);
          bulk_load_e(c.sb + SM_V, c.mail + (uint32_t)(M_KVQ + (min(g, XEND - 1) & (NSLOT - 1)) * M_REG + c.h * 24576 + 8192), 8192, BAR(B_VFULL));
        }
      };
      if (XEND < NSEG && g >= XEND && g < NSEG) { mbar_wait(BAR(B_SC), s & 1); load_v(); }
      if (g < XEND) {
        const uint32_t tx_ = c.sb + SM_TAB + 1536 + (g & 3) * 128 + c.w * 32, tag = (g >> 2) & 1;
        if (c.w == 0) mbar_expect_e(BAR(B_LAND), EXP_PEER * 12288);
        auto load_x = [&]() {
          if (c.w == 3 && g + 1 < XEND) {
            mbar_wait(BAR(B_XEMPTY), g & 1);
            mbar_expect_e(BAR(B_XFULL), 16384 * EXP_NXT);
            for (int i = 0; i < EXP_NXT; i++) tma4d_e(c.sb + SM_XT + i * 16384, &tx, c.b * 8, (g + 1) * 4 + 2 * (c.b ^ i), BAR(B_XFULL));
          }
        };
        if (X_AT == 0 && g > 0) load_x();
        TR(s, 6);
        if (E30 && g == 0) mbar_wait(BAR(B_PROBE), 1);
        mbar_wait(BAR(B_LAND), g & 1);
        TR(s, 7);
        if (DLY_F && g > 0) delay_cycles(DLY_F);
        auto total = [&](int w, int lane, uint32_t o0, uint32_t o1) {
          const uint32_t a = c.sb + SM_LAND + land_off(w, lane);
          if (EXP_FL == 1) return make_uint4(a, a, a, a);
          const uint4 t = add4(lds128(a + o0), lds128(a + o1 + 2048));
          const uint32_t a2 = dep(dep(a, t.x ^ t.y ^ t.z, c.sb), t.w, c.sb);
          return add4(t, add4(lds128(a2 + o0 + 4096), lds128(a2 + o1 + 6144)));
        };
        auto get = [&](int e) {
          const int ln = tid_now() & 31;
          return e == 0 ? total(c.w, ln, 16384, 16384)
               : e == 1 ? total((c.w & 2) + ((ln >> 1) & 1), (ln & 1) * 16 + (c.w & 1) * 8 + (ln >> 2), 8192, 0)
                        : total((c.w & 2) + ((ln >> 1) & 1), (ln & 1) * 16 + (ln >> 3) * 4 + (c.w & 1) * 2 + ((ln >> 2) & 1), 0, 8192);
        };
        auto put = [&](int e, uint4 v) {
          const int ln = tid_now() & 31;
          const uint2 d = lds64(tx_ + e * 8);
          if (e < 2) {
            v.x = tagged(v.x, tag);
            st_pub4(mk_ptr(d.x | (e ? (ln & 24) * 32 + (ln & 7) * 16 : ln * 16), d.y), v);
          } else {
            char* dst = mk_ptr(d.x | ((ln & 7) * 16 + (ln >> 3) * 4), d.y);
            const uint32_t bit = ln < 8;
            st_pub(dst, put_tag(v.x, bit, tag)); st_pub(dst + 128, put_tag(v.y, bit, tag));
            st_pub(dst + 2048, put_tag(v.z, bit, tag)); st_pub(dst + 2176, put_tag(v.w, bit, tag));
          }
        };
        auto after_sc = [&]() { if (g > 0) { mbar_wait(BAR(B_SC), s & 1); if (DLY_FK) delay_cycles(DLY_FK); if (X_AT == 1) load_x(); } };
        if (FIN_AT == 5) {
          put(0, get(0));
          if (DLY_F2 && g > 0) delay_cycles(DLY_F2); else sched_fence(c.sb);
          const uint4 k = get(1);
          sched_fence(c.sb);
          const uint4 q = get(2);
          if (g > 0) mbar_wait(BAR(B_VST), s & 1);
          put(1, k); put(2, q);
          TR(s, 5);
          mbar_arrive_both(BAR(B_LFREE), c.b ^ 1);
          after_sc();
          load_v();
          continue;
        }
        if (FIN_AT < 3) {
          if (EXP_FIN & 1) put(0, get(0));
          TR(s, 3);
          if (FIN_AT == 1) after_sc();
          if (V_TMA == 1) load_v();
          if (EXP_FIN & 2) put(1, get(1));
        } else {
          const uint4 v = get(0);
          sched_fence(c.sb);
          const uint4 k = get(1);
          if (g > 0) { mbar_wait(BAR(B_VST), s & 1); if (DLY_FS) delay_cycles(DLY_FS); }
          put(0, v); put(1, k);
        }
        TR(s, 4);
        if (FIN_AT == 4) {
          const uint4 q = get(2);
          after_sc();
          load_v();
          put(2, q);
        } else {
          if (FIN_AT >= 2) after_sc();
          if (V_TMA == 2) load_v();
          if (EXP_FIN & 4) put(2, get(2));
        }
        mbar_arrive_both(BAR(B_LFREE), c.b ^ 1);
        if (V_TMA == 3) load_v();
        TR(s, 5);
        if (!FIN_AT && X_AT && g > 0) { mbar_wait(BAR(B_SC), s & 1); if (DLY_FK) delay_cycles(DLY_FK); load_x(); }
      }
    }
    const int tile = tile_of(c), m0 = (tile >> 3) * 128 + c.b * 64, n0 = (tile & 7) * 128;
    auto load_b = [&](int kb, uint32_t o, uint32_t bar) {
      mbar_expect_e(bar, 32768);
      tma2d_e(c.sb + o + 16384, &tw, n0, kb * 64, bar);
      tma2d_e(c.sb + o + 24576, &tw, n0 + 64, kb * 64, bar);
    };
    auto load_a = [&](int kb, uint32_t o, uint32_t bar) { tma2d_mc_e(c.sb + o + c.b * 8192, &ta, kb * 64, m0, bar); };
    if (c.w == 1) {
      mbar_wait(BAR(B_PVDONE), 0);
      count_e(g_ctl + C_EARLY);
      st_pub(c.mail + (uint32_t)((tid_now() & 6) * (M_REG / 2) + M_SEL + (tid_now() & 1) * 4096 + c.r * 4), 0);
      await_count(g_ctl + C_COLS, 4);
      mbar_expect_e(BAR(B_TW), 8192);
      bulk_load_e(c.sb + SM_TW, g_tw, 8192, BAR(B_TW));
    } else if (c.w == 2) {
      const uint32_t ln = tid_now() & 31, rel = mapa(BAR(B_GEMPTY) + (ln >> 2) * 8, ln & 1);
      mbar_wait(BAR(B_VST), 1); mbar_wait(BAR(PRE_AT), 1);
      arrive_remote_if(rel, ln < 12);
      mbar_wait(BAR(B_E2TRIG), 1);
      if (GATE) mbar_wait(BAR(B_DONE), 0);
      arrive_remote_if(rel, ln >= 12 && ln < 20);
    } else {
      auto ahead = [&](int k) {
        if (c.w) { if (PF_A && (k & 3) == (tile >> 1 & 3)) prefetch2d_e(&ta, k * 64, m0); }
        else if (PF_B && (k & 7) == (tile >> 4)) prefetch2d_e(&tw, n0 + (tile & 8) * 8, k * 64);
      };
#pragma unroll 1
      for (int k = 0; k < PF_D; k++) ahead(k);
      if (c.w == 3) { await_count(g_ctl + C_EARLY, 128); if (tile >= 120) { if (LASTM == 2) await_flags(g_ctl + C_LAST + (tid_now() & 31) * 4); else await_count(g_ctl + C_LAST, 512); } }
      if (tid_now() == 480) TL(10);
      __syncwarp();
      uint32_t o = SM_XT, st = 0, ph = 0;
#pragma unroll 1
      for (int kb = 0; kb < 64; kb++, o = next_stage(o)) {
        mbar_wait(BAR(B_GEMPTY + st), ph);
        const int k = (kb + (tile < 120 ? 0 : LROT)) & 63;
        if (c.w) load_a(k, o, BAR(B_GFULL + st)); else load_b(k, o, BAR(B_GFULL + st));
        if (kb + PF_D < 64) ahead(kb + PF_D);
        if (++st == 5) { st = 0; ph ^= 1; }
      }
    }
    return;
  } else if (c.m == 2) {
    asm volatile("setmaxnreg.dec.sync.aligned.u32 %0;" :: "n"(512 - 2 * REG_F - REG_H));
    c.lane = lane_id();
    {
      uint32_t tl = clock_lo() + (PACE0 + WO_AT * PACE);
      TR(-2, 0);
      sched_fence(i0 ^ i1);
      TR(-2, 7);
      int far1 = 0;
#pragma unroll 1
      for (int rep = EARLY; rep <= NPROBE; rep++) {
        const int lag = race_init(own + (rep & 1) * 4096, own + (~rep & 1) * 4096, SENT);
        if (rep) far1 += ((rep ^ c.r >> 5) & 1 ? 1 : -1) * min(lag, 200);
      }
      sts32(c.sb + SM_SEL + 512 + c.w * 4, (8 + far1 / (16 * NPROBE)) << 4 * c.w);
      TR(-2, 1);
      if (tid_now() == 256) TL2(14);
      __syncwarp();
      mbar_arrive_warp(BAR(B_PROBE));
      if (c.w == 0) {
        mbar_wait(BAR(B_PROBE), 0);
        const uint4 bits = lds128(c.sb + SM_SEL + 512);
        const uint32_t res = bits.x | bits.y | bits.z | bits.w;
        st_pub_if(c.mail + (uint32_t)((c.lane & 6) * (M_REG / 2) + M_SEL + (c.lane & 1) * 4096 + c.r * 4), res | tile_key(), c.lane < 8);
        const int q = (res >> 4 * ((c.lane + c.r) & 3) & 15) - 8, best = __reduce_max_sync(~0u, abs(q) * 64 + (c.lane & 3) * 16 + ((c.lane + c.r) & 3) * 2 + (q <= 0));
        const char* src = c.mail + (uint32_t)((best & 6) * (M_REG / 2) + M_SEL + (best & 1) * 4096 + c.lane * 16);
        if (SEL_AT) delay_until(tl - (PACE0 + WO_AT * PACE - SEL_AT));
        uint4 v; uint32_t n = 0;
        TR(-2, 4);
        while (true) {
          delay_cycles(DLY_SEL);
          TR(-2, 6);
          v = ld_poll(src);
          if (__all_sync(~0u, v.x && v.y && v.z && v.w)) break;
          watchdog(n, POLL_LIMIT);
        }
        TR(-2, 5);
        int ta = 0, tb = 0, pa = 0, pb = 0;
        uint32_t flip = 0;
#pragma unroll 1
        for (int i = 0; i < 4; i++) {
          const int a = (v.x >> 4 * i & 15) + (v.y >> 4 * i & 15) - 16, b = (v.z >> 4 * i & 15) + (v.w >> 4 * i & 15) - 16;
          const bool f = __reduce_add_sync(~0u, a * ta + b * tb) < 0;
          ta += f ? -a : a; tb += f ? -b : b; flip |= (uint32_t)f << i;
        }
#pragma unroll 1
        for (uint32_t g = 0; g < 8; g++) {
          const bool a = (v.x >> 16) - g * 256 < 120, b = (v.z >> 16) - g * 256 < 120;
          const int n = __reduce_add_sync(~0u, (a ? ta : 0) + (b ? tb : 0)) > 0 ? PRIOR : -PRIOR;
          if (a) pa = n;
          if (b) pb = n;
        }
        const uint32_t ka = AWARE && ta + pa > 0 ? ~flip : flip, kb = AWARE && tb + pb > 0 ? ~flip : flip;
        sts128(c.sb + SM_SEL + c.lane * 16, make_uint4(ka, ka, kb, kb));
        mbar_arrive_warp(BAR(B_SEL));
        const uint32_t key = __shfl_sync(~0u, c.a ? v.z : v.x, c.h);
        const int u = __popc(__ballot_sync(~0u, v.x < key)) + __popc(__ballot_sync(~0u, v.z < key));
        sts32(c.sb + SM_SEL + 528, (u & 32) * 2 + (u & 7) * 8 + (u >> 2 & 6) + c.b);
        TR(-2, 2);
        if (c.lane == 0) TL2(13);
        __syncwarp();
        bar_sync(14, 160);
        if (ZDLY) delay_cycles(ZDLY);
#pragma unroll 4
        for (int k = c.lane >> 3; k < (ZINIT ? 128 : 0); k += 4) {
          const int e = k & 7;
          const uint2 d = lds64(c.sb + SM_TAB + (e == 3 ? k - 1 : k) * 8);
          st_pub4(mk_ptr((d.x & ~127u) + (e < 2 ? (k & 8) * 32 : e == 3 ? 128 : 0) + (c.lane & 7) * 16, d.y), make_uint4(0, 0, 0, 0));
        }
        __syncwarp();
        if (c.lane < 4) asm volatile("mbarrier.arrive.shared::cta.b64 _, [%0];" :: "r"(BAR(B_PROBE)) : "memory");
        __syncwarp();
        TR(-2, 8);
      }
      if (c.w == 2) {
        mbar_wait(BAR(B_P1), 0);
        if (P1_AT) { mbar_wait(BAR(B_WFULL), 0); mbar_wait(BAR(B_WFULL + 1), 0); }
        st_pub_if(g_ctl + C_COLS + (c.r & 15) * 32 + c.lane, 0, c.r < (C_END - C_COLS) / 32);
        count_e(g_ctl + C_P1);
        TR(-2, 3);
      }
      if (c.w == 1) for (int i = 0; i < WO_N; i++) { delay_until(tl += WO_P * PACE); prefetch2d_e(&to, c.j * 256 + (i ^ WO_X) * 64, c.h * 128); }
      if (c.w == 3) {
        mbar_wait(BAR(B_WREAD0), 0);
        for (int i = 0; i < 2; i++) tma4d_e(c.sb + SM_WO + i * 16384, &tx, c.b * 8, 2 * (c.b ^ i), BAR(B_PFULL));
        mbar_expect_e(BAR(B_WOFULL), 65536);
#pragma unroll 1
        for (int i = 3; i >= 0; i--) {
          if (i & 1) mbar_wait(BAR(i < 2 ? B_XEMPTY : B_WREAD), 0);
          TMA_O(c.sb + SM_WO + i * 16384, &to, c.j * 256 + i * 64, c.h * 128, BAR(B_WOFULL));
        }
      }
    }
    asm volatile("barrier.cluster.wait;" ::: "memory");
    const int g = c.w, src0 = c.h * 4 + (g >> 1) * 2;
    mbar_wait(BAR(B_SEL), 0);
    c.sel = __shfl_sync(~0u, (e1_box(c, 0, src0 + (c.lane >> 5)) & 4096) | (e1_box(c, 1, src0) & 4096) * 2, 0);
    mbar_wait(BAR(B_WREAD), 0);
    uint32_t l16 = c.sb + g * 512 + c.lane * 16;
    auto lane = [&](uint32_t v) { l16 = dep(l16, v, c.sb); return (int)((l16 & 511) >> 4); };
    pad<PAD2>();
    for (int s = 0; s < NSEG; s++) {
      l16 = vary(l16, s, c.sb);
      int ln = (l16 & 511) >> 4;
      uint4 kf[4], qx;
      {
        const int gs = min(s, XEND - 1);
        const char* pk = c.mail + (uint32_t)(M_KVQ + (gs & (NSLOT - 1)) * M_REG + c.h * 24576 + g * 2048 + ln * 16);
        const char* pq = pk + (16384 + c.j * 2048 - g * 1536);
        const uint32_t tg = (gs / NSLOT) & 1;
        touch(pk, c.sb); touch(pq, c.sb);
        TR(s, 0);
        mbar_wait(BAR(B_VFULL), s & 1);
        TR(s, 1);
        if (s > 0) mbar_wait(BAR(B_PUB), (s - 1) & 1);
        for (uint32_t n = 0; ; ) {
          uint4 k[4];
#pragma unroll
          for (int t = 0; t < 4; t++) k[t] = ld_poll(pk + t * 512);
          qx = ld_poll(pq);
#pragma unroll
          for (int t = 0; t < 2; t++) {
            auto cp = [&](uint32_t v) { return dep(v, 0, c.sb); };
            kf[t] = make_uint4(cp(k[2 * t].x), cp(k[2 * t].y), cp(k[2 * t + 1].x), cp(k[2 * t + 1].y));
            kf[2 + t] = make_uint4(cp(k[2 * t].z), cp(k[2 * t].w), cp(k[2 * t + 1].z), cp(k[2 * t + 1].w));
          }
          if (all_clear(stale1(stale2(k[0].x, k[1].x, tg) | stale2(k[2].x, k[3].x, tg), qx.x, tg), EXP_CHK)) break;
          watchdog(n, POLL_LIMIT); CNT(4);
        }
        TR(s, 2);
      }
      if (X_AT >= 2 && g == 0 && s + 2 < XEND) {
        mbar_wait(BAR(B_XEMPTY), ~s & 1);
        mbar_expect_e(BAR(B_XFULL), 16384 * EXP_NXT);
        for (int i = 0; i < EXP_NXT; i++) tma4d_e(c.sb + SM_XT + i * 16384, &tx, c.b * 8, (s + 2) * 4 + 2 * (c.b ^ i), BAR(B_XFULL));
      }
      ln = lane(kf[0].y);
      const char* pa = c.mail + (uint32_t)(box(s & 1, src0) + 8192 + (c.sel >> (s & 1) & 4096) + (g & 1) * 512 + (EXP_LIN ? ln * 16 : read_off(ln)));
      const uint32_t spw = c.sb + SM_SP + g * 1280 + (ln & 3) * 64 + ((((ln >> 3) ^ ln) & 2) << 4) + (ln & 4) * 4 + (ln & 8),
                     spr = c.sb + SM_SP + (ln & 4) * 80 + (ln >> 3) * 64 + (((ln & 3) ^ ((ln >> 3) & 2)) << 4), l8 = ln * 8;
      const uint32_t tg = s >> 1;
      float sx[2][4];
      uint32_t sm;
      uint4 km;
      touch(pa, c.sb);
      mbar_wait(BAR(B_E1TRIG), s & 1);
      const uint32_t t0 = clock_lo();
      TRV(s, 3, t0);
      scores_x<false>(sx, kf, qx, 0);
      store_scores(sx, spw + 640);
      delay_fine(t0 + DLY_E1);
      uint32_t nr = 0;
      while (true) {
        const uint4 q0 = ld_poll(pa), q1 = ld_poll(pa + 2048), k0 = ld_poll(pa + 1024), k1 = ld_poll(pa + 3072);
        uint4 qm = add4(q0, q1);
        const uint32_t bq = stale2(q0.x, q1.x, tg);
        qm.x = dep(qm.x, bq, c.sb);
        scores_x<SC_F>(sx, kf, qm, c.sb);
        const uint32_t bk = stale2(k0.x, k1.x, tg);
        km = add4(k0, k1);
        km.x = dep(km.x, bk, c.sb);
        const bool ok = all_clear(bq | bk, 1);
        sm = scores_m(qm, km);
        store_scores(sx, spw);
        if (ok) break;
        nr++; CNT(2);
      }
      sts32(l8 + (c.sb + SM_SPM + (g >> 1) * 256 + (g & 1) * 4), sm);
      bar_sync(NB_ATT, 128);
      TR(s, 5); TRV(s, 13, nr);
      float o[2][4];
      uint32_t sp[5];
      uint4 vf[4];
      load_scores(sp, spr, l8 + (c.sb + SM_SPM));
      const uint32_t m5 = max5(sp);
      uint32_t m1;
      float off = row_off(m5, m1), f[10];
      l16 = dep(l16, VF_AT ? m1 : m5, c.sb);
#pragma unroll
      for (int t = 0; t < 4; t++) vf[(t >> 1) + 2 * (t & 1)] = lds128(l16 + SM_V + ((t >> 1) + 2 * (t & 1)) * 2048);
      qx.x = dep(qx.x, sp[0], c.sb);
      sts32(l8 + (c.sb + SM_SPM + 512 + (g >> 1) * 256 + (g & 1) * 4), scores_m(qx, km));
      mbar_arrive_warp(BAR(B_SC));
      unpack(f, sp);
      if (UP_F) sched_fence(c.sb);
      uint4 vm;
      if (VM_AT < 2) {
        bar_sync(NB_VM, 384);
        sp[1] = exp_pair(f, 1, off);
        const uint32_t av = dep(l8, VM_AT ? sp[1] : __float_as_uint(off), c.sb) + (c.sb + g * 512 + SM_VM);
        const uint2 vm0 = lds64(av), vm1 = lds64(av + 256);
        vm = make_uint4(vm0.x, vm0.y, vm1.x, vm1.y);
#pragma unroll
        for (int i = 2; i < 6; i++) sp[i % 5] = exp_pair(f, i % 5, off);
      } else {
#pragma unroll
        for (int i = 1; i < 6; i++) sp[i % 5] = exp_pair(f, i % 5, off);
        bar_sync(VM_AT == 2 ? dep(dep(0, sp[1] ^ sp[2], c.sb) + NB_VM, sp[0], c.sb) : dep(dep(0, sp[0] ^ sp[1] ^ sp[2], c.sb) + NB_VM, sp[3], c.sb), 384);
        const uint32_t av = l8 + (c.sb + g * 512 + SM_VM);
        const uint2 vm0 = lds64(av), vm1 = lds64(av + 256);
        vm = make_uint4(vm0.x, vm0.y, vm1.x, vm1.y);
      }
      float sum;
      auto rows_m = [&]() {
        const uint32_t tv = min(s, XEND - 1) / NSLOT;
        sum = pv(o, sp, vf, vm);
        stsm4<false>(l16 + SM_OM, pack_bf16(o[0][0], o[0][1]), pack_bf16(o[0][2], o[0][3]), pack_bf16(o[1][0], o[1][1]), pack_bf16(o[1][2], o[1][3]));
        sts32(c.sb + SM_SUM + ((l16 >> 4) & 28), __float_as_uint(sum));
        return arrive_if_clear(stale2(vf[0].x, vf[1].x, tv) | stale2(vf[2].x, vf[3].x, tv), EXP_CHK, NB_OM, 384);
      };
      if (!rows_m()) {
        const char* pv_ = c.mail + (uint32_t)(M_KVQ + (min(s, XEND - 1) & (NSLOT - 1)) * M_REG + c.h * 24576 + 8192 + (l16 - c.sb));
        uint32_t n = 0;
        do {
#pragma unroll
          for (int t = 0; t < 4; t++) vf[t] = ld_poll(pv_ + t * 2048);
          watchdog(n, POLL_LIMIT); CNT(5);
        } while (!rows_m());
      }
      const uint32_t tom = clock_lo();
      TRV(s, 8, tom);
      sched_fence(c.sb);
      ln = lane(tom);
      const int n = ln >> 2, jj = ln & 3, tq_ = 8 * c.j + (n & 4) + 2 * (n & 1) + ((n >> 1) & 1), lim = 16 * (tq_ - 2 * jj + 1);
      if (DLY_X) delay_until(tom + DLY_X);
      load_scores(sp, spr + 640, c.sb + SM_SPM + 512 + ln * 8);
#pragma unroll
      for (int w = 0; w < 4; w++) {
        uint32_t m; asm("shl.b32 %0, 0xffffffff, %1;" : "=r"(m) : "r"(max(lim - 128 * w, 0)));
        sp[1 + w] = (sp[1 + w] & ~m) | (0xD029D029u & m);
      }
      mbar_arrive_warp(dep(dep(0, sp[0], c.sb), sp[1], c.sb) + BAR(B_SPFREE));
      off = row_off(max5(sp), m1);
      unpack(f, sp);
#pragma unroll
      for (int i = 1; i < 6; i++) sp[i % 5] = exp_pair(f, i % 5, off);
      sum = pv(o, sp, vf, vm);
      TR(s, 7);
      sum = rcp(sum);
      const float i0 = __shfl_sync(~0u, sum, 8 * jj), i1 = __shfl_sync(~0u, sum, 8 * jj + 4);
      const uint32_t oxs = c.sb + SM_OX + g * 512;
      stsm4<true>(oxs + (ln & 7) * 64 + (((ln >> 3) ^ ((ln >> 1) & 3)) << 4),
                  pack_bf16(o[0][0] * i0, o[0][1] * i1), pack_bf16(o[0][2] * i0, o[0][3] * i1), pack_bf16(o[1][0] * i0, o[1][1] * i1), pack_bf16(o[1][2] * i0, o[1][3] * i1));
      __syncwarp();
      *(uint4*)(g_ox + (uint32_t)((32 * s + tq_) * 4096 + c.h * 128 + 32 * g + 8 * jj)) = lds128(oxs + n * 64 + ((jj ^ (n >> 1)) << 4));
      mbar_arrive_warp(BAR(B_PVDONE));
      TR(s, 9);
    }
    if (LASTM) {
      const int ln = tid_now() & 31, n = ln >> 2, jj = ln & 3, tq_ = 8 * c.j + (n & 4) + 2 * (n & 1) + ((n >> 1) & 1);
      store_count(g_ox + (uint32_t)((S_ - 32 + tq_) * 4096 + c.h * 128 + 32 * g + 8 * jj), lds128(c.sb + SM_OX + g * 512 + n * 64 + ((jj ^ (n >> 1)) << 4)), (char*)(g_ctl + C_LAST) + (LASTM == 2 ? c.r * 4 + g : 0));
    } else count_e(g_ctl + C_LAST);
    mbar_arrive_warp(BAR(B_DONE));
    if (tid_now() == 256) TL(8);
    __syncwarp();
    mbar_wait(BAR(B_E2TRIG), 1); mbar_wait(BAR(B_DONE), 0); mbar_wait(BAR(B_TW), 0);
    asm volatile("setmaxnreg.inc.sync.aligned.u32 128;");
  } else {
    {
      const int w = c.m * 4 + c.w;
      mbar_expect_e(BAR(B_ROWS), 4096 + 256);
      for (int i = 0; i < 2; i++) bulk_load_e(c.sb + SM_FFT + (1024 + w * ROW_BUF) * 8 + i * 2048, x + (size_t)(z_row(c.r * 8 + w) + i * 1024) * D_, 2048, BAR(B_ROWS));
      bulk_load_e(c.sb + SM_GW + w * 256, gw + w * 128, 256, BAR(B_ROWS));
    }
    asm volatile("setmaxnreg.inc.sync.aligned.u32 %0;" :: "n"(REG_F));
    c.lane = lane_id();
    uint32_t wa[16][4], wb[16][4], wv[16][4];
    TR(-2, 4);
    fft_rows_fwd((float2*)(smraw + SM_FFT), (const __nv_bfloat16*)(smraw + SM_GW), c.r, threadIdx.x, BAR(B_ROWS), BAR(B_FREE), [&](int e) { TR(-2, e); }, [&]() {
      mbar_spin(BAR(B_PFULL), 0);
#pragma unroll
      for (int k = 0; k < NP; k++) ldsm4t(wa[k], c.sb + SM_POOL + c.m * NP * 2048 + frag_off(c.w, c.lane) + k * 2048);
      bar_sync(NB_XCH, 256);
#pragma unroll
      for (int k = 0; k < NP; k++) sts128(c.sb + SM_POOL + c.m * 2048 + c.w * 512 + c.lane * 16 + k * 4096, make_uint4(wa[k][0], wa[k][1], wa[k][2], wa[k][3]));
    });
    mbar_arrive_warp(BAR(B_P1));
    TR(-2, 0);
    if (tid_now() == 0) TL2(1);
    __syncwarp();
    mbar_spin(BAR(B_WFULL + c.m), 0);
    TR(-2, 1);
    if ((tid_now() & 127) == 0) TL2(16);
    __syncwarp();
    {
      const uint32_t st = c.sb + c.m * ST_WG + frag_off(c.w, c.lane);
#pragma unroll
      for (int k = 0; k < 16; k++) ldsm4t(wb[k], st + k * 2048);
#pragma unroll
      for (int k = NP; k < 16; k++) ldsm4t(wa[k], st + (16 + k - NP) * 2048);
#pragma unroll
      for (int k = 0; k < NV; k++) ldsm4t(wv[k], st + (32 - NP + k) * 2048);
      mbar_arrive_warp(BAR(B_WREAD));
      if (c.m == 0) mbar_arrive_warp(BAR(B_WREAD0));
#pragma unroll
      for (int k = 0; k < (LP_IN == 2 ? 0 : NP); k++) lds_frag(wa[k], c.sb + SM_POOL + c.m * 2048 + c.w * 512 + c.lane * 16 + k * 4096);
      TR(-2, 2);
    }
    TR(-2, 3);
    if (tid_now() == 0) TL2(12);
    __syncwarp();
    asm volatile("barrier.cluster.wait;" ::: "memory");
    uint32_t t16 = c.m * 2048 + c.w * 512 + c.lane * 16;
    uint32_t pk = (c.m * NHV * 2048 + frag_off(c.w, c.lane)) | (tile_off(2 * (c.w & 1), c.lane) << 16) | ((c.lane & 12) ? 0u : 0x80000000u);
    const uint32_t dx1 = desc_lo(c.sb + SM_XT + c.m * 4096), dh = desc_lo(c.sb + SM_HV + c.m * NHV * 2048);
    mbar_spin(BAR(B_PFULL), 1);
    pad<PAD0>();
    for (int s = -2; ; s++) {
      t16 = vary(t16, s, c.sb); pk = vary(pk, s, c.sb);
      const uint32_t dx = dx1 - (s == -2 ? (SM_XT - SM_WO) / 16 : 0);
      auto ldp = [&](int k0, int k1, int d, int back = 0) {
#pragma unroll
        for (int k = k0; k < k1; k++) lds_frag(wa[k], (k < k0 + d - back ? t16 : dep(t16, wa[k < d ? 0 : k - d][0], c.sb)) + (c.sb + SM_POOL + k * 4096));
      };
      if (s >= 0) {
        uint32_t af[16][4], bf[4][4], wo;
        const uint32_t tab = ((t16 >> 3) & 0x1C0) + (c.sb + SM_TAB + (s & 1) * 512);
        const char* pa;
        mem_proj(wa, wb, wv, af, wo, pa, tab, t16, pk, c, s);
        const uint32_t t0 = clock_lo();
        t16 = dep(t16, t0, c.sb);
        auto ldwo = [&](int f) { ldsm4t(af[f], (f < WO_D ? wo : dep(wo, af[f < WO_D ? 0 : f - WO_D][0], c.sb)) + (c.sb + SM_WO + (f & 1) * 32768 + (f >> 1) * 2048)); };
        {
          const uint32_t tg = s >> 1, vm = t16 >> 1, chk = (~t16 >> 4) & 1;
          if (WO_S && s == 0) {
            mbar_spin(BAR(B_WOFULL), 0);
#pragma unroll
            for (int f = 0; f < WO_0; f++) ldwo(f);
          }
#pragma unroll
          for (int f = WO_0; f < WO_1; f++) ldwo(f);
          delay_fine(t0 + DLY_V);
          uint2 v0 = ld_poll2(pa), v1 = ld_poll2(pa + 1024), v2 = ld_poll2(pa + 2048), v3 = ld_poll2(pa + 3072);
          TR(s, 3);
#pragma unroll
          for (int f = WO_1; f < 16 - WO_L; f++) ldwo(f);
          TR(s, 4);
          uint32_t n = 0;
          while (true) {
            sts64(vm + (c.sb + SM_VM), sum4(v0.x, v1.x, v2.x, v3.x), sum4(v0.y, v1.y, v2.y, v3.y));
            if (arrive_if_clear(stale1(stale1(stale2(v0.x, v1.x, tg), v2.x, tg), v3.x, tg), chk, NB_VM, 384)) break;
            v0 = ld_poll2(pa); v1 = ld_poll2(pa + 1024); v2 = ld_poll2(pa + 2048); v3 = ld_poll2(pa + 3072);
            n++; CNT(3);
          }
          TR(s, 12); TRV(s, 15, n);
        }
        const uint32_t ob = dep(dep(t16 & 511, af[14 - WO_L][0], c.sb), af[15 - WO_L][0], c.sb);
        uint32_t l4 = ob >> 2;
        const uint32_t bit = (t16 & 48) ? 0u : 1u;
        if (LF_AT) mbar_spin2_if(BAR(B_XFULL), BAR(B_LFREE), s & 1, s + 2 < XEND); else mbar_spin_if(BAR(B_XFULL), s & 1, s + 2 < XEND);
        bar_sync(NB_OM, 384);
        TR(s, 5);
#pragma unroll
        for (int i = 0; i < 4; i++) ldsm4t(bf[i], ob + (c.sb + SM_OM + i * 512));
        uint2 sum = lds64(((t16 >> 1) & 24) + (c.sb + SM_SUM));
        if (OM_F) sched_fence(c.sb);
        float d[WO_C][4] = {};
        uint4 d0, d1;
#pragma unroll
        for (int f = 0; f < 16; f++) {
          mma_a(d[f % WO_C], af[f], bf[f >> 2][f & 2], bf[f >> 2][(f & 2) + 1]);
          if (f >= WO_C && f < WO_C + WO_L) {
            const int l = 16 - WO_L + f - WO_C;
            ldsm4t(af[l], (WO_LD ? dep(wo, __float_as_uint(d[(f + 1) % WO_C][0]), c.sb) : wo) + (c.sb + SM_WO + (l & 1) * 32768 + (l >> 1) * 2048));
          }
          if (f == WO_T) {
            const uint32_t tb2 = dep((t16 >> 3) & 0x1C0, __float_as_uint(d[f % WO_C][0]), c.sb) + (c.sb + SM_TAB + (s & 1) * 512);
            d0 = lds128(tb2 + 32); d1 = lds128(tb2 + 48);
          }
          if (f >= PL_WA && f < PL_WA + PL_W) lds_frag(wa[f - PL_WA], (PL_WD ? dep(t16, __float_as_uint(d[(f + PL_WD) % WO_C][0]), c.sb) : t16) + (c.sb + SM_POOL + (f - PL_WA) * 4096));
          if (PL_W && PL_WF && f == PL_WA + PL_W - 1) sched_fence(c.sb);
          if (f == 4) { sum.x = dep(sum.x, __float_as_uint(d[0][0]), c.sb); sum.y = dep(sum.y, __float_as_uint(d[0][0]), c.sb); }
        }
        if (PL_W && !PL_WF) {
          uint32_t all = 0;
#pragma unroll
          for (int k = 0; k < PL_W; k++) all ^= wa[k][0];
          l4 = dep(l4, all, c.sb);
        }
        char* dst[4] = {mk_ptr(d0.x | l4, d0.y), mk_ptr(d0.z | l4, d0.w), mk_ptr(d1.x | l4, d1.y), mk_ptr(d1.z | l4, d1.w)};
        const float i0 = rcp(__uint_as_float(sum.x)), i1 = rcp(__uint_as_float(sum.y));
#pragma unroll
        for (int i = 0; i < 4; i++) {
          const int t = i >> 1, e = 2 * (i & 1);
          const float y0 = WO_C == 2 ? d[t][e] : d[t][e] + d[(t + 2) % WO_C][e], y1 = WO_C == 2 ? d[t][e + 1] : d[t][e + 1] + d[(t + 2) % WO_C][e + 1];
          st_pub(dst[i], put_tag(pack_bf16(y0 * i0, y1 * i1), bit, s >> 1));
        }
        if (ANCH2) sts32(c.sb + SM_SUM + 64, clock_lo());
        mbar_arrive_warp(BAR(B_E2TRIG));
        TR(s, 6);
        sched_fence(c.sb);
        if (W_E2 == 2) mbar_spin(BAR(B_E2TRIG), s & 1);
        if (!LP_IN) { if (s == NSEG - 1) break; ldp(PL_W, PL_0, PL_D); }
      }
      if (__builtin_expect(s + 2 < XEND, 1)) {
        const uint32_t tg0 = DLY_P ? clock_lo() + DLY_P : 0;
        if (LP_IN) ldp(0, PL_0, PL_D);
        float xa[16];
        uint32_t q[4];
        if (W_E2 == 1 && s >= 0) mbar_spin(BAR(B_E2TRIG), s & 1);
        TR(s, 7);
        constexpr int S1 = ORDER ? 0 : 2, S2 = ORDER == 0 ? 0 : ORDER == 1 ? 2 : 1, S3 = ORDER == 2 ? 2 : 1;
        if (ORDER) issue_qk<0, 16>(xa, wb, vary(dx, s, c.sb)); else issue_v(xa, wv, vary(dx, s, c.sb), vary(dh, s, c.sb));
        if (DLY_P) delay_until(tg0); else if (IS_F) sched_fence(c.sb);
        ldp(PL_0, PL_1, PL_D1);
        const uint32_t land = (t16 ^ ((t16 >> 3) & 0x60)) + vary(c.sb + SM_LAND + c.b * 4096, s, c.sb);
        TR(s, 14);
        if (LF_AT == 1) mbar_spin_if(BAR(B_LFREE), s & 1, s < 0); else if (!LF_AT) mbar_spin(BAR(B_LFREE), s & 1);
        TR(s, 15);
        WG_WAIT(0);
        TR(s, 8);
        park_own<S1 == 2>(q, xa, land, S1, c.sb);
        if (W_PUB == 4 && s >= 0) mbar_spin(BAR(B_PUB), s & 1);
        if (ORDER == 1) issue_v(xa, wv, vary(dx, s, c.sb + 32), vary(dh, s, c.sb)); else issue_qk<0, 16>(xa, ORDER ? wa : wb, vary(dx, s, c.sb + 32));
        if (IS_F) sched_fence(c.sb);
        ldp(PL_1, PL_2, PL_D1);
        if (W_PUB == 1) mbar_spin_if(BAR(B_PUB), s & 1, s >= 0);
        uint32_t tp = clock_lo(), q1[4] = {q[0], q[1], q[2], q[3]};
        if (PL_2B) ldp(PL_2, NP - PL_L, PL_D1);
        if (W_PUB != 3) park_peer(q, land, S1, c);
        if (!PL_2B) ldp(PL_2, NP - PL_L, PL_D1);
        TR(s, 13);
        WG_WAIT(0);
        TR(s, 9);
        park_own<S2 == 2>(q, xa, land, S2, c.sb);
        if (ORDER == 2) issue_v(xa, wv, vary(dx, s, c.sb + 64), vary(dh, s, c.sb));
        else {
          issue_qk<0, PL_L ? NP - PL_L : 16>(xa, wa, vary(dx, s, c.sb + 64));
          ldp(NP - PL_L, NP, PL_E);
          if (PL_L) issue_qk<NP - PL_L, 16>(xa, wa, vary(dx, s, c.sb + 64));
        }
        if ((W_PUB == 2 || W_PUB == 3) && s >= 0) { mbar_spin(BAR(B_PUB), s & 1); tp = clock_lo(); }
        if (W_PUB == 3) park_peer(q1, land, S1, c);
        if (DLY_S && s >= 0) delay_until(tp + DLY_S);
        park_peer(q, land, S2, c);
        WG_WAIT(0);
        TR(s, 10);
        mbar_arrive_warp(BAR(B_XEMPTY));
        park_own<S3 == 2>(q, xa, land, S3, c.sb);
        park_peer(q, land, S3, c);
        TR(s, 11);
      } else { if (LP_IN && s == NSEG - 1) break; ldp(LP_IN ? 0 : PL_0, NP, LP_IN ? 2 : 1); }
    }
    asm volatile("setmaxnreg.dec.sync.aligned.u32 128;");
    const int tid = tid_now(), lane = tid & 31, tile = tile_of(c), m0 = (tile >> 3) * 128, n0 = (tile & 7) * 128;
    float acc[64];
#pragma unroll
    for (int i = 0; i < 64; i++) acc[i] = 0.f;
    const uint32_t rel = mapa(BAR(B_GEMPTY), lane & 1), la = desc_lo(c.sb + c.m * 8192), lb = ((c.sb + 16384) & 0x3FFFF) >> 4 | (8192 >> 4) << 16;
    const bool relon = (tid & 127) < 2;
    const float g0 = __ldcg(g_gate + m0 + (tid >> 5) * 16 + (lane >> 2)), g1 = __ldcg(g_gate + m0 + (tid >> 5) * 16 + (lane >> 2) + 8);
    uint32_t o = SM_XT, st = 0, ph = 0, prev = 0;
    if (tid == 0) TL(9);
    __syncwarp();
#pragma unroll 1
    for (int kb = 0; kb < 64; kb++, o = next_stage(o)) {
      mbar_lim(BAR(B_GFULL + st), ph);
      WG_FENCE();
#pragma unroll
      for (int k = 0; k < 4; k++) wgmma_ss_n128_tb(acc, desc128(la + (o >> 4) + k * 2), desc128(lb + (o >> 4) + k * 128));
      WG_COMMIT();
      WG_WAIT(1);
      arrive_remote_if(rel + 8 * prev, relon && kb > 0 && kb < 60);
      prev = st;
      if (++st == 5) { st = 0; ph ^= 1; }
    }
    WG_WAIT(0);
    if (tid == 0) TL(4);
    __syncwarp();
    const uint32_t row = (tid >> 5) * 2048 + (lane & 15) * 128 + (((lane >> 4) ^ (lane & 7)) << 4);
    mbar_lim(BAR(B_BT), 0);
    if (EPI) asm volatile("fence.proxy.async.global;" ::: "memory");
#pragma unroll
    for (int hf = 0; hf < 2; hf++) {
      uint32_t b[4][4];
      if (!EPI) for (int t = 0; t < 4; t++) ldsm4(b[t], (row ^ t * 32) + (c.sb + SM_BT + hf * 16384));
#pragma unroll
      for (int t = 0; t < 4; t++) {
        uint32_t y[4];
#pragma unroll
        for (int i = 0; i < 4; i++) {
          const float* a = acc + 32 * hf + 8 * t + 2 * i, g = i & 1 ? g1 : g0;
          y[i] = EPI ? pack_bf16(g * a[0], g * a[1]) : pack_bf16(fmaf(g, a[0], __uint_as_float(b[t][i] << 16)), fmaf(g, a[1], __uint_as_float(b[t][i] & 0xFFFF0000u)));
        }
        stsm4<false>((row ^ t * 32) + (c.sb + SM_BT + hf * 16384), y[0], y[1], y[2], y[3]);
      }
      FENCE_ASYNC_SMEM();
      __syncwarp();
      tma2d_out_e(&tout, n0 + hf * 64, m0 + (c.m * 4 + c.w) * 16, c.sb + SM_BT + hf * 16384 + (c.m * 4 + c.w) * 2048);
    }
    asm volatile("cp.async.bulk.commit_group; cp.async.bulk.wait_group" WAITRD " 0;" ::: "memory");
    if (tid == 0) TL(11);
    return;
  }
  const bool col = c.r >= 128;
  const int tile = col ? 0 : tile_of(c);
  const int q0 = col ? 256 - 16 * NCR + (c.r - 128) * 4 + c.m : tile < 120 ? tile : 256, dq = col ? 16 : 120, qe = col ? 256 : 256 - 16 * NCR;
  const uint32_t zs = c.sb + (col ? COL_Z + c.m * 32768 : SM_BT), zb = BAR(B_Z + c.m);
  auto load_z = [&](int q) { if (c.w == 0 && q < qe) { mbar_expect_e(zb, 32768); tma2d_e(zs, &tz, q * 64, 0, zb); } };
  asm volatile("fence.proxy.async.global;" ::: "memory");
  load_z(q0);
  uint32_t ph = 0;
#pragma unroll 1
  for (int q = q0; q < qe; q += dq, ph ^= 1) {
    mbar_lim(zb, ph);
    const int p = q * 4 + c.w;
    if (EXP_INV) fft_rows_inv(zs, (float2*)(smraw + (col ? 8192 + c.m * ROW_BUF * 16 : SM_MEM)) + c.w * (ROW_BUF / 2), (const float2*)(smraw + (col ? 0 : SM_TW)), p, tid_now() & 31, EPI ? out : g_b,
                              [&]() { bar_sync(5 + c.m, 128); load_z(q + dq); });
    else { bar_sync(5 + c.m, 128); load_z(q + dq); }
  }
  asm volatile("fence.acq_rel.gpu;" ::: "memory");
  __syncwarp();
  { const int q = q0 + (tid_now() & 31) * dq; if (q < qe) asm volatile("red.relaxed.gpu.global.add.u32 [%0], 1;" :: "l"(g_ctl + C_ROWS + (q >> 5) * 32) : "memory"); }
  if (tid_now() == 256) { if (col) TL(27); else TL(3); }
  __syncwarp();
  if (!col && c.w == 0) {
    await_count(g_ctl + C_ROWS + ((tile >> 3) & 7) * 32, 128);
    mbar_expect_e(BAR(B_BT), EPI ? 0 : 32768);
    if (!EPI) for (int i = 0; i < 2; i++) tma2d_e(c.sb + SM_BT + i * 16384, &tb, (tile & 7) * 128 + i * 64, (tile >> 3) * 128, BAR(B_BT));
    if (tid_now() == 256) TL(5);
  }
}

typedef CUresult (*EncodeFn)(CUtensorMap*, CUtensorMapDataType, cuuint32_t, void*, const cuuint64_t*, const cuuint64_t*,
                             const cuuint32_t*, const cuuint32_t*, CUtensorMapInterleave, CUtensorMapSwizzle,
                             CUtensorMapL2promotion, CUtensorMapFloatOOBfill);

void make_map(EncodeFn enc, CUtensorMap* tm, const void* p, int rank, const cuuint64_t* dims, const cuuint64_t* strides, const cuuint32_t* box, bool swz = true) {
  const cuuint32_t es[4] = {1, 1, 1, 1};
  enc(tm, CU_TENSOR_MAP_DATA_TYPE_BFLOAT16, rank, (void*)p, dims, strides, box, es, CU_TENSOR_MAP_INTERLEAVE_NONE,
      swz ? CU_TENSOR_MAP_SWIZZLE_128B : CU_TENSOR_MAP_SWIZZLE_NONE, CU_TENSOR_MAP_L2_PROMOTION_L2_128B, CU_TENSOR_MAP_FLOAT_OOB_FILL_NONE);
}
void make_map2(EncodeFn enc, CUtensorMap* tm, const void* p, uint64_t cols, uint64_t rows, uint32_t boxrows) {
  const cuuint64_t dims[2] = {cols, rows}, strides[1] = {cols * 2};
  const cuuint32_t box[2] = {64, boxrows};
  make_map(enc, tm, p, 2, dims, strides, box);
}

}

extern "C" void kernel_launch(void* const* d_in, const int* in_sizes, int n_in, void* d_out, int out_size) {
  (void)in_sizes; (void)n_in; (void)out_size;
  const __nv_bfloat16* x = (const __nv_bfloat16*)d_in[0];
  const __nv_bfloat16* mem0 = (const __nv_bfloat16*)d_in[1];
  const __nv_bfloat16* gw = (const __nv_bfloat16*)d_in[10];

  EncodeFn enc = nullptr;
  cudaDriverEntryPointQueryResult qr;
  cudaGetDriverEntryPoint("cuTensorMapEncodeTiled", (void**)&enc, cudaEnableDefault, &qr);
  void *p_ox, *p_b, *p_z, *p_mail;
  cudaGetSymbolAddress(&p_ox, g_ox); cudaGetSymbolAddress(&p_b, g_b); cudaGetSymbolAddress(&p_z, g_z); cudaGetSymbolAddress(&p_mail, g_mail);
  CUtensorMap tq, tk, tv, tv16, to, tx, twr, twi, ta, tw, tb, tout, tz;
  make_map2(enc, &tq, d_in[2], 4096, 1024, 64);
  make_map2(enc, &tk, d_in[3], 4096, 1024, 64);
  make_map2(enc, &tv, d_in[4], 4096, 1024, 64);
  make_map2(enc, &tv16, d_in[4], 4096, 1024, 16);
  make_map2(enc, &to, d_in[5], 1024, 4096, 128);
  make_map2(enc, &tw, d_in[5], 1024, 4096, 64);
  make_map2(enc, &ta, p_ox, 4096, 2048, 64);
  make_map2(enc, &tb, p_b, 1024, 2048, 128);
  make_map2(enc, &tout, d_out, 1024, 2048, 16);
  make_map2(enc, &tz, p_z, 16384, 257, 256);
  {
    const cuuint64_t dims[4] = {64, 8, 16, 256}, strides[3] = {2048, 128, 16384};
    const cuuint32_t box[4] = {64, 8, 8, 2};
    make_map(enc, &tx, x, 4, dims, strides, box);
  }
  {
    const cuuint64_t dims[2] = {8 * 513, 256}, strides[1] = {8 * 513 * 2};
    const cuuint32_t box[2] = {8, 256};
    make_map(enc, &twr, d_in[8], 2, dims, strides, box, false);
    make_map(enc, &twi, d_in[9], 2, dims, strides, box, false);
  }
  cudaFuncSetAttribute(chain_kernel, cudaFuncAttributeMaxDynamicSharedMemorySize, CHAIN_SMEM);

  cudaStream_t st = cudaStreamPerThread;
  char* mail = (char*)(((uintptr_t)p_mail + M_REG - 1) & ~(uintptr_t)(M_REG - 1));
  chain_kernel<<<132, 512, CHAIN_SMEM, st>>>(tq, tk, tv, tv16, to, tx, twr, twi, ta, tw, tb, tout, tz, mem0, mail, x, gw, (__nv_bfloat16*)d_out);
}
```

```cpp
#include <cuda_runtime.h>
#include <cuda_bf16.h>
#include <cuda.h>
#include <stdint.h>

#define DLY_E1 300
#define DLY_V 330
#define DLY_E2 320
#define DLY_E3 500
#define DLY_X 1
#define DLY_S 0
#define DLY_F 150
#define VM_AT 1
#define VM_F 0
#define OM_F 1
#define SXX_IN 0
#define C1_AT 1
#define NLAG 4
#define WO_D 2
#define WO_0 2
#define WO_1 10
#define PL_0 8
#define PL_1 10
#define PL_D 2
#define PL_L 0
#define DUAL 0
#define HV_D 3
#define DLY_FK 0
#define QX_SM 0
#define REG_F 216
#define REG_H 24
#define SC_F 1
#define E2_F 1
#define KVQ_AT 0
#define DLY_K 0
#define X_AT 2
#define W_PV 0
#define PL_2 10
#define BF_E 3
#define PL_E 2
#define ORDER 1
#define SSPOS 1
#define W_PUB 1
#define FIN_AT 5
#define AWARE 1
#define NPROBE 2
#define NP_ 12
#define USE_PDL 1
#define DLY_GRP 3000
#define P2_BULK 0
#define EXP_NV 4
#define EXP_NK 4
#define EXP_CHK 1
#define EXP_NXT 2
#define EXP_PEER 1
#define EXP_FIN 7
#define EXP_NWG 16
#define ANCH2 1
#define XF_AT 1
#define IS_F 1
#define PL_D1 2
#define W_E2 0
#define V_TMA 2
#define V_W 2
#define RED_L 3
#define RED_T 1
#define RED_P 1
#define DLY_E3B 0
#define HV_E 0
#define HV_R 4
#define HOLD 0
#define PACE 550
#define PACE0 0
#define EXP_ST 7
#define HOLD_AT NPROBE
#define WO_AT 38
#define WO_P 2
#define DLY_SEL 500
#define P1_AT 1
#define EXP_ZG 1
#define TMA_W tma2d_once
#define BULK_F bulk_once
#define TMA_O tma2d_once
#define PACE_Z 500
#define PACE_F 800
#define EXP_INV 1
#define VF_AT 0
#define UP_F 1
#define WO_L (12 - NP_)
#define WO_C 4
#define WO_T 3
#define WO_LD 0
#define EXP_LIN 0
#define PL_W 0
#define PL_WA 4
#define PL_WD 0
#define PL_WF 1
#define STAG 0
#define EXP_FL 0
#define DLY_FS 0
#define DLY_F2 0
#define LROT 0
#define PF_D 4
#define PF_A 1
#define PF_B 1
#define SIDE 1
#define ROLE 1
#define LOOSE 0x765498
#define E1OFF 1
#define EVOFF E1OFF
#define EPI 0
#define WAITRD ".read"
#define X01 1
#define E3I 1
#define START 1000
#define WUNR 1
#define WO_N 0
#define WO_H 0
#define PL_2B 1
#define DLY_P 430
#define LP_IN 1
#define LF_AT 1
#define FINE 0
#define LAG_F 0
#define E30 1
#define WO_S 1
#define POOL_AT 8
#define COL_DLY 0
#define WO_F 0
#define PAD0 0
#define PAD2 0
#define PAD3 0
#define WO_X 0
#define PRIOR 12
#define EARLY 1
#define SEL_AT 3000
#define CUNR 1
#define FUNR 0
#define ZINIT 1
#define ZDLY 0
#define NCR 7
#define GATE 0
#define LASTM 1
#define X_ONCE 1
#define ONCE 29
#define Z_PF 0
#define EXP_W 1
#define W_PROMO CU_TENSOR_MAP_L2_PROMOTION_L2_128B
#define Z_ST 1
#define W_FINE 0
#define X128 2
#define T128_ 1
#define W_AT 0
#define SKEW 8
#define AW_NS 0
#define QSH 1
#define PRE_AT B_SC

namespace {
constexpr int wunr = WUNR;

constexpr int S_ = 2048, D_ = 1024, NSEG = 64;
constexpr uint32_t SENT = 0xFFFFFFFFu;
constexpr int NSLOT = 4;

constexpr uint32_t M_REG = 1 << 21, M_E3 = 64 * 16384, M_KVQ = M_E3 + 4 * 8192, M_SEL = M_KVQ + 32 * 24576;
__device__ __align__(1024) unsigned char g_mail[5 * M_REG];
constexpr int C_P1 = 0, C_COLS = C_P1 + 32, C_EARLY = C_COLS + 32, C_LAST = C_EARLY + 32, C_ROWS = C_LAST + 128, C_END = C_ROWS + 8 * 32;
__device__ __align__(1024) uint32_t g_ctl[C_END];
#define CLK(i)
#define TL(i)
#define TL2(i)
#define FT(i, v)
#define GT(i)
#define CNT(i)
__device__ __align__(1024) __nv_bfloat16 g_ox[S_ * 4096];
__device__ __align__(1024) float2 g_z[257 * 4096];
__device__ __align__(1024) __nv_bfloat16 g_b[S_ * D_];
__device__ float g_gate[S_];
__device__ __align__(1024) float2 g_tw[1024];

#define TRV(s, ev, val)
#define TR(s, ev)
#define TRSYNC(ev)
__device__ __forceinline__ uint32_t smem_u32(const void* p) { return (uint32_t)__cvta_generic_to_shared(p); }
__device__ __forceinline__ void watchdog(uint32_t& n, uint32_t limit) {
  asm volatile("{ .reg .pred p; add.u32 %0, %0, 1; setp.gt.u32 p, %0, %1; @p trap; }" : "+r"(n) : "r"(limit));
}
__device__ __forceinline__ void mbar_init(uint32_t bar, uint32_t cnt) {
  asm volatile("mbarrier.init.shared::cta.b64 [%0], %1;" :: "r"(bar), "r"(cnt) : "memory");
}
__device__ __forceinline__ void mbar_arrive_warp(uint32_t bar) {
  __syncwarp();
  asm volatile("{ .reg .pred p; elect.sync _|p, 0xffffffff; @p mbarrier.arrive.shared::cta.b64 _, [%0]; }" :: "r"(bar) : "memory");
}
__device__ __forceinline__ uint32_t clock_lo() {
  uint32_t r; asm volatile("{ .reg .u64 c; .reg .u32 h; mov.u64 c, %%clock64; mov.b64 {%0, h}, c; }" : "=r"(r) :: "memory"); return r;
}
__device__ __forceinline__ void delay_until(uint32_t t) {
  asm volatile("{ .reg .pred p; .reg .u64 c; .reg .u32 l, h;\n"
               "DLY: mov.u64 c, %%clock64; mov.b64 {l, h}, c; sub.s32 l, l, %0; setp.lt.s32 p, l, 0; @p bra.uni DLY; }" :: "r"(t) : "memory");
}
__device__ __forceinline__ void delay_fine(uint32_t t) {
  delay_until(t);
}
__device__ __forceinline__ void delay_cycles(uint32_t n) { delay_until(clock_lo() + n); }
__device__ __forceinline__ void sched_fence(uint32_t z) {
  asm volatile("{ .reg .pred p; setp.eq.u32 p, %0, 0x7fff0000; @p pmevent 1; }" :: "r"(z) : "memory");
}
__device__ __forceinline__ void pdl_wait() { asm volatile("griddepcontrol.wait;" ::: "memory"); }
__device__ __forceinline__ void pdl_launch() { asm volatile("griddepcontrol.launch_dependents;" ::: "memory"); }
__device__ __forceinline__ float ex2(float x) { float r; asm("ex2.approx.ftz.f32 %0, %1;" : "=f"(r) : "f"(x)); return r; }
__device__ __forceinline__ float rcp(float x) { float r; asm("rcp.approx.ftz.f32 %0, %1;" : "=f"(r) : "f"(x)); return r; }
__device__ __forceinline__ void mbar_expect(uint32_t bar, uint32_t bytes) {
  asm volatile("mbarrier.arrive.expect_tx.shared::cta.b64 _, [%0], %1;" :: "r"(bar), "r"(bytes) : "memory");
}
__device__ __forceinline__ bool mbar_try(uint32_t bar, uint32_t ph) {
  uint32_t ok;
  asm volatile("{ .reg .pred p; mbarrier.try_wait.parity.shared::cta.b64 p, [%1], %2; selp.u32 %0, 1, 0, p; }"
               : "=r"(ok) : "r"(bar), "r"(ph) : "memory");
  return ok;
}
__device__ __forceinline__ void mbar_wait(uint32_t bar, uint32_t ph) {
  uint32_t n = 0;
  while (!mbar_try(bar, ph)) { watchdog(n, (1u << 20)); }
}
__device__ __forceinline__ void mbar_spin(uint32_t bar, uint32_t ph) { while (!mbar_try(bar, ph)) {} }
__device__ __forceinline__ void mbar_spin_if(uint32_t bar, uint32_t ph, bool on) {
  asm volatile("{ .reg .pred p, q; setp.ne.u32 p, %2, 0;\n"
               "SPN: setp.eq.u32 q, 0, 0; @p mbarrier.try_wait.parity.shared::cta.b64 q, [%0], %1; @!q bra.uni SPN; }" :: "r"(bar), "r"(ph), "r"((uint32_t)on) : "memory");
}
__device__ __forceinline__ void mbar_spin2_if(uint32_t bar, uint32_t bar2, uint32_t ph, bool on) {
  asm volatile("{ .reg .pred p, q, r; setp.ne.u32 p, %3, 0;\n"
               "SPN: setp.eq.u32 q, 0, 0; setp.eq.u32 r, 0, 0; @p mbarrier.try_wait.parity.shared::cta.b64 q, [%0], %2;\n"
               "@p mbarrier.try_wait.parity.shared::cta.b64 r, [%1], %2; and.pred q, q, r; @!q bra.uni SPN; }" :: "r"(bar), "r"(bar2), "r"(ph), "r"((uint32_t)on) : "memory");
}
__device__ __forceinline__ void mbar_spin_cluster(uint32_t bar, uint32_t ph) {
  uint32_t ok;
  do {
    asm volatile("{ .reg .pred p; mbarrier.try_wait.parity.acquire.cluster.shared::cta.b64 p, [%1], %2; selp.u32 %0, 1, 0, p; }"
                 : "=r"(ok) : "r"(bar), "r"(ph) : "memory");
  } while (!ok);
}
#define ONCE_H "mov.b64 h, 0x12F0000000000000; "
__device__ __forceinline__ void tma2d(uint32_t dst, const CUtensorMap* tm, int c0, int c1, uint32_t bar) {
  if (ONCE & 32) asm volatile("{ .reg .b64 h; " ONCE_H "cp.async.bulk.tensor.2d.shared::cluster.global.mbarrier::complete_tx::bytes.L2::cache_hint [%0], [%1, {%3, %4}], [%2], h; }"
               :: "r"(dst), "l"(tm), "r"(bar), "r"(c0), "r"(c1) : "memory");
  else asm volatile("cp.async.bulk.tensor.2d.shared::cluster.global.mbarrier::complete_tx::bytes [%0], [%1, {%3, %4}], [%2];"
               :: "r"(dst), "l"(tm), "r"(bar), "r"(c0), "r"(c1) : "memory");
}
__device__ __forceinline__ void mbar_expect_e(uint32_t bar, uint32_t bytes) {
  asm volatile("{ .reg .pred p; elect.sync _|p, 0xffffffff; @p mbarrier.arrive.expect_tx.shared::cta.b64 _, [%0], %1; }" :: "r"(bar), "r"(bytes) : "memory");
}
__device__ __forceinline__ void tma2d_e(uint32_t dst, const CUtensorMap* tm, int c0, int c1, uint32_t bar) {
  asm volatile("{ .reg .pred p; elect.sync _|p, 0xffffffff;\n"
               "@p cp.async.bulk.tensor.2d.shared::cluster.global.mbarrier::complete_tx::bytes [%0], [%1, {%3, %4}], [%2]; }"
               :: "r"(dst), "l"(tm), "r"(bar), "r"(c0), "r"(c1) : "memory");
}
__device__ __forceinline__ void tma2d_st_e(const CUtensorMap* tm, int c0, int c1, uint32_t src) {
  asm volatile("{ .reg .pred p; elect.sync _|p, 0xffffffff;\n"
               "@p cp.async.bulk.tensor.2d.global.shared::cta.bulk_group [%0, {%2, %3}], [%1]; }" :: "l"(tm), "r"(src), "r"(c0), "r"(c1) : "memory");
}
__device__ __forceinline__ void tma2d_out_e(const CUtensorMap* tm, int c0, int c1, uint32_t src) {
  if (EPI) asm volatile("{ .reg .pred p; elect.sync _|p, 0xffffffff;\n"
               "@p cp.reduce.async.bulk.tensor.2d.global.shared::cta.add.bulk_group [%0, {%2, %3}], [%1]; }" :: "l"(tm), "r"(src), "r"(c0), "r"(c1) : "memory");
  else if (ONCE & 16) asm volatile("{ .reg .pred p; .reg .b64 h; " ONCE_H "elect.sync _|p, 0xffffffff;\n"
               "@p cp.async.bulk.tensor.2d.global.shared::cta.bulk_group.L2::cache_hint [%0, {%2, %3}], [%1], h; }" :: "l"(tm), "r"(src), "r"(c0), "r"(c1) : "memory");
  else asm volatile("{ .reg .pred p; elect.sync _|p, 0xffffffff;\n"
               "@p cp.async.bulk.tensor.2d.global.shared::cta.bulk_group [%0, {%2, %3}], [%1]; }" :: "l"(tm), "r"(src), "r"(c0), "r"(c1) : "memory");
}
__device__ __forceinline__ void tma2d_once(uint32_t dst, const CUtensorMap* tm, int c0, int c1, uint32_t bar) {
  asm volatile("{ .reg .pred p; .reg .b64 h; " ONCE_H "elect.sync _|p, 0xffffffff;\n"
               "@p cp.async.bulk.tensor.2d.shared::cluster.global.mbarrier::complete_tx::bytes.L2::cache_hint [%0], [%1, {%3, %4}], [%2], h; }"
               :: "r"(dst), "l"(tm), "r"(bar), "r"(c0), "r"(c1) : "memory");
}
__device__ __forceinline__ void bulk_once(uint32_t dst, const void* src, uint32_t bytes, uint32_t bar) {
  asm volatile("{ .reg .pred p; .reg .b64 h; " ONCE_H "elect.sync _|p, 0xffffffff;\n"
               "@p cp.async.bulk.shared::cluster.global.mbarrier::complete_tx::bytes.L2::cache_hint [%0], [%1], %2, [%3], h; }"
               :: "r"(dst), "l"(src), "r"(bytes), "r"(bar) : "memory");
}
__device__ __forceinline__ void tma4d_e(uint32_t dst, const CUtensorMap* tm, int c2, int c3, uint32_t bar) {
  asm volatile("{ .reg .pred p; .reg .b64 h; " ONCE_H "elect.sync _|p, 0xffffffff;\n"
               "@p cp.async.bulk.tensor.4d.shared::cluster.global.mbarrier::complete_tx::bytes.L2::cache_hint [%0], [%1, {0, 0, %3, %4}], [%2], h; }"
               :: "r"(dst), "l"(tm), "r"(bar), "r"(c2), "r"(c3) : "memory");
}
__device__ __forceinline__ void bulk_load_e(uint32_t dst, const void* src, uint32_t bytes, uint32_t bar) {
  asm volatile("{ .reg .pred p; elect.sync _|p, 0xffffffff;\n"
               "@p cp.async.bulk.shared::cluster.global.mbarrier::complete_tx::bytes [%0], [%1], %2, [%3]; }"
               :: "r"(dst), "l"(src), "r"(bytes), "r"(bar) : "memory");
}
template<bool O> __device__ __forceinline__ void tma2d_o(uint32_t dst, const CUtensorMap* tm, int c0, int c1, uint32_t bar) {
  if (O) tma2d_once(dst, tm, c0, c1, bar); else tma2d_e(dst, tm, c0, c1, bar);
}
__device__ __forceinline__ float2 ld_once(const float2* p) {
  float2 v;
  if (ONCE & 64) asm volatile("{ .reg .b64 h; " ONCE_H "ld.global.cg.L2::cache_hint.v2.f32 {%0, %1}, [%2], h; }" : "=f"(v.x), "=f"(v.y) : "l"(p));
  else v = __ldcg(p);
  return v;
}
template<bool O = false> __device__ __forceinline__ void prefetch2d_e(const CUtensorMap* tm, int c0, int c1) {
  if (O) asm volatile("{ .reg .pred p; .reg .b64 h; " ONCE_H "elect.sync _|p, 0xffffffff;\n"
               "@p cp.async.bulk.prefetch.tensor.2d.L2.global.L2::cache_hint [%0, {%1, %2}], h; }" :: "l"(tm), "r"(c0), "r"(c1) : "memory");
  else asm volatile("{ .reg .pred p; elect.sync _|p, 0xffffffff;\n"
               "@p cp.async.bulk.prefetch.tensor.2d.L2.global [%0, {%1, %2}]; }" :: "l"(tm), "r"(c0), "r"(c1) : "memory");
}
__device__ __forceinline__ void st_pub4(void* p, uint4 v) {
  asm volatile("st.relaxed.gpu.global.v4.u32 [%0], {%1,%2,%3,%4};" :: "l"(p), "r"(v.x), "r"(v.y), "r"(v.z), "r"(v.w) : "memory");
}
__device__ __forceinline__ void st_pub_if(void* p, uint32_t v, bool on) {
  asm volatile("{ .reg .pred p; setp.ne.u32 p, %2, 0; @p st.relaxed.gpu.global.u32 [%0], %1; }" :: "l"(p), "r"(v), "r"((uint32_t)on) : "memory");
}
__device__ __forceinline__ uint32_t mapa(uint32_t a, uint32_t r) {
  uint32_t d; asm volatile("mapa.shared::cluster.u32 %0, %1, %2;" : "=r"(d) : "r"(a), "r"(r)); return d;
}
__device__ __forceinline__ void st_async4(uint32_t a, uint32_t x, uint32_t y, uint32_t z, uint32_t w, uint32_t bar) {
  asm volatile("st.async.shared::cluster.mbarrier::complete_tx::bytes.v4.u32 [%0], {%1,%2,%3,%4}, [%5];"
               :: "r"(a), "r"(x), "r"(y), "r"(z), "r"(w), "r"(bar) : "memory");
}
__device__ __forceinline__ uint4 ld_poll(const void* p) {
  uint4 v;
  asm volatile("ld.volatile.global.v4.u32 {%0,%1,%2,%3}, [%4];" : "=r"(v.x), "=r"(v.y), "=r"(v.z), "=r"(v.w) : "l"(p) : "memory");
  return v;
}
__device__ __forceinline__ uint2 ld_poll2(const void* p) {
  uint2 v; asm volatile("ld.volatile.global.v2.u32 {%0,%1}, [%2];" : "=r"(v.x), "=r"(v.y) : "l"(p) : "memory"); return v;
}
__device__ __forceinline__ void st_pub2(void* p, uint32_t a, uint32_t b) {
  asm volatile("st.relaxed.gpu.global.v2.u32 [%0], {%1,%2};" :: "l"(p), "r"(a), "r"(b) : "memory");
}
__device__ __forceinline__ uint32_t ld_poll1(const void* p) {
  uint32_t v; asm volatile("ld.volatile.global.u32 %0, [%1];" : "=r"(v) : "l"(p) : "memory"); return v;
}
__device__ __forceinline__ uint32_t ld_acquire(const uint32_t* p) {
  uint32_t v; asm volatile("ld.acquire.gpu.global.u32 %0, [%1];" : "=r"(v) : "l"(p) : "memory"); return v;
}
__device__ __forceinline__ void st_pub(void* p, uint32_t v) {
  asm volatile("st.relaxed.gpu.global.u32 [%0], %1;" :: "l"(p), "r"(v) : "memory");
}
__device__ __forceinline__ uint32_t lds32(uint32_t a) {
  uint32_t v; asm volatile("ld.shared.u32 %0, [%1];" : "=r"(v) : "r"(a) : "memory"); return v;
}
__device__ __forceinline__ int race_init(void* p0, void* p1, uint32_t val) {
  int t;
  asm volatile("{ .reg .pred r; .reg .u32 a, b, u, v;\n"
               "atom.relaxed.gpu.global.exch.b32 u, [%1], %3; atom.relaxed.gpu.global.exch.b32 v, [%2], %3;\n"
               "setp.eq.u32 r, u, 0x12345; @r pmevent 1; mov.u32 a, %%clock;\n"
               "setp.eq.u32 r, v, 0x12345; @r pmevent 1; mov.u32 b, %%clock; sub.u32 %0, b, a; }" : "=r"(t) : "l"(p0), "l"(p1), "r"(val) : "memory");
  return t;
}
__device__ __forceinline__ void race_init2(void* p0, void* p1, uint32_t val) {
  asm volatile("{ .reg .pred r; .reg .u32 a, b, u, v;\n"
               "atom.relaxed.gpu.global.exch.b32 u, [%0], %2; atom.relaxed.gpu.global.exch.b32 v, [%1], %2;\n"
               "atom.relaxed.gpu.global.exch.b32 a, [%0 + 4096], %2; atom.relaxed.gpu.global.exch.b32 b, [%1 + 4096], %2;\n"
               "lop3.b32 u, u, v, a, 0x96; setp.eq.u32 r, u, 0x12345; setp.eq.and.u32 r, b, u, r; @r pmevent 1; }" :: "l"(p0), "l"(p1), "r"(val) : "memory");
}
__device__ __forceinline__ uint4 lds128(uint32_t a) {
  uint4 v; asm volatile("ld.shared.v4.u32 {%0,%1,%2,%3}, [%4];" : "=r"(v.x), "=r"(v.y), "=r"(v.z), "=r"(v.w) : "r"(a) : "memory"); return v;
}
__device__ __forceinline__ uint2 lds64(uint32_t a) {
  uint2 v; asm volatile("ld.shared.v2.u32 {%0,%1}, [%2];" : "=r"(v.x), "=r"(v.y) : "r"(a) : "memory"); return v;
}
__device__ __forceinline__ void sts128(uint32_t a, uint4 v) {
  asm volatile("st.shared.v4.u32 [%0], {%1,%2,%3,%4};" :: "r"(a), "r"(v.x), "r"(v.y), "r"(v.z), "r"(v.w) : "memory");
}
__device__ __forceinline__ void sts64(uint32_t a, uint32_t x, uint32_t y) { asm volatile("st.shared.v2.u32 [%0], {%1,%2};" :: "r"(a), "r"(x), "r"(y) : "memory"); }
__device__ __forceinline__ void sts32(uint32_t a, uint32_t x) { asm volatile("st.shared.u32 [%0], %1;" :: "r"(a), "r"(x) : "memory"); }
__device__ __forceinline__ void ldsm4t(uint32_t (&r)[4], uint32_t a) {
  asm volatile("ldmatrix.sync.aligned.m8n8.x4.trans.shared.b16 {%0,%1,%2,%3}, [%4];"
               : "=r"(r[0]), "=r"(r[1]), "=r"(r[2]), "=r"(r[3]) : "r"(a) : "memory");
}
__device__ __forceinline__ void ldsm4(uint32_t (&r)[4], uint32_t a) {
  asm volatile("ldmatrix.sync.aligned.m8n8.x4.shared.b16 {%0,%1,%2,%3}, [%4];"
               : "=r"(r[0]), "=r"(r[1]), "=r"(r[2]), "=r"(r[3]) : "r"(a) : "memory");
}
template<bool TRANS> __device__ __forceinline__ void stsm4(uint32_t a, uint32_t r0, uint32_t r1, uint32_t r2, uint32_t r3) {
  if (TRANS) asm volatile("stmatrix.sync.aligned.m8n8.x4.trans.shared.b16 [%0], {%1,%2,%3,%4};" :: "r"(a), "r"(r0), "r"(r1), "r"(r2), "r"(r3) : "memory");
  else       asm volatile("stmatrix.sync.aligned.m8n8.x4.shared.b16 [%0], {%1,%2,%3,%4};" :: "r"(a), "r"(r0), "r"(r1), "r"(r2), "r"(r3) : "memory");
}
__device__ __forceinline__ void mma16816(float (&d)[4], uint32_t a0, uint32_t a1, uint32_t a2, uint32_t a3, uint32_t b0, uint32_t b1) {
  asm volatile("mma.sync.aligned.m16n8k16.row.col.f32.bf16.bf16.f32 {%0,%1,%2,%3}, {%4,%5,%6,%7}, {%8,%9}, {%0,%1,%2,%3};"
               : "+f"(d[0]), "+f"(d[1]), "+f"(d[2]), "+f"(d[3]) : "r"(a0), "r"(a1), "r"(a2), "r"(a3), "r"(b0), "r"(b1));
}
__device__ __forceinline__ void mma1688(float (&d)[4], uint32_t a0, uint32_t a1, uint32_t b0) {
  asm volatile("mma.sync.aligned.m16n8k8.row.col.f32.bf16.bf16.f32 {%0,%1,%2,%3}, {%4,%5}, {%6}, {%0,%1,%2,%3};"
               : "+f"(d[0]), "+f"(d[1]), "+f"(d[2]), "+f"(d[3]) : "r"(a0), "r"(a1), "r"(b0));
}
__device__ __forceinline__ uint32_t pack_bf16(float lo, float hi) {
  uint32_t r; asm("cvt.rn.bf16x2.f32 %0, %1, %2;" : "=r"(r) : "f"(hi), "f"(lo)); return r;
}
__device__ __forceinline__ uint32_t add_bf16x2(uint32_t a, uint32_t b) {
  uint32_t r; asm("add.rn.bf16x2 %0, %1, %2;" : "=r"(r) : "r"(a), "r"(b)); return r;
}
__device__ __forceinline__ uint32_t umax4(uint4 v) { return max(max(v.x, v.y), max(v.z, v.w)); }
__device__ __forceinline__ uint32_t opaque(uint32_t x) { uint32_t r; asm volatile("mov.u32 %0, %1;" : "=r"(r) : "r"(x)); return r; }
template<class T> __device__ __forceinline__ void pin(T*& p) { asm volatile("" : "+l"(p)); }
__device__ __forceinline__ void pin(uint32_t& v) { asm volatile("" : "+r"(v)); }
__device__ __forceinline__ uint32_t desc_lo(uint32_t addr) { return ((addr & 0x3FFFF) >> 4) | 0x10000; }
__device__ __forceinline__ uint64_t desc128(uint32_t lo) {
  uint64_t d; asm("mov.b64 %0, {%1, %2};" : "=l"(d) : "r"(lo), "r"(0x40000040)); return d;
}
#define WG_FENCE()  asm volatile("wgmma.fence.sync.aligned;" ::: "memory")
#define WG_COMMIT() asm volatile("wgmma.commit_group.sync.aligned;" ::: "memory")
#define WG_WAIT(n)  asm volatile("wgmma.wait_group.sync.aligned " #n ";" ::: "memory")
#define FENCE_ASYNC_SMEM() asm volatile("fence.proxy.async.shared::cta;" ::: "memory")
__device__ __forceinline__ void bar_sync(int id, int n) { asm volatile("bar.sync %0, %1;" :: "r"(id), "r"(n) : "memory"); }

#define D16(c) c(d[0]), c(d[1]), c(d[2]), c(d[3]), c(d[4]), c(d[5]), c(d[6]), c(d[7]), \
               c(d[8]), c(d[9]), c(d[10]), c(d[11]), c(d[12]), c(d[13]), c(d[14]), c(d[15])
template<bool FIRST> __device__ __forceinline__ void wgmma_rs_n32(float (&d)[16], const uint32_t (&a)[4], uint64_t b) {
  if (FIRST)
    asm volatile("wgmma.mma_async.sync.aligned.m64n32k16.f32.bf16.bf16 {%0,%1,%2,%3,%4,%5,%6,%7,%8,%9,%10,%11,%12,%13,%14,%15}, {%16,%17,%18,%19}, %20, 0, 1, 1, 0;"
      : D16("=f") : "r"(a[0]), "r"(a[1]), "r"(a[2]), "r"(a[3]), "l"(b));
  else
    asm volatile("wgmma.mma_async.sync.aligned.m64n32k16.f32.bf16.bf16 {%0,%1,%2,%3,%4,%5,%6,%7,%8,%9,%10,%11,%12,%13,%14,%15}, {%16,%17,%18,%19}, %20, 1, 1, 1, 0;"
      : D16("+f") : "r"(a[0]), "r"(a[1]), "r"(a[2]), "r"(a[3]), "l"(b));
}
template<bool FIRST> __device__ __forceinline__ void wgmma_ss_n32_ta(float (&d)[16], uint64_t a, uint64_t b) {
  if (FIRST)
    asm volatile("wgmma.mma_async.sync.aligned.m64n32k16.f32.bf16.bf16 {%0,%1,%2,%3,%4,%5,%6,%7,%8,%9,%10,%11,%12,%13,%14,%15}, %16, %17, 0, 1, 1, 1, 0;"
      : D16("=f") : "l"(a), "l"(b));
  else
    asm volatile("wgmma.mma_async.sync.aligned.m64n32k16.f32.bf16.bf16 {%0,%1,%2,%3,%4,%5,%6,%7,%8,%9,%10,%11,%12,%13,%14,%15}, %16, %17, 1, 1, 1, 1, 0;"
      : D16("+f") : "l"(a), "l"(b));
}
__device__ __forceinline__ void wgmma_ss_n128_tb(float (&d)[64], uint64_t a, uint64_t b) {
  asm volatile("wgmma.mma_async.sync.aligned.m64n128k16.f32.bf16.bf16 "
    "{%0,%1,%2,%3,%4,%5,%6,%7,%8,%9,%10,%11,%12,%13,%14,%15,%16,%17,%18,%19,%20,%21,%22,%23,%24,%25,%26,%27,%28,%29,%30,%31,"
    "%32,%33,%34,%35,%36,%37,%38,%39,%40,%41,%42,%43,%44,%45,%46,%47,%48,%49,%50,%51,%52,%53,%54,%55,%56,%57,%58,%59,%60,%61,%62,%63}, "
    "%64, %65, 1, 1, 1, 0, 1;"
    : "+f"(d[0]), "+f"(d[1]), "+f"(d[2]), "+f"(d[3]), "+f"(d[4]), "+f"(d[5]), "+f"(d[6]), "+f"(d[7]),
      "+f"(d[8]), "+f"(d[9]), "+f"(d[10]), "+f"(d[11]), "+f"(d[12]), "+f"(d[13]), "+f"(d[14]), "+f"(d[15]),
      "+f"(d[16]), "+f"(d[17]), "+f"(d[18]), "+f"(d[19]), "+f"(d[20]), "+f"(d[21]), "+f"(d[22]), "+f"(d[23]),
      "+f"(d[24]), "+f"(d[25]), "+f"(d[26]), "+f"(d[27]), "+f"(d[28]), "+f"(d[29]), "+f"(d[30]), "+f"(d[31]),
      "+f"(d[32]), "+f"(d[33]), "+f"(d[34]), "+f"(d[35]), "+f"(d[36]), "+f"(d[37]), "+f"(d[38]), "+f"(d[39]),
      "+f"(d[40]), "+f"(d[41]), "+f"(d[42]), "+f"(d[43]), "+f"(d[44]), "+f"(d[45]), "+f"(d[46]), "+f"(d[47]),
      "+f"(d[48]), "+f"(d[49]), "+f"(d[50]), "+f"(d[51]), "+f"(d[52]), "+f"(d[53]), "+f"(d[54]), "+f"(d[55]),
      "+f"(d[56]), "+f"(d[57]), "+f"(d[58]), "+f"(d[59]), "+f"(d[60]), "+f"(d[61]), "+f"(d[62]), "+f"(d[63])
    : "l"(a), "l"(b));
}

__device__ __forceinline__ void tma3d_mc_e(uint32_t dst, const CUtensorMap* tm, int c1, int c2, uint32_t bar) {
  asm volatile("{ .reg .pred p; .reg .b64 h; " ONCE_H "elect.sync _|p, 0xffffffff;\n"
               "@p cp.async.bulk.tensor.3d.shared::cluster.global.mbarrier::complete_tx::bytes.multicast::cluster.L2::cache_hint [%0], [%1, {0, %3, %4}], [%2], %5, h; }"
               :: "r"(dst), "l"(tm), "r"(bar), "r"(c1), "r"(c2), "h"((uint16_t)3) : "memory");
}
__device__ __forceinline__ void prefetch3d_e(const CUtensorMap* tm, int c1, int c2) {
  asm volatile("{ .reg .pred p; elect.sync _|p, 0xffffffff;\n"
               "@p cp.async.bulk.prefetch.tensor.3d.L2.global [%0, {0, %1, %2}]; }" :: "l"(tm), "r"(c1), "r"(c2) : "memory");
}

__device__ __forceinline__ void count_e(uint32_t* p) {
  asm volatile("fence.acq_rel.gpu;" ::: "memory");
  __syncwarp();
  asm volatile("{ .reg .pred p; elect.sync _|p, 0xffffffff; @p red.relaxed.gpu.global.add.u32 [%0], 1; }" :: "l"(p) : "memory");
}
template<int NS = 0> __device__ __forceinline__ void await_count(const uint32_t* p, uint32_t n) {
  for (uint32_t i = 0; ld_acquire(p) < n && i < (1u << 22); i++) { if (NS) __nanosleep(NS); }
  asm volatile("fence.proxy.async.global;" ::: "memory");
}
__device__ __forceinline__ void await_flags(const uint32_t* p) {
  for (uint32_t i = 0; i < (1u << 22); i++) {
    uint4 v;
    asm volatile("ld.acquire.gpu.global.v4.u32 {%0,%1,%2,%3}, [%4];" : "=r"(v.x), "=r"(v.y), "=r"(v.z), "=r"(v.w) : "l"(p) : "memory");
    if (__all_sync(~0u, (v.x & v.y & v.z & v.w) == 0x01010101u)) break;
  }
  asm volatile("fence.proxy.async.global;" ::: "memory");
}
__device__ __forceinline__ void mbar_lim(uint32_t bar, uint32_t ph) { for (uint32_t i = 0; !mbar_try(bar, ph) && i < (1u << 20); i++) {} }

struct cf { float x, y; };
__host__ __device__ constexpr float cos64(int k) {
  return k == 0 ? 1.0f : k == 1 ? 0.99518472667219689f : k == 2 ? 0.98078528040323045f : k == 3 ? 0.95694033573220887f :
         k == 4 ? 0.92387953251128676f : k == 5 ? 0.88192126434835503f : k == 6 ? 0.83146961230254524f : k == 7 ? 0.77301045336273696f :
         k == 8 ? 0.70710678118654752f : k == 9 ? 0.63439328416364550f : k == 10 ? 0.55557023301960222f : k == 11 ? 0.47139673682599765f :
         k == 12 ? 0.38268343236508977f : k == 13 ? 0.29028467725446236f : k == 14 ? 0.19509032201612827f : k == 15 ? 0.09801714032956060f : 0.0f;
}
__host__ __device__ constexpr float c64(int k) { return k <= 16 ? cos64(k) : -cos64(32 - k); }
__host__ __device__ constexpr float s64(int k) { return k <= 16 ? cos64(16 - k) : cos64(k - 16); }

template<int N, int ST, bool INV> struct Fft {
  template<int K> static __device__ __forceinline__ void bf(const cf* e, const cf* o, cf* out) {
    if constexpr (K < N / 2) {
      constexpr int idx = K * (64 / N);
      const cf a = e[K], b = o[K];
      if constexpr (idx == 0) {
        out[K] = {a.x + b.x, a.y + b.y}; out[K + N / 2] = {a.x - b.x, a.y - b.y};
      } else if constexpr (idx == 16) {
        if constexpr (INV) { out[K] = {a.x - b.y, a.y + b.x}; out[K + N / 2] = {a.x + b.y, a.y - b.x}; }
        else               { out[K] = {a.x + b.y, a.y - b.x}; out[K + N / 2] = {a.x - b.y, a.y + b.x}; }
      } else {
        constexpr float c = c64(idx), s = INV ? s64(idx) : -s64(idx);
        cf p; p.x = fmaf(-s, b.y, fmaf(c, b.x, a.x)); p.y = fmaf(s, b.x, fmaf(c, b.y, a.y));
        out[K] = p; out[K + N / 2] = {fmaf(2.0f, a.x, -p.x), fmaf(2.0f, a.y, -p.y)};
      }
      bf<K + 1>(e, o, out);
    }
  }
  static __device__ __forceinline__ void run(const cf* in, cf* out) {
    cf e[N / 2], o[N / 2];
    Fft<N / 2, 2 * ST, INV>::run(in, e);
    Fft<N / 2, 2 * ST, INV>::run(in + ST, o);
    bf<0>(e, o, out);
  }
};
template<int ST, bool INV> struct Fft<1, ST, INV> {
  static __device__ __forceinline__ void run(const cf* in, cf* out) { out[0] = in[0]; }
};
template<bool INV> __device__ __forceinline__ void fft32(cf (&v)[32]) {
  cf o[32]; Fft<32, 1, INV>::run(v, o);
#pragma unroll
  for (int i = 0; i < 32; i++) v[i] = o[i];
}
__device__ __forceinline__ cf cmul(cf a, float c, float s) { return {fmaf(-a.y, s, a.x * c), fmaf(a.x, s, a.y * c)}; }
__device__ __forceinline__ float bf2f(__nv_bfloat16 v) { return __bfloat162float(v); }

__device__ __forceinline__ int tw_at(int i) { return (i & ~63) | (i & 31) << 1 | (i >> 5 & 1); }
template<bool INV, bool T128 = true> __device__ __forceinline__ void twiddles(cf (&v)[32], const float4* __restrict__ tw) {
#pragma unroll
  for (int j = 0; j < 32; j += 2) {
    float4 w;
    if (T128) w = tw[j * 16];
    else { const uint2 a = lds64(smem_u32(tw + j * 16)), b = lds64(smem_u32(tw + j * 16) + 8); w = make_float4(__uint_as_float(a.x), __uint_as_float(a.y), __uint_as_float(b.x), __uint_as_float(b.y)); }
    if (j) v[j] = cmul(v[j], w.x, INV ? -w.y : w.y);
    v[j + 1] = cmul(v[j + 1], w.z, INV ? -w.w : w.w);
  }
}
template<bool INV, class F> __device__ __forceinline__ void warp_fft1024(cf (&v)[32], float2* __restrict__ buf, const float2* __restrict__ tw, int t, int u, F mid) {
#pragma unroll 1
  for (uint32_t h = 0; h < 2; h++) {
    fft32<INV>(v);
    if (FUNR ? h : opaque(h)) continue;
    twiddles<INV>(v, (const float4*)tw + u);
    if (INV) {
      float* f = (float*)buf;
#pragma unroll
      for (int j = 0; j < 32; j++) f[j * 36 + t] = v[j].x;
      __syncwarp();
#pragma unroll
      for (int j = 0; j < 32; j += 4) { const float4 r = *(const float4*)(f + u * 36 + j); v[j].x = r.x; v[j + 1].x = r.y; v[j + 2].x = r.z; v[j + 3].x = r.w; }
      __syncwarp();
#pragma unroll
      for (int j = 0; j < 32; j++) f[j * 36 + t] = v[j].y;
      __syncwarp();
#pragma unroll
      for (int j = 0; j < 32; j += 4) { const float4 r = *(const float4*)(f + u * 36 + j); v[j].y = r.x; v[j + 1].y = r.y; v[j + 2].y = r.z; v[j + 3].y = r.w; }
    } else {
#pragma unroll
      for (int j = 0; j < 32; j++) buf[j * 33 + t] = make_float2(v[j].x, v[j].y);
      __syncwarp();
#pragma unroll
      for (int j = 0; j < 32; j++) { const float2 r = buf[u * 33 + j]; v[j] = {r.x, r.y}; }
    }
    __syncwarp();
    mid();
  }
}
constexpr int ROW_BUF = 32 * 33, INV_BUF = 32 * 18;

__device__ __forceinline__ int z_row(int p) { return (p & ~31) | (p & 7) << 2 | (p & 31) >> 3; }
__device__ __forceinline__ int inv_lane(int t) { return (t & ~14) | (t & 12) >> 1 | (t & 2) << 2; }
__device__ __forceinline__ float2 twiddle(int i) { float s, c; sincospif(-(float)((i >> 5) * (i & 31)) * (1.0f / 512.0f), &s, &c); return make_float2(c, s); }
template<class F, class G> __device__ __forceinline__ void fft_rows_fwd(float2* sm2, const __nv_bfloat16* gw, int cta, int tid, uint32_t full_bar, uint32_t release_bar, F ev, G extra) {
  const int t = tid & 31, w = tid >> 5, n = z_row(cta * 8 + w);
#pragma unroll 1
  for (int i = tid; i < 1024; i += 256) sm2[tw_at(i)] = twiddle(i);
  ev(5);
  mbar_spin(full_bar, 0);
  if (tid == 0) TL2(6);
  __syncwarp();
  const __nv_bfloat16* xa = (const __nv_bfloat16*)(sm2 + 1024 + w * ROW_BUF) + t;
  cf v[32];
  float ga = 0.f, gb = 0.f;
#pragma unroll
  for (int j = 0; j < 32; j++) {
    v[j] = {bf2f(xa[32 * j]), bf2f(xa[D_ + 32 * j])};
    const float g = bf2f(gw[32 * j + t]); ga = fmaf(v[j].x, g, ga); gb = fmaf(v[j].y, g, gb);
  }
#pragma unroll
  for (int o = 16; o; o >>= 1) { ga += __shfl_xor_sync(~0u, ga, o); gb += __shfl_xor_sync(~0u, gb, o); }
  if (t < 2) g_gate[n + 1024 * t] = __fdividef(1.0f, 1.0f + __expf(-(t ? gb : ga)));
  ev(6);
  bar_sync(13, 256);
  warp_fft1024<false>(v, sm2 + 1024 + w * ROW_BUF, sm2, t, t, [&]() { FENCE_ASYNC_SMEM(); mbar_arrive_warp(release_bar); });
  float ws, wc; sincospif(-(float)n * (1.0f / 1024.0f), &ws, &wc);
  ev(12);
  uint32_t tz = clock_lo();
  float4* z = (float4*)g_z + ((size_t)(t >> 1) * 1024 + cta * 8 + w) * 2 + (t & 1);
#pragma unroll
  for (int j = 0; j < 17; j++) {
    cf q = v[(32 - j) & 31];
    if (j < 16) {
      const cf r = {__shfl_sync(~0u, v[31 - j].x, 32 - t), __shfl_sync(~0u, v[31 - j].y, 32 - t)};
      if (t != 0) q = r;
    }
    const cf a = {v[j].x + q.x, v[j].y - q.y}, b = {v[j].y + q.y, q.x - v[j].x};
    const cf d = cmul({a.x - b.x, a.y - b.y}, wc, ws);
    if (j == POOL_AT) extra();
    if (PACE_Z && j && j < 16) delay_until(tz += PACE_Z);
    if ((j < 16 || t == 0) && ((EXP_ST & 4) || d.x == 123.f)) z[j * 32768] = make_float4(a.x + b.x, a.y + b.y, d.x, d.y);
  }
}
constexpr int CP = X128 == 0 ? 33 : X128 == 2 ? 34 : 36, COL_FS = 32 * 36 + 8, COL_W = (8192 + 16 * COL_FS * 4 + 127) & ~127, COL_SMEM = COL_W + 131072 + 128;

__device__ __forceinline__ void fft_cols(float2* sm2, int cta, const CUtensorMap* twr, const CUtensorMap* twi, const CUtensorMap* tzs) {
  const int grp = __shfl_sync(~0u, (int)(threadIdx.x >> 7), 0), tid = threadIdx.x & 127, tp = tid >> 2, w = __shfl_sync(~0u, tid >> 5, 0);
  float* buf = (float*)(sm2 + 1024) + (grp * 4 + (tid & 3)) * COL_FS;
  const uint32_t wsm = smem_u32(sm2) + COL_W, wbar = wsm + 131072 + (W_FINE ? w * 32 : 0);
  const int res = w * 2 + (tid & 1), el = res + grp * 2 + ((tid >> 1) & 1);
  uint32_t wa = (el >> 3) * 65536 + res * 4096 + (tp & 7) * 16 + (el & 7) * 2;
  auto load_w = [&](int q) {
    const uint32_t bar = wbar + (q & 1) * 8;
    mbar_expect(bar, W_FINE ? 16384 : 65536);
#pragma unroll 1
    for (int i = W_FINE ? 4 * w : 0; i < (W_FINE ? 4 * w + 4 : 16); i++) tma2d(wsm + (q & 1) * 65536 + (i & 1) * 32768 + (i >> 1) * 4096, i & 1 ? twi : twr, (i >> 1) * 512 + q * 8, 0, bar);
  };
  const bool lead = (tid & (W_FINE ? 31 : 127)) == 0, first = grp < 2 && lead;
  if (first) { mbar_init(wbar + grp * 8, 1); sts32(wbar + 16 + grp * 4, grp ? 0 : w); asm volatile("fence.mbarrier_init.release.cluster;" ::: "memory"); }
#pragma unroll 1
  for (int i = threadIdx.x; i < 1024; i += 512) {
    const float2 t = twiddle(z_row(i));
    sm2[tw_at(i)] = t;
    if (cta == 0) g_tw[tw_at(inv_lane(z_row(i)))] = t;
  }
  for (uint32_t n = 0; ld_acquire(g_ctl + C_P1) < 128; ) { watchdog(n, 1u << 22); __nanosleep(200); }
  if (COL_DLY) delay_cycles(COL_DLY);
  if (first) load_w(cta * 16 + grp);
  __syncthreads();
  delay_cycles(1 + grp * DLY_GRP);
  mbar_wait(wbar, 0);
  const int end = cta * 64 + 64 + (cta == 3);
  for (int item = cta * 64 + grp; item < end; item += 4, wa ^= 65536) {
    float2* zp = g_z + (size_t)item * 4096;
    auto next_w = [&]() {
      const int q = (item >> 2) + (W_FINE && grp + w > 3);
      uint32_t n; asm volatile("atom.shared.inc.u32 %0, [%1], 3;" : "=r"(n) : "r"(wbar + 16 + (q & 1) * 4) : "memory");
      if (EXP_W && n == 3 && q < (cta * 16 + 15)) load_w(q + 2);
    };
    cf v[32];
#pragma unroll
    for (int j = 0; j < 32; j++) { const float2 a = ld_once(zp + tid + j * 128); v[j] = {a.x, a.y}; }
#pragma unroll 1
    for (int ph = 0; ; ph++) {
      fft32<false>(v);
      twiddles<false, T128_>(v, (const float4*)sm2 + tp);
      if (Z_ST) asm volatile("cp.async.bulk.wait_group.read 0;" ::: "memory");
      bar_sync(1 + grp, 128);
      if (lead) {
        if (ph) {
          if (!W_AT) next_w();
        } else if (Z_PF && item + 4 < end) asm volatile("cp.async.bulk.prefetch.L2.global [%0], %1;" :: "l"(zp + 4 * 4096 + w * 1024), "n"(W_FINE ? 8192 : 32768) : "memory");
      }
      __syncwarp();
#pragma unroll
      for (int j = 0; j < 32; j++) buf[((j & 3) * 8 + (j >> 2)) * CP + tp] = v[j].x;
      bar_sync(1 + grp, 128);
      if (X128 == 0) {
#pragma unroll
        for (int j = 0; j < 32; j++) v[j].x = buf[tp * CP + (j & 3) * 8 + (j >> 2)];
      } else if (X128 == 2) {
#pragma unroll
        for (int j = 0; j < 16; j++) { const float2 r = *(const float2*)(buf + tp * CP + 2 * j); cf* d = v + (j & 3) * 8 + (j >> 2); d[0].x = r.x; d[4].x = r.y; }
      } else
#pragma unroll
      for (int j = 0; j < 8; j++) {
        const float4 r = *(const float4*)(buf + tp * 36 + 4 * j);
        cf* d = v + (j & 1) * 16 + (j >> 1);
        d[0].x = r.x; d[4].x = r.y; d[8].x = r.z; d[12].x = r.w;
      }
      bar_sync(1 + grp, 128);
#pragma unroll
      for (int j = 0; j < 32; j++) buf[((j & 3) * 8 + (j >> 2)) * CP + tp] = v[j].y;
      bar_sync(1 + grp, 128);
      if (X128 == 0) {
#pragma unroll
        for (int j = 0; j < 32; j++) v[j].y = buf[tp * CP + (j & 3) * 8 + (j >> 2)];
      } else if (X128 == 2) {
#pragma unroll
        for (int j = 0; j < 16; j++) { const float2 r = *(const float2*)(buf + tp * CP + 2 * j); cf* d = v + (j & 3) * 8 + (j >> 2); d[0].y = r.x; d[4].y = r.y; }
      } else
#pragma unroll
      for (int j = 0; j < 8; j++) {
        const float4 r = *(const float4*)(buf + tp * 36 + 4 * j);
        cf* d = v + (j & 1) * 16 + (j >> 1);
        d[0].y = r.x; d[4].y = r.y; d[8].y = r.z; d[12].y = r.w;
      }
      fft32<false>(v);
      if (ph) break;
      const int q = min((item >> 2) + (!W_FINE || grp + w >= 3), 64);
      if (EXP_W) mbar_wait(wbar + (q & 1) * 8, (q >> 1) & 1);
#pragma unroll
      for (int j = 0; j < 32; j++) {
        uint32_t re, im;
        asm volatile("ld.shared.u16 %0, [%1];" : "=r"(re) : "r"(wsm + wa + j * 128) : "memory");
        asm volatile("ld.shared.u16 %0, [%1];" : "=r"(im) : "r"(wsm + wa + 32768 + j * 128) : "memory");
        const cf r = cmul(v[j], __uint_as_float(re << 16), __uint_as_float(im << 16));
        v[j] = {r.y, r.x};
      }
    }
    if (Z_ST) {
      float2* st = sm2 + 1024 + grp * (COL_FS * 2) + w * 512;
      bar_sync(1 + grp, 128);
#pragma unroll
      for (int h = 0; h < 2; h++) {
        if (h && Z_ST == 2) {
#pragma unroll
          for (int j = 16; j < 32; j++) zp[tid + j * 128] = make_float2(v[j].y, v[j].x);
          break;
        }
        if (h) { asm volatile("cp.async.bulk.wait_group.read 0;" ::: "memory"); __syncwarp(); }
#pragma unroll
        for (int j = 0; j < 16; j++) st[j * 32 + (tid & 31)] = make_float2(v[h * 16 + j].y, v[h * 16 + j].x);
        FENCE_ASYNC_SMEM();
        __syncwarp();
        tma2d_st_e(tzs, w * 128, item * 32 + h * 16, smem_u32(st));
        asm volatile("cp.async.bulk.commit_group;" ::: "memory");
      }
    } else {
#pragma unroll
      for (int j = 0; j < 32; j++) zp[tid + j * 128] = make_float2(v[j].y, v[j].x);
    }
    if (W_AT) { if (lead) next_w(); __syncwarp(); }
  }
  if (Z_ST) asm volatile("cp.async.bulk.wait_group 0; fence.proxy.async.global;" ::: "memory");
  __syncthreads();
  if (threadIdx.x < 32) {
    count_e(g_ctl + C_COLS);
    await_count(g_ctl + C_COLS, 4);
    g_ctl[C_P1] = 0;
  }
  __syncthreads();
  ((float4*)sm2)[threadIdx.x] = __ldcg((const float4*)g_tw + threadIdx.x);
  __syncthreads();
}

template<class F> __device__ __forceinline__ void fft_rows_inv(uint32_t zs, float2* buf, const float2* tw, int p, int lane, __nv_bfloat16* out, F read) {
  const int n = z_row(p), t = (lane & 17) | (lane & 6) << 1 | (lane & 8) >> 2, src = inv_lane(-t & 31);
  const uint32_t z = zs + (t >> 1) * 128 + ((((p & 3) * 2 + (t & 1)) ^ (t >> 1 & 7)) << 4);
  FT(0, 0.f);
  float4 e[17];
  uint32_t all = 0;
  e[16] = __ldcg((const float4*)g_z + ((size_t)256 * 1024 + p) * 2);
  const float g0 = __ldcg(g_gate + n), g1 = __ldcg(g_gate + n + 1024);
#pragma unroll
  for (int j = 0; j < 16; j++) { const uint4 u = lds128(z + j * 2048); e[j] = make_float4(__uint_as_float(u.x), __uint_as_float(u.y), __uint_as_float(u.z), __uint_as_float(u.w)); all |= u.x; }
  sched_fence(all);
  read();
  float ws, wc; sincospif((float)n * (1.0f / 1024.0f), &ws, &wc);
  cf v[32], q[17];
#pragma unroll
  for (int j = 0; j < 17; j++) {
    const cf d = cmul({e[j].z, e[j].w}, wc, ws);
    cf a = {e[j].x + d.x, e[j].y + d.y}, b = {e[j].x - d.x, e[j].y - d.y};
    if (j == 16 || (j == 0 && t == 0)) { a.y = 0.f; b.y = 0.f; }
    if (j < 16) v[j] = {a.x - b.y, a.y + b.x};
    q[j] = {a.x + b.y, b.x - a.y};
  }
#pragma unroll
  for (int j = 16; j < 32; j++) {
    v[j] = {__shfl_sync(~0u, q[31 - j].x, src), __shfl_sync(~0u, q[31 - j].y, src)};
    if (t == 0) v[j] = q[32 - j];
  }
  FT(1, v[0].x + v[16].x + v[31].x);
  warp_fft1024<true>(v, buf, tw, t, lane, []() {});
  FT(3, v[31].y + v[0].x);
  const float sc = 0.5f / (2048.0f * 1024.0f), s0 = (1.f - g0) * sc, s1 = (1.f - g1) * sc;
  uint2* o = (uint2*)(out + (size_t)n * D_) + (lane ^ (n & 1) << 3);
#pragma unroll
  for (int j = 0; j < 32; j += 4) {
    o[8 * j] = make_uint2(pack_bf16(v[j].x * s0, v[j + 1].x * s0), pack_bf16(v[j + 2].x * s0, v[j + 3].x * s0));
    o[256 * D_ + 8 * j] = make_uint2(pack_bf16(v[j].y * s1, v[j + 1].y * s1), pack_bf16(v[j + 2].y * s1, v[j + 3].y * s1));
  }
  FT(4, 0.f);
}

constexpr int NP = NP_, NHV = REG_F == 216 ? 5 : 7, NV = 16 - NHV;
constexpr int XEND = NSEG;
constexpr uint32_t SM_WO = 0, SM_V = 65536, SM_LAND = SM_V + 8192, SM_MEM = SM_LAND + 24576, SM_SP = SM_MEM, SM_SPM = SM_MEM + 5120, SM_OM = SM_MEM + 6144,
                   SM_OX = SM_MEM + 8192, SM_RED = SM_OX + 2048, SM_XCH = SM_RED + 1024, SM_SUM = SM_XCH + 4096, SM_VM = SM_SUM + 128, SM_TAB = SM_VM + 2048, SM_TRACE = SM_TAB + 2048,
                   ST_WG = (32 - NP + NV) * 2048,
                   SM_XT = 2 * ST_WG, SM_POOL = SM_XT + 32768, SM_HV = SM_POOL + 2 * NP * 2048,
                   SM_BAR = SM_HV + 2 * NHV * 2048, SM_SEL = SM_BAR + 320, CHAIN_SMEM = SM_SEL + 544 + 1024;
constexpr uint32_t SM_FFT = 49152, SM_GW = SM_XT - 2048;
static_assert(NP % 4 == 0 && NV == 11 && SM_TRACE + 4096 <= SM_XT, "shared memory layout");
static_assert(CHAIN_SMEM <= 232448 && COL_SMEM <= SM_BAR && SM_FFT + (1024 + 8 * ROW_BUF) * 8 <= SM_GW && NP == 12, "shared memory budget");
enum { B_WFULL = 0, B_WREAD = 2, B_WOFULL, B_XFULL, B_XEMPTY, B_E1TRIG, B_E2TRIG, B_PVDONE, B_PUB, B_SC, B_PFULL, B_SPFREE,
       B_LAND, B_LFREE, B_DONE, B_SEL, B_PROBE, B_FREE, B_P1, B_ROWS, B_VFULL, B_VST, B_TW, B_BT, B_WREAD0, B_Z, B_GFULL = B_Z + 4, B_GEMPTY = B_GFULL + 5, B_END = B_GEMPTY + 5 };
static_assert(B_END * 8 <= 320, "barriers");
__host__ __device__ constexpr uint32_t bar_codes(int g) {
  uint32_t r = 0;
  for (int i = 16 * g; i < 16 * g + 16; i++)
    r |= (i == B_LAND ? 3u : i == B_WREAD || i == B_XEMPTY || i == B_E1TRIG || i == B_E2TRIG || i == B_LFREE || i == B_FREE || i == B_VST || i == B_P1 || i == B_ROWS ? 2u :
          i >= B_GEMPTY || i == B_WREAD0 || i == B_PROBE || i == B_DONE || i == B_PVDONE || i == B_PUB || i == B_SC || i == B_SPFREE ? 1u : 0u) << 2 * (i & 15);
  return r;
}
constexpr uint32_t SM_BT = 65536, SM_TW = SM_XT - 8192, COL_Z = 80 * 1024;
static_assert(SM_XT + 3 * 32768 <= SM_BAR && SM_BT + 32768 <= SM_MEM && SM_TRACE <= SM_TW && SM_MEM + 4 * INV_BUF * 8 <= SM_TRACE &&
              8192 + 16 * INV_BUF * 8 <= COL_Z && COL_Z + 131072 <= SM_BAR, "shared memory layout");
__device__ __forceinline__ uint32_t next_stage(uint32_t o) { return o == SM_XT + 65536 ? 0 : o == 32768 ? SM_XT : o + 32768; }

struct ChainCtx { char* mail; uint32_t sb, sel; int r, h, a, b, j, m, w, lane; };
#define BAR(i) (c.sb + SM_BAR + 8 * (i))

__device__ __forceinline__ uint32_t tile_off(int line, int lane) {
  return line * 128 + (((lane & 3) ^ line) << 5) + (lane >> 2) * 4;
}
__device__ __forceinline__ uint32_t read_off(int lane) {
  const int n = lane >> 2, jj = lane & 3, l = 2 * (jj >> 1) + (n & 1);
  return l * 128 + (((n >> 1) ^ l) << 5) + (jj & 1) * 16;
}
__device__ __forceinline__ uint32_t frag_off(int w, int lane) {
  const int mi = lane >> 3, r = lane & 7;
  return ((mi >> 1) * 8 + r) * 128 + (((2 * w + (mi & 1)) ^ r) << 4);
}
__device__ __forceinline__ uint32_t land_off(int w, int lane) { return w * 512 + ((lane ^ (((lane >> 4) | ((w & 1) << 1)) << 1)) << 4); }
__device__ __forceinline__ uint32_t tagged(uint32_t v, uint32_t tag) { return (v | 1u) ^ tag; }
__device__ __forceinline__ void mma_a(float (&d)[4], const uint32_t (&a)[4], uint32_t b0, uint32_t b1) { mma16816(d, a[0], a[1], a[2], a[3], b0, b1); }
__device__ __forceinline__ void mma_q(float (&d)[4], const uint4& a, uint32_t b0, uint32_t b1) { mma16816(d, a.x, a.y, a.z, a.w, b0, b1); }
__device__ __forceinline__ uint4 add4(uint4 a, uint4 b) {
  return make_uint4(add_bf16x2(a.x, b.x), add_bf16x2(a.y, b.y), add_bf16x2(a.z, b.z), add_bf16x2(a.w, b.w));
}
__device__ __forceinline__ void mbar_arrive_both(uint32_t bar, int peer) {
  __syncwarp();
  asm volatile("{ .reg .pred p; .reg .u32 a; mapa.shared::cluster.u32 a, %0, %1; elect.sync _|p, 0xffffffff;\n"
               "@p mbarrier.arrive.shared::cta.b64 _, [%0]; @p mbarrier.arrive.shared::cluster.b64 _, [a]; }" :: "r"(bar), "r"(peer) : "memory");
}

__device__ __forceinline__ void arrive_remote_if(uint32_t a, bool on) {
  asm volatile("{ .reg .pred p; setp.ne.u32 p, %1, 0; @p mbarrier.arrive.shared::cluster.b64 _, [%0]; }" :: "r"(a), "r"((uint32_t)on) : "memory");
}
__device__ __forceinline__ void store_count(void* p, uint4 v, void* cnt) {
  asm volatile("{ .reg .pred p, q; .reg .b128 a, b; .reg .b64 l, h; mov.b64 l, {%1, %2}; mov.b64 h, {%3, %4}; mov.b128 a, {l, h};\n"
               "atom.relaxed.gpu.global.exch.b128 b, [%0], a; mov.b128 {l, h}, b; setp.eq.u64 q, l, 0x7fc17fc17fc17fc1; @q pmevent 1;\n"
               "elect.sync _|p, 0xffffffff; @p red.relaxed.gpu.global.add.u32 [%5], 1; }"
               :: "l"(p), "r"(v.x), "r"(v.y), "r"(v.z), "r"(v.w), "l"(cnt) : "memory");
}

template<int N> __device__ __forceinline__ void pad() {
#pragma unroll
  for (int i = 0; i < N; i++) asm volatile("pmevent 3;");
}
__device__ __forceinline__ int lane_id() {
  int l; asm volatile("{ .reg .u32 t; mov.u32 t, %%laneid; shfl.sync.idx.b32 %0, t, t, 31, 0xffffffff; }" : "=r"(l)); return l;
}
__device__ __forceinline__ uint32_t tid_now() { uint32_t t; asm volatile("mov.u32 %0, %%tid.x;" : "=r"(t)); return t; }
enum { NB_ATT = 1, NB_OM = 2, NB_VM = 3, NB_XCH = 4, NB_MEM = 8, NB_HELP = 12 };
__device__ __forceinline__ uint32_t dep(uint32_t a, uint32_t v, uint32_t z) { uint32_t r; asm("shf.l.wrap.b32 %0, %2, %1, %3;" : "=r"(r) : "r"(a), "r"(v), "r"(z)); return r; }
__device__ __forceinline__ uint32_t vary(uint32_t a, int s, uint32_t z) { return dep(a, 0, z + 32 * s); }
__device__ __forceinline__ char* mk_ptr(uint32_t lo, uint32_t hi) { uint64_t r; asm("mov.b64 %0, {%1, %2};" : "=l"(r) : "r"(lo), "r"(hi)); return (char*)r; }
__device__ __forceinline__ void lds_frag(uint32_t (&r)[4], uint32_t a) {
  asm volatile("ld.shared.v4.u32 {%0,%1,%2,%3}, [%4];" : "=r"(r[0]), "=r"(r[1]), "=r"(r[2]), "=r"(r[3]) : "r"(a) : "memory");
}
__device__ __forceinline__ uint32_t stale2(uint32_t a, uint32_t b, uint32_t t) { uint32_t r; asm("lop3.b32 %0, %1, %2, %3, 0xbd;" : "=r"(r) : "r"(a), "r"(b), "r"(t)); return r; }
__device__ __forceinline__ uint32_t stale1(uint32_t acc, uint32_t a, uint32_t t) { uint32_t r; asm("lop3.b32 %0, %1, %2, %3, 0xf9;" : "=r"(r) : "r"(acc), "r"(a), "r"(t)); return r; }
__device__ __forceinline__ bool all_clear(uint32_t x, uint32_t m) {
  uint32_t r;
  asm volatile("{ .reg .pred p; .reg .u32 t; and.b32 t, %1, %2; setp.eq.u32 p, t, 0; vote.sync.all.pred p, p, 0xffffffff; selp.u32 %0, 1, 0, p; }" : "=r"(r) : "r"(x), "r"(m));
  return r;
}
__device__ __forceinline__ bool arrive_if_all(bool ok, int id, int n) {
  uint32_t r;
  asm volatile("{ .reg .pred p, q; setp.ne.u32 p, %1, 0; vote.sync.all.pred q, p, 0xffffffff; @q bar.arrive %2, %3; selp.u32 %0, 1, 0, q; }"
               : "=r"(r) : "r"((uint32_t)ok), "r"(id), "r"(n) : "memory");
  return r;
}
__device__ __forceinline__ bool arrive_if_clear(uint32_t x, uint32_t m, int id, int n) {
  uint32_t r;
  asm volatile("{ .reg .pred p; .reg .u32 t; and.b32 t, %1, %2; setp.eq.u32 p, t, 0; vote.sync.all.pred p, p, 0xffffffff; @p bar.arrive %3, %4; selp.u32 %0, 1, 0, p; }"
               : "=r"(r) : "r"(x), "r"(m), "r"(id), "r"(n) : "memory");
  return r;
}
__device__ __forceinline__ void touch(const void* p, uint32_t z) {
  asm volatile("{ .reg .pred p; setp.eq.u32 p, %1, 0x7fff0000; @p prefetch.global.L2 [%0]; }" :: "l"(p), "r"(z) : "memory");
}

__device__ __forceinline__ uint64_t desc_x(uint32_t lo, int k) {
  uint64_t d; asm("mov.b64 %0, {%1, %2};" : "=l"(d) : "r"(lo + (k >> 2) * 64 + (k & 3) * 2), "r"(0x40000200)); return d;
}
template<int K0, int K1> __device__ __forceinline__ void issue_qk(float (&xa)[16], const uint32_t (&wt)[16][4], uint32_t lo) {
  WG_FENCE();
#pragma unroll
  for (int k = K0; k < K1; k++) {
    if (k >= EXP_NWG) continue;
    if (k == 0) wgmma_rs_n32<true>(xa, wt[0], desc_x(lo, 0));
    else wgmma_rs_n32<false>(xa, wt[k], desc_x(lo, k));
  }
  WG_COMMIT();
}
__host__ __device__ constexpr int v_order(int i) { return SSPOS == 0 ? i : SSPOS == 2 ? (i + NV) % 16 : NHV == 5 ? (i % 3 == 2 ? NV + i / 3 : i - i / 3) : (i == 15 ? NV - 1 : i % 2 ? NV + i / 2 : i / 2); }
__device__ __forceinline__ void issue_v(float (&xa)[16], const uint32_t (&wv)[16][4], uint32_t lo, uint32_t la) {
  WG_FENCE();
#pragma unroll
  for (int i = 0; i < EXP_NWG; i++) {
    const int k = v_order(i);
    const uint64_t b = desc_x(lo, k);
    if (k < NV) { if (i == 0) wgmma_rs_n32<true>(xa, wv[k], b); else wgmma_rs_n32<false>(xa, wv[k], b); }
    else        { if (i == 0) wgmma_ss_n32_ta<true>(xa, desc128(la + (k - NV) * 128), b); else wgmma_ss_n32_ta<false>(xa, desc128(la + (k - NV) * 128), b); }
  }
  WG_COMMIT();
}
template<bool ISV> __device__ __forceinline__ void park_own(uint32_t (&q)[4], float (&xa)[16], uint32_t dst, int slot, uint32_t z) {
  uint32_t p[8];
#pragma unroll
  for (int i = 0; i < 16; i++) asm volatile("" : "+f"(xa[i]) :: "memory");
#pragma unroll
  for (int i = 0; i < 2; i++) {
    const float* k = xa + 8 * i;
    if (ISV) { p[4 * i] = pack_bf16(k[0], k[1]); p[4 * i + 1] = pack_bf16(k[2], k[3]); p[4 * i + 2] = pack_bf16(k[4], k[5]); p[4 * i + 3] = pack_bf16(k[6], k[7]); }
    else     { p[4 * i] = pack_bf16(k[0], k[2]); p[4 * i + 1] = pack_bf16(k[1], k[3]); p[4 * i + 2] = pack_bf16(k[4], k[6]); p[4 * i + 3] = pack_bf16(k[5], k[7]); }
  }
  sts128(dep(dep(dst, p[4] ^ p[5] ^ p[6], z), p[7], z) + slot * 8192, make_uint4(p[0], p[1], p[2], p[3]));
#pragma unroll
  for (int i = 0; i < 4; i++) q[i] = p[4 + i];
}
__device__ __forceinline__ void park_peer(const uint32_t (&q)[4], uint32_t dst, int slot, const ChainCtx& c) {
  const uint32_t bar = BAR(B_LAND);
  if (EXP_PEER) st_async4(mapa(dst + slot * 8192, c.b ^ 1), q[0], q[1], q[2], q[3], mapa(bar, c.b ^ 1));
  else touch((void*)(uintptr_t)(q[0] ^ q[1] ^ q[2] ^ q[3]), c.sb);
  mbar_arrive_warp(bar);
}
__device__ __forceinline__ uint32_t put_tag(uint32_t v, uint32_t bit, uint32_t t) {
  uint32_t r; asm("lop3.b32 %0, %1, %2, %3, 0x74;" : "=r"(r) : "r"(v), "r"(bit), "r"(t)); return r;
}
__device__ __forceinline__ void mem_proj(const uint32_t (&wa)[16][4], const uint32_t (&wb)[16][4], uint32_t (&wv)[16][4], uint32_t (&af)[16][4],
                                         uint32_t& wo, const char*& pa, uint32_t tab, uint32_t t16, uint32_t pk, const ChainCtx& c, int s) {
  const uint32_t mp = t16 & ~0x600u, id = NB_MEM + (t16 >> 11);
  uint32_t r[8][4];
  float la[4][4] = {}, lg[NLAG][4] = {}, lv[4][4] = {};
  auto lead = [&](int k) { mma_a(la[k & 3], wa[k], r[k >> 1][2 * (k & 1)], r[k >> 1][2 * (k & 1) + 1]); };
  auto lag = [&](int k) { mma_a(lg[k % NLAG], wb[k], r[k >> 1][2 * (k & 1)], r[k >> 1][2 * (k & 1) + 1]); };
  auto sum = [](const float (&d)[4][4], int i) { return (d[0][i] + d[1][i]) + (d[2][i] + d[3][i]); };
  bar_sync(id, 160);
  TR(s, 0);
#pragma unroll
  for (int i = 0; i < 4; i++) ldsm4t(r[i], mp + (c.sb + SM_MEM + i * 512));
  const uint4 tq = lds128(tab);
  bar_sync(id + 2, 160);
#pragma unroll
  for (int k = 0; k < 8; k++) lead(k);
  const uint32_t ta = tq.x | ((pk >> 16) & 511), tb = tq.z ^ ((pk >> 16) & 511);
  char* dst = mk_ptr(ta, tq.y);
  char* dst2 = mk_ptr(tb, tq.w);
  const uint32_t mp1 = dep(mp, __float_as_uint(la[C1_AT][0]) ^ ta ^ tb, c.sb);
#pragma unroll
  for (int i = 4; i < 8; i++) ldsm4t(r[i], mp1 + (c.sb + SM_MEM + 2048 + i * 512));
  const uint32_t hv = pk & 0xFFFF;
#pragma unroll
  for (int k = NV; k < NV + HV_E; k++) ldsm4t(wv[k], dep(hv, r[HV_R][0], c.sb) + (c.sb + SM_HV + (k - NV) * 2048));
#pragma unroll
  for (int k = 0; k < 8; k++) lag(k);
#pragma unroll
  for (int k = 8; k < 16; k++) lead(k);
  sts128((HV_E ? dep(t16, wv[NV][0] ^ wv[NV + HV_E / 2][1] ^ wv[NV + HV_E - (HV_E > 0)][2], c.sb) : t16) + (c.sb + SM_XCH), make_uint4(__float_as_uint(sum(la, 0)), __float_as_uint(sum(la, 1)), __float_as_uint(sum(la, 2)), __float_as_uint(sum(la, 3))));
  bar_sync(NB_XCH | ((t16 >> 9) & 3), 64);
  const uint4 o = lds128((t16 ^ 2048) + (c.sb + SM_XCH));
#pragma unroll
  for (int k = 8; k < 16; k++) lag(k);
  float t[4];
#pragma unroll
  for (int i = 0; i < 4; i++) {
    const float oi = __uint_as_float(i == 0 ? o.x : i == 1 ? o.y : i == 2 ? o.z : o.w);
    t[i] = NLAG == 4 ? (((lg[0][i] + lg[1][i]) + lg[2 % NLAG][i]) + lg[3 % NLAG][i]) + oi : NLAG == 3 ? (lg[1][i] + lg[2 % NLAG][i]) + (lg[0][i] + oi) : (lg[0][i] + oi) + lg[1][i];
  }
  const uint32_t y0 = put_tag(pack_bf16(t[0], t[2]), pk >> 31, s >> 1), y1 = put_tag(pack_bf16(t[1], t[3]), pk >> 31, s >> 1);
  st_pub(dst, y0); st_pub(dst2, y1);
  mbar_arrive_warp(BAR(B_E1TRIG));
  TR(s, 1);
  sched_fence(c.sb);
  const uint4 tv = lds128(tab + 16);
#pragma unroll
  for (int k = NV + HV_E; k < 16; k++) ldsm4t(wv[k], (k < NV + HV_E + HV_D ? hv : dep(hv, k == NV + HV_E + HV_D ? wv[k - HV_D][0] ^ tv.x : wv[k - HV_D][0], c.sb)) + (c.sb + SM_HV + (k - NV) * 2048));
  wo = (hv & 2047) | ((t16 & 2048) << 3);
  const uint32_t l8 = (t16 >> 1) & 255;
  char* dv = mk_ptr(tv.x | l8, tv.y);
  pa = mk_ptr(tv.z | l8, tv.w);
#pragma unroll
  for (int f = 0; f < WO_0; f++) ldsm4t(af[f], dep(wo, f < WO_D ? wv[16 - WO_D + f][0] : af[f < WO_D ? 0 : f - WO_D][0], c.sb) + (c.sb + SM_WO + (f & 1) * 32768 + (f >> 1) * 2048));
#pragma unroll
  for (int k = 0; k < 16; k++) mma_a(lv[k & 3], wv[k], r[k >> 1][2 * (k & 1)], r[k >> 1][2 * (k & 1) + 1]);
  const uint32_t z0 = put_tag(pack_bf16(sum(lv, 0), sum(lv, 1)), (~t16 >> 4) & 1, s >> 1), z1 = pack_bf16(sum(lv, 2), sum(lv, 3));
  st_pub2(dv, z0, z1);
  if (FIN_AT >= 3) mbar_arrive_warp(BAR(B_VST));
  TR(s, 2);
}
__device__ __forceinline__ uint32_t max_bf16x2(uint32_t a, uint32_t b) { uint32_t r; asm("max.bf16x2 %0, %1, %2;" : "=r"(r) : "r"(a), "r"(b)); return r; }
constexpr float SCL = 0.08838834764831845f * 1.4426950408889634f;
__device__ __forceinline__ uint32_t max5(const uint32_t (&sc)[5]) { return max_bf16x2(max_bf16x2(max_bf16x2(max_bf16x2(sc[0], sc[1]), sc[2]), sc[3]), sc[4]); }
__device__ __forceinline__ float row_off(uint32_t m, uint32_t& m1) {
  m1 = __shfl_xor_sync(~0u, m, 1);
  const uint32_t m2 = __shfl_xor_sync(~0u, m, 2), m3 = __shfl_xor_sync(~0u, m, 3);
  const uint32_t mm = max_bf16x2(max_bf16x2(max_bf16x2(m, m1), m2), m3);
  return -SCL * fmaxf(__uint_as_float(mm << 16), __uint_as_float(mm & 0xFFFF0000u));
}
__device__ __forceinline__ void unpack(float (&f)[10], const uint32_t (&sc)[5]) {
#pragma unroll
  for (int i = 0; i < 5; i++) {
    asm volatile("shl.b32 %0, %1, 16;" : "=f"(f[2 * i]) : "r"(sc[i]));
    asm volatile("and.b32 %0, %1, 0xffff0000;" : "=f"(f[2 * i + 1]) : "r"(sc[i]));
  }
}
__device__ __forceinline__ uint32_t exp_pair(const float (&f)[10], int i, float off) {
  return pack_bf16(ex2(fmaf(f[2 * i], SCL, off)), ex2(fmaf(f[2 * i + 1], SCL, off)));
}
template<bool SPLIT> __device__ __forceinline__ void scores_x(float (&a)[2][4], const uint4 (&kf)[4], const uint4& q, uint32_t z) {
#pragma unroll
  for (int t = 0; t < 2; t++) { a[t][0] = a[t][1] = a[t][2] = a[t][3] = 0.f; }
  mma_q(a[0], kf[0], q.x, q.y); mma_q(a[1], kf[2], q.x, q.y);
  if (SPLIT) sched_fence(z);
  mma_q(a[0], kf[1], q.z, q.w); mma_q(a[1], kf[3], q.z, q.w);
}
__device__ __forceinline__ uint32_t scores_m(const uint4& q, const uint4& k) {
  float a[4] = {}, b[4] = {};
  mma_q(a, q, k.x, k.z); mma_q(b, q, k.y, k.w);
  return pack_bf16(a[0] + b[2], a[1] + b[3]);
}
__device__ __forceinline__ void store_scores(const float (&a)[2][4], uint32_t dst) {
  sts64(dst, pack_bf16(a[0][0], a[0][2]), pack_bf16(a[1][0], a[1][2]));
  sts64(dst + 320, pack_bf16(a[0][1], a[0][3]), pack_bf16(a[1][1], a[1][3]));
}
__device__ __forceinline__ uint32_t sum4(uint32_t a, uint32_t b, uint32_t d, uint32_t e) { return add_bf16x2(add_bf16x2(a, b), add_bf16x2(d, e)); }
__device__ __forceinline__ void load_scores(uint32_t (&sc)[5], uint32_t ax, uint32_t am) {
  uint4 p[4];
#pragma unroll
  for (int i = 0; i < 4; i++) p[i] = lds128(ax + i * 1280);
  const uint2 m0 = lds64(am), m1 = lds64(am + 256);
  const uint4 t = add4(add4(add4(p[0], p[1]), p[2]), p[3]);
  sc[1] = t.x; sc[2] = t.y; sc[3] = t.z; sc[4] = t.w;
  sc[0] = sum4(m0.x, m0.y, m1.x, m1.y);
}
constexpr uint32_t ONES = 0x3F803F80u;
__device__ __forceinline__ float pv(float (&o)[2][4], const uint32_t (&p)[5], const uint4 (&vf)[4], const uint4& vm) {
  float a[4] = {}, b[4] = {};
#pragma unroll
  for (int t = 0; t < 2; t++) { o[t][0] = o[t][1] = o[t][2] = o[t][3] = 0.f; }
  mma_q(o[0], vf[0], p[1], p[2]); mma_q(o[1], vf[2], p[1], p[2]);
  mma_q(o[0], vf[1], p[3], p[4]); mma_q(o[1], vf[3], p[3], p[4]);
  mma16816(a, p[1], p[2], p[3], p[4], ONES, ONES);
  mma1688(o[0], vm.x, vm.y, p[0]); mma1688(o[1], vm.z, vm.w, p[0]);
  mma1688(b, p[0], ONES, ONES);
  return (a[0] + a[2]) + b[0];
}
constexpr uint32_t POLL_LIMIT = 1u << 21;
__device__ __forceinline__ uint32_t box(int slot, int cta) { return (slot * 2 + (cta >> 6)) * M_REG + (cta & 63) * 16384; }
__device__ __forceinline__ uint32_t near_page(const ChainCtx& c, int cta, uint32_t off) {
  return off + (((lds32(c.sb + SM_SEL + cta * 4) >> (off >> 21)) ^ __popc(off & 0xB2000)) & 1) * 4096;
}
__device__ __forceinline__ uint32_t e1_box(const ChainCtx& c, int slot, int cta) { return near_page(c, E1OFF ? cta ^ 2 : cta, box(slot, cta) + 8192) ^ (E1OFF ? 0 : 4096); }
__device__ __forceinline__ uint32_t tile_key() {
  uint32_t sm; asm volatile("mov.u32 %0, %%smid;" : "=r"(sm));
  return (sm < 64 ? sm / 2 % 8 : sm < 120 ? 1 + (sm / 2 - 32) % 7 : 0) << 24 | sm << 16;
}
__device__ __forceinline__ uint32_t ox_at(int s, int row, int g, int jj) { return s * 131072 + ((g >> 1) * 32 + row) * 64 + (g & 1) * 32 + 8 * jj; }
__device__ __forceinline__ int tile_of(const ChainCtx& c) { return SIDE ? __shfl_sync(~0u, lds32(c.sb + SM_SEL + 528), 0) : c.r; }

__global__ void __cluster_dims__(2, 1, 1) __launch_bounds__(512, 1)
chain_kernel(const __grid_constant__ CUtensorMap tq, const __grid_constant__ CUtensorMap tk, const __grid_constant__ CUtensorMap tv,
             const __grid_constant__ CUtensorMap tv16, const __grid_constant__ CUtensorMap to, const __grid_constant__ CUtensorMap tx,
             const __grid_constant__ CUtensorMap twr, const __grid_constant__ CUtensorMap twi,
             const __grid_constant__ CUtensorMap ta, const __grid_constant__ CUtensorMap tw,
             const __grid_constant__ CUtensorMap tb, const __grid_constant__ CUtensorMap tout, const __grid_constant__ CUtensorMap tz,
             const __grid_constant__ CUtensorMap tzs, const __grid_constant__ CUtensorMap ta32,
             const __nv_bfloat16* __restrict__ mem0, char* __restrict__ mail, const __nv_bfloat16* __restrict__ x,
             const __nv_bfloat16* __restrict__ gw) {
  extern __shared__ __align__(1024) unsigned char smraw[];
  if (threadIdx.x == 0) TL(0);
  ChainCtx c;
  c.sb = __shfl_sync(~0u, smem_u32(smraw), 0);
  c.mail = mail; c.sel = 0; c.r = blockIdx.x;
  if (ROLE) {
    const uint32_t u = blockIdx.x >> 1, n = u < 36 ? 8 : 7, k = u - (u < 36 ? 4 : 36), q = k * (u < 36 ? 32 : 37) >> 8;
    c.r = __shfl_sync(~0u, 2 * (u - 4 < 60 ? u + k - q * n - (q & 1) * (n - 1) : u) + (blockIdx.x & 1) + (threadIdx.x >> 9), 0);
  }
  c.h = c.r >> 2; c.a = (c.r >> 1) & 1; c.b = c.r & 1; c.j = c.r & 3;
  c.m = __shfl_sync(~0u, (int)(threadIdx.x >> 7), 0); c.w = __shfl_sync(~0u, (int)((threadIdx.x >> 5) & 3), 0);
  char* own = c.mail + (uint32_t)(c.w * M_REG + M_E3 + (c.r >> 5) * 8192 + (c.r & 31) * 128 + (threadIdx.x & 31) * 4);
  uint32_t i0 = 0, i1 = 0;
  if (EARLY) asm volatile("{ .reg .pred p; setp.ne.u32 p, %4, 0; @p atom.relaxed.gpu.global.exch.b32 %0, [%2], %3; @p atom.relaxed.gpu.global.exch.b32 %1, [%2 + 4096], %3; }"
               : "+r"(i0), "+r"(i1) : "l"(own), "r"(SENT), "r"((uint32_t)(c.m == 2 && c.r < 128)) : "memory");
#pragma unroll
  for (int g = 0; g < 3; g++) {
    const int i = c.m * 4 + c.w;
    if (g < 2 || i < B_END - 32)
      asm volatile("{ .reg .pred p; elect.sync _|p, 0xffffffff; @p mbarrier.init.shared::cta.b64 [%0], %1; }"
                   :: "r"(BAR(g * 16 + i)), "r"(0x19080401u >> (bar_codes(g) >> 2 * i & 3) * 8 & 255) : "memory");
  }
  asm volatile("fence.mbarrier_init.release.cluster;" ::: "memory");
  __syncthreads();
  asm volatile("barrier.cluster.arrive.relaxed.aligned;" ::: "memory");

  if (c.r >= 128) {
    fft_cols((float2*)smraw, c.r - 128, &twr, &twi, &tzs);
    if ((threadIdx.x & 127) == 0) TL(7);
    __syncwarp();
  } else if (c.m == 3) {
    asm volatile("setmaxnreg.dec.sync.aligned.u32 %0;" :: "n"(REG_H));
    c.lane = lane_id();
    if (c.sb & 1023) asm volatile("trap;");
    const int col = c.h * 128 + c.a * 64;
    uint32_t tl = clock_lo();
    TR(-2, 3);
    if (c.w == 0) {
      if (START) delay_until(tl + START);
      if (HOLD == 2) mbar_wait(BAR(B_PROBE), 0);
      if (HOLD == 3) mbar_wait(BAR(B_SEL), 0);
      if (HOLD == 1) mbar_wait(BAR(B_PROBE), 0);
      TR(-2, 4);
      tl = clock_lo();
      mbar_expect_e(BAR(B_PFULL), 2 * NP * 2048);
      mbar_expect_e(BAR(B_WFULL), (48 - NP) * 2048);
      mbar_expect_e(BAR(B_WFULL + 1), (48 - NP) * 2048);
    }
    auto dst_x = [&](int e, int w) {
      const uint32_t g2 = 2 * c.a + (w >> 1), u = w & 1;
      return M_KVQ + c.h * 24576 + (e == 0 ? 8192 + (2 * u + c.b) * 2048 + g2 * 512 : e == 1 ? g2 * 2048 + u * 1024 + c.b * 128 : 16384 + c.b * 4096 + g2 * 512 + u * 256);
    };
    if (c.w == 0) {
      tl += PACE0;
#pragma unroll wunr
      for (int i = 0; i < 24; i++) {
        const int m = i < 4 || i >= 16, k = i < 4 ? i : m ? i - 12 : i - 4;
        const int row = c.b * 512 + m * 256;
        const uint32_t st = c.sb + m * ST_WG, bar = BAR(k < 3 ? B_PFULL : B_WFULL + m);
        if (PACE) delay_until(tl += PACE);
        if (i == 14) { mbar_wait(BAR(B_FREE), 0); if (c.lane == 0) TL2(2); __syncwarp(); }
        if (k < 11) TMA_W(k < 3 ? c.sb + SM_POOL + m * NP * 2048 + k * 8192 : k == 3 ? c.sb + SM_HV + (m * NHV + 1) * 2048 : st + (k - 4) * 8192,
                          k == 3 || k > 8 ? &tv : (k >> 2 & 1) == m ? &tk : &tq, col, row + (k < 8 ? k & 3 : (k - 9) & 3) * 64, bar);
        else {
#pragma unroll 1
          for (int j = 8; j < 12; j++) TMA_W(j < NV ? st + (32 - NP + j) * 2048 : c.sb + SM_HV + m * NHV * 2048, &tv16, col, row + j * 16, bar);
        }
      }
      TR(-2, 7);
    } else if (c.w == 2) {
      const unsigned short* mp = (const unsigned short*)mem0 + (2 * (c.lane & 3)) * D_ + 8 * c.r + (c.lane >> 2);
      uint32_t mv = (uint32_t)mp[0] | (uint32_t)mp[D_] << 16;
      if (mv == SENT) mv = 0x7FFF7FFFu;
      mbar_wait(BAR(B_PROBE), 0);
      char* dst = c.mail + (uint32_t)(M_E3 + (c.r >> 5) * 8192 + (c.r & 31) * 128 + c.lane * 4);
      st_pub(dst, mv); st_pub(dst + 4096, mv);
    } else if (c.w == 3) {
      mbar_wait(BAR(B_FREE), 0);
      mbar_wait(BAR(B_PFULL), 0);
      mbar_expect_e(BAR(B_PFULL), 65536);
      for (int i = 0; i < 2; i++) tma4d_e(c.sb + SM_XT + i * 16384, &tx, c.b * 8, 4 + 2 * (c.b ^ i), BAR(B_PFULL));
    }
    {
      mbar_wait(BAR(B_SEL), 0);
      const int i = tid_now() & 127, sl = i & 3, e = (i >> 2) & 3;
      uint32_t ox = dst_x(e, i >> 5) + sl * M_REG;
      uint32_t oh = e & 1 ? (sl ^ (e & 2)) * M_REG + M_E3 + (c.r >> 5) * 8192 + (c.w & 1) * 4096 + (c.r & 31) * 128
                          : near_page(c, c.r, e ? sl * M_REG + M_E3 + (c.b * 2 + (c.w >> 1)) * 8192 : box(~sl & 1, c.r)) + (e ? (c.w & 1) * 2048 : c.w * 1024), of;
      {
        const int e = i & 7, w = (i >> 3) & 3, m = (i >> 5) & 1, sl = i >> 6;
        const int cta = e < 2 ? c.r & ~1 : e == 2 ? c.r | 1 : e == 3 ? c.h * 4 + 2 * m + 1 : c.j * 32 + m * 8 + 2 * w + (e & 2) * 8 + (e & 1);
        const uint32_t off = e < 2 ? c.b * 2048 + m * 1024 + (w >> 1) * 512 + e * 160 : e == 2 ? c.b * 2048 + m * 1024 + w * 256 : e == 3 ? w * 256 : c.h * 128;
        of = (e < 4 ? e1_box(c, sl, cta) : near_page(c, cta, box(sl, cta))) + off;
      }
      char *px = c.mail + ox, *ph = c.mail + oh, *pf = c.mail + of;
      uint32_t at = sl * 128 + (i >> 5) * 32 + e * 8, af = i * 8;
      pin(px); pin(ph); pin(pf); pin(at); pin(af);
      asm volatile("barrier.cluster.wait;" ::: "memory");
      TR(-2, 0);
      mbar_wait(BAR(B_WREAD), 0);
      TR(-2, 1);
      mbar_arrive_both(BAR(B_LFREE), c.b ^ 1);
      sts64(at + (c.sb + SM_TAB + 1536), (uint32_t)(uintptr_t)px, (uint32_t)((uintptr_t)px >> 32));
      sts64(at + (c.sb + SM_TAB + 1024), (uint32_t)(uintptr_t)ph, (uint32_t)((uintptr_t)ph >> 32));
      sts64(af + (c.sb + SM_TAB), (uint32_t)(uintptr_t)pf, (uint32_t)((uintptr_t)pf >> 32));
      TR(-2, 2);
      if (tid_now() == 384) TL2(25);
      __syncwarp();
      bar_sync(14, 160);
    }
    pad<PAD3>();
    for (int s = -1; s < NSEG; s++) {
      if (E30 ? s != 0 : s >= 0) {
        const uint32_t tab = c.sb + SM_TAB + 1024 + (max(s, 0) & 3) * 128 + c.w * 32;
        uint32_t t0;
        if (s > 0) {
          const uint32_t ln = tid_now() & 31;
          const uint4 ta = lds128(tab);
          const char* src = mk_ptr(ta.x | ln * 4, ta.y);
          char* dst = mk_ptr(ta.z | ln * 4, ta.w);
          const uint32_t tg = (s - 1) >> 1, chk = (ln & 3) ? 0u : 1u, red = ln * (RED_L == 3 ? 4 : 8);
          touch(src, dep(c.sb, chk, c.sb)); touch(dst, dep(c.sb, red, c.sb));
          mbar_wait(BAR(B_E2TRIG), (s - 1) & 1);
          TR(s, 0);
          if (ANCH2) delay_fine(lds32(c.sb + SM_SUM + 64) + DLY_E2); else delay_cycles(DLY_E2);
          uint32_t n = 0;
          while (true) {
            uint32_t v[8];
#pragma unroll
            for (int i = 0; i < 8; i++) v[i] = ld_poll1(src + i * 128);
            if (E2_F) sched_fence(c.sb);
            const uint32_t bad = RED_T ? (stale2(v[0], v[1], tg) | stale2(v[2], v[3], tg) | stale2(v[4], v[5], tg)) | stale2(v[6], v[7], tg)
                                       : stale1(stale1(stale2(v[0], v[1], tg), v[2], tg), v[3], tg) | stale1(stale1(stale2(v[4], v[5], tg), v[6], tg), v[7], tg);
            const bool ok = all_clear(bad, chk);
#pragma unroll
            for (int l = 0; l < RED_L; l++)
#pragma unroll
              for (int i = 0; i < (4 >> l); i++) v[i] = add_bf16x2(v[2 * i], v[2 * i + 1]);
            if (RED_L == 3) sts32(red + (c.sb + SM_RED + c.w * 128), v[0]);
            else {
              float lo[8], hi[8];
#pragma unroll
              for (int i = 0; i < (8 >> RED_L); i++) { lo[i] = __uint_as_float(v[i] << 16); hi[i] = __uint_as_float(v[i] & 0xFFFF0000u); }
#pragma unroll
              for (int l = RED_L; l < 3; l++)
#pragma unroll
                for (int i = 0; i < (4 >> l); i++) { lo[i] = lo[2 * i] + lo[2 * i + 1]; hi[i] = hi[2 * i] + hi[2 * i + 1]; }
              sts64(red + (c.sb + SM_RED + c.w * 256), __float_as_uint(lo[0]), __float_as_uint(hi[0]));
            }
            if (ok) break;
            n++; CNT(0);
          }
          bar_sync(NB_HELP, 128);
          const uint32_t rd = red + (c.sb + SM_RED);
          if (!RED_P || c.w < 2) {
            if (RED_L == 3) st_pub_if(dst, sum4(lds32(rd), lds32(rd + 128), lds32(rd + 256), lds32(rd + 384)), c.w < 2);
            else {
              const uint2 p0 = lds64(rd), p1 = lds64(rd + 256), p2 = lds64(rd + 512), p3 = lds64(rd + 768);
              st_pub_if(dst, pack_bf16((__uint_as_float(p0.x) + __uint_as_float(p1.x)) + (__uint_as_float(p2.x) + __uint_as_float(p3.x)),
                                       (__uint_as_float(p0.y) + __uint_as_float(p1.y)) + (__uint_as_float(p2.y) + __uint_as_float(p3.y))), c.w < 2);
            }
          }
          t0 = clock_lo();
          mbar_arrive_warp(BAR(B_PUB));
          TRV(s, 15, n);
          mbar_wait(BAR(B_SPFREE), (s - 1) & 1);
        } else {
          if (tid_now() == 384) TL2(24);
          __syncwarp();
          if (!E30) mbar_wait(BAR(B_PROBE), 1);
          if (!WO_S) mbar_wait(BAR(B_WOFULL), 0);
          if (tid_now() == 384) TL2(19);
          __syncwarp();
          t0 = clock_lo() - DLY_E3;
        }
        TRV(s, 1, t0);
        {
          const uint32_t l16 = (tid_now() & 31) * 16, dst = vary(l16, s, c.sb) + (c.sb + SM_MEM + (c.w & 1) * 4096 + (c.w >> 1) * 2048);
          const uint4 tb = lds128(tab + 16);
          st_pub_if(mk_ptr(tb.z | l16 >> 2, tb.w), SENT, c.w >= 2);
          const char* src = mk_ptr(tb.x | l16, tb.y);
          touch(src, dep(c.sb, dst, c.sb));
          delay_fine(t0 + (DLY_E3 + (c.w & 1) * DLY_E3B));
          uint32_t n = 0;
          while (true) {
            uint4 v[4];
#pragma unroll
            for (int i = 0; i < 4; i++) v[i] = ld_poll(src + i * 512);
#pragma unroll
            for (int i = 0; i < 4; i++) sts128(dst + i * 512, v[i]);
            if (arrive_if_all(max(max(v[0].x, v[1].x), max(v[2].x, v[3].x)) != SENT, NB_MEM + (c.w & 1) * 2 + (c.w >> 1), 160)) break;
            n++; CNT(1);
          }
          TR(s, 2); TRV(s, 14, n);
        }
        if (s == 1) CLK(1); if (s == 8) CLK(2); if (s == 56) CLK(3);
        if (c.w == 2 && s == 15) TRSYNC(8);
        if (c.w == 2 && s == 21) TRSYNC(10);
      }
      const int g = s + 1;
      auto load_v = [&]() {
        if (V_TMA && c.w == V_W) {
          mbar_expect_e(BAR(B_VFULL), 8192);
          bulk_load_e(c.sb + SM_V, c.mail + (uint32_t)(M_KVQ + (min(g, XEND - 1) & (NSLOT - 1)) * M_REG + c.h * 24576 + 8192), 8192, BAR(B_VFULL));
        }
      };
      if (XEND < NSEG && g >= XEND && g < NSEG) { mbar_wait(BAR(B_SC), s & 1); load_v(); }
      if (g < XEND) {
        const uint32_t tx_ = c.sb + SM_TAB + 1536 + (g & 3) * 128 + c.w * 32, tag = (g >> 2) & 1;
        if (c.w == 0) mbar_expect_e(BAR(B_LAND), EXP_PEER * 12288);
        auto load_x = [&]() {
          if (c.w == 3 && g + 1 < XEND) {
            mbar_wait(BAR(B_XEMPTY), g & 1);
            mbar_expect_e(BAR(B_XFULL), 16384 * EXP_NXT);
            for (int i = 0; i < EXP_NXT; i++) tma4d_e(c.sb + SM_XT + i * 16384, &tx, c.b * 8, (g + 1) * 4 + 2 * (c.b ^ i), BAR(B_XFULL));
          }
        };
        if (X_AT == 0 && g > 0) load_x();
        TR(s, 6);
        if (E30 && g == 0) mbar_wait(BAR(B_PROBE), 1);
        mbar_wait(BAR(B_LAND), g & 1);
        TR(s, 7);
        if (DLY_F && g > 0) delay_cycles(DLY_F);
        auto total = [&](int w, int lane, uint32_t o0, uint32_t o1) {
          const uint32_t a = c.sb + SM_LAND + land_off(w, lane);
          if (EXP_FL == 1) return make_uint4(a, a, a, a);
          const uint4 t = add4(lds128(a + o0), lds128(a + o1 + 2048));
          const uint32_t a2 = dep(dep(a, t.x ^ t.y ^ t.z, c.sb), t.w, c.sb);
          return add4(t, add4(lds128(a2 + o0 + 4096), lds128(a2 + o1 + 6144)));
        };
        auto get = [&](int e) {
          const int ln = tid_now() & 31;
          return e == 0 ? total(c.w, ln, 16384, 16384)
               : e == 1 ? total((c.w & 2) + ((ln >> 1) & 1), (ln & 1) * 16 + (c.w & 1) * 8 + (ln >> 2), 8192, 0)
                        : total((c.w & 2) + ((ln >> 1) & 1), (ln & 1) * 16 + (ln >> 3) * 4 + (c.w & 1) * 2 + ((ln >> 2) & 1), 0, 8192);
        };
        auto put = [&](int e, uint4 v) {
          const int ln = tid_now() & 31;
          const uint2 d = lds64(tx_ + e * 8);
          if (e < 2) {
            v.x = tagged(v.x, tag);
            st_pub4(mk_ptr(d.x | (e ? (ln & 24) * 32 + (ln & 7) * 16 : ln * 16), d.y), v);
          } else {
            char* dst = mk_ptr(d.x | ((ln & 7) * 16 + (ln >> 3) * 4), d.y);
            const uint32_t bit = ln < 8;
            st_pub(dst, put_tag(v.x, bit, tag)); st_pub(dst + 128, put_tag(v.y, bit, tag));
            st_pub(dst + 2048, put_tag(v.z, bit, tag)); st_pub(dst + 2176, put_tag(v.w, bit, tag));
          }
        };
        auto after_sc = [&]() { if (g > 0) { mbar_wait(BAR(B_SC), s & 1); if (DLY_FK) delay_cycles(DLY_FK); if (X_AT == 1) load_x(); } };
        if (FIN_AT == 5) {
          put(0, get(0));
          if (DLY_F2 && g > 0) delay_cycles(DLY_F2); else sched_fence(c.sb);
          const uint4 k = get(1);
          sched_fence(c.sb);
          const uint4 q = get(2);
          if (g > 0) mbar_wait(BAR(B_VST), s & 1);
          put(1, k); put(2, q);
          TR(s, 5);
          mbar_arrive_both(BAR(B_LFREE), c.b ^ 1);
          after_sc();
          load_v();
          continue;
        }
        if (FIN_AT < 3) {
          if (EXP_FIN & 1) put(0, get(0));
          TR(s, 3);
          if (FIN_AT == 1) after_sc();
          if (V_TMA == 1) load_v();
          if (EXP_FIN & 2) put(1, get(1));
        } else {
          const uint4 v = get(0);
          sched_fence(c.sb);
          const uint4 k = get(1);
          if (g > 0) { mbar_wait(BAR(B_VST), s & 1); if (DLY_FS) delay_cycles(DLY_FS); }
          put(0, v); put(1, k);
        }
        TR(s, 4);
        if (FIN_AT == 4) {
          const uint4 q = get(2);
          after_sc();
          load_v();
          put(2, q);
        } else {
          if (FIN_AT >= 2) after_sc();
          if (V_TMA == 2) load_v();
          if (EXP_FIN & 4) put(2, get(2));
        }
        mbar_arrive_both(BAR(B_LFREE), c.b ^ 1);
        if (V_TMA == 3) load_v();
        TR(s, 5);
        if (!FIN_AT && X_AT && g > 0) { mbar_wait(BAR(B_SC), s & 1); if (DLY_FK) delay_cycles(DLY_FK); load_x(); }
      }
    }
    const int tile = tile_of(c), s0 = (tile >> 3) * 4, n0 = (tile & 7) * 128;
    if (c.w == 1) {
      mbar_wait(BAR(B_PVDONE), 0);
      count_e(g_ctl + C_EARLY);
      st_pub(c.mail + (uint32_t)((tid_now() & 6) * (M_REG / 2) + M_SEL + (tid_now() & 1) * 4096 + c.r * 4), 0);
      await_count(g_ctl + C_COLS, 4);
      mbar_expect_e(BAR(B_TW), 8192);
      bulk_load_e(c.sb + SM_TW, g_tw, 8192, BAR(B_TW));
    } else if (c.w == 2) {
      const uint32_t ln = tid_now() & 31, rel = mapa(BAR(B_GEMPTY) + (ln >> 2) * 8, ln & 1);
      mbar_wait(BAR(B_VST), 1); mbar_wait(BAR(PRE_AT), 1);
      arrive_remote_if(rel, ln < 12);
      mbar_wait(BAR(B_E2TRIG), 1);
      if (GATE) mbar_wait(BAR(B_DONE), 0);
      arrive_remote_if(rel, ln >= 12 && ln < 20);
    } else {
      auto ahead = [&](int k) {
        if (c.w) { if (PF_A && (k & 3) == (tile >> 1 & 3)) prefetch3d_e(&ta, k * 32, s0 + 2 * c.b); }
        else if (PF_B && (k & 7) == (tile >> 4)) prefetch2d_e<(ONCE & 512) != 0>(&tw, n0 + (tile & 8) * 8, k * 64);
      };
#pragma unroll 1
      for (int k = 0; k < PF_D; k++) ahead(k);
      if (c.w == 3) await_count(g_ctl + C_EARLY, 128);
      const int skew = tile < 120 ? 0 : SKEW;
      uint32_t o = SM_XT, st = 0, ph = 0;
#pragma unroll 1
      for (int kb = 0; kb < 64 + skew; kb++, o = next_stage(o)) {
        const bool solo = kb < skew || kb >= 64;
        const uint32_t bar = BAR(B_GFULL + st), k = kb & 63;
        if (c.w && kb == skew) {
          if (tile >= 120) await_count(g_ctl + C_LAST, 512);
          if (tid_now() == 480) TL(10);
          __syncwarp();
        }
        mbar_wait(BAR(B_GEMPTY + st), ph);
        if (c.w) {
          const int r = solo ? (kb >> 5) + c.b : c.b * 2;
          tma3d_mc_e(c.sb + o + r * 4096, solo ? &ta32 : &ta, k * 32, s0 + r, bar);
        } else {
          mbar_expect_e(bar, solo ? 24576 : 32768);
          tma2d_o<(ONCE & 2) != 0>(c.sb + o + 16384, &tw, n0, k * 64, bar);
          tma2d_o<(ONCE & 2) != 0>(c.sb + o + 24576, &tw, n0 + 64, k * 64, bar);
        }
        if (kb + PF_D < 64) ahead(kb + PF_D);
        if (++st == 5) { st = 0; ph ^= 1; }
      }
    }
    return;
  } else if (c.m == 2) {
    asm volatile("setmaxnreg.dec.sync.aligned.u32 %0;" :: "n"(512 - 2 * REG_F - REG_H));
    c.lane = lane_id();
    {
      uint32_t tl = clock_lo() + (PACE0 + WO_AT * PACE);
      TR(-2, 0);
      sched_fence(i0 ^ i1);
      TR(-2, 7);
      int far1 = 0;
#pragma unroll 1
      for (int rep = EARLY; rep <= NPROBE; rep++) {
        const int lag = race_init(own + (rep & 1) * 4096, own + (~rep & 1) * 4096, SENT);
        if (rep) far1 += ((rep ^ c.r >> 5) & 1 ? 1 : -1) * min(lag, 200);
      }
      sts32(c.sb + SM_SEL + 512 + c.w * 4, (8 + far1 / (16 * NPROBE)) << 4 * c.w);
      TR(-2, 1);
      if (tid_now() == 256) TL2(14);
      __syncwarp();
      mbar_arrive_warp(BAR(B_PROBE));
      if (c.w == 0) {
        mbar_wait(BAR(B_PROBE), 0);
        const uint4 bits = lds128(c.sb + SM_SEL + 512);
        const uint32_t res = bits.x | bits.y | bits.z | bits.w;
        st_pub_if(c.mail + (uint32_t)((c.lane & 6) * (M_REG / 2) + M_SEL + (c.lane & 1) * 4096 + c.r * 4), res | tile_key(), c.lane < 8);
        const int q = (res >> 4 * ((c.lane + c.r) & 3) & 15) - 8, best = __reduce_max_sync(~0u, abs(q) * 64 + (c.lane & 3) * 16 + ((c.lane + c.r) & 3) * 2 + (q <= 0));
        const char* src = c.mail + (uint32_t)((best & 6) * (M_REG / 2) + M_SEL + (best & 1) * 4096 + c.lane * 16);
        if (SEL_AT) delay_until(tl - (PACE0 + WO_AT * PACE - SEL_AT));
        uint4 v; uint32_t n = 0;
        TR(-2, 4);
        while (true) {
          delay_cycles(DLY_SEL);
          TR(-2, 6);
          v = ld_poll(src);
          if (__all_sync(~0u, v.x && v.y && v.z && v.w)) break;
          watchdog(n, POLL_LIMIT);
        }
        TR(-2, 5);
        int ta = 0, tb = 0, pa = 0, pb = 0;
        uint32_t flip = 0;
#pragma unroll 1
        for (int i = 0; i < 4; i++) {
          const int a = (v.x >> 4 * i & 15) + (v.y >> 4 * i & 15) - 16, b = (v.z >> 4 * i & 15) + (v.w >> 4 * i & 15) - 16;
          const bool f = __reduce_add_sync(~0u, a * ta + b * tb) < 0;
          ta += f ? -a : a; tb += f ? -b : b; flip |= (uint32_t)f << i;
        }
#pragma unroll 1
        for (uint32_t g = 0; g < 8; g++) {
          const bool a = (v.x >> 16) - g * 256 < 120, b = (v.z >> 16) - g * 256 < 120;
          const int n = __reduce_add_sync(~0u, (a ? ta : 0) + (b ? tb : 0)) > 0 ? PRIOR : -PRIOR;
          if (a) pa = n;
          if (b) pb = n;
        }
        const uint32_t ka = AWARE && ta + pa > 0 ? ~flip : flip, kb = AWARE && tb + pb > 0 ? ~flip : flip;
        sts128(c.sb + SM_SEL + c.lane * 16, make_uint4(ka, ka, kb, kb));
        mbar_arrive_warp(BAR(B_SEL));
        const uint32_t key = __shfl_sync(~0u, c.a ? v.z : v.x, c.h);
        const int u = __popc(__ballot_sync(~0u, v.x < key)) + __popc(__ballot_sync(~0u, v.z < key));
        sts32(c.sb + SM_SEL + 528, (u & 32) * 2 + (u & 7) * 8 + (u >> 2 & 6) + c.b);
        TR(-2, 2);
        if (c.lane == 0) TL2(13);
        __syncwarp();
        bar_sync(14, 160);
        if (ZDLY) delay_cycles(ZDLY);
#pragma unroll 4
        for (int k = c.lane >> 3; k < (ZINIT ? 128 : 0); k += 4) {
          const int e = k & 7;
          const uint2 d = lds64(c.sb + SM_TAB + (e == 3 ? k - 1 : k) * 8);
          st_pub4(mk_ptr((d.x & ~127u) + (e < 2 ? (k & 8) * 32 : e == 3 ? 128 : 0) + (c.lane & 7) * 16, d.y), make_uint4(0, 0, 0, 0));
        }
        __syncwarp();
        if (c.lane < 4) asm volatile("mbarrier.arrive.shared::cta.b64 _, [%0];" :: "r"(BAR(B_PROBE)) : "memory");
        __syncwarp();
        TR(-2, 8);
      }
      if (c.w == 2) {
        mbar_wait(BAR(B_P1), 0);
        if (P1_AT) { mbar_wait(BAR(B_WFULL), 0); mbar_wait(BAR(B_WFULL + 1), 0); }
        st_pub_if(g_ctl + C_COLS + (c.r & 15) * 32 + c.lane, 0, c.r < (C_END - C_COLS) / 32);
        count_e(g_ctl + C_P1);
        TR(-2, 3);
      }
      if (c.w == 1) for (int i = 0; i < WO_N; i++) { delay_until(tl += WO_P * PACE); prefetch2d_e(&to, c.j * 256 + (i ^ WO_X) * 64, c.h * 128); }
      if (c.w == 3) {
        mbar_wait(BAR(B_WREAD0), 0);
        for (int i = 0; i < 2; i++) tma4d_e(c.sb + SM_WO + i * 16384, &tx, c.b * 8, 2 * (c.b ^ i), BAR(B_PFULL));
        mbar_expect_e(BAR(B_WOFULL), 65536);
#pragma unroll 1
        for (int i = 3; i >= 0; i--) {
          if (i & 1) mbar_wait(BAR(i < 2 ? B_XEMPTY : B_WREAD), 0);
          TMA_O(c.sb + SM_WO + i * 16384, &to, c.j * 256 + i * 64, c.h * 128, BAR(B_WOFULL));
        }
      }
    }
    asm volatile("barrier.cluster.wait;" ::: "memory");
    const int g = c.w, src0 = c.h * 4 + (g >> 1) * 2;
    mbar_wait(BAR(B_SEL), 0);
    c.sel = __shfl_sync(~0u, (e1_box(c, 0, src0 + (c.lane >> 5)) & 4096) | (e1_box(c, 1, src0) & 4096) * 2, 0);
    mbar_wait(BAR(B_WREAD), 0);
    uint32_t l16 = c.sb + g * 512 + c.lane * 16;
    auto lane = [&](uint32_t v) { l16 = dep(l16, v, c.sb); return (int)((l16 & 511) >> 4); };
    pad<PAD2>();
    for (int s = 0; s < NSEG; s++) {
      l16 = vary(l16, s, c.sb);
      int ln = (l16 & 511) >> 4;
      uint4 kf[4], qx;
      {
        const int gs = min(s, XEND - 1);
        const char* pk = c.mail + (uint32_t)(M_KVQ + (gs & (NSLOT - 1)) * M_REG + c.h * 24576 + g * 2048 + ln * 16);
        const char* pq = pk + (16384 + c.j * 2048 - g * 1536);
        const uint32_t tg = (gs / NSLOT) & 1;
        touch(pk, c.sb); touch(pq, c.sb);
        TR(s, 0);
        mbar_wait(BAR(B_VFULL), s & 1);
        TR(s, 1);
        if (s > 0) mbar_wait(BAR(B_PUB), (s - 1) & 1);
        for (uint32_t n = 0; ; ) {
          uint4 k[4];
#pragma unroll
          for (int t = 0; t < 4; t++) k[t] = ld_poll(pk + t * 512);
          qx = ld_poll(pq);
#pragma unroll
          for (int t = 0; t < 2; t++) {
            auto cp = [&](uint32_t v) { return dep(v, 0, c.sb); };
            kf[t] = make_uint4(cp(k[2 * t].x), cp(k[2 * t].y), cp(k[2 * t + 1].x), cp(k[2 * t + 1].y));
            kf[2 + t] = make_uint4(cp(k[2 * t].z), cp(k[2 * t].w), cp(k[2 * t + 1].z), cp(k[2 * t + 1].w));
          }
          if (all_clear(stale1(stale2(k[0].x, k[1].x, tg) | stale2(k[2].x, k[3].x, tg), qx.x, tg), EXP_CHK)) break;
          watchdog(n, POLL_LIMIT); CNT(4);
        }
        TR(s, 2);
      }
      if (X_AT >= 2 && g == 0 && s + 2 < XEND) {
        mbar_wait(BAR(B_XEMPTY), ~s & 1);
        mbar_expect_e(BAR(B_XFULL), 16384 * EXP_NXT);
        for (int i = 0; i < EXP_NXT; i++) tma4d_e(c.sb + SM_XT + i * 16384, &tx, c.b * 8, (s + 2) * 4 + 2 * (c.b ^ i), BAR(B_XFULL));
      }
      ln = lane(kf[0].y);
      const char* pa = c.mail + (uint32_t)(box(s & 1, src0) + 8192 + (c.sel >> (s & 1) & 4096) + (g & 1) * 512 + (EXP_LIN ? ln * 16 : read_off(ln)));
      const uint32_t spw = c.sb + SM_SP + g * 1280 + (ln & 3) * 64 + ((((ln >> 3) ^ ln) & 2) << 4) + (ln & 4) * 4 + (ln & 8),
                     spr = c.sb + SM_SP + (ln & 4) * 80 + (ln >> 3) * 64 + (((ln & 3) ^ ((ln >> 3) & 2)) << 4), l8 = ln * 8;
      const uint32_t tg = s >> 1;
      float sx[2][4];
      uint32_t sm;
      uint4 km;
      touch(pa, c.sb);
      mbar_wait(BAR(B_E1TRIG), s & 1);
      const uint32_t t0 = clock_lo();
      TRV(s, 3, t0);
      scores_x<false>(sx, kf, qx, 0);
      store_scores(sx, spw + 640);
      delay_fine(t0 + DLY_E1);
      uint32_t nr = 0;
      while (true) {
        const uint4 q0 = ld_poll(pa), q1 = ld_poll(pa + 2048), k0 = ld_poll(pa + 1024), k1 = ld_poll(pa + 3072);
        uint4 qm = add4(q0, q1);
        const uint32_t bq = stale2(q0.x, q1.x, tg);
        qm.x = dep(qm.x, bq, c.sb);
        scores_x<SC_F>(sx, kf, qm, c.sb);
        const uint32_t bk = stale2(k0.x, k1.x, tg);
        km = add4(k0, k1);
        km.x = dep(km.x, bk, c.sb);
        const bool ok = all_clear(bq | bk, 1);
        sm = scores_m(qm, km);
        store_scores(sx, spw);
        if (ok) break;
        nr++; CNT(2);
      }
      sts32(l8 + (c.sb + SM_SPM + (g >> 1) * 256 + (g & 1) * 4), sm);
      bar_sync(NB_ATT, 128);
      TR(s, 5); TRV(s, 13, nr);
      float o[2][4];
      uint32_t sp[5];
      uint4 vf[4];
      load_scores(sp, spr, l8 + (c.sb + SM_SPM));
      const uint32_t m5 = max5(sp);
      uint32_t m1;
      float off = row_off(m5, m1), f[10];
      l16 = dep(l16, VF_AT ? m1 : m5, c.sb);
#pragma unroll
      for (int t = 0; t < 4; t++) vf[(t >> 1) + 2 * (t & 1)] = lds128(l16 + SM_V + ((t >> 1) + 2 * (t & 1)) * 2048);
      qx.x = dep(qx.x, sp[0], c.sb);
      sts32(l8 + (c.sb + SM_SPM + 512 + (g >> 1) * 256 + (g & 1) * 4), scores_m(qx, km));
      mbar_arrive_warp(BAR(B_SC));
      unpack(f, sp);
      if (UP_F) sched_fence(c.sb);
      uint4 vm;
      if (VM_AT < 2) {
        bar_sync(NB_VM, 384);
        sp[1] = exp_pair(f, 1, off);
        const uint32_t av = dep(l8, VM_AT ? sp[1] : __float_as_uint(off), c.sb) + (c.sb + g * 512 + SM_VM);
        const uint2 vm0 = lds64(av), vm1 = lds64(av + 256);
        vm = make_uint4(vm0.x, vm0.y, vm1.x, vm1.y);
#pragma unroll
        for (int i = 2; i < 6; i++) sp[i % 5] = exp_pair(f, i % 5, off);
      } else {
#pragma unroll
        for (int i = 1; i < 6; i++) sp[i % 5] = exp_pair(f, i % 5, off);
        bar_sync(VM_AT == 2 ? dep(dep(0, sp[1] ^ sp[2], c.sb) + NB_VM, sp[0], c.sb) : dep(dep(0, sp[0] ^ sp[1] ^ sp[2], c.sb) + NB_VM, sp[3], c.sb), 384);
        const uint32_t av = l8 + (c.sb + g * 512 + SM_VM);
        const uint2 vm0 = lds64(av), vm1 = lds64(av + 256);
        vm = make_uint4(vm0.x, vm0.y, vm1.x, vm1.y);
      }
      float sum;
      auto rows_m = [&]() {
        const uint32_t tv = min(s, XEND - 1) / NSLOT;
        sum = pv(o, sp, vf, vm);
        stsm4<false>(l16 + SM_OM, pack_bf16(o[0][0], o[0][1]), pack_bf16(o[0][2], o[0][3]), pack_bf16(o[1][0], o[1][1]), pack_bf16(o[1][2], o[1][3]));
        sts32(c.sb + SM_SUM + ((l16 >> 4) & 28), __float_as_uint(sum));
        return arrive_if_clear(stale2(vf[0].x, vf[1].x, tv) | stale2(vf[2].x, vf[3].x, tv), EXP_CHK, NB_OM, 384);
      };
      if (!rows_m()) {
        const char* pv_ = c.mail + (uint32_t)(M_KVQ + (min(s, XEND - 1) & (NSLOT - 1)) * M_REG + c.h * 24576 + 8192 + (l16 - c.sb));
        uint32_t n = 0;
        do {
#pragma unroll
          for (int t = 0; t < 4; t++) vf[t] = ld_poll(pv_ + t * 2048);
          watchdog(n, POLL_LIMIT); CNT(5);
        } while (!rows_m());
      }
      const uint32_t tom = clock_lo();
      TRV(s, 8, tom);
      sched_fence(c.sb);
      ln = lane(tom);
      const int n = ln >> 2, jj = ln & 3, tq_ = 8 * c.j + (n & 4) + 2 * (n & 1) + ((n >> 1) & 1), lim = 16 * (tq_ - 2 * jj + 1);
      if (DLY_X) delay_until(tom + DLY_X);
      load_scores(sp, spr + 640, c.sb + SM_SPM + 512 + ln * 8);
#pragma unroll
      for (int w = 0; w < 4; w++) {
        uint32_t m; asm("shl.b32 %0, 0xffffffff, %1;" : "=r"(m) : "r"(max(lim - 128 * w, 0)));
        sp[1 + w] = (sp[1 + w] & ~m) | (0xD029D029u & m);
      }
      mbar_arrive_warp(dep(dep(0, sp[0], c.sb), sp[1], c.sb) + BAR(B_SPFREE));
      off = row_off(max5(sp), m1);
      unpack(f, sp);
#pragma unroll
      for (int i = 1; i < 6; i++) sp[i % 5] = exp_pair(f, i % 5, off);
      sum = pv(o, sp, vf, vm);
      TR(s, 7);
      sum = rcp(sum);
      const float i0 = __shfl_sync(~0u, sum, 8 * jj), i1 = __shfl_sync(~0u, sum, 8 * jj + 4);
      const uint32_t oxs = c.sb + SM_OX + g * 512;
      stsm4<true>(oxs + (ln & 7) * 64 + (((ln >> 3) ^ ((ln >> 1) & 3)) << 4),
                  pack_bf16(o[0][0] * i0, o[0][1] * i1), pack_bf16(o[0][2] * i0, o[0][3] * i1), pack_bf16(o[1][0] * i0, o[1][1] * i1), pack_bf16(o[1][2] * i0, o[1][3] * i1));
      __syncwarp();
      *(uint4*)(g_ox + ox_at(s, tq_, c.h * 4 + g, jj)) = lds128(oxs + n * 64 + ((jj ^ (n >> 1)) << 4));
      mbar_arrive_warp(BAR(B_PVDONE));
      TR(s, 9);
    }
    if (LASTM) {
      const int ln = tid_now() & 31, n = ln >> 2, jj = ln & 3, tq_ = 8 * c.j + (n & 4) + 2 * (n & 1) + ((n >> 1) & 1);
      store_count(g_ox + ox_at(NSEG - 1, tq_, c.h * 4 + g, jj), lds128(c.sb + SM_OX + g * 512 + n * 64 + ((jj ^ (n >> 1)) << 4)), (char*)(g_ctl + C_LAST) + (LASTM == 2 ? c.r * 4 + g : 0));
    } else count_e(g_ctl + C_LAST);
    mbar_arrive_warp(BAR(B_DONE));
    if (tid_now() == 256) TL(8);
    __syncwarp();
    mbar_wait(BAR(B_E2TRIG), 1); mbar_wait(BAR(B_DONE), 0); mbar_wait(BAR(B_TW), 0);
    asm volatile("setmaxnreg.inc.sync.aligned.u32 128;");
  } else {
    {
      const int w = c.m * 4 + c.w;
      mbar_expect_e(BAR(B_ROWS), 4096 + 256);
      for (int i = 0; i < 2; i++) bulk_load_e(c.sb + SM_FFT + (1024 + w * ROW_BUF) * 8 + i * 2048, x + (size_t)(z_row(c.r * 8 + w) + i * 1024) * D_, 2048, BAR(B_ROWS));
      bulk_load_e(c.sb + SM_GW + w * 256, gw + w * 128, 256, BAR(B_ROWS));
    }
    asm volatile("setmaxnreg.inc.sync.aligned.u32 %0;" :: "n"(REG_F));
    c.lane = lane_id();
    uint32_t wa[16][4], wb[16][4], wv[16][4];
    TR(-2, 4);
    fft_rows_fwd((float2*)(smraw + SM_FFT), (const __nv_bfloat16*)(smraw + SM_GW), c.r, threadIdx.x, BAR(B_ROWS), BAR(B_FREE), [&](int e) { TR(-2, e); }, [&]() {
      mbar_spin(BAR(B_PFULL), 0);
#pragma unroll
      for (int k = 0; k < NP; k++) ldsm4t(wa[k], c.sb + SM_POOL + c.m * NP * 2048 + frag_off(c.w, c.lane) + k * 2048);
      bar_sync(NB_XCH, 256);
#pragma unroll
      for (int k = 0; k < NP; k++) sts128(c.sb + SM_POOL + c.m * 2048 + c.w * 512 + c.lane * 16 + k * 4096, make_uint4(wa[k][0], wa[k][1], wa[k][2], wa[k][3]));
    });
    mbar_arrive_warp(BAR(B_P1));
    TR(-2, 0);
    if (tid_now() == 0) TL2(1);
    __syncwarp();
    mbar_spin(BAR(B_WFULL + c.m), 0);
    TR(-2, 1);
    if ((tid_now() & 127) == 0) TL2(16);
    __syncwarp();
    {
      const uint32_t st = c.sb + c.m * ST_WG + frag_off(c.w, c.lane);
#pragma unroll
      for (int k = 0; k < 16; k++) ldsm4t(wb[k], st + k * 2048);
#pragma unroll
      for (int k = NP; k < 16; k++) ldsm4t(wa[k], st + (16 + k - NP) * 2048);
#pragma unroll
      for (int k = 0; k < NV; k++) ldsm4t(wv[k], st + (32 - NP + k) * 2048);
      mbar_arrive_warp(BAR(B_WREAD));
      if (c.m == 0) mbar_arrive_warp(BAR(B_WREAD0));
#pragma unroll
      for (int k = 0; k < (LP_IN == 2 ? 0 : NP); k++) lds_frag(wa[k], c.sb + SM_POOL + c.m * 2048 + c.w * 512 + c.lane * 16 + k * 4096);
      TR(-2, 2);
    }
    TR(-2, 3);
    if (tid_now() == 0) TL2(12);
    __syncwarp();
    asm volatile("barrier.cluster.wait;" ::: "memory");
    uint32_t t16 = c.m * 2048 + c.w * 512 + c.lane * 16;
    uint32_t pk = (c.m * NHV * 2048 + frag_off(c.w, c.lane)) | (tile_off(2 * (c.w & 1), c.lane) << 16) | ((c.lane & 12) ? 0u : 0x80000000u);
    const uint32_t dx1 = desc_lo(c.sb + SM_XT + c.m * 4096), dh = desc_lo(c.sb + SM_HV + c.m * NHV * 2048);
    mbar_spin(BAR(B_PFULL), 1);
    pad<PAD0>();
    for (int s = -2; ; s++) {
      t16 = vary(t16, s, c.sb); pk = vary(pk, s, c.sb);
      const uint32_t dx = dx1 - (s == -2 ? (SM_XT - SM_WO) / 16 : 0);
      auto ldp = [&](int k0, int k1, int d, int back = 0) {
#pragma unroll
        for (int k = k0; k < k1; k++) lds_frag(wa[k], (k < k0 + d - back ? t16 : dep(t16, wa[k < d ? 0 : k - d][0], c.sb)) + (c.sb + SM_POOL + k * 4096));
      };
      if (s >= 0) {
        uint32_t af[16][4], bf[4][4], wo;
        const uint32_t tab = ((t16 >> 3) & 0x1C0) + (c.sb + SM_TAB + (s & 1) * 512);
        const char* pa;
        mem_proj(wa, wb, wv, af, wo, pa, tab, t16, pk, c, s);
        const uint32_t t0 = clock_lo();
        t16 = dep(t16, t0, c.sb);
        auto ldwo = [&](int f) { ldsm4t(af[f], (f < WO_D ? wo : dep(wo, af[f < WO_D ? 0 : f - WO_D][0], c.sb)) + (c.sb + SM_WO + (f & 1) * 32768 + (f >> 1) * 2048)); };
        {
          const uint32_t tg = s >> 1, vm = t16 >> 1, chk = (~t16 >> 4) & 1;
          if (WO_S && s == 0) {
            mbar_spin(BAR(B_WOFULL), 0);
#pragma unroll
            for (int f = 0; f < WO_0; f++) ldwo(f);
          }
#pragma unroll
          for (int f = WO_0; f < WO_1; f++) ldwo(f);
          delay_fine(t0 + DLY_V);
          uint2 v0 = ld_poll2(pa), v1 = ld_poll2(pa + 1024), v2 = ld_poll2(pa + 2048), v3 = ld_poll2(pa + 3072);
          TR(s, 3);
#pragma unroll
          for (int f = WO_1; f < 16 - WO_L; f++) ldwo(f);
          TR(s, 4);
          uint32_t n = 0;
          while (true) {
            sts64(vm + (c.sb + SM_VM), sum4(v0.x, v1.x, v2.x, v3.x), sum4(v0.y, v1.y, v2.y, v3.y));
            if (arrive_if_clear(stale1(stale1(stale2(v0.x, v1.x, tg), v2.x, tg), v3.x, tg), chk, NB_VM, 384)) break;
            v0 = ld_poll2(pa); v1 = ld_poll2(pa + 1024); v2 = ld_poll2(pa + 2048); v3 = ld_poll2(pa + 3072);
            n++; CNT(3);
          }
          TR(s, 12); TRV(s, 15, n);
        }
        const uint32_t ob = dep(dep(t16 & 511, af[14 - WO_L][0], c.sb), af[15 - WO_L][0], c.sb);
        uint32_t l4 = ob >> 2;
        const uint32_t bit = (t16 & 48) ? 0u : 1u;
        if (LF_AT) mbar_spin2_if(BAR(B_XFULL), BAR(B_LFREE), s & 1, s + 2 < XEND); else mbar_spin_if(BAR(B_XFULL), s & 1, s + 2 < XEND);
        bar_sync(NB_OM, 384);
        TR(s, 5);
#pragma unroll
        for (int i = 0; i < 4; i++) ldsm4t(bf[i], ob + (c.sb + SM_OM + i * 512));
        uint2 sum = lds64(((t16 >> 1) & 24) + (c.sb + SM_SUM));
        if (OM_F) sched_fence(c.sb);
        float d[WO_C][4] = {};
        uint4 d0, d1;
#pragma unroll
        for (int f = 0; f < 16; f++) {
          mma_a(d[f % WO_C], af[f], bf[f >> 2][f & 2], bf[f >> 2][(f & 2) + 1]);
          if (f >= WO_C && f < WO_C + WO_L) {
            const int l = 16 - WO_L + f - WO_C;
            ldsm4t(af[l], (WO_LD ? dep(wo, __float_as_uint(d[(f + 1) % WO_C][0]), c.sb) : wo) + (c.sb + SM_WO + (l & 1) * 32768 + (l >> 1) * 2048));
          }
          if (f == WO_T) {
            const uint32_t tb2 = dep((t16 >> 3) & 0x1C0, __float_as_uint(d[f % WO_C][0]), c.sb) + (c.sb + SM_TAB + (s & 1) * 512);
            d0 = lds128(tb2 + 32); d1 = lds128(tb2 + 48);
          }
          if (f >= PL_WA && f < PL_WA + PL_W) lds_frag(wa[f - PL_WA], (PL_WD ? dep(t16, __float_as_uint(d[(f + PL_WD) % WO_C][0]), c.sb) : t16) + (c.sb + SM_POOL + (f - PL_WA) * 4096));
          if (PL_W && PL_WF && f == PL_WA + PL_W - 1) sched_fence(c.sb);
          if (f == 4) { sum.x = dep(sum.x, __float_as_uint(d[0][0]), c.sb); sum.y = dep(sum.y, __float_as_uint(d[0][0]), c.sb); }
        }
        if (PL_W && !PL_WF) {
          uint32_t all = 0;
#pragma unroll
          for (int k = 0; k < PL_W; k++) all ^= wa[k][0];
          l4 = dep(l4, all, c.sb);
        }
        char* dst[4] = {mk_ptr(d0.x | l4, d0.y), mk_ptr(d0.z | l4, d0.w), mk_ptr(d1.x | l4, d1.y), mk_ptr(d1.z | l4, d1.w)};
        const float i0 = rcp(__uint_as_float(sum.x)), i1 = rcp(__uint_as_float(sum.y));
#pragma unroll
        for (int i = 0; i < 4; i++) {
          const int t = i >> 1, e = 2 * (i & 1);
          const float y0 = WO_C == 2 ? d[t][e] : d[t][e] + d[(t + 2) % WO_C][e], y1 = WO_C == 2 ? d[t][e + 1] : d[t][e + 1] + d[(t + 2) % WO_C][e + 1];
          st_pub(dst[i], put_tag(pack_bf16(y0 * i0, y1 * i1), bit, s >> 1));
        }
        if (ANCH2) sts32(c.sb + SM_SUM + 64, clock_lo());
        mbar_arrive_warp(BAR(B_E2TRIG));
        TR(s, 6);
        sched_fence(c.sb);
        if (W_E2 == 2) mbar_spin(BAR(B_E2TRIG), s & 1);
        if (!LP_IN) { if (s == NSEG - 1) break; ldp(PL_W, PL_0, PL_D); }
      }
      if (__builtin_expect(s + 2 < XEND, 1)) {
        const uint32_t tg0 = DLY_P ? clock_lo() + DLY_P : 0;
        if (LP_IN) ldp(0, PL_0, PL_D);
        float xa[16];
        uint32_t q[4];
        if (W_E2 == 1 && s >= 0) mbar_spin(BAR(B_E2TRIG), s & 1);
        TR(s, 7);
        constexpr int S1 = ORDER ? 0 : 2, S2 = ORDER == 0 ? 0 : ORDER == 1 ? 2 : 1, S3 = ORDER == 2 ? 2 : 1;
        if (ORDER) issue_qk<0, 16>(xa, wb, vary(dx, s, c.sb)); else issue_v(xa, wv, vary(dx, s, c.sb), vary(dh, s, c.sb));
        if (DLY_P) delay_until(tg0); else if (IS_F) sched_fence(c.sb);
        ldp(PL_0, PL_1, PL_D1);
        const uint32_t land = (t16 ^ ((t16 >> 3) & 0x60)) + vary(c.sb + SM_LAND + c.b * 4096, s, c.sb);
        TR(s, 14);
        if (LF_AT == 1) mbar_spin_if(BAR(B_LFREE), s & 1, s < 0); else if (!LF_AT) mbar_spin(BAR(B_LFREE), s & 1);
        TR(s, 15);
        WG_WAIT(0);
        TR(s, 8);
        park_own<S1 == 2>(q, xa, land, S1, c.sb);
        if (W_PUB == 4 && s >= 0) mbar_spin(BAR(B_PUB), s & 1);
        if (ORDER == 1) issue_v(xa, wv, vary(dx, s, c.sb + 32), vary(dh, s, c.sb)); else issue_qk<0, 16>(xa, ORDER ? wa : wb, vary(dx, s, c.sb + 32));
        if (IS_F) sched_fence(c.sb);
        ldp(PL_1, PL_2, PL_D1);
        if (W_PUB == 1) mbar_spin_if(BAR(B_PUB), s & 1, s >= 0);
        uint32_t tp = clock_lo(), q1[4] = {q[0], q[1], q[2], q[3]};
        if (PL_2B) ldp(PL_2, NP - PL_L, PL_D1);
        if (W_PUB != 3) park_peer(q, land, S1, c);
        if (!PL_2B) ldp(PL_2, NP - PL_L, PL_D1);
        TR(s, 13);
        WG_WAIT(0);
        TR(s, 9);
        park_own<S2 == 2>(q, xa, land, S2, c.sb);
        if (ORDER == 2) issue_v(xa, wv, vary(dx, s, c.sb + 64), vary(dh, s, c.sb));
        else {
          issue_qk<0, PL_L ? NP - PL_L : 16>(xa, wa, vary(dx, s, c.sb + 64));
          ldp(NP - PL_L, NP, PL_E);
          if (PL_L) issue_qk<NP - PL_L, 16>(xa, wa, vary(dx, s, c.sb + 64));
        }
        if ((W_PUB == 2 || W_PUB == 3) && s >= 0) { mbar_spin(BAR(B_PUB), s & 1); tp = clock_lo(); }
        if (W_PUB == 3) park_peer(q1, land, S1, c);
        if (DLY_S && s >= 0) delay_until(tp + DLY_S);
        park_peer(q, land, S2, c);
        WG_WAIT(0);
        TR(s, 10);
        mbar_arrive_warp(BAR(B_XEMPTY));
        park_own<S3 == 2>(q, xa, land, S3, c.sb);
        park_peer(q, land, S3, c);
        TR(s, 11);
      } else { if (LP_IN && s == NSEG - 1) break; ldp(LP_IN ? 0 : PL_0, NP, LP_IN ? 2 : 1); }
    }
    asm volatile("setmaxnreg.dec.sync.aligned.u32 128;");
    const int tid = tid_now(), lane = tid & 31, tile = tile_of(c), m0 = (tile >> 3) * 128, n0 = (tile & 7) * 128;
    float acc[64];
#pragma unroll
    for (int i = 0; i < 64; i++) acc[i] = 0.f;
    const uint32_t rel = mapa(BAR(B_GEMPTY), lane & 1), la = desc_lo(c.sb + c.m * 8192), lb = ((c.sb + 16384) & 0x3FFFF) >> 4 | (8192 >> 4) << 16;
    bool relon = false;
    const int skew = tile < 120 ? 0 : SKEW, kend = 64 + skew - c.m * skew;
    const float g0 = __ldcg(g_gate + m0 + (tid >> 5) * 16 + (lane >> 2)), g1 = __ldcg(g_gate + m0 + (tid >> 5) * 16 + (lane >> 2) + 8);
    uint32_t o = SM_XT, st = 0, ph = 0, prev = 0;
    if (tid == 0) TL(9);
    __syncwarp();
    GT(0);
#pragma unroll 1
    for (int kb = -c.m * skew; kb < kend; kb++, o = next_stage(o)) {
      mbar_lim(BAR(B_GFULL + st), ph);
      if ((uint32_t)kb < 64) {
        WG_FENCE();
#pragma unroll
        for (int k = 0; k < 4; k++) wgmma_ss_n128_tb(acc, desc128(la + (o >> 4) + k * 2), desc128(lb + (o >> 4) + k * 128));
        WG_COMMIT();
        WG_WAIT(1);
      } else WG_WAIT(0);
      arrive_remote_if(rel + 8 * prev, relon && kb < kend - 4);
      relon = (tid & 127) < 2;
      prev = st;
      if (++st == 5) { st = 0; ph ^= 1; }
    }
    WG_WAIT(0);
    GT(17);
    if (tid == 0) TL(4);
    __syncwarp();
    const uint32_t row = (tid >> 5) * 2048 + (lane & 15) * 128 + (((lane >> 4) ^ (lane & 7)) << 4);
    mbar_lim(BAR(B_BT), 0);
    uint32_t b[2][4][4];
    const uint32_t rb = (tid >> 5) * 2048 + (lane >> 2) * 128 + (((lane & 7) ^ (lane >> 2)) << 4);
#pragma unroll
    for (int i = 0; i < 8; i++) lds_frag(b[i & 1][i >> 1], (rb ^ (i & 2) * 32) + (c.sb + SM_BT + (i >> 2) * 16384 + (i & 1) * 1024));
#pragma unroll
    for (int hf = 0; hf < 2; hf++) {
#pragma unroll
      for (int t = 0; t < 4; t++) {
        uint32_t y[4];
#pragma unroll
        for (int i = 0; i < 4; i++) {
          const float* a = acc + 32 * hf + 8 * t + 2 * i, g = i & 1 ? g1 : g0;
          const uint32_t* q = b[i & 1][2 * (t & 1) + (i >> 1)] + hf;
          y[i] = pack_bf16(fmaf(g, a[0], __uint_as_float(t & 2 ? q[0] & 0xFFFF0000u : q[0] << 16)), fmaf(g, a[1], __uint_as_float(t & 2 ? q[2] & 0xFFFF0000u : q[2] << 16)));
        }
        stsm4<false>((row ^ t * 32) + (c.sb + SM_BT + hf * 16384), y[0], y[1], y[2], y[3]);
      }
      FENCE_ASYNC_SMEM();
      __syncwarp();
      tma2d_out_e(&tout, n0 + hf * 64, m0 + (c.m * 4 + c.w) * 16, c.sb + SM_BT + hf * 16384 + (c.m * 4 + c.w) * 2048);
    }
    asm volatile("cp.async.bulk.commit_group; cp.async.bulk.wait_group" WAITRD " 0;" ::: "memory");
    GT(18);
    if (tid == 0) TL(11);
    return;
  }
  static_assert(!QSH || NCR >= 7, "rounds");
  const bool col = c.r >= 128;
  const int tile = col ? 0 : tile_of(c);
  const int q0 = col ? 256 - 16 * NCR + (c.r - 128) * 4 + c.m : tile < 120 ? tile : 256, dq = col ? 16 : QSH ? 120 + (tile >> 2) - tile : 120, qe = col ? 256 : 256 - 16 * NCR,
            qw = col || !QSH || c.w == (tile & 3) ? qe : 120;
  const uint32_t zs = c.sb + (col ? COL_Z + c.m * 32768 : SM_BT), zb = BAR(B_Z + c.m);
  auto load_z = [&](int q) { if (c.w == 0 && q < qe) { mbar_expect_e(zb, 32768); tma2d_o<(ONCE & 4) != 0>(zs, &tz, q * 64, 0, zb); } };
  asm volatile("fence.proxy.async.global;" ::: "memory");
  load_z(q0);
  uint32_t ph = 0;
#pragma unroll 1
  for (int q = q0; q < qe; q += dq, ph ^= 1) {
    mbar_lim(zb, ph);
    const int p = q * 4 + c.w;
    if (EXP_INV && q < qw) fft_rows_inv(zs, (float2*)(smraw + (col ? 8192 + c.m * INV_BUF * 32 : SM_MEM)) + c.w * INV_BUF, (const float2*)(smraw + (col ? 0 : SM_TW)), p, tid_now() & 31, g_b,
                              [&]() { bar_sync(5 + c.m, 128); load_z(q + dq); });
    else { bar_sync(5 + c.m, 128); load_z(q + dq); }
  }
  asm volatile("fence.acq_rel.gpu;" ::: "memory");
  __syncwarp();
  { const int q = q0 + (tid_now() & 31) * dq; if (q < qw) asm volatile("red.relaxed.gpu.global.add.u32 [%0], 1;" :: "l"(g_ctl + C_ROWS + (q >> 5) * 32) : "memory"); }
  if (tid_now() == 256) { if (col) TL(27); else TL(3); }
  __syncwarp();
  if (!col && c.w == 0) {
    await_count<AW_NS>(g_ctl + C_ROWS + ((tile >> 3) & 7) * 32, 128);
    mbar_expect_e(BAR(B_BT), 32768);
    for (int i = 0; i < 2; i++) tma2d_o<(ONCE & 8) != 0>(c.sb + SM_BT + i * 16384, &tb, (tile & 7) * 128 + i * 64, (tile >> 3) * 128, BAR(B_BT));
    if (tid_now() == 256) TL(5);
  }
}

typedef CUresult (*EncodeFn)(CUtensorMap*, CUtensorMapDataType, cuuint32_t, void*, const cuuint64_t*, const cuuint64_t*,
                             const cuuint32_t*, const cuuint32_t*, CUtensorMapInterleave, CUtensorMapSwizzle,
                             CUtensorMapL2promotion, CUtensorMapFloatOOBfill);

void make_map(EncodeFn enc, CUtensorMap* tm, const void* p, int rank, const cuuint64_t* dims, const cuuint64_t* strides, const cuuint32_t* box, bool swz = true) {
  const cuuint32_t es[4] = {1, 1, 1, 1};
  enc(tm, CU_TENSOR_MAP_DATA_TYPE_BFLOAT16, rank, (void*)p, dims, strides, box, es, CU_TENSOR_MAP_INTERLEAVE_NONE,
      swz ? CU_TENSOR_MAP_SWIZZLE_128B : CU_TENSOR_MAP_SWIZZLE_NONE, swz ? CU_TENSOR_MAP_L2_PROMOTION_L2_128B : W_PROMO, CU_TENSOR_MAP_FLOAT_OOB_FILL_NONE);
}
void make_map2(EncodeFn enc, CUtensorMap* tm, const void* p, uint64_t cols, uint64_t rows, uint32_t boxrows) {
  const cuuint64_t dims[2] = {cols, rows}, strides[1] = {cols * 2};
  const cuuint32_t box[2] = {64, boxrows};
  make_map(enc, tm, p, 2, dims, strides, box);
}

}

extern "C" void kernel_launch(void* const* d_in, const int* in_sizes, int n_in, void* d_out, int out_size) {
  (void)in_sizes; (void)n_in; (void)out_size;
  const __nv_bfloat16* x = (const __nv_bfloat16*)d_in[0];
  const __nv_bfloat16* mem0 = (const __nv_bfloat16*)d_in[1];
  const __nv_bfloat16* gw = (const __nv_bfloat16*)d_in[10];

  EncodeFn enc = nullptr;
  cudaDriverEntryPointQueryResult qr;
  cudaGetDriverEntryPoint("cuTensorMapEncodeTiled", (void**)&enc, cudaEnableDefault, &qr);
  void *p_ox, *p_b, *p_z, *p_mail;
  cudaGetSymbolAddress(&p_ox, g_ox); cudaGetSymbolAddress(&p_b, g_b); cudaGetSymbolAddress(&p_z, g_z); cudaGetSymbolAddress(&p_mail, g_mail);
  CUtensorMap tq, tk, tv, tv16, to, tx, twr, twi, ta, tw, tb, tout, tz, tzs, ta32;
  make_map2(enc, &tq, d_in[2], 4096, 1024, 64);
  make_map2(enc, &tk, d_in[3], 4096, 1024, 64);
  make_map2(enc, &tv, d_in[4], 4096, 1024, 64);
  make_map2(enc, &tv16, d_in[4], 4096, 1024, 16);
  make_map2(enc, &to, d_in[5], 1024, 4096, 128);
  make_map2(enc, &tw, d_in[5], 1024, 4096, 64);
  {
    const cuuint64_t dims[3] = {64, 2048, 64}, strides[2] = {128, 262144};
    const cuuint32_t box[3] = {64, 32, 2}, box1[3] = {64, 32, 1};
    make_map(enc, &ta, p_ox, 3, dims, strides, box);
    make_map(enc, &ta32, p_ox, 3, dims, strides, box1);
  }
  make_map2(enc, &tb, p_b, 1024, 2048, 128);
  make_map2(enc, &tout, d_out, 1024, 2048, 16);
  make_map2(enc, &tz, p_z, 16384, 257, 256);
  {
    const cuuint64_t dims[4] = {64, 8, 16, 256}, strides[3] = {2048, 128, 16384};
    const cuuint32_t box[4] = {64, 8, 8, 2};
    make_map(enc, &tx, x, 4, dims, strides, box);
  }
  {
    const cuuint64_t dims[2] = {512, 257 * 32}, strides[1] = {1024};
    const cuuint32_t box[2] = {128, 16};
    make_map(enc, &tzs, p_z, 2, dims, strides, box, false);
  }
  {
    const cuuint64_t dims[2] = {8 * 513, 256}, strides[1] = {8 * 513 * 2};
    const cuuint32_t box[2] = {8, 256};
    make_map(enc, &twr, d_in[8], 2, dims, strides, box, false);
    make_map(enc, &twi, d_in[9], 2, dims, strides, box, false);
  }
  cudaFuncSetAttribute(chain_kernel, cudaFuncAttributeMaxDynamicSharedMemorySize, CHAIN_SMEM);

  cudaStream_t st = cudaStreamPerThread;
  char* mail = (char*)(((uintptr_t)p_mail + M_REG - 1) & ~(uintptr_t)(M_REG - 1));
  chain_kernel<<<132, 512, CHAIN_SMEM, st>>>(tq, tk, tv, tv16, to, tx, twr, twi, ta, tw, tb, tout, tz, tzs, ta32, mem0, mail, x, gw);
}
```

```cpp
#include <cuda_runtime.h>
#include <cuda_bf16.h>
#include <cuda.h>
#include <stdint.h>

#define DLY_E1 190
#define DLY_V 270
#define DLY_E2 320
#define DLY_E3 500
#define DLY_X 1
#define DLY_S 0
#define DLY_F 150
#define VM_AT 1
#define VM_F 0
#define OM_F 1
#define SXX_IN 0
#define C1_AT 1
#define NLAG 2
#define WO_D 2
#define WO_0 2
#define WO_1 10
#define PL_0 8
#define PL_1 10
#define PL_D 2
#define PL_L 0
#define DUAL 0
#define HV_D 5
#define DLY_FK 0
#define QX_SM 0
#define REG_F 216
#define REG_H 24
#define SC_F 1
#define E2_F 0
#define KVQ_AT 0
#define DLY_K 0
#define X_AT 2
#define W_PV 0
#define PL_2 10
#define BF_E 3
#define PL_E 2
#define ORDER 1
#define SSPOS 1
#define W_PUB 1
#define FIN_AT 5
#define AWARE 1
#define NPROBE 2
#define NP_ 12
#define USE_PDL 1
#define DLY_GRP 3000
#define P2_BULK 0
#define EXP_NV 4
#define EXP_NK 4
#define EXP_CHK 1
#define EXP_NXT 2
#define EXP_PEER 1
#define EXP_FIN 7
#define EXP_NWG 16
#define ANCH2 1
#define XF_AT 1
#define IS_F 0
#define PL_D1 2
#define W_E2 0
#define V_TMA 2
#define V_W 2
#define RED_L 3
#define RED_T 1
#define RED_P 1
#define DLY_E3B 0
#define HV_E 0
#define HV_R 4
#define HOLD 0
#define PACE 550
#define PACE0 0
#define EXP_ST 7
#define HOLD_AT NPROBE
#define WO_AT 38
#define WO_P 2
#define DLY_SEL 500
#define P1_AT 1
#define EXP_ZG 1
#define TMA_W tma2d_once
#define BULK_F bulk_once
#define TMA_O tma2d_once
#define PACE_Z 500
#define PACE_F 800
#define EXP_INV 1
#define VF_AT 0
#define UP_F 1
#define WO_L (12 - NP_)
#define WO_C 4
#define WO_T 3
#define WO_LD 0
#define EXP_LIN 0
#define PL_W 0
#define PL_WA 4
#define PL_WD 0
#define PL_WF 1
#define STAG 0
#define EXP_FL 0
#define DLY_FS 0
#define DLY_F2 0
#define LROT 0
#define PF_D 4
#define PF_A 1
#define PF_B 1
#define SIDE 1
#define ROLE 1
#define LOOSE 0x765498
#define E1OFF 1
#define EVOFF E1OFF
#define EPI 0
#define WAITRD ".read"
#define X01 1
#define E3I 1
#define START 1000
#define WUNR 1
#define WO_N 0
#define WO_H 0
#define PL_2B 1
#define DLY_P 430
#define LP_IN 1
#define LF_AT 1
#define FINE 0
#define LAG_F 0
#define E30 1
#define WO_S 1
#define POOL_AT 8
#define COL_DLY 0
#define WO_F 0
#define PAD0 0
#define PAD2 0
#define PAD3 0
#define WO_X 0
#define PRIOR 12
#define EARLY 1
#define SEL_AT 3000
#define CUNR 1
#define FUNR 0
#define ZINIT 1
#define ZDLY 0
#define NCR 7
#define GATE 0
#define LASTM 1
#define X_ONCE 1
#define ONCE 29
#define Z_PF 0
#define EXP_W 1
#define W_PROMO CU_TENSOR_MAP_L2_PROMOTION_L2_128B
#define Z_ST 1
#define W_FINE 0
#define X128 2
#define T128_ 1
#define W_AT 0
#define SKEW 8
#define AW_NS 0
#define QSH 2
#define NOWO 0
#define EARLY2 1
#define LEAD 3
#define BPRE 2
#define EP_F 1
#define PRE_AT B_SC

namespace {
constexpr int wunr = WUNR;

constexpr int S_ = 2048, D_ = 1024, NSEG = 64;
constexpr uint32_t SENT = 0xFFFFFFFFu;
constexpr int NSLOT = 4;

constexpr uint32_t M_REG = 1 << 21, M_E3 = 64 * 16384, M_KVQ = M_E3 + 4 * 8192, M_SEL = M_KVQ + 32 * 24576;
__device__ __align__(1024) unsigned char g_mail[5 * M_REG];
constexpr int C_P1 = 0, C_COLS = C_P1 + 32, C_EARLY = C_COLS + 32, C_LAST = C_EARLY + 32, C_ROWS = C_LAST + 128, C_END = C_ROWS + 8 * 32;
__device__ __align__(1024) uint32_t g_ctl[C_END];
#define CLK(i)
#define TL(i)
#define TL2(i)
#define FT(i, v)
#define GT(i)
#define CNT(i)
__device__ __align__(1024) __nv_bfloat16 g_ox[S_ * 4096];
__device__ __align__(1024) float2 g_z[257 * 4096];
__device__ __align__(1024) __nv_bfloat16 g_b[S_ * D_];
__device__ float g_gate[S_];
__device__ __align__(1024) float2 g_tw[1024];

#define TRV(s, ev, val)
#define TR(s, ev)
#define TRSYNC(ev)
__device__ __forceinline__ uint32_t smem_u32(const void* p) { return (uint32_t)__cvta_generic_to_shared(p); }
__device__ __forceinline__ void watchdog(uint32_t& n, uint32_t limit) {
  asm volatile("{ .reg .pred p; add.u32 %0, %0, 1; setp.gt.u32 p, %0, %1; @p trap; }" : "+r"(n) : "r"(limit));
}
__device__ __forceinline__ void mbar_init(uint32_t bar, uint32_t cnt) {
  asm volatile("mbarrier.init.shared::cta.b64 [%0], %1;" :: "r"(bar), "r"(cnt) : "memory");
}
__device__ __forceinline__ void mbar_arrive_warp(uint32_t bar) {
  __syncwarp();
  asm volatile("{ .reg .pred p; elect.sync _|p, 0xffffffff; @p mbarrier.arrive.shared::cta.b64 _, [%0]; }" :: "r"(bar) : "memory");
}
__device__ __forceinline__ uint32_t clock_lo() {
  uint32_t r; asm volatile("{ .reg .u64 c; .reg .u32 h; mov.u64 c, %%clock64; mov.b64 {%0, h}, c; }" : "=r"(r) :: "memory"); return r;
}
__device__ __forceinline__ void delay_until(uint32_t t) {
  asm volatile("{ .reg .pred p; .reg .u64 c; .reg .u32 l, h;\n"
               "DLY: mov.u64 c, %%clock64; mov.b64 {l, h}, c; sub.s32 l, l, %0; setp.lt.s32 p, l, 0; @p bra.uni DLY; }" :: "r"(t) : "memory");
}
__device__ __forceinline__ void delay_fine(uint32_t t) {
  delay_until(t);
}
__device__ __forceinline__ void delay_cycles(uint32_t n) { delay_until(clock_lo() + n); }
__device__ __forceinline__ void sched_fence(uint32_t z) {
  asm volatile("{ .reg .pred p; setp.eq.u32 p, %0, 0x7fff0000; @p pmevent 1; }" :: "r"(z) : "memory");
}
__device__ __forceinline__ void pdl_wait() { asm volatile("griddepcontrol.wait;" ::: "memory"); }
__device__ __forceinline__ void pdl_launch() { asm volatile("griddepcontrol.launch_dependents;" ::: "memory"); }
__device__ __forceinline__ float ex2(float x) { float r; asm("ex2.approx.ftz.f32 %0, %1;" : "=f"(r) : "f"(x)); return r; }
__device__ __forceinline__ float rcp(float x) { float r; asm("rcp.approx.ftz.f32 %0, %1;" : "=f"(r) : "f"(x)); return r; }
__device__ __forceinline__ void mbar_expect(uint32_t bar, uint32_t bytes) {
  asm volatile("mbarrier.arrive.expect_tx.shared::cta.b64 _, [%0], %1;" :: "r"(bar), "r"(bytes) : "memory");
}
__device__ __forceinline__ bool mbar_try(uint32_t bar, uint32_t ph) {
  uint32_t ok;
  asm volatile("{ .reg .pred p; mbarrier.try_wait.parity.shared::cta.b64 p, [%1], %2; selp.u32 %0, 1, 0, p; }"
               : "=r"(ok) : "r"(bar), "r"(ph) : "memory");
  return ok;
}
__device__ __forceinline__ void mbar_wait(uint32_t bar, uint32_t ph) {
  uint32_t n = 0;
  while (!mbar_try(bar, ph)) { watchdog(n, (1u << 20)); }
}
__device__ __forceinline__ void mbar_spin(uint32_t bar, uint32_t ph) { while (!mbar_try(bar, ph)) {} }
__device__ __forceinline__ void mbar_spin_if(uint32_t bar, uint32_t ph, bool on) {
  asm volatile("{ .reg .pred p, q; setp.ne.u32 p, %2, 0;\n"
               "SPN: setp.eq.u32 q, 0, 0; @p mbarrier.try_wait.parity.shared::cta.b64 q, [%0], %1; @!q bra.uni SPN; }" :: "r"(bar), "r"(ph), "r"((uint32_t)on) : "memory");
}
__device__ __forceinline__ void mbar_spin2_if(uint32_t bar, uint32_t bar2, uint32_t ph, bool on) {
  asm volatile("{ .reg .pred p, q, r; setp.ne.u32 p, %3, 0;\n"
               "SPN: setp.eq.u32 q, 0, 0; setp.eq.u32 r, 0, 0; @p mbarrier.try_wait.parity.shared::cta.b64 q, [%0], %2;\n"
               "@p mbarrier.try_wait.parity.shared::cta.b64 r, [%1], %2; and.pred q, q, r; @!q bra.uni SPN; }" :: "r"(bar), "r"(bar2), "r"(ph), "r"((uint32_t)on) : "memory");
}
__device__ __forceinline__ void mbar_spin_cluster(uint32_t bar, uint32_t ph) {
  uint32_t ok;
  do {
    asm volatile("{ .reg .pred p; mbarrier.try_wait.parity.acquire.cluster.shared::cta.b64 p, [%1], %2; selp.u32 %0, 1, 0, p; }"
                 : "=r"(ok) : "r"(bar), "r"(ph) : "memory");
  } while (!ok);
}
#define ONCE_H "mov.b64 h, 0x12F0000000000000; "
__device__ __forceinline__ void tma2d(uint32_t dst, const CUtensorMap* tm, int c0, int c1, uint32_t bar) {
  if (ONCE & 32) asm volatile("{ .reg .b64 h; " ONCE_H "cp.async.bulk.tensor.2d.shared::cluster.global.mbarrier::complete_tx::bytes.L2::cache_hint [%0], [%1, {%3, %4}], [%2], h; }"
               :: "r"(dst), "l"(tm), "r"(bar), "r"(c0), "r"(c1) : "memory");
  else asm volatile("cp.async.bulk.tensor.2d.shared::cluster.global.mbarrier::complete_tx::bytes [%0], [%1, {%3, %4}], [%2];"
               :: "r"(dst), "l"(tm), "r"(bar), "r"(c0), "r"(c1) : "memory");
}
__device__ __forceinline__ void mbar_expect_e(uint32_t bar, uint32_t bytes) {
  asm volatile("{ .reg .pred p; elect.sync _|p, 0xffffffff; @p mbarrier.arrive.expect_tx.shared::cta.b64 _, [%0], %1; }" :: "r"(bar), "r"(bytes) : "memory");
}
__device__ __forceinline__ void tma2d_e(uint32_t dst, const CUtensorMap* tm, int c0, int c1, uint32_t bar) {
  asm volatile("{ .reg .pred p; elect.sync _|p, 0xffffffff;\n"
               "@p cp.async.bulk.tensor.2d.shared::cluster.global.mbarrier::complete_tx::bytes [%0], [%1, {%3, %4}], [%2]; }"
               :: "r"(dst), "l"(tm), "r"(bar), "r"(c0), "r"(c1) : "memory");
}
__device__ __forceinline__ void tma2d_st_e(const CUtensorMap* tm, int c0, int c1, uint32_t src) {
  asm volatile("{ .reg .pred p; elect.sync _|p, 0xffffffff;\n"
               "@p cp.async.bulk.tensor.2d.global.shared::cta.bulk_group [%0, {%2, %3}], [%1]; }" :: "l"(tm), "r"(src), "r"(c0), "r"(c1) : "memory");
}
__device__ __forceinline__ void tma2d_out_e(const CUtensorMap* tm, int c0, int c1, uint32_t src) {
  if (EPI) asm volatile("{ .reg .pred p; elect.sync _|p, 0xffffffff;\n"
               "@p cp.reduce.async.bulk.tensor.2d.global.shared::cta.add.bulk_group [%0, {%2, %3}], [%1]; }" :: "l"(tm), "r"(src), "r"(c0), "r"(c1) : "memory");
  else if (ONCE & 16) asm volatile("{ .reg .pred p; .reg .b64 h; " ONCE_H "elect.sync _|p, 0xffffffff;\n"
               "@p cp.async.bulk.tensor.2d.global.shared::cta.bulk_group.L2::cache_hint [%0, {%2, %3}], [%1], h; }" :: "l"(tm), "r"(src), "r"(c0), "r"(c1) : "memory");
  else asm volatile("{ .reg .pred p; elect.sync _|p, 0xffffffff;\n"
               "@p cp.async.bulk.tensor.2d.global.shared::cta.bulk_group [%0, {%2, %3}], [%1]; }" :: "l"(tm), "r"(src), "r"(c0), "r"(c1) : "memory");
}
__device__ __forceinline__ void tma2d_once(uint32_t dst, const CUtensorMap* tm, int c0, int c1, uint32_t bar) {
  asm volatile("{ .reg .pred p; .reg .b64 h; " ONCE_H "elect.sync _|p, 0xffffffff;\n"
               "@p cp.async.bulk.tensor.2d.shared::cluster.global.mbarrier::complete_tx::bytes.L2::cache_hint [%0], [%1, {%3, %4}], [%2], h; }"
               :: "r"(dst), "l"(tm), "r"(bar), "r"(c0), "r"(c1) : "memory");
}
__device__ __forceinline__ void bulk_once(uint32_t dst, const void* src, uint32_t bytes, uint32_t bar) {
  asm volatile("{ .reg .pred p; .reg .b64 h; " ONCE_H "elect.sync _|p, 0xffffffff;\n"
               "@p cp.async.bulk.shared::cluster.global.mbarrier::complete_tx::bytes.L2::cache_hint [%0], [%1], %2, [%3], h; }"
               :: "r"(dst), "l"(src), "r"(bytes), "r"(bar) : "memory");
}
__device__ __forceinline__ void tma4d_e(uint32_t dst, const CUtensorMap* tm, int c2, int c3, uint32_t bar) {
  asm volatile("{ .reg .pred p; .reg .b64 h; " ONCE_H "elect.sync _|p, 0xffffffff;\n"
               "@p cp.async.bulk.tensor.4d.shared::cluster.global.mbarrier::complete_tx::bytes.L2::cache_hint [%0], [%1, {0, 0, %3, %4}], [%2], h; }"
               :: "r"(dst), "l"(tm), "r"(bar), "r"(c2), "r"(c3) : "memory");
}
__device__ __forceinline__ void bulk_load_e(uint32_t dst, const void* src, uint32_t bytes, uint32_t bar) {
  asm volatile("{ .reg .pred p; elect.sync _|p, 0xffffffff;\n"
               "@p cp.async.bulk.shared::cluster.global.mbarrier::complete_tx::bytes [%0], [%1], %2, [%3]; }"
               :: "r"(dst), "l"(src), "r"(bytes), "r"(bar) : "memory");
}
template<bool O> __device__ __forceinline__ void tma2d_o(uint32_t dst, const CUtensorMap* tm, int c0, int c1, uint32_t bar) {
  if (O) tma2d_once(dst, tm, c0, c1, bar); else tma2d_e(dst, tm, c0, c1, bar);
}
__device__ __forceinline__ float2 ld_once(const float2* p) {
  float2 v;
  if (ONCE & 64) asm volatile("{ .reg .b64 h; " ONCE_H "ld.global.cg.L2::cache_hint.v2.f32 {%0, %1}, [%2], h; }" : "=f"(v.x), "=f"(v.y) : "l"(p));
  else v = __ldcg(p);
  return v;
}
template<bool O = false> __device__ __forceinline__ void prefetch2d_e(const CUtensorMap* tm, int c0, int c1) {
  if (O) asm volatile("{ .reg .pred p; .reg .b64 h; " ONCE_H "elect.sync _|p, 0xffffffff;\n"
               "@p cp.async.bulk.prefetch.tensor.2d.L2.global.L2::cache_hint [%0, {%1, %2}], h; }" :: "l"(tm), "r"(c0), "r"(c1) : "memory");
  else asm volatile("{ .reg .pred p; elect.sync _|p, 0xffffffff;\n"
               "@p cp.async.bulk.prefetch.tensor.2d.L2.global [%0, {%1, %2}]; }" :: "l"(tm), "r"(c0), "r"(c1) : "memory");
}
__device__ __forceinline__ void st_pub4(void* p, uint4 v) {
  asm volatile("st.relaxed.gpu.global.v4.u32 [%0], {%1,%2,%3,%4};" :: "l"(p), "r"(v.x), "r"(v.y), "r"(v.z), "r"(v.w) : "memory");
}
__device__ __forceinline__ void st_pub_if(void* p, uint32_t v, bool on) {
  asm volatile("{ .reg .pred p; setp.ne.u32 p, %2, 0; @p st.relaxed.gpu.global.u32 [%0], %1; }" :: "l"(p), "r"(v), "r"((uint32_t)on) : "memory");
}
__device__ __forceinline__ uint32_t mapa(uint32_t a, uint32_t r) {
  uint32_t d; asm volatile("mapa.shared::cluster.u32 %0, %1, %2;" : "=r"(d) : "r"(a), "r"(r)); return d;
}
__device__ __forceinline__ void st_async4(uint32_t a, uint32_t x, uint32_t y, uint32_t z, uint32_t w, uint32_t bar) {
  asm volatile("st.async.shared::cluster.mbarrier::complete_tx::bytes.v4.u32 [%0], {%1,%2,%3,%4}, [%5];"
               :: "r"(a), "r"(x), "r"(y), "r"(z), "r"(w), "r"(bar) : "memory");
}
__device__ __forceinline__ uint4 ld_poll(const void* p) {
  uint4 v;
  asm volatile("ld.volatile.global.v4.u32 {%0,%1,%2,%3}, [%4];" : "=r"(v.x), "=r"(v.y), "=r"(v.z), "=r"(v.w) : "l"(p) : "memory");
  return v;
}
__device__ __forceinline__ uint2 ld_poll2(const void* p) {
  uint2 v; asm volatile("ld.volatile.global.v2.u32 {%0,%1}, [%2];" : "=r"(v.x), "=r"(v.y) : "l"(p) : "memory"); return v;
}
__device__ __forceinline__ void st_pub2(void* p, uint32_t a, uint32_t b) {
  asm volatile("st.relaxed.gpu.global.v2.u32 [%0], {%1,%2};" :: "l"(p), "r"(a), "r"(b) : "memory");
}
__device__ __forceinline__ uint32_t ld_poll1(const void* p) {
  uint32_t v; asm volatile("ld.volatile.global.u32 %0, [%1];" : "=r"(v) : "l"(p) : "memory"); return v;
}
__device__ __forceinline__ uint32_t ld_acquire(const uint32_t* p) {
  uint32_t v; asm volatile("ld.acquire.gpu.global.u32 %0, [%1];" : "=r"(v) : "l"(p) : "memory"); return v;
}
__device__ __forceinline__ void st_pub(void* p, uint32_t v) {
  asm volatile("st.relaxed.gpu.global.u32 [%0], %1;" :: "l"(p), "r"(v) : "memory");
}
__device__ __forceinline__ uint32_t lds32(uint32_t a) {
  uint32_t v; asm volatile("ld.shared.u32 %0, [%1];" : "=r"(v) : "r"(a) : "memory"); return v;
}
__device__ __forceinline__ int race_init(void* p0, void* p1, uint32_t val) {
  int t;
  asm volatile("{ .reg .pred r; .reg .u32 a, b, u, v;\n"
               "atom.relaxed.gpu.global.exch.b32 u, [%1], %3; atom.relaxed.gpu.global.exch.b32 v, [%2], %3;\n"
               "setp.eq.u32 r, u, 0x12345; @r pmevent 1; mov.u32 a, %%clock;\n"
               "setp.eq.u32 r, v, 0x12345; @r pmevent 1; mov.u32 b, %%clock; sub.u32 %0, b, a; }" : "=r"(t) : "l"(p0), "l"(p1), "r"(val) : "memory");
  return t;
}
__device__ __forceinline__ void race_init2(void* p0, void* p1, uint32_t val) {
  asm volatile("{ .reg .pred r; .reg .u32 a, b, u, v;\n"
               "atom.relaxed.gpu.global.exch.b32 u, [%0], %2; atom.relaxed.gpu.global.exch.b32 v, [%1], %2;\n"
               "atom.relaxed.gpu.global.exch.b32 a, [%0 + 4096], %2; atom.relaxed.gpu.global.exch.b32 b, [%1 + 4096], %2;\n"
               "lop3.b32 u, u, v, a, 0x96; setp.eq.u32 r, u, 0x12345; setp.eq.and.u32 r, b, u, r; @r pmevent 1; }" :: "l"(p0), "l"(p1), "r"(val) : "memory");
}
__device__ __forceinline__ uint4 lds128(uint32_t a) {
  uint4 v; asm volatile("ld.shared.v4.u32 {%0,%1,%2,%3}, [%4];" : "=r"(v.x), "=r"(v.y), "=r"(v.z), "=r"(v.w) : "r"(a) : "memory"); return v;
}
__device__ __forceinline__ uint2 lds64(uint32_t a) {
  uint2 v; asm volatile("ld.shared.v2.u32 {%0,%1}, [%2];" : "=r"(v.x), "=r"(v.y) : "r"(a) : "memory"); return v;
}
__device__ __forceinline__ void sts128(uint32_t a, uint4 v) {
  asm volatile("st.shared.v4.u32 [%0], {%1,%2,%3,%4};" :: "r"(a), "r"(v.x), "r"(v.y), "r"(v.z), "r"(v.w) : "memory");
}
__device__ __forceinline__ void sts64(uint32_t a, uint32_t x, uint32_t y) { asm volatile("st.shared.v2.u32 [%0], {%1,%2};" :: "r"(a), "r"(x), "r"(y) : "memory"); }
__device__ __forceinline__ void sts32(uint32_t a, uint32_t x) { asm volatile("st.shared.u32 [%0], %1;" :: "r"(a), "r"(x) : "memory"); }
__device__ __forceinline__ void ldsm4t(uint32_t (&r)[4], uint32_t a) {
  asm volatile("ldmatrix.sync.aligned.m8n8.x4.trans.shared.b16 {%0,%1,%2,%3}, [%4];"
               : "=r"(r[0]), "=r"(r[1]), "=r"(r[2]), "=r"(r[3]) : "r"(a) : "memory");
}
__device__ __forceinline__ void ldsm4(uint32_t (&r)[4], uint32_t a) {
  asm volatile("ldmatrix.sync.aligned.m8n8.x4.shared.b16 {%0,%1,%2,%3}, [%4];"
               : "=r"(r[0]), "=r"(r[1]), "=r"(r[2]), "=r"(r[3]) : "r"(a) : "memory");
}
template<bool TRANS> __device__ __forceinline__ void stsm4(uint32_t a, uint32_t r0, uint32_t r1, uint32_t r2, uint32_t r3) {
  if (TRANS) asm volatile("stmatrix.sync.aligned.m8n8.x4.trans.shared.b16 [%0], {%1,%2,%3,%4};" :: "r"(a), "r"(r0), "r"(r1), "r"(r2), "r"(r3) : "memory");
  else       asm volatile("stmatrix.sync.aligned.m8n8.x4.shared.b16 [%0], {%1,%2,%3,%4};" :: "r"(a), "r"(r0), "r"(r1), "r"(r2), "r"(r3) : "memory");
}
__device__ __forceinline__ void mma16816(float (&d)[4], uint32_t a0, uint32_t a1, uint32_t a2, uint32_t a3, uint32_t b0, uint32_t b1) {
  asm volatile("mma.sync.aligned.m16n8k16.row.col.f32.bf16.bf16.f32 {%0,%1,%2,%3}, {%4,%5,%6,%7}, {%8,%9}, {%0,%1,%2,%3};"
               : "+f"(d[0]), "+f"(d[1]), "+f"(d[2]), "+f"(d[3]) : "r"(a0), "r"(a1), "r"(a2), "r"(a3), "r"(b0), "r"(b1));
}
__device__ __forceinline__ void mma1688(float (&d)[4], uint32_t a0, uint32_t a1, uint32_t b0) {
  asm volatile("mma.sync.aligned.m16n8k8.row.col.f32.bf16.bf16.f32 {%0,%1,%2,%3}, {%4,%5}, {%6}, {%0,%1,%2,%3};"
               : "+f"(d[0]), "+f"(d[1]), "+f"(d[2]), "+f"(d[3]) : "r"(a0), "r"(a1), "r"(b0));
}
__device__ __forceinline__ uint32_t pack_bf16(float lo, float hi) {
  uint32_t r; asm("cvt.rn.bf16x2.f32 %0, %1, %2;" : "=r"(r) : "f"(hi), "f"(lo)); return r;
}
__device__ __forceinline__ uint32_t add_bf16x2(uint32_t a, uint32_t b) {
  uint32_t r; asm("add.rn.bf16x2 %0, %1, %2;" : "=r"(r) : "r"(a), "r"(b)); return r;
}
__device__ __forceinline__ uint32_t umax4(uint4 v) { return max(max(v.x, v.y), max(v.z, v.w)); }
__device__ __forceinline__ uint32_t opaque(uint32_t x) { uint32_t r; asm volatile("mov.u32 %0, %1;" : "=r"(r) : "r"(x)); return r; }
template<class T> __device__ __forceinline__ void pin(T*& p) { asm volatile("" : "+l"(p)); }
__device__ __forceinline__ void pin(uint32_t& v) { asm volatile("" : "+r"(v)); }
__device__ __forceinline__ uint32_t desc_lo(uint32_t addr) { return ((addr & 0x3FFFF) >> 4) | 0x10000; }
__device__ __forceinline__ uint64_t desc128(uint32_t lo) {
  uint64_t d; asm("mov.b64 %0, {%1, %2};" : "=l"(d) : "r"(lo), "r"(0x40000040)); return d;
}
#define WG_FENCE()  asm volatile("wgmma.fence.sync.aligned;" ::: "memory")
#define WG_COMMIT() asm volatile("wgmma.commit_group.sync.aligned;" ::: "memory")
#define WG_WAIT(n)  asm volatile("wgmma.wait_group.sync.aligned " #n ";" ::: "memory")
#define FENCE_ASYNC_SMEM() asm volatile("fence.proxy.async.shared::cta;" ::: "memory")
__device__ __forceinline__ void bar_sync(int id, int n) { asm volatile("bar.sync %0, %1;" :: "r"(id), "r"(n) : "memory"); }

#define D16(c) c(d[0]), c(d[1]), c(d[2]), c(d[3]), c(d[4]), c(d[5]), c(d[6]), c(d[7]), \
               c(d[8]), c(d[9]), c(d[10]), c(d[11]), c(d[12]), c(d[13]), c(d[14]), c(d[15])
template<bool FIRST> __device__ __forceinline__ void wgmma_rs_n32(float (&d)[16], const uint32_t (&a)[4], uint64_t b) {
  if (FIRST)
    asm volatile("wgmma.mma_async.sync.aligned.m64n32k16.f32.bf16.bf16 {%0,%1,%2,%3,%4,%5,%6,%7,%8,%9,%10,%11,%12,%13,%14,%15}, {%16,%17,%18,%19}, %20, 0, 1, 1, 0;"
      : D16("=f") : "r"(a[0]), "r"(a[1]), "r"(a[2]), "r"(a[3]), "l"(b));
  else
    asm volatile("wgmma.mma_async.sync.aligned.m64n32k16.f32.bf16.bf16 {%0,%1,%2,%3,%4,%5,%6,%7,%8,%9,%10,%11,%12,%13,%14,%15}, {%16,%17,%18,%19}, %20, 1, 1, 1, 0;"
      : D16("+f") : "r"(a[0]), "r"(a[1]), "r"(a[2]), "r"(a[3]), "l"(b));
}
template<bool FIRST> __device__ __forceinline__ void wgmma_ss_n32_ta(float (&d)[16], uint64_t a, uint64_t b) {
  if (FIRST)
    asm volatile("wgmma.mma_async.sync.aligned.m64n32k16.f32.bf16.bf16 {%0,%1,%2,%3,%4,%5,%6,%7,%8,%9,%10,%11,%12,%13,%14,%15}, %16, %17, 0, 1, 1, 1, 0;"
      : D16("=f") : "l"(a), "l"(b));
  else
    asm volatile("wgmma.mma_async.sync.aligned.m64n32k16.f32.bf16.bf16 {%0,%1,%2,%3,%4,%5,%6,%7,%8,%9,%10,%11,%12,%13,%14,%15}, %16, %17, 1, 1, 1, 1, 0;"
      : D16("+f") : "l"(a), "l"(b));
}
__device__ __forceinline__ void wgmma_ss_n128_tb(float (&d)[64], uint64_t a, uint64_t b) {
  asm volatile("wgmma.mma_async.sync.aligned.m64n128k16.f32.bf16.bf16 "
    "{%0,%1,%2,%3,%4,%5,%6,%7,%8,%9,%10,%11,%12,%13,%14,%15,%16,%17,%18,%19,%20,%21,%22,%23,%24,%25,%26,%27,%28,%29,%30,%31,"
    "%32,%33,%34,%35,%36,%37,%38,%39,%40,%41,%42,%43,%44,%45,%46,%47,%48,%49,%50,%51,%52,%53,%54,%55,%56,%57,%58,%59,%60,%61,%62,%63}, "
    "%64, %65, 1, 1, 1, 0, 1;"
    : "+f"(d[0]), "+f"(d[1]), "+f"(d[2]), "+f"(d[3]), "+f"(d[4]), "+f"(d[5]), "+f"(d[6]), "+f"(d[7]),
      "+f"(d[8]), "+f"(d[9]), "+f"(d[10]), "+f"(d[11]), "+f"(d[12]), "+f"(d[13]), "+f"(d[14]), "+f"(d[15]),
      "+f"(d[16]), "+f"(d[17]), "+f"(d[18]), "+f"(d[19]), "+f"(d[20]), "+f"(d[21]), "+f"(d[22]), "+f"(d[23]),
      "+f"(d[24]), "+f"(d[25]), "+f"(d[26]), "+f"(d[27]), "+f"(d[28]), "+f"(d[29]), "+f"(d[30]), "+f"(d[31]),
      "+f"(d[32]), "+f"(d[33]), "+f"(d[34]), "+f"(d[35]), "+f"(d[36]), "+f"(d[37]), "+f"(d[38]), "+f"(d[39]),
      "+f"(d[40]), "+f"(d[41]), "+f"(d[42]), "+f"(d[43]), "+f"(d[44]), "+f"(d[45]), "+f"(d[46]), "+f"(d[47]),
      "+f"(d[48]), "+f"(d[49]), "+f"(d[50]), "+f"(d[51]), "+f"(d[52]), "+f"(d[53]), "+f"(d[54]), "+f"(d[55]),
      "+f"(d[56]), "+f"(d[57]), "+f"(d[58]), "+f"(d[59]), "+f"(d[60]), "+f"(d[61]), "+f"(d[62]), "+f"(d[63])
    : "l"(a), "l"(b));
}

__device__ __forceinline__ void tma3d_mc_e(uint32_t dst, const CUtensorMap* tm, int c1, int c2, uint32_t bar) {
  asm volatile("{ .reg .pred p; .reg .b64 h; " ONCE_H "elect.sync _|p, 0xffffffff;\n"
               "@p cp.async.bulk.tensor.3d.shared::cluster.global.mbarrier::complete_tx::bytes.multicast::cluster.L2::cache_hint [%0], [%1, {0, %3, %4}], [%2], %5, h; }"
               :: "r"(dst), "l"(tm), "r"(bar), "r"(c1), "r"(c2), "h"((uint16_t)3) : "memory");
}
__device__ __forceinline__ void prefetch3d_e(const CUtensorMap* tm, int c1, int c2) {
  asm volatile("{ .reg .pred p; elect.sync _|p, 0xffffffff;\n"
               "@p cp.async.bulk.prefetch.tensor.3d.L2.global [%0, {0, %1, %2}]; }" :: "l"(tm), "r"(c1), "r"(c2) : "memory");
}

__device__ __forceinline__ void count_e(uint32_t* p) {
  asm volatile("fence.acq_rel.gpu;" ::: "memory");
  __syncwarp();
  asm volatile("{ .reg .pred p; elect.sync _|p, 0xffffffff; @p red.relaxed.gpu.global.add.u32 [%0], 1; }" :: "l"(p) : "memory");
}
template<int NS = 0> __device__ __forceinline__ void await_count(const uint32_t* p, uint32_t n) {
  for (uint32_t i = 0; ld_acquire(p) < n && i < (1u << 22); i++) { if (NS) __nanosleep(NS); }
  asm volatile("fence.proxy.async.global;" ::: "memory");
}
__device__ __forceinline__ void await_flags(const uint32_t* p) {
  for (uint32_t i = 0; i < (1u << 22); i++) {
    uint4 v;
    asm volatile("ld.acquire.gpu.global.v4.u32 {%0,%1,%2,%3}, [%4];" : "=r"(v.x), "=r"(v.y), "=r"(v.z), "=r"(v.w) : "l"(p) : "memory");
    if (__all_sync(~0u, (v.x & v.y & v.z & v.w) == 0x01010101u)) break;
  }
  asm volatile("fence.proxy.async.global;" ::: "memory");
}
__device__ __forceinline__ void mbar_lim(uint32_t bar, uint32_t ph) { for (uint32_t i = 0; !mbar_try(bar, ph) && i < (1u << 20); i++) {} }

struct cf { float x, y; };
__host__ __device__ constexpr float cos64(int k) {
  return k == 0 ? 1.0f : k == 1 ? 0.99518472667219689f : k == 2 ? 0.98078528040323045f : k == 3 ? 0.95694033573220887f :
         k == 4 ? 0.92387953251128676f : k == 5 ? 0.88192126434835503f : k == 6 ? 0.83146961230254524f : k == 7 ? 0.77301045336273696f :
         k == 8 ? 0.70710678118654752f : k == 9 ? 0.63439328416364550f : k == 10 ? 0.55557023301960222f : k == 11 ? 0.47139673682599765f :
         k == 12 ? 0.38268343236508977f : k == 13 ? 0.29028467725446236f : k == 14 ? 0.19509032201612827f : k == 15 ? 0.09801714032956060f : 0.0f;
}
__host__ __device__ constexpr float c64(int k) { return k <= 16 ? cos64(k) : -cos64(32 - k); }
__host__ __device__ constexpr float s64(int k) { return k <= 16 ? cos64(16 - k) : cos64(k - 16); }

template<int N, int ST, bool INV> struct Fft {
  template<int K> static __device__ __forceinline__ void bf(const cf* e, const cf* o, cf* out) {
    if constexpr (K < N / 2) {
      constexpr int idx = K * (64 / N);
      const cf a = e[K], b = o[K];
      if constexpr (idx == 0) {
        out[K] = {a.x + b.x, a.y + b.y}; out[K + N / 2] = {a.x - b.x, a.y - b.y};
      } else if constexpr (idx == 16) {
        if constexpr (INV) { out[K] = {a.x - b.y, a.y + b.x}; out[K + N / 2] = {a.x + b.y, a.y - b.x}; }
        else               { out[K] = {a.x + b.y, a.y - b.x}; out[K + N / 2] = {a.x - b.y, a.y + b.x}; }
      } else {
        constexpr float c = c64(idx), s = INV ? s64(idx) : -s64(idx);
        cf p; p.x = fmaf(-s, b.y, fmaf(c, b.x, a.x)); p.y = fmaf(s, b.x, fmaf(c, b.y, a.y));
        out[K] = p; out[K + N / 2] = {fmaf(2.0f, a.x, -p.x), fmaf(2.0f, a.y, -p.y)};
      }
      bf<K + 1>(e, o, out);
    }
  }
  static __device__ __forceinline__ void run(const cf* in, cf* out) {
    cf e[N / 2], o[N / 2];
    Fft<N / 2, 2 * ST, INV>::run(in, e);
    Fft<N / 2, 2 * ST, INV>::run(in + ST, o);
    bf<0>(e, o, out);
  }
};
template<int ST, bool INV> struct Fft<1, ST, INV> {
  static __device__ __forceinline__ void run(const cf* in, cf* out) { out[0] = in[0]; }
};
template<bool INV> __device__ __forceinline__ void fft32(cf (&v)[32]) {
  cf o[32]; Fft<32, 1, INV>::run(v, o);
#pragma unroll
  for (int i = 0; i < 32; i++) v[i] = o[i];
}
__device__ __forceinline__ cf cmul(cf a, float c, float s) { return {fmaf(-a.y, s, a.x * c), fmaf(a.x, s, a.y * c)}; }
__device__ __forceinline__ float bf2f(__nv_bfloat16 v) { return __bfloat162float(v); }

__device__ __forceinline__ int tw_at(int i) { return (i & ~63) | (i & 31) << 1 | (i >> 5 & 1); }
template<bool INV, bool T128 = true> __device__ __forceinline__ void twiddles(cf (&v)[32], const float4* __restrict__ tw) {
#pragma unroll
  for (int j = 0; j < 32; j += 2) {
    float4 w;
    if (T128) w = tw[j * 16];
    else { const uint2 a = lds64(smem_u32(tw + j * 16)), b = lds64(smem_u32(tw + j * 16) + 8); w = make_float4(__uint_as_float(a.x), __uint_as_float(a.y), __uint_as_float(b.x), __uint_as_float(b.y)); }
    if (j) v[j] = cmul(v[j], w.x, INV ? -w.y : w.y);
    v[j + 1] = cmul(v[j + 1], w.z, INV ? -w.w : w.w);
  }
}
template<bool INV, class F> __device__ __forceinline__ void warp_fft1024(cf (&v)[32], float2* __restrict__ buf, const float2* __restrict__ tw, int t, int u, F mid) {
#pragma unroll 1
  for (uint32_t h = 0; h < 2; h++) {
    fft32<INV>(v);
    if (FUNR ? h : opaque(h)) continue;
    twiddles<INV>(v, (const float4*)tw + u);
    if (INV) {
      float* f = (float*)buf;
#pragma unroll
      for (int j = 0; j < 32; j++) f[j * 36 + t] = v[j].x;
      __syncwarp();
#pragma unroll
      for (int j = 0; j < 32; j += 4) { const float4 r = *(const float4*)(f + u * 36 + j); v[j].x = r.x; v[j + 1].x = r.y; v[j + 2].x = r.z; v[j + 3].x = r.w; }
      __syncwarp();
#pragma unroll
      for (int j = 0; j < 32; j++) f[j * 36 + t] = v[j].y;
      __syncwarp();
#pragma unroll
      for (int j = 0; j < 32; j += 4) { const float4 r = *(const float4*)(f + u * 36 + j); v[j].y = r.x; v[j + 1].y = r.y; v[j + 2].y = r.z; v[j + 3].y = r.w; }
    } else {
#pragma unroll
      for (int j = 0; j < 32; j++) buf[j * 33 + t] = make_float2(v[j].x, v[j].y);
      __syncwarp();
#pragma unroll
      for (int j = 0; j < 32; j++) { const float2 r = buf[u * 33 + j]; v[j] = {r.x, r.y}; }
    }
    __syncwarp();
    mid();
  }
}
constexpr int ROW_BUF = 32 * 33, INV_BUF = 32 * 18;

__device__ __forceinline__ int z_row(int p) { return (p & ~31) | (p & 7) << 2 | (p & 31) >> 3; }
__device__ __forceinline__ int inv_lane(int t) { return (t & ~14) | (t & 12) >> 1 | (t & 2) << 2; }
__device__ __forceinline__ float2 twiddle(int i) { float s, c; sincospif(-(float)((i >> 5) * (i & 31)) * (1.0f / 512.0f), &s, &c); return make_float2(c, s); }
template<class F, class G> __device__ __forceinline__ void fft_rows_fwd(float2* sm2, const __nv_bfloat16* gw, int cta, int tid, uint32_t full_bar, uint32_t release_bar, F ev, G extra) {
  const int t = tid & 31, w = tid >> 5, n = z_row(cta * 8 + w);
#pragma unroll 1
  for (int i = tid; i < 1024; i += 256) sm2[tw_at(i)] = twiddle(i);
  ev(5);
  mbar_spin(full_bar, 0);
  if (tid == 0) TL2(6);
  __syncwarp();
  const __nv_bfloat16* xa = (const __nv_bfloat16*)(sm2 + 1024 + w * ROW_BUF) + t;
  cf v[32];
  float ga = 0.f, gb = 0.f;
#pragma unroll
  for (int j = 0; j < 32; j++) {
    v[j] = {bf2f(xa[32 * j]), bf2f(xa[D_ + 32 * j])};
    const float g = bf2f(gw[32 * j + t]); ga = fmaf(v[j].x, g, ga); gb = fmaf(v[j].y, g, gb);
  }
#pragma unroll
  for (int o = 16; o; o >>= 1) { ga += __shfl_xor_sync(~0u, ga, o); gb += __shfl_xor_sync(~0u, gb, o); }
  if (t < 2) g_gate[n + 1024 * t] = __fdividef(1.0f, 1.0f + __expf(-(t ? gb : ga)));
  ev(6);
  bar_sync(13, 256);
  warp_fft1024<false>(v, sm2 + 1024 + w * ROW_BUF, sm2, t, t, [&]() { FENCE_ASYNC_SMEM(); mbar_arrive_warp(release_bar); });
  float ws, wc; sincospif(-(float)n * (1.0f / 1024.0f), &ws, &wc);
  ev(12);
  uint32_t tz = clock_lo();
  float4* z = (float4*)g_z + ((size_t)(t >> 1) * 1024 + cta * 8 + w) * 2 + (t & 1);
#pragma unroll
  for (int j = 0; j < 17; j++) {
    cf q = v[(32 - j) & 31];
    if (j < 16) {
      const cf r = {__shfl_sync(~0u, v[31 - j].x, 32 - t), __shfl_sync(~0u, v[31 - j].y, 32 - t)};
      if (t != 0) q = r;
    }
    const cf a = {v[j].x + q.x, v[j].y - q.y}, b = {v[j].y + q.y, q.x - v[j].x};
    const cf d = cmul({a.x - b.x, a.y - b.y}, wc, ws);
    if (j == POOL_AT) extra();
    if (PACE_Z && j && j < 16) delay_until(tz += PACE_Z);
    if ((j < 16 || t == 0) && ((EXP_ST & 4) || d.x == 123.f)) z[j * 32768] = make_float4(a.x + b.x, a.y + b.y, d.x, d.y);
  }
}
constexpr int CP = X128 == 0 ? 33 : X128 == 2 ? 34 : 36, COL_FS = 32 * 36 + 8, COL_W = (8192 + 16 * COL_FS * 4 + 127) & ~127, COL_SMEM = COL_W + 131072 + 128;

__device__ __forceinline__ void fft_cols(float2* sm2, int cta, const CUtensorMap* twr, const CUtensorMap* twi, const CUtensorMap* tzs) {
  const int grp = __shfl_sync(~0u, (int)(threadIdx.x >> 7), 0), tid = threadIdx.x & 127, tp = tid >> 2, w = __shfl_sync(~0u, tid >> 5, 0);
  float* buf = (float*)(sm2 + 1024) + (grp * 4 + (tid & 3)) * COL_FS;
  const uint32_t wsm = smem_u32(sm2) + COL_W, wbar = wsm + 131072 + (W_FINE ? w * 32 : 0);
  const int res = w * 2 + (tid & 1), el = res + grp * 2 + ((tid >> 1) & 1);
  uint32_t wa = (el >> 3) * 65536 + res * 4096 + (tp & 7) * 16 + (el & 7) * 2;
  auto load_w = [&](int q) {
    const uint32_t bar = wbar + (q & 1) * 8;
    mbar_expect(bar, W_FINE ? 16384 : 65536);
#pragma unroll 1
    for (int i = W_FINE ? 4 * w : 0; i < (W_FINE ? 4 * w + 4 : 16); i++) tma2d(wsm + (q & 1) * 65536 + (i & 1) * 32768 + (i >> 1) * 4096, i & 1 ? twi : twr, (i >> 1) * 512 + q * 8, 0, bar);
  };
  const bool lead = (tid & (W_FINE ? 31 : 127)) == 0, first = grp < 2 && lead;
  if (first) { mbar_init(wbar + grp * 8, 1); sts32(wbar + 16 + grp * 4, grp ? 0 : w); asm volatile("fence.mbarrier_init.release.cluster;" ::: "memory"); }
#pragma unroll 1
  for (int i = threadIdx.x; i < 1024; i += 512) {
    const float2 t = twiddle(z_row(i));
    sm2[tw_at(i)] = t;
    if (cta == 0) g_tw[tw_at(inv_lane(z_row(i)))] = t;
  }
  for (uint32_t n = 0; ld_acquire(g_ctl + C_P1) < 128; ) { watchdog(n, 1u << 22); __nanosleep(200); }
  if (COL_DLY) delay_cycles(COL_DLY);
  if (first) load_w(cta * 16 + grp);
  __syncthreads();
  delay_cycles(1 + grp * DLY_GRP);
  mbar_wait(wbar, 0);
  const int end = cta * 64 + 64 + (cta == 3);
  for (int item = cta * 64 + grp; item < end; item += 4, wa ^= 65536) {
    float2* zp = g_z + (size_t)item * 4096;
    auto next_w = [&]() {
      const int q = (item >> 2) + (W_FINE && grp + w > 3);
      uint32_t n; asm volatile("atom.shared.inc.u32 %0, [%1], 3;" : "=r"(n) : "r"(wbar + 16 + (q & 1) * 4) : "memory");
      if (EXP_W && n == 3 && q < (cta * 16 + 15)) load_w(q + 2);
    };
    cf v[32];
#pragma unroll
    for (int j = 0; j < 32; j++) { const float2 a = ld_once(zp + tid + j * 128); v[j] = {a.x, a.y}; }
#pragma unroll 1
    for (int ph = 0; ; ph++) {
      fft32<false>(v);
      twiddles<false, T128_>(v, (const float4*)sm2 + tp);
      if (Z_ST) asm volatile("cp.async.bulk.wait_group.read 0;" ::: "memory");
      bar_sync(1 + grp, 128);
      if (lead) {
        if (ph) {
          if (!W_AT) next_w();
        } else if (Z_PF && item + 4 < end) asm volatile("cp.async.bulk.prefetch.L2.global [%0], %1;" :: "l"(zp + 4 * 4096 + w * 1024), "n"(W_FINE ? 8192 : 32768) : "memory");
      }
      __syncwarp();
#pragma unroll
      for (int j = 0; j < 32; j++) buf[((j & 3) * 8 + (j >> 2)) * CP + tp] = v[j].x;
      bar_sync(1 + grp, 128);
      if (X128 == 0) {
#pragma unroll
        for (int j = 0; j < 32; j++) v[j].x = buf[tp * CP + (j & 3) * 8 + (j >> 2)];
      } else if (X128 == 2) {
#pragma unroll
        for (int j = 0; j < 16; j++) { const float2 r = *(const float2*)(buf + tp * CP + 2 * j); cf* d = v + (j & 3) * 8 + (j >> 2); d[0].x = r.x; d[4].x = r.y; }
      } else
#pragma unroll
      for (int j = 0; j < 8; j++) {
        const float4 r = *(const float4*)(buf + tp * 36 + 4 * j);
        cf* d = v + (j & 1) * 16 + (j >> 1);
        d[0].x = r.x; d[4].x = r.y; d[8].x = r.z; d[12].x = r.w;
      }
      bar_sync(1 + grp, 128);
#pragma unroll
      for (int j = 0; j < 32; j++) buf[((j & 3) * 8 + (j >> 2)) * CP + tp] = v[j].y;
      bar_sync(1 + grp, 128);
      if (X128 == 0) {
#pragma unroll
        for (int j = 0; j < 32; j++) v[j].y = buf[tp * CP + (j & 3) * 8 + (j >> 2)];
      } else if (X128 == 2) {
#pragma unroll
        for (int j = 0; j < 16; j++) { const float2 r = *(const float2*)(buf + tp * CP + 2 * j); cf* d = v + (j & 3) * 8 + (j >> 2); d[0].y = r.x; d[4].y = r.y; }
      } else
#pragma unroll
      for (int j = 0; j < 8; j++) {
        const float4 r = *(const float4*)(buf + tp * 36 + 4 * j);
        cf* d = v + (j & 1) * 16 + (j >> 1);
        d[0].y = r.x; d[4].y = r.y; d[8].y = r.z; d[12].y = r.w;
      }
      fft32<false>(v);
      if (ph) break;
      const int q = min((item >> 2) + (!W_FINE || grp + w >= 3), 64);
      if (EXP_W) mbar_wait(wbar + (q & 1) * 8, (q >> 1) & 1);
#pragma unroll
      for (int j = 0; j < 32; j++) {
        uint32_t re, im;
        asm volatile("ld.shared.u16 %0, [%1];" : "=r"(re) : "r"(wsm + wa + j * 128) : "memory");
        asm volatile("ld.shared.u16 %0, [%1];" : "=r"(im) : "r"(wsm + wa + 32768 + j * 128) : "memory");
        const cf r = cmul(v[j], __uint_as_float(re << 16), __uint_as_float(im << 16));
        v[j] = {r.y, r.x};
      }
    }
    if (Z_ST) {
      float2* st = sm2 + 1024 + grp * (COL_FS * 2) + w * 512;
      bar_sync(1 + grp, 128);
#pragma unroll
      for (int h = 0; h < 2; h++) {
        if (h && Z_ST == 2) {
#pragma unroll
          for (int j = 16; j < 32; j++) zp[tid + j * 128] = make_float2(v[j].y, v[j].x);
          break;
        }
        if (h) { asm volatile("cp.async.bulk.wait_group.read 0;" ::: "memory"); __syncwarp(); }
#pragma unroll
        for (int j = 0; j < 16; j++) st[j * 32 + (tid & 31)] = make_float2(v[h * 16 + j].y, v[h * 16 + j].x);
        FENCE_ASYNC_SMEM();
        __syncwarp();
        tma2d_st_e(tzs, w * 128, item * 32 + h * 16, smem_u32(st));
        asm volatile("cp.async.bulk.commit_group;" ::: "memory");
      }
    } else {
#pragma unroll
      for (int j = 0; j < 32; j++) zp[tid + j * 128] = make_float2(v[j].y, v[j].x);
    }
    if (W_AT) { if (lead) next_w(); __syncwarp(); }
  }
  if (Z_ST) asm volatile("cp.async.bulk.wait_group 0; fence.proxy.async.global;" ::: "memory");
  __syncthreads();
  if (threadIdx.x < 32) {
    count_e(g_ctl + C_COLS);
    await_count(g_ctl + C_COLS, 4);
    g_ctl[C_P1] = 0;
  }
  __syncthreads();
  ((float4*)sm2)[threadIdx.x] = __ldcg((const float4*)g_tw + threadIdx.x);
  __syncthreads();
}

template<class F> __device__ __forceinline__ void fft_rows_inv(uint32_t zs, float2* buf, const float2* tw, int p, int lane, __nv_bfloat16* out, F read) {
  const int n = z_row(p), t = (lane & 17) | (lane & 6) << 1 | (lane & 8) >> 2, src = inv_lane(-t & 31);
  const uint32_t z = zs + (t >> 1) * 128 + ((((p & 3) * 2 + (t & 1)) ^ (t >> 1 & 7)) << 4);
  FT(0, 0.f);
  float4 e[17];
  uint32_t all = 0;
  e[16] = __ldcg((const float4*)g_z + ((size_t)256 * 1024 + p) * 2);
  const float g0 = __ldcg(g_gate + n), g1 = __ldcg(g_gate + n + 1024);
#pragma unroll
  for (int j = 0; j < 16; j++) { const uint4 u = lds128(z + j * 2048); e[j] = make_float4(__uint_as_float(u.x), __uint_as_float(u.y), __uint_as_float(u.z), __uint_as_float(u.w)); all |= u.x; }
  sched_fence(all);
  read();
  float ws, wc; sincospif((float)n * (1.0f / 1024.0f), &ws, &wc);
  cf v[32], q[17];
#pragma unroll
  for (int j = 0; j < 17; j++) {
    const cf d = cmul({e[j].z, e[j].w}, wc, ws);
    cf a = {e[j].x + d.x, e[j].y + d.y}, b = {e[j].x - d.x, e[j].y - d.y};
    if (j == 16 || (j == 0 && t == 0)) { a.y = 0.f; b.y = 0.f; }
    if (j < 16) v[j] = {a.x - b.y, a.y + b.x};
    q[j] = {a.x + b.y, b.x - a.y};
  }
#pragma unroll
  for (int j = 16; j < 32; j++) {
    v[j] = {__shfl_sync(~0u, q[31 - j].x, src), __shfl_sync(~0u, q[31 - j].y, src)};
    if (t == 0) v[j] = q[32 - j];
  }
  FT(1, v[0].x + v[16].x + v[31].x);
  warp_fft1024<true>(v, buf, tw, t, lane, []() {});
  FT(3, v[31].y + v[0].x);
  const float sc = 0.5f / (2048.0f * 1024.0f), s0 = (1.f - g0) * sc, s1 = (1.f - g1) * sc;
  uint2* o = (uint2*)(out + (size_t)n * D_) + (lane ^ (n & 1) << 3);
#pragma unroll
  for (int j = 0; j < 32; j += 4) {
    o[8 * j] = make_uint2(pack_bf16(v[j].x * s0, v[j + 1].x * s0), pack_bf16(v[j + 2].x * s0, v[j + 3].x * s0));
    o[256 * D_ + 8 * j] = make_uint2(pack_bf16(v[j].y * s1, v[j + 1].y * s1), pack_bf16(v[j + 2].y * s1, v[j + 3].y * s1));
  }
  FT(4, 0.f);
}

constexpr int NP = NP_, NHV = REG_F == 216 ? 5 : 7, NV = 16 - NHV;
constexpr int XEND = NSEG;
constexpr uint32_t SM_WO = 0, SM_V = 65536, SM_LAND = SM_V + 8192, SM_MEM = SM_LAND + 24576, SM_SP = SM_MEM, SM_SPM = SM_MEM + 5120, SM_OM = SM_MEM + 6144,
                   SM_OX = SM_MEM + 8192, SM_RED = SM_OX + 2048, SM_XCH = SM_RED + 1024, SM_SUM = SM_XCH + 4096, SM_VM = SM_SUM + 128, SM_TAB = SM_VM + 2048, SM_TRACE = SM_TAB + 2048,
                   ST_WG = (32 - NP + NV) * 2048,
                   SM_XT = 2 * ST_WG, SM_POOL = SM_XT + 32768, SM_HV = SM_POOL + 2 * NP * 2048,
                   SM_BAR = SM_HV + 2 * NHV * 2048, SM_SEL = SM_BAR + 320, CHAIN_SMEM = SM_SEL + 544 + 1024;
constexpr uint32_t SM_FFT = 49152, SM_GW = SM_XT - 2048;
static_assert(NP % 4 == 0 && NV == 11 && SM_TRACE + 4096 <= SM_XT, "shared memory layout");
static_assert(CHAIN_SMEM <= 232448 && COL_SMEM <= SM_BAR && SM_FFT + (1024 + 8 * ROW_BUF) * 8 <= SM_GW && NP == 12, "shared memory budget");
enum { B_WFULL = 0, B_WREAD = 2, B_WOFULL, B_XFULL, B_XEMPTY, B_E1TRIG, B_E2TRIG, B_PVDONE, B_PUB, B_SC, B_PFULL, B_SPFREE,
       B_LAND, B_LFREE, B_DONE, B_SEL, B_PROBE, B_FREE, B_P1, B_ROWS, B_VFULL, B_VST, B_TW, B_BT, B_WREAD0, B_Z, B_GFULL = B_Z + 4, B_GEMPTY = B_GFULL + 5, B_END = B_GEMPTY + 5 };
static_assert(B_END * 8 <= 320, "barriers");
__host__ __device__ constexpr uint32_t bar_codes(int g) {
  uint32_t r = 0;
  for (int i = 16 * g; i < 16 * g + 16; i++)
    r |= (i == B_LAND ? 3u : i == B_WREAD || i == B_XEMPTY || i == B_E1TRIG || i == B_E2TRIG || i == B_LFREE || i == B_FREE || i == B_VST || i == B_P1 || i == B_ROWS ? 2u :
          i >= B_GEMPTY || i == B_WREAD0 || i == B_PROBE || i == B_DONE || i == B_PVDONE || i == B_PUB || i == B_SC || i == B_SPFREE ? 1u : 0u) << 2 * (i & 15);
  return r;
}
constexpr uint32_t SM_BT = 65536, SM_TW = SM_XT - 8192, COL_Z = 80 * 1024;
static_assert(SM_XT + 3 * 32768 <= SM_BAR && SM_BT + 32768 <= SM_MEM && SM_TRACE <= SM_TW && SM_MEM + 4 * INV_BUF * 8 <= SM_TRACE &&
              8192 + 16 * INV_BUF * 8 <= COL_Z && COL_Z + 131072 <= SM_BAR, "shared memory layout");
__device__ __forceinline__ uint32_t next_stage(uint32_t o) { return o == SM_XT + 65536 ? 0 : o == 32768 ? SM_XT : o + 32768; }

struct ChainCtx { char* mail; uint32_t sb, sel; int r, h, a, b, j, m, w, lane; };
#define BAR(i) (c.sb + SM_BAR + 8 * (i))

__device__ __forceinline__ uint32_t tile_off(int line, int lane) {
  return line * 128 + (((lane & 3) ^ line) << 5) + (lane >> 2) * 4;
}
__device__ __forceinline__ uint32_t read_off(int lane) {
  const int n = lane >> 2, jj = lane & 3, l = 2 * (jj >> 1) + (n & 1);
  return l * 128 + (((n >> 1) ^ l) << 5) + (jj & 1) * 16;
}
__device__ __forceinline__ uint32_t frag_off(int w, int lane) {
  const int mi = lane >> 3, r = lane & 7;
  return ((mi >> 1) * 8 + r) * 128 + (((2 * w + (mi & 1)) ^ r) << 4);
}
__device__ __forceinline__ uint32_t land_off(int w, int lane) { return w * 512 + ((lane ^ (((lane >> 4) | ((w & 1) << 1)) << 1)) << 4); }
__device__ __forceinline__ uint32_t tagged(uint32_t v, uint32_t tag) { return (v | 1u) ^ tag; }
__device__ __forceinline__ void mma_a(float (&d)[4], const uint32_t (&a)[4], uint32_t b0, uint32_t b1) { mma16816(d, a[0], a[1], a[2], a[3], b0, b1); }
__device__ __forceinline__ void mma_q(float (&d)[4], const uint4& a, uint32_t b0, uint32_t b1) { mma16816(d, a.x, a.y, a.z, a.w, b0, b1); }
__device__ __forceinline__ uint4 add4(uint4 a, uint4 b) {
  return make_uint4(add_bf16x2(a.x, b.x), add_bf16x2(a.y, b.y), add_bf16x2(a.z, b.z), add_bf16x2(a.w, b.w));
}
__device__ __forceinline__ void mbar_arrive_both(uint32_t bar, int peer) {
  __syncwarp();
  asm volatile("{ .reg .pred p; .reg .u32 a; mapa.shared::cluster.u32 a, %0, %1; elect.sync _|p, 0xffffffff;\n"
               "@p mbarrier.arrive.shared::cta.b64 _, [%0]; @p mbarrier.arrive.shared::cluster.b64 _, [a]; }" :: "r"(bar), "r"(peer) : "memory");
}

__device__ __forceinline__ void arrive_remote_if(uint32_t a, bool on) {
  asm volatile("{ .reg .pred p; setp.ne.u32 p, %1, 0; @p mbarrier.arrive.shared::cluster.b64 _, [%0]; }" :: "r"(a), "r"((uint32_t)on) : "memory");
}
__device__ __forceinline__ void store_count(void* p, uint4 v, void* cnt) {
  asm volatile("{ .reg .pred p, q; .reg .b128 a, b; .reg .b64 l, h; mov.b64 l, {%1, %2}; mov.b64 h, {%3, %4}; mov.b128 a, {l, h};\n"
               "atom.relaxed.gpu.global.exch.b128 b, [%0], a; mov.b128 {l, h}, b; setp.eq.u64 q, l, 0x7fc17fc17fc17fc1; @q pmevent 1;\n"
               "elect.sync _|p, 0xffffffff; @p red.relaxed.gpu.global.add.u32 [%5], 1; }"
               :: "l"(p), "r"(v.x), "r"(v.y), "r"(v.z), "r"(v.w), "l"(cnt) : "memory");
}

template<int N> __device__ __forceinline__ void pad() {
#pragma unroll
  for (int i = 0; i < N; i++) asm volatile("pmevent 3;");
}
__device__ __forceinline__ int lane_id() {
  int l; asm volatile("{ .reg .u32 t; mov.u32 t, %%laneid; shfl.sync.idx.b32 %0, t, t, 31, 0xffffffff; }" : "=r"(l)); return l;
}
__device__ __forceinline__ uint32_t tid_now() { uint32_t t; asm volatile("mov.u32 %0, %%tid.x;" : "=r"(t)); return t; }
enum { NB_ATT = 1, NB_OM = 2, NB_VM = 3, NB_XCH = 4, NB_MEM = 8, NB_HELP = 12 };
__device__ __forceinline__ uint32_t dep(uint32_t a, uint32_t v, uint32_t z) { uint32_t r; asm("shf.l.wrap.b32 %0, %2, %1, %3;" : "=r"(r) : "r"(a), "r"(v), "r"(z)); return r; }
__device__ __forceinline__ uint32_t vary(uint32_t a, int s, uint32_t z) { return dep(a, 0, z + 32 * s); }
__device__ __forceinline__ char* mk_ptr(uint32_t lo, uint32_t hi) { uint64_t r; asm("mov.b64 %0, {%1, %2};" : "=l"(r) : "r"(lo), "r"(hi)); return (char*)r; }
__device__ __forceinline__ void lds_frag(uint32_t (&r)[4], uint32_t a) {
  asm volatile("ld.shared.v4.u32 {%0,%1,%2,%3}, [%4];" : "=r"(r[0]), "=r"(r[1]), "=r"(r[2]), "=r"(r[3]) : "r"(a) : "memory");
}
__device__ __forceinline__ uint32_t stale2(uint32_t a, uint32_t b, uint32_t t) { uint32_t r; asm("lop3.b32 %0, %1, %2, %3, 0xbd;" : "=r"(r) : "r"(a), "r"(b), "r"(t)); return r; }
__device__ __forceinline__ uint32_t stale1(uint32_t acc, uint32_t a, uint32_t t) { uint32_t r; asm("lop3.b32 %0, %1, %2, %3, 0xf9;" : "=r"(r) : "r"(acc), "r"(a), "r"(t)); return r; }
__device__ __forceinline__ bool all_clear(uint32_t x, uint32_t m) {
  uint32_t r;
  asm volatile("{ .reg .pred p; .reg .u32 t; and.b32 t, %1, %2; setp.eq.u32 p, t, 0; vote.sync.all.pred p, p, 0xffffffff; selp.u32 %0, 1, 0, p; }" : "=r"(r) : "r"(x), "r"(m));
  return r;
}
__device__ __forceinline__ bool arrive_if_all(bool ok, int id, int n) {
  uint32_t r;
  asm volatile("{ .reg .pred p, q; setp.ne.u32 p, %1, 0; vote.sync.all.pred q, p, 0xffffffff; @q bar.arrive %2, %3; selp.u32 %0, 1, 0, q; }"
               : "=r"(r) : "r"((uint32_t)ok), "r"(id), "r"(n) : "memory");
  return r;
}
__device__ __forceinline__ bool arrive_if_clear(uint32_t x, uint32_t m, int id, int n) {
  uint32_t r;
  asm volatile("{ .reg .pred p; .reg .u32 t; and.b32 t, %1, %2; setp.eq.u32 p, t, 0; vote.sync.all.pred p, p, 0xffffffff; @p bar.arrive %3, %4; selp.u32 %0, 1, 0, p; }"
               : "=r"(r) : "r"(x), "r"(m), "r"(id), "r"(n) : "memory");
  return r;
}
__device__ __forceinline__ void touch(const void* p, uint32_t z) {
  asm volatile("{ .reg .pred p; setp.eq.u32 p, %1, 0x7fff0000; @p prefetch.global.L2 [%0]; }" :: "l"(p), "r"(z) : "memory");
}

__device__ __forceinline__ uint64_t desc_x(uint32_t lo, int k) {
  uint64_t d; asm("mov.b64 %0, {%1, %2};" : "=l"(d) : "r"(lo + (k >> 2) * 64 + (k & 3) * 2), "r"(0x40000200)); return d;
}
template<int K0, int K1> __device__ __forceinline__ void issue_qk(float (&xa)[16], const uint32_t (&wt)[16][4], uint32_t lo) {
  WG_FENCE();
#pragma unroll
  for (int k = K0; k < K1; k++) {
    if (k >= EXP_NWG) continue;
    if (k == 0) wgmma_rs_n32<true>(xa, wt[0], desc_x(lo, 0));
    else wgmma_rs_n32<false>(xa, wt[k], desc_x(lo, k));
  }
  WG_COMMIT();
}
__host__ __device__ constexpr int v_order(int i) { return SSPOS == 0 ? i : SSPOS == 2 ? (i + NV) % 16 : NHV == 5 ? (i % 3 == 2 ? NV + i / 3 : i - i / 3) : (i == 15 ? NV - 1 : i % 2 ? NV + i / 2 : i / 2); }
__device__ __forceinline__ void issue_v(float (&xa)[16], const uint32_t (&wv)[16][4], uint32_t lo, uint32_t la) {
  WG_FENCE();
#pragma unroll
  for (int i = 0; i < EXP_NWG; i++) {
    const int k = v_order(i);
    const uint64_t b = desc_x(lo, k);
    if (k < NV) { if (i == 0) wgmma_rs_n32<true>(xa, wv[k], b); else wgmma_rs_n32<false>(xa, wv[k], b); }
    else        { if (i == 0) wgmma_ss_n32_ta<true>(xa, desc128(la + (k - NV) * 128), b); else wgmma_ss_n32_ta<false>(xa, desc128(la + (k - NV) * 128), b); }
  }
  WG_COMMIT();
}
template<bool ISV> __device__ __forceinline__ void park_own(uint32_t (&q)[4], float (&xa)[16], uint32_t dst, int slot, uint32_t z) {
  uint32_t p[8];
#pragma unroll
  for (int i = 0; i < 16; i++) asm volatile("" : "+f"(xa[i]) :: "memory");
#pragma unroll
  for (int i = 0; i < 2; i++) {
    const float* k = xa + 8 * i;
    if (ISV) { p[4 * i] = pack_bf16(k[0], k[1]); p[4 * i + 1] = pack_bf16(k[2], k[3]); p[4 * i + 2] = pack_bf16(k[4], k[5]); p[4 * i + 3] = pack_bf16(k[6], k[7]); }
    else     { p[4 * i] = pack_bf16(k[0], k[2]); p[4 * i + 1] = pack_bf16(k[1], k[3]); p[4 * i + 2] = pack_bf16(k[4], k[6]); p[4 * i + 3] = pack_bf16(k[5], k[7]); }
  }
  sts128(dep(dep(dst, p[4] ^ p[5] ^ p[6], z), p[7], z) + slot * 8192, make_uint4(p[0], p[1], p[2], p[3]));
#pragma unroll
  for (int i = 0; i < 4; i++) q[i] = p[4 + i];
}
__device__ __forceinline__ void park_peer(const uint32_t (&q)[4], uint32_t dst, int slot, const ChainCtx& c) {
  const uint32_t bar = BAR(B_LAND);
  if (EXP_PEER) st_async4(mapa(dst + slot * 8192, c.b ^ 1), q[0], q[1], q[2], q[3], mapa(bar, c.b ^ 1));
  else touch((void*)(uintptr_t)(q[0] ^ q[1] ^ q[2] ^ q[3]), c.sb);
  mbar_arrive_warp(bar);
}
__device__ __forceinline__ uint32_t put_tag(uint32_t v, uint32_t bit, uint32_t t) {
  uint32_t r; asm("lop3.b32 %0, %1, %2, %3, 0x74;" : "=r"(r) : "r"(v), "r"(bit), "r"(t)); return r;
}
__device__ __forceinline__ void mem_proj(const uint32_t (&wa)[16][4], const uint32_t (&wb)[16][4], uint32_t (&wv)[16][4], uint32_t (&af)[16][4],
                                         uint32_t& wo, const char*& pa, uint32_t tab, uint32_t t16, uint32_t pk, const ChainCtx& c, int s) {
  const uint32_t mp = t16 & ~0x600u, id = NB_MEM + (t16 >> 11);
  uint32_t r[8][4];
  float la[4][4] = {}, lg[NLAG][4] = {}, lv[4][4] = {};
  auto lead = [&](int k) { mma_a(la[k & 3], wa[k], r[k >> 1][2 * (k & 1)], r[k >> 1][2 * (k & 1) + 1]); };
  auto lag = [&](int k) { mma_a(lg[k % NLAG], wb[k], r[k >> 1][2 * (k & 1)], r[k >> 1][2 * (k & 1) + 1]); };
  auto sum = [](const float (&d)[4][4], int i) { return (d[0][i] + d[1][i]) + (d[2][i] + d[3][i]); };
  bar_sync(id, 160);
  TR(s, 0);
#pragma unroll
  for (int i = 0; i < 4; i++) ldsm4t(r[i], mp + (c.sb + SM_MEM + i * 512));
  const uint4 tq = lds128(tab);
  bar_sync(id + 2, 160);
#pragma unroll
  for (int k = 0; k < 8; k++) lead(k);
  const uint32_t ta = tq.x | ((pk >> 16) & 511), tb = tq.z ^ ((pk >> 16) & 511);
  char* dst = mk_ptr(ta, tq.y);
  char* dst2 = mk_ptr(tb, tq.w);
  const uint32_t mp1 = dep(mp, __float_as_uint(la[C1_AT][0]) ^ ta ^ tb, c.sb);
#pragma unroll
  for (int i = 4; i < 8; i++) ldsm4t(r[i], mp1 + (c.sb + SM_MEM + 2048 + i * 512));
  const uint32_t hv = pk & 0xFFFF;
#pragma unroll
  for (int k = NV; k < NV + HV_E; k++) ldsm4t(wv[k], dep(hv, r[HV_R][0], c.sb) + (c.sb + SM_HV + (k - NV) * 2048));
#pragma unroll
  for (int k = 0; k < 8; k++) lag(k);
#pragma unroll
  for (int k = 8; k < 16; k++) lead(k);
  sts128((HV_E ? dep(t16, wv[NV][0] ^ wv[NV + HV_E / 2][1] ^ wv[NV + HV_E - (HV_E > 0)][2], c.sb) : t16) + (c.sb + SM_XCH), make_uint4(__float_as_uint(sum(la, 0)), __float_as_uint(sum(la, 1)), __float_as_uint(sum(la, 2)), __float_as_uint(sum(la, 3))));
  bar_sync(NB_XCH | ((t16 >> 9) & 3), 64);
  const uint4 o = lds128((t16 ^ 2048) + (c.sb + SM_XCH));
#pragma unroll
  for (int k = 8; k < 16; k++) lag(k);
  float t[4];
#pragma unroll
  for (int i = 0; i < 4; i++) {
    const float oi = __uint_as_float(i == 0 ? o.x : i == 1 ? o.y : i == 2 ? o.z : o.w);
    t[i] = NLAG == 4 ? (((lg[0][i] + lg[1][i]) + lg[2 % NLAG][i]) + lg[3 % NLAG][i]) + oi : NLAG == 3 ? (lg[1][i] + lg[2 % NLAG][i]) + (lg[0][i] + oi) : (lg[0][i] + oi) + lg[1][i];
  }
  const uint32_t y0 = put_tag(pack_bf16(t[0], t[2]), pk >> 31, s >> 1), y1 = put_tag(pack_bf16(t[1], t[3]), pk >> 31, s >> 1);
  st_pub(dst, y0); st_pub(dst2, y1);
  mbar_arrive_warp(BAR(B_E1TRIG));
  TR(s, 1);
  sched_fence(c.sb);
  const uint4 tv = lds128(tab + 16);
#pragma unroll
  for (int k = NV + HV_E; k < 16; k++) ldsm4t(wv[k], (k < NV + HV_E + HV_D ? hv : dep(hv, k == NV + HV_E + HV_D ? wv[k - HV_D][0] ^ tv.x : wv[k - HV_D][0], c.sb)) + (c.sb + SM_HV + (k - NV) * 2048));
  wo = (hv & 2047) | ((t16 & 2048) << 3);
  const uint32_t l8 = (t16 >> 1) & 255;
  char* dv = mk_ptr(tv.x | l8, tv.y);
  pa = mk_ptr(tv.z | l8, tv.w);
#pragma unroll
  for (int f = 0; f < WO_0; f++) ldsm4t(af[f], dep(wo, f < WO_D ? wv[16 - WO_D + f][0] : af[f < WO_D ? 0 : f - WO_D][0], c.sb) + (c.sb + SM_WO + (f & 1) * 32768 + (f >> 1) * 2048));
#pragma unroll
  for (int k = 0; k < 16; k++) mma_a(lv[k & 3], wv[k], r[k >> 1][2 * (k & 1)], r[k >> 1][2 * (k & 1) + 1]);
  const uint32_t z0 = put_tag(pack_bf16(sum(lv, 0), sum(lv, 1)), (~t16 >> 4) & 1, s >> 1), z1 = pack_bf16(sum(lv, 2), sum(lv, 3));
  st_pub2(dv, z0, z1);
  if (FIN_AT >= 3) mbar_arrive_warp(BAR(B_VST));
  TR(s, 2);
}
__device__ __forceinline__ uint32_t max_bf16x2(uint32_t a, uint32_t b) { uint32_t r; asm("max.bf16x2 %0, %1, %2;" : "=r"(r) : "r"(a), "r"(b)); return r; }
constexpr float SCL = 0.08838834764831845f * 1.4426950408889634f;
__device__ __forceinline__ uint32_t max5(const uint32_t (&sc)[5]) { return max_bf16x2(max_bf16x2(max_bf16x2(max_bf16x2(sc[0], sc[1]), sc[2]), sc[3]), sc[4]); }
__device__ __forceinline__ float row_off(uint32_t m, uint32_t& m1) {
  m1 = __shfl_xor_sync(~0u, m, 1);
  const uint32_t m2 = __shfl_xor_sync(~0u, m, 2), m3 = __shfl_xor_sync(~0u, m, 3);
  const uint32_t mm = max_bf16x2(max_bf16x2(max_bf16x2(m, m1), m2), m3);
  return -SCL * fmaxf(__uint_as_float(mm << 16), __uint_as_float(mm & 0xFFFF0000u));
}
__device__ __forceinline__ void unpack(float (&f)[10], const uint32_t (&sc)[5]) {
#pragma unroll
  for (int i = 0; i < 5; i++) {
    asm volatile("shl.b32 %0, %1, 16;" : "=f"(f[2 * i]) : "r"(sc[i]));
    asm volatile("and.b32 %0, %1, 0xffff0000;" : "=f"(f[2 * i + 1]) : "r"(sc[i]));
  }
}
__device__ __forceinline__ uint32_t exp_pair(const float (&f)[10], int i, float off) {
  return pack_bf16(ex2(fmaf(f[2 * i], SCL, off)), ex2(fmaf(f[2 * i + 1], SCL, off)));
}
template<bool SPLIT> __device__ __forceinline__ void scores_x(float (&a)[2][4], const uint4 (&kf)[4], const uint4& q, uint32_t z) {
#pragma unroll
  for (int t = 0; t < 2; t++) { a[t][0] = a[t][1] = a[t][2] = a[t][3] = 0.f; }
  mma_q(a[0], kf[0], q.x, q.y); mma_q(a[1], kf[2], q.x, q.y);
  if (SPLIT) sched_fence(z);
  mma_q(a[0], kf[1], q.z, q.w); mma_q(a[1], kf[3], q.z, q.w);
}
__device__ __forceinline__ uint32_t scores_m(const uint4& q, const uint4& k) {
  float a[4] = {}, b[4] = {};
  mma_q(a, q, k.x, k.z); mma_q(b, q, k.y, k.w);
  return pack_bf16(a[0] + b[2], a[1] + b[3]);
}
__device__ __forceinline__ void store_scores(const float (&a)[2][4], uint32_t dst) {
  sts64(dst, pack_bf16(a[0][0], a[0][2]), pack_bf16(a[1][0], a[1][2]));
  sts64(dst + 320, pack_bf16(a[0][1], a[0][3]), pack_bf16(a[1][1], a[1][3]));
}
__device__ __forceinline__ uint32_t sum4(uint32_t a, uint32_t b, uint32_t d, uint32_t e) { return add_bf16x2(add_bf16x2(a, b), add_bf16x2(d, e)); }
__device__ __forceinline__ void load_scores(uint32_t (&sc)[5], uint32_t ax, uint32_t am) {
  uint4 p[4];
#pragma unroll
  for (int i = 0; i < 4; i++) p[i] = lds128(ax + i * 1280);
  const uint2 m0 = lds64(am), m1 = lds64(am + 256);
  const uint4 t = add4(add4(add4(p[0], p[1]), p[2]), p[3]);
  sc[1] = t.x; sc[2] = t.y; sc[3] = t.z; sc[4] = t.w;
  sc[0] = sum4(m0.x, m0.y, m1.x, m1.y);
}
constexpr uint32_t ONES = 0x3F803F80u;
__device__ __forceinline__ float pv(float (&o)[2][4], const uint32_t (&p)[5], const uint4 (&vf)[4], const uint4& vm) {
  float a[4] = {}, b[4] = {};
#pragma unroll
  for (int t = 0; t < 2; t++) { o[t][0] = o[t][1] = o[t][2] = o[t][3] = 0.f; }
  mma_q(o[0], vf[0], p[1], p[2]); mma_q(o[1], vf[2], p[1], p[2]);
  mma_q(o[0], vf[1], p[3], p[4]); mma_q(o[1], vf[3], p[3], p[4]);
  mma16816(a, p[1], p[2], p[3], p[4], ONES, ONES);
  mma1688(o[0], vm.x, vm.y, p[0]); mma1688(o[1], vm.z, vm.w, p[0]);
  mma1688(b, p[0], ONES, ONES);
  return (a[0] + a[2]) + b[0];
}
constexpr uint32_t POLL_LIMIT = 1u << 21;
__device__ __forceinline__ uint32_t box(int slot, int cta) { return (slot * 2 + (cta >> 6)) * M_REG + (cta & 63) * 16384; }
__device__ __forceinline__ uint32_t near_page(const ChainCtx& c, int cta, uint32_t off) {
  return off + (((lds32(c.sb + SM_SEL + cta * 4) >> (off >> 21)) ^ __popc(off & 0xB2000)) & 1) * 4096;
}
__device__ __forceinline__ uint32_t e1_box(const ChainCtx& c, int slot, int cta) { return near_page(c, E1OFF ? cta ^ 2 : cta, box(slot, cta) + 8192) ^ (E1OFF ? 0 : 4096); }
__device__ __forceinline__ uint32_t tile_key() {
  uint32_t sm; asm volatile("mov.u32 %0, %%smid;" : "=r"(sm));
  return (sm < 64 ? sm / 2 % 8 : sm < 120 ? 1 + (sm / 2 - 32) % 7 : 0) << 24 | sm << 16;
}
__device__ __forceinline__ uint32_t ox_at(int s, int row, int g, int jj) { return s * 131072 + ((g >> 1) * 32 + row) * 64 + (g & 1) * 32 + 8 * jj; }
__device__ __forceinline__ int tile_of(const ChainCtx& c) { return SIDE ? __shfl_sync(~0u, lds32(c.sb + SM_SEL + 528), 0) : c.r; }

__global__ void __cluster_dims__(2, 1, 1) __launch_bounds__(512, 1)
chain_kernel(const __grid_constant__ CUtensorMap tq, const __grid_constant__ CUtensorMap tk, const __grid_constant__ CUtensorMap tv,
             const __grid_constant__ CUtensorMap tv16, const __grid_constant__ CUtensorMap to, const __grid_constant__ CUtensorMap tx,
             const __grid_constant__ CUtensorMap twr, const __grid_constant__ CUtensorMap twi,
             const __grid_constant__ CUtensorMap ta, const __grid_constant__ CUtensorMap tw,
             const __grid_constant__ CUtensorMap tb, const __grid_constant__ CUtensorMap tout, const __grid_constant__ CUtensorMap tz,
             const __grid_constant__ CUtensorMap tzs, const __grid_constant__ CUtensorMap ta32,
             const __nv_bfloat16* __restrict__ mem0, char* __restrict__ mail, const __nv_bfloat16* __restrict__ x,
             const __nv_bfloat16* __restrict__ gw) {
  extern __shared__ __align__(1024) unsigned char smraw[];
  if (threadIdx.x == 0) TL(0);
  ChainCtx c;
  c.sb = __shfl_sync(~0u, smem_u32(smraw), 0);
  c.mail = mail; c.sel = 0; c.r = blockIdx.x;
  if (ROLE) {
    const uint32_t u = blockIdx.x >> 1, n = u < 36 ? 8 : 7, k = u - (u < 36 ? 4 : 36), q = k * (u < 36 ? 32 : 37) >> 8;
    c.r = __shfl_sync(~0u, 2 * (u - 4 < 60 ? u + k - q * n - (q & 1) * (n - 1) : u) + (blockIdx.x & 1) + (threadIdx.x >> 9), 0);
  }
  c.h = c.r >> 2; c.a = (c.r >> 1) & 1; c.b = c.r & 1; c.j = c.r & 3;
  c.m = __shfl_sync(~0u, (int)(threadIdx.x >> 7), 0); c.w = __shfl_sync(~0u, (int)((threadIdx.x >> 5) & 3), 0);
  char* own = c.mail + (uint32_t)(c.w * M_REG + M_E3 + (c.r >> 5) * 8192 + (c.r & 31) * 128 + (threadIdx.x & 31) * 4);
  uint32_t i0 = 0, i1 = 0;
  if (EARLY) asm volatile("{ .reg .pred p; setp.ne.u32 p, %4, 0; @p atom.relaxed.gpu.global.exch.b32 %0, [%2], %3; @p atom.relaxed.gpu.global.exch.b32 %1, [%2 + 4096], %3; }"
               : "+r"(i0), "+r"(i1) : "l"(own), "r"(SENT), "r"((uint32_t)(c.m == 2 && c.r < 128)) : "memory");
#pragma unroll
  for (int g = 0; g < 3; g++) {
    const int i = c.m * 4 + c.w;
    if (g < 2 || i < B_END - 32)
      asm volatile("{ .reg .pred p; elect.sync _|p, 0xffffffff; @p mbarrier.init.shared::cta.b64 [%0], %1; }"
                   :: "r"(BAR(g * 16 + i)), "r"(0x19080401u >> (bar_codes(g) >> 2 * i & 3) * 8 & 255) : "memory");
  }
  asm volatile("fence.mbarrier_init.release.cluster;" ::: "memory");
  __syncthreads();
  asm volatile("barrier.cluster.arrive.relaxed.aligned;" ::: "memory");

  if (c.r >= 128) {
    fft_cols((float2*)smraw, c.r - 128, &twr, &twi, &tzs);
    if ((threadIdx.x & 127) == 0) TL(7);
    __syncwarp();
  } else if (c.m == 3) {
    asm volatile("setmaxnreg.dec.sync.aligned.u32 %0;" :: "n"(REG_H));
    c.lane = lane_id();
    if (c.sb & 1023) asm volatile("trap;");
    const int col = c.h * 128 + c.a * 64;
    uint32_t tl = clock_lo();
    TR(-2, 3);
    if (c.w == 0) {
      if (START) delay_until(tl + START);
      if (HOLD == 2) mbar_wait(BAR(B_PROBE), 0);
      if (HOLD == 3) mbar_wait(BAR(B_SEL), 0);
      if (HOLD == 1) mbar_wait(BAR(B_PROBE), 0);
      TR(-2, 4);
      tl = clock_lo();
      mbar_expect_e(BAR(B_PFULL), 2 * NP * 2048);
      mbar_expect_e(BAR(B_WFULL), (48 - NP) * 2048);
      mbar_expect_e(BAR(B_WFULL + 1), (48 - NP) * 2048);
    }
    auto dst_x = [&](int e, int w) {
      const uint32_t g2 = 2 * c.a + (w >> 1), u = w & 1;
      return M_KVQ + c.h * 24576 + (e == 0 ? 8192 + (2 * u + c.b) * 2048 + g2 * 512 : e == 1 ? g2 * 2048 + u * 1024 + c.b * 128 : 16384 + c.b * 4096 + g2 * 512 + u * 256);
    };
    if (c.w == 0) {
      tl += PACE0;
#pragma unroll wunr
      for (int i = 0; i < 24; i++) {
        const int m = i < 4 || i >= 16, k = i < 4 ? i : m ? i - 12 : i - 4;
        const int row = c.b * 512 + m * 256;
        const uint32_t st = c.sb + m * ST_WG, bar = BAR(k < 3 ? B_PFULL : B_WFULL + m);
        if (PACE) delay_until(tl += PACE);
        if (i == 14) { mbar_wait(BAR(B_FREE), 0); if (c.lane == 0) TL2(2); __syncwarp(); }
        if (k < 11) TMA_W(k < 3 ? c.sb + SM_POOL + m * NP * 2048 + k * 8192 : k == 3 ? c.sb + SM_HV + (m * NHV + 1) * 2048 : st + (k - 4) * 8192,
                          k == 3 || k > 8 ? &tv : (k >> 2 & 1) == m ? &tk : &tq, col, row + (k < 8 ? k & 3 : (k - 9) & 3) * 64, bar);
        else {
#pragma unroll 1
          for (int j = 8; j < 12; j++) TMA_W(j < NV ? st + (32 - NP + j) * 2048 : c.sb + SM_HV + m * NHV * 2048, &tv16, col, row + j * 16, bar);
        }
      }
      TR(-2, 7);
    } else if (c.w == 2) {
      const unsigned short* mp = (const unsigned short*)mem0 + (2 * (c.lane & 3)) * D_ + 8 * c.r + (c.lane >> 2);
      uint32_t mv = (uint32_t)mp[0] | (uint32_t)mp[D_] << 16;
      if (mv == SENT) mv = 0x7FFF7FFFu;
      mbar_wait(BAR(B_PROBE), 0);
      char* dst = c.mail + (uint32_t)(M_E3 + (c.r >> 5) * 8192 + (c.r & 31) * 128 + c.lane * 4);
      st_pub(dst, mv); st_pub(dst + 4096, mv);
    } else if (c.w == 3) {
      mbar_wait(BAR(B_FREE), 0);
      mbar_wait(BAR(B_PFULL), 0);
      mbar_expect_e(BAR(B_PFULL), 65536);
      for (int i = 0; i < 2; i++) tma4d_e(c.sb + SM_XT + i * 16384, &tx, c.b * 8, 4 + 2 * (c.b ^ i), BAR(B_PFULL));
    }
    {
      mbar_wait(BAR(B_SEL), 0);
      const int i = tid_now() & 127, sl = i & 3, e = (i >> 2) & 3;
      uint32_t ox = dst_x(e, i >> 5) + sl * M_REG;
      uint32_t oh = e & 1 ? (sl ^ (e & 2)) * M_REG + M_E3 + (c.r >> 5) * 8192 + (c.w & 1) * 4096 + (c.r & 31) * 128
                          : near_page(c, c.r, e ? sl * M_REG + M_E3 + (c.b * 2 + (c.w >> 1)) * 8192 : box(~sl & 1, c.r)) + (e ? (c.w & 1) * 2048 : c.w * 1024), of;
      {
        const int e = i & 7, w = (i >> 3) & 3, m = (i >> 5) & 1, sl = i >> 6;
        const int cta = e < 2 ? c.r & ~1 : e == 2 ? c.r | 1 : e == 3 ? c.h * 4 + 2 * m + 1 : c.j * 32 + m * 8 + 2 * w + (e & 2) * 8 + (e & 1);
        const uint32_t off = e < 2 ? c.b * 2048 + m * 1024 + (w >> 1) * 512 + e * 160 : e == 2 ? c.b * 2048 + m * 1024 + w * 256 : e == 3 ? w * 256 : c.h * 128;
        of = (e < 4 ? e1_box(c, sl, cta) : near_page(c, cta, box(sl, cta))) + off;
      }
      char *px = c.mail + ox, *ph = c.mail + oh, *pf = c.mail + of;
      uint32_t at = sl * 128 + (i >> 5) * 32 + e * 8, af = i * 8;
      pin(px); pin(ph); pin(pf); pin(at); pin(af);
      asm volatile("barrier.cluster.wait;" ::: "memory");
      TR(-2, 0);
      mbar_wait(BAR(B_WREAD), 0);
      TR(-2, 1);
      mbar_arrive_both(BAR(B_LFREE), c.b ^ 1);
      sts64(at + (c.sb + SM_TAB + 1536), (uint32_t)(uintptr_t)px, (uint32_t)((uintptr_t)px >> 32));
      sts64(at + (c.sb + SM_TAB + 1024), (uint32_t)(uintptr_t)ph, (uint32_t)((uintptr_t)ph >> 32));
      sts64(af + (c.sb + SM_TAB), (uint32_t)(uintptr_t)pf, (uint32_t)((uintptr_t)pf >> 32));
      TR(-2, 2);
      if (tid_now() == 384) TL2(25);
      __syncwarp();
      bar_sync(14, 160);
    }
    pad<PAD3>();
    for (int s = -1; s < NSEG; s++) {
      if (E30 ? s != 0 : s >= 0) {
        const uint32_t tab = c.sb + SM_TAB + 1024 + (max(s, 0) & 3) * 128 + c.w * 32;
        uint32_t t0;
        if (s > 0) {
          const uint32_t ln = tid_now() & 31;
          const uint4 ta = lds128(tab);
          const char* src = mk_ptr(ta.x | ln * 4, ta.y);
          char* dst = mk_ptr(ta.z | ln * 4, ta.w);
          const uint32_t tg = (s - 1) >> 1, chk = (ln & 3) ? 0u : 1u, red = ln * (RED_L == 3 ? 4 : 8);
          touch(src, dep(c.sb, chk, c.sb)); touch(dst, dep(c.sb, red, c.sb));
          mbar_wait(BAR(B_E2TRIG), (s - 1) & 1);
          TR(s, 0);
          if (ANCH2) delay_fine(lds32(c.sb + SM_SUM + 64) + DLY_E2); else delay_cycles(DLY_E2);
          uint32_t n = 0;
          while (true) {
            uint32_t v[8];
#pragma unroll
            for (int i = 0; i < 8; i++) v[i] = ld_poll1(src + i * 128);
            if (E2_F) sched_fence(c.sb);
            const uint32_t bad = RED_T ? (stale2(v[0], v[1], tg) | stale2(v[2], v[3], tg) | stale2(v[4], v[5], tg)) | stale2(v[6], v[7], tg)
                                       : stale1(stale1(stale2(v[0], v[1], tg), v[2], tg), v[3], tg) | stale1(stale1(stale2(v[4], v[5], tg), v[6], tg), v[7], tg);
            const bool ok = all_clear(bad, chk);
#pragma unroll
            for (int l = 0; l < RED_L; l++)
#pragma unroll
              for (int i = 0; i < (4 >> l); i++) v[i] = add_bf16x2(v[2 * i], v[2 * i + 1]);
            if (RED_L == 3) sts32(red + (c.sb + SM_RED + c.w * 128), v[0]);
            else {
              float lo[8], hi[8];
#pragma unroll
              for (int i = 0; i < (8 >> RED_L); i++) { lo[i] = __uint_as_float(v[i] << 16); hi[i] = __uint_as_float(v[i] & 0xFFFF0000u); }
#pragma unroll
              for (int l = RED_L; l < 3; l++)
#pragma unroll
                for (int i = 0; i < (4 >> l); i++) { lo[i] = lo[2 * i] + lo[2 * i + 1]; hi[i] = hi[2 * i] + hi[2 * i + 1]; }
              sts64(red + (c.sb + SM_RED + c.w * 256), __float_as_uint(lo[0]), __float_as_uint(hi[0]));
            }
            if (ok) break;
            n++; CNT(0);
          }
          bar_sync(NB_HELP, 128);
          const uint32_t rd = red + (c.sb + SM_RED);
          if (!RED_P || c.w < 2) {
            if (RED_L == 3) st_pub_if(dst, sum4(lds32(rd), lds32(rd + 128), lds32(rd + 256), lds32(rd + 384)), c.w < 2);
            else {
              const uint2 p0 = lds64(rd), p1 = lds64(rd + 256), p2 = lds64(rd + 512), p3 = lds64(rd + 768);
              st_pub_if(dst, pack_bf16((__uint_as_float(p0.x) + __uint_as_float(p1.x)) + (__uint_as_float(p2.x) + __uint_as_float(p3.x)),
                                       (__uint_as_float(p0.y) + __uint_as_float(p1.y)) + (__uint_as_float(p2.y) + __uint_as_float(p3.y))), c.w < 2);
            }
          }
          t0 = clock_lo();
          mbar_arrive_warp(BAR(B_PUB));
          TRV(s, 15, n);
          mbar_wait(BAR(B_SPFREE), (s - 1) & 1);
        } else {
          if (tid_now() == 384) TL2(24);
          __syncwarp();
          if (!E30) mbar_wait(BAR(B_PROBE), 1);
          if (!WO_S) mbar_wait(BAR(B_WOFULL), 0);
          if (tid_now() == 384) TL2(19);
          __syncwarp();
          t0 = clock_lo() - DLY_E3;
        }
        TRV(s, 1, t0);
        {
          const uint32_t l16 = (tid_now() & 31) * 16, dst = vary(l16, s, c.sb) + (c.sb + SM_MEM + (c.w & 1) * 4096 + (c.w >> 1) * 2048);
          const uint4 tb = lds128(tab + 16);
          st_pub_if(mk_ptr(tb.z | l16 >> 2, tb.w), SENT, c.w >= 2);
          const char* src = mk_ptr(tb.x | l16, tb.y);
          touch(src, dep(c.sb, dst, c.sb));
          delay_fine(t0 + (DLY_E3 + (c.w & 1) * DLY_E3B));
          uint32_t n = 0;
          while (true) {
            uint4 v[4];
#pragma unroll
            for (int i = 0; i < 4; i++) v[i] = ld_poll(src + i * 512);
#pragma unroll
            for (int i = 0; i < 4; i++) sts128(dst + i * 512, v[i]);
            if (arrive_if_all(max(max(v[0].x, v[1].x), max(v[2].x, v[3].x)) != SENT, NB_MEM + (c.w & 1) * 2 + (c.w >> 1), 160)) break;
            n++; CNT(1);
          }
          TR(s, 2); TRV(s, 14, n);
        }

        if (s == 1) CLK(1); if (s == 8) CLK(2); if (s == 56) CLK(3);
        if (c.w == 2 && s == 15) TRSYNC(8);
        if (c.w == 2 && s == 21) TRSYNC(10);
      }
      const int g = s + 1;
      auto load_v = [&]() {
        if (V_TMA && c.w == V_W) {
          mbar_expect_e(BAR(B_VFULL), 8192);
          bulk_load_e(c.sb + SM_V, c.mail + (uint32_t)(M_KVQ + (min(g, XEND - 1) & (NSLOT - 1)) * M_REG + c.h * 24576 + 8192), 8192, BAR(B_VFULL));
        }
      };
      if (XEND < NSEG && g >= XEND && g < NSEG) { mbar_wait(BAR(B_SC), s & 1); load_v(); }
      if (g < XEND) {
        const uint32_t tx_ = c.sb + SM_TAB + 1536 + (g & 3) * 128 + c.w * 32, tag = (g >> 2) & 1;
        if (c.w == 0) mbar_expect_e(BAR(B_LAND), EXP_PEER * 12288);
        auto load_x = [&]() {
          if (c.w == 3 && g + 1 < XEND) {
            mbar_wait(BAR(B_XEMPTY), g & 1);
            mbar_expect_e(BAR(B_XFULL), 16384 * EXP_NXT);
            for (int i = 0; i < EXP_NXT; i++) tma4d_e(c.sb + SM_XT + i * 16384, &tx, c.b * 8, (g + 1) * 4 + 2 * (c.b ^ i), BAR(B_XFULL));
          }
        };
        if (X_AT == 0 && g > 0) load_x();
        TR(s, 6);
        if (E30 && g == 0) mbar_wait(BAR(B_PROBE), 1);
        mbar_wait(BAR(B_LAND), g & 1);
        TR(s, 7);
        if (DLY_F && g > 0) delay_cycles(DLY_F);
        auto total = [&](int w, int lane, uint32_t o0, uint32_t o1) {
          const uint32_t a = c.sb + SM_LAND + land_off(w, lane);
          if (EXP_FL == 1) return make_uint4(a, a, a, a);
          const uint4 t = add4(lds128(a + o0), lds128(a + o1 + 2048));
          const uint32_t a2 = dep(dep(a, t.x ^ t.y ^ t.z, c.sb), t.w, c.sb);
          return add4(t, add4(lds128(a2 + o0 + 4096), lds128(a2 + o1 + 6144)));
        };
        auto get = [&](int e) {
          const int ln = tid_now() & 31;
          return e == 0 ? total(c.w, ln, 16384, 16384)
               : e == 1 ? total((c.w & 2) + ((ln >> 1) & 1), (ln & 1) * 16 + (c.w & 1) * 8 + (ln >> 2), 8192, 0)
                        : total((c.w & 2) + ((ln >> 1) & 1), (ln & 1) * 16 + (ln >> 3) * 4 + (c.w & 1) * 2 + ((ln >> 2) & 1), 0, 8192);
        };
        auto put = [&](int e, uint4 v) {
          const int ln = tid_now() & 31;
          const uint2 d = lds64(tx_ + e * 8);
          if (e < 2) {
            v.x = tagged(v.x, tag);
            st_pub4(mk_ptr(d.x | (e ? (ln & 24) * 32 + (ln & 7) * 16 : ln * 16), d.y), v);
          } else {
            char* dst = mk_ptr(d.x | ((ln & 7) * 16 + (ln >> 3) * 4), d.y);
            const uint32_t bit = ln < 8;
            st_pub(dst, put_tag(v.x, bit, tag)); st_pub(dst + 128, put_tag(v.y, bit, tag));
            st_pub(dst + 2048, put_tag(v.z, bit, tag)); st_pub(dst + 2176, put_tag(v.w, bit, tag));
          }
        };
        auto after_sc = [&]() { if (g > 0) { mbar_wait(BAR(B_SC), s & 1); if (DLY_FK) delay_cycles(DLY_FK); if (X_AT == 1) load_x(); } };
        if (FIN_AT == 5) {
          put(0, get(0));
          if (DLY_F2 && g > 0) delay_cycles(DLY_F2); else sched_fence(c.sb);
          const uint4 k = get(1);
          sched_fence(c.sb);
          const uint4 q = get(2);
          if (g > 0) mbar_wait(BAR(B_VST), s & 1);
          put(1, k); put(2, q);
          TR(s, 5);
          mbar_arrive_both(BAR(B_LFREE), c.b ^ 1);
          after_sc();
          load_v();
          continue;
        }
        if (FIN_AT < 3) {
          if (EXP_FIN & 1) put(0, get(0));
          TR(s, 3);
          if (FIN_AT == 1) after_sc();
          if (V_TMA == 1) load_v();
          if (EXP_FIN & 2) put(1, get(1));
        } else {
          const uint4 v = get(0);
          sched_fence(c.sb);
          const uint4 k = get(1);
          if (g > 0) { mbar_wait(BAR(B_VST), s & 1); if (DLY_FS) delay_cycles(DLY_FS); }
          put(0, v); put(1, k);
        }
        TR(s, 4);
        if (FIN_AT == 4) {
          const uint4 q = get(2);
          after_sc();
          load_v();
          put(2, q);
        } else {
          if (FIN_AT >= 2) after_sc();
          if (V_TMA == 2) load_v();
          if (EXP_FIN & 4) put(2, get(2));
        }
        mbar_arrive_both(BAR(B_LFREE), c.b ^ 1);
        if (V_TMA == 3) load_v();
        TR(s, 5);
        if (!FIN_AT && X_AT && g > 0) { mbar_wait(BAR(B_SC), s & 1); if (DLY_FK) delay_cycles(DLY_FK); load_x(); }
      }
    }
    const int tile = tile_of(c), s0 = (tile >> 3) * 4, n0 = (tile & 7) * 128;
    if (c.w == 1) {
      mbar_wait(BAR(B_PVDONE), 0);
      count_e(g_ctl + (EARLY2 ? C_LAST : C_EARLY));
      st_pub(c.mail + (uint32_t)((tid_now() & 6) * (M_REG / 2) + M_SEL + (tid_now() & 1) * 4096 + c.r * 4), 0);
      await_count(g_ctl + C_COLS, 4);
      mbar_expect_e(BAR(B_TW), 8192);
      bulk_load_e(c.sb + SM_TW, g_tw, 8192, BAR(B_TW));
    } else if (c.w == 2) {
      const uint32_t ln = tid_now() & 31, rel = mapa(BAR(B_GEMPTY) + (ln >> 2) * 8, ln & 1);
      mbar_wait(BAR(B_VST), 1); mbar_wait(BAR(PRE_AT), 1);
      arrive_remote_if(rel, ln < 12);
      mbar_wait(BAR(B_E2TRIG), 1);
      if (GATE) mbar_wait(BAR(B_DONE), 0);
      arrive_remote_if(rel, ln >= 12 && ln < 20);
    } else {
      auto ahead = [&](int k) {
        if (c.w) { if (PF_A && (k & 3) == (tile >> 1 & 3)) prefetch3d_e(&ta, k * 32, s0 + 2 * c.b); }
        else if (PF_B && (k & 7) == (tile >> 4)) prefetch2d_e<(ONCE & 512) != 0>(&tw, n0 + (tile & 8) * 8, k * 64);
      };
#pragma unroll 1
      for (int k = 0; k < PF_D; k++) ahead(k);
      if (c.w == 3) await_count(g_ctl + C_EARLY, 128);
      const int skew = tile < 120 ? 0 : SKEW;
      uint32_t o = SM_XT, st = 0, ph = 0;
#pragma unroll 1
      for (int kb = 0; kb < 64 + skew; kb++, o = next_stage(o)) {
        const bool solo = kb < skew || kb >= 64;
        const uint32_t bar = BAR(B_GFULL + st), k = kb & 63;
        if (c.w && kb == skew) {
          if (tile >= 120) await_count(g_ctl + C_LAST, EARLY2 ? 640 : 512);
          if (tid_now() == 480) TL(10);
          __syncwarp();
        }
        mbar_wait(BAR(B_GEMPTY + st), ph);
        if (c.w) {
          const int r = solo ? (kb >> 5) + c.b : c.b * 2;
          tma3d_mc_e(c.sb + o + r * 4096, solo ? &ta32 : &ta, k * 32, s0 + r, bar);
        } else {
          mbar_expect_e(bar, solo ? 24576 : 32768);
          tma2d_o<(ONCE & 2) != 0>(c.sb + o + 16384, &tw, n0, k * 64, bar);
          tma2d_o<(ONCE & 2) != 0>(c.sb + o + 24576, &tw, n0 + 64, k * 64, bar);
        }
        if (kb + PF_D < 64) ahead(kb + PF_D);
        if (++st == 5) { st = 0; ph ^= 1; }
      }
    }
    return;
  } else if (c.m == 2) {
    asm volatile("setmaxnreg.dec.sync.aligned.u32 %0;" :: "n"(512 - 2 * REG_F - REG_H));
    c.lane = lane_id();
    {
      uint32_t tl = clock_lo() + (PACE0 + WO_AT * PACE);
      TR(-2, 0);
      sched_fence(i0 ^ i1);
      TR(-2, 7);
      int far1 = 0;
#pragma unroll 1
      for (int rep = EARLY; rep <= NPROBE; rep++) {
        const int lag = race_init(own + (rep & 1) * 4096, own + (~rep & 1) * 4096, SENT);
        if (rep) far1 += ((rep ^ c.r >> 5) & 1 ? 1 : -1) * min(lag, 200);
      }
      sts32(c.sb + SM_SEL + 512 + c.w * 4, (8 + far1 / (16 * NPROBE)) << 4 * c.w);
      TR(-2, 1);
      if (tid_now() == 256) TL2(14);
      __syncwarp();
      mbar_arrive_warp(BAR(B_PROBE));
      if (c.w == 0) {
        mbar_wait(BAR(B_PROBE), 0);
        const uint4 bits = lds128(c.sb + SM_SEL + 512);
        const uint32_t res = bits.x | bits.y | bits.z | bits.w;
        st_pub_if(c.mail + (uint32_t)((c.lane & 6) * (M_REG / 2) + M_SEL + (c.lane & 1) * 4096 + c.r * 4), res | tile_key(), c.lane < 8);
        const int q = (res >> 4 * ((c.lane + c.r) & 3) & 15) - 8, best = __reduce_max_sync(~0u, abs(q) * 64 + (c.lane & 3) * 16 + ((c.lane + c.r) & 3) * 2 + (q <= 0));
        const char* src = c.mail + (uint32_t)((best & 6) * (M_REG / 2) + M_SEL + (best & 1) * 4096 + c.lane * 16);
        if (SEL_AT) delay_until(tl - (PACE0 + WO_AT * PACE - SEL_AT));
        uint4 v; uint32_t n = 0;
        TR(-2, 4);
        while (true) {
          delay_cycles(DLY_SEL);
          TR(-2, 6);
          v = ld_poll(src);
          if (__all_sync(~0u, v.x && v.y && v.z && v.w)) break;
          watchdog(n, POLL_LIMIT);
        }
        TR(-2, 5);
        int ta = 0, tb = 0, pa = 0, pb = 0;
        uint32_t flip = 0;
#pragma unroll 1
        for (int i = 0; i < 4; i++) {
          const int a = (v.x >> 4 * i & 15) + (v.y >> 4 * i & 15) - 16, b = (v.z >> 4 * i & 15) + (v.w >> 4 * i & 15) - 16;
          const bool f = __reduce_add_sync(~0u, a * ta + b * tb) < 0;
          ta += f ? -a : a; tb += f ? -b : b; flip |= (uint32_t)f << i;
        }
#pragma unroll 1
        for (uint32_t g = 0; g < 8; g++) {
          const bool a = (v.x >> 16) - g * 256 < 120, b = (v.z >> 16) - g * 256 < 120;
          const int n = __reduce_add_sync(~0u, (a ? ta : 0) + (b ? tb : 0)) > 0 ? PRIOR : -PRIOR;
          if (a) pa = n;
          if (b) pb = n;
        }
        const uint32_t ka = AWARE && ta + pa > 0 ? ~flip : flip, kb = AWARE && tb + pb > 0 ? ~flip : flip;
        sts128(c.sb + SM_SEL + c.lane * 16, make_uint4(ka, ka, kb, kb));
        mbar_arrive_warp(BAR(B_SEL));
        const uint32_t key = __shfl_sync(~0u, c.a ? v.z : v.x, c.h);
        const int u = __popc(__ballot_sync(~0u, v.x < key)) + __popc(__ballot_sync(~0u, v.z < key));
        sts32(c.sb + SM_SEL + 528, (u & 32) * 2 + (u & 7) * 8 + (u >> 2 & 6) + c.b);
        TR(-2, 2);
        if (c.lane == 0) TL2(13);
        __syncwarp();
        bar_sync(14, 160);
        if (ZDLY) delay_cycles(ZDLY);
#pragma unroll 4
        for (int k = c.lane >> 3; k < (ZINIT ? 128 : 0); k += 4) {
          const int e = k & 7;
          const uint2 d = lds64(c.sb + SM_TAB + (e == 3 ? k - 1 : k) * 8);
          st_pub4(mk_ptr((d.x & ~127u) + (e < 2 ? (k & 8) * 32 : e == 3 ? 128 : 0) + (c.lane & 7) * 16, d.y), make_uint4(0, 0, 0, 0));
        }
        __syncwarp();
        if (c.lane < 4) asm volatile("mbarrier.arrive.shared::cta.b64 _, [%0];" :: "r"(BAR(B_PROBE)) : "memory");
        __syncwarp();
        TR(-2, 8);
      }
      if (c.w == 2) {
        mbar_wait(BAR(B_P1), 0);
        if (P1_AT) { mbar_wait(BAR(B_WFULL), 0); mbar_wait(BAR(B_WFULL + 1), 0); }
        st_pub_if(g_ctl + C_COLS + (c.r & 15) * 32 + c.lane, 0, c.r < (C_END - C_COLS) / 32);
        count_e(g_ctl + C_P1);
        TR(-2, 3);
      }
      if (c.w == 1) for (int i = 0; i < WO_N; i++) { delay_until(tl += WO_P * PACE); prefetch2d_e(&to, c.j * 256 + (i ^ WO_X) * 64, c.h * 128); }
      if (c.w == 3) {
        mbar_wait(BAR(B_WREAD0), 0);
        for (int i = 0; i < 2; i++) tma4d_e(c.sb + SM_WO + i * 16384, &tx, c.b * 8, 2 * (c.b ^ i), BAR(B_PFULL));
        mbar_expect_e(BAR(B_WOFULL), 65536);
#pragma unroll 1
        for (int i = 3; i >= 0; i--) {
          if (i & 1) mbar_wait(BAR(i < 2 ? B_XEMPTY : B_WREAD), 0);
          TMA_O(c.sb + SM_WO + i * 16384, &to, c.j * 256 + i * 64, c.h * 128, BAR(B_WOFULL));
        }
      }
    }
    asm volatile("barrier.cluster.wait;" ::: "memory");
    const int g = c.w, src0 = c.h * 4 + (g >> 1) * 2;
    mbar_wait(BAR(B_SEL), 0);
    c.sel = __shfl_sync(~0u, (e1_box(c, 0, src0 + (c.lane >> 5)) & 4096) | (e1_box(c, 1, src0) & 4096) * 2, 0);
    mbar_wait(BAR(B_WREAD), 0);
    uint32_t l16 = c.sb + g * 512 + c.lane * 16;
    auto lane = [&](uint32_t v) { l16 = dep(l16, v, c.sb); return (int)((l16 & 511) >> 4); };
    pad<PAD2>();
    for (int s = 0; s < NSEG; s++) {
      l16 = vary(l16, s, c.sb);
      int ln = (l16 & 511) >> 4;
      uint4 kf[4], qx;
      {
        const int gs = min(s, XEND - 1);
        const char* pk = c.mail + (uint32_t)(M_KVQ + (gs & (NSLOT - 1)) * M_REG + c.h * 24576 + g * 2048 + ln * 16);
        const char* pq = pk + (16384 + c.j * 2048 - g * 1536);
        const uint32_t tg = (gs / NSLOT) & 1;
        touch(pk, c.sb); touch(pq, c.sb);
        TR(s, 0);
        mbar_wait(BAR(B_VFULL), s & 1);
        TR(s, 1);
        if (s > 0) mbar_wait(BAR(B_PUB), (s - 1) & 1);
        for (uint32_t n = 0; ; ) {
          uint4 k[4];
#pragma unroll
          for (int t = 0; t < 4; t++) k[t] = ld_poll(pk + t * 512);
          qx = ld_poll(pq);
#pragma unroll
          for (int t = 0; t < 2; t++) {
            auto cp = [&](uint32_t v) { return dep(v, 0, c.sb); };
            kf[t] = make_uint4(cp(k[2 * t].x), cp(k[2 * t].y), cp(k[2 * t + 1].x), cp(k[2 * t + 1].y));
            kf[2 + t] = make_uint4(cp(k[2 * t].z), cp(k[2 * t].w), cp(k[2 * t + 1].z), cp(k[2 * t + 1].w));
          }
          if (all_clear(stale1(stale2(k[0].x, k[1].x, tg) | stale2(k[2].x, k[3].x, tg), qx.x, tg), EXP_CHK)) break;
          watchdog(n, POLL_LIMIT); CNT(4);
        }
        TR(s, 2);
      }
      if (X_AT >= 2 && g == 0 && s + 2 < XEND) {
        mbar_wait(BAR(B_XEMPTY), ~s & 1);
        mbar_expect_e(BAR(B_XFULL), 16384 * EXP_NXT);
        for (int i = 0; i < EXP_NXT; i++) tma4d_e(c.sb + SM_XT + i * 16384, &tx, c.b * 8, (s + 2) * 4 + 2 * (c.b ^ i), BAR(B_XFULL));
      }
      ln = lane(kf[0].y);
      const char* pa = c.mail + (uint32_t)(box(s & 1, src0) + 8192 + (c.sel >> (s & 1) & 4096) + (g & 1) * 512 + (EXP_LIN ? ln * 16 : read_off(ln)));
      const uint32_t spw = c.sb + SM_SP + g * 1280 + (ln & 3) * 64 + ((((ln >> 3) ^ ln) & 2) << 4) + (ln & 4) * 4 + (ln & 8),
                     spr = c.sb + SM_SP + (ln & 4) * 80 + (ln >> 3) * 64 + (((ln & 3) ^ ((ln >> 3) & 2)) << 4), l8 = ln * 8;
      const uint32_t tg = s >> 1;
      float sx[2][4];
      uint32_t sm;
      uint4 km;
      touch(pa, c.sb);
      mbar_wait(BAR(B_E1TRIG), s & 1);
      const uint32_t t0 = clock_lo();
      TRV(s, 3, t0);
      scores_x<false>(sx, kf, qx, 0);
      store_scores(sx, spw + 640);
      if (DLY_E1) delay_fine(t0 + DLY_E1);
      uint32_t nr = 0;
      while (true) {
        const uint4 q0 = ld_poll(pa), q1 = ld_poll(pa + 2048), k0 = ld_poll(pa + 1024), k1 = ld_poll(pa + 3072);
        uint4 qm = add4(q0, q1);
        const uint32_t bq = stale2(q0.x, q1.x, tg);
        qm.x = dep(qm.x, bq, c.sb);
        scores_x<SC_F>(sx, kf, qm, c.sb);
        const uint32_t bk = stale2(k0.x, k1.x, tg);
        km = add4(k0, k1);
        km.x = dep(km.x, bk, c.sb);
        const bool ok = all_clear(bq | bk, 1);
        sm = scores_m(qm, km);
        store_scores(sx, spw);
        if (ok) break;
        nr++; CNT(2);
      }
      sts32(l8 + (c.sb + SM_SPM + (g >> 1) * 256 + (g & 1) * 4), sm);
      bar_sync(NB_ATT, 128);
      TR(s, 5); TRV(s, 13, nr);
      float o[2][4];
      uint32_t sp[5];
      uint4 vf[4];
      load_scores(sp, spr, l8 + (c.sb + SM_SPM));
      const uint32_t m5 = max5(sp);
      uint32_t m1;
      float off = row_off(m5, m1), f[10];
      l16 = dep(l16, VF_AT ? m1 : m5, c.sb);
#pragma unroll
      for (int t = 0; t < 4; t++) vf[(t >> 1) + 2 * (t & 1)] = lds128(l16 + SM_V + ((t >> 1) + 2 * (t & 1)) * 2048);
      qx.x = dep(qx.x, sp[0], c.sb);
      sts32(l8 + (c.sb + SM_SPM + 512 + (g >> 1) * 256 + (g & 1) * 4), scores_m(qx, km));
      mbar_arrive_warp(BAR(B_SC));
      unpack(f, sp);
      if (UP_F) sched_fence(c.sb);
      uint4 vm;
      if (VM_AT < 2) {
        bar_sync(NB_VM, 384);
        sp[1] = exp_pair(f, 1, off);
        const uint32_t av = dep(l8, VM_AT ? sp[1] : __float_as_uint(off), c.sb) + (c.sb + g * 512 + SM_VM);
        const uint2 vm0 = lds64(av), vm1 = lds64(av + 256);
        vm = make_uint4(vm0.x, vm0.y, vm1.x, vm1.y);
#pragma unroll
        for (int i = 2; i < 6; i++) sp[i % 5] = exp_pair(f, i % 5, off);
      } else {
#pragma unroll
        for (int i = 1; i < 6; i++) sp[i % 5] = exp_pair(f, i % 5, off);
        bar_sync(VM_AT == 2 ? dep(dep(0, sp[1] ^ sp[2], c.sb) + NB_VM, sp[0], c.sb) : dep(dep(0, sp[0] ^ sp[1] ^ sp[2], c.sb) + NB_VM, sp[3], c.sb), 384);
        const uint32_t av = l8 + (c.sb + g * 512 + SM_VM);
        const uint2 vm0 = lds64(av), vm1 = lds64(av + 256);
        vm = make_uint4(vm0.x, vm0.y, vm1.x, vm1.y);
      }
      float sum;
      auto rows_m = [&]() {
        const uint32_t tv = min(s, XEND - 1) / NSLOT;
        sum = pv(o, sp, vf, vm);
        stsm4<false>(l16 + SM_OM, pack_bf16(o[0][0], o[0][1]), pack_bf16(o[0][2], o[0][3]), pack_bf16(o[1][0], o[1][1]), pack_bf16(o[1][2], o[1][3]));
        sts32(c.sb + SM_SUM + ((l16 >> 4) & 28), __float_as_uint(sum));
        return arrive_if_clear(stale2(vf[0].x, vf[1].x, tv) | stale2(vf[2].x, vf[3].x, tv), EXP_CHK, NB_OM, 384);
      };
      if (!rows_m()) {
        const char* pv_ = c.mail + (uint32_t)(M_KVQ + (min(s, XEND - 1) & (NSLOT - 1)) * M_REG + c.h * 24576 + 8192 + (l16 - c.sb));
        uint32_t n = 0;
        do {
#pragma unroll
          for (int t = 0; t < 4; t++) vf[t] = ld_poll(pv_ + t * 2048);
          watchdog(n, POLL_LIMIT); CNT(5);
        } while (!rows_m());
      }
      const uint32_t tom = clock_lo();
      TRV(s, 8, tom);
      sched_fence(c.sb);
      ln = lane(tom);
      const int n = ln >> 2, jj = ln & 3, tq_ = 8 * c.j + (n & 4) + 2 * (n & 1) + ((n >> 1) & 1), lim = 16 * (tq_ - 2 * jj + 1);
      if (DLY_X) delay_until(tom + DLY_X);
      load_scores(sp, spr + 640, c.sb + SM_SPM + 512 + ln * 8);
#pragma unroll
      for (int w = 0; w < 4; w++) {
        uint32_t m; asm("shl.b32 %0, 0xffffffff, %1;" : "=r"(m) : "r"(max(lim - 128 * w, 0)));
        sp[1 + w] = (sp[1 + w] & ~m) | (0xD029D029u & m);
      }
      mbar_arrive_warp(dep(dep(0, sp[0], c.sb), sp[1], c.sb) + BAR(B_SPFREE));
      off = row_off(max5(sp), m1);
      unpack(f, sp);
#pragma unroll
      for (int i = 1; i < 6; i++) sp[i % 5] = exp_pair(f, i % 5, off);
      sum = pv(o, sp, vf, vm);
      TR(s, 7);
      sum = rcp(sum);
      const float i0 = __shfl_sync(~0u, sum, 8 * jj), i1 = __shfl_sync(~0u, sum, 8 * jj + 4);
      const uint32_t oxs = c.sb + SM_OX + g * 512;
      stsm4<true>(oxs + (ln & 7) * 64 + (((ln >> 3) ^ ((ln >> 1) & 3)) << 4),
                  pack_bf16(o[0][0] * i0, o[0][1] * i1), pack_bf16(o[0][2] * i0, o[0][3] * i1), pack_bf16(o[1][0] * i0, o[1][1] * i1), pack_bf16(o[1][2] * i0, o[1][3] * i1));
      __syncwarp();
      *(uint4*)(g_ox + ox_at(s, tq_, c.h * 4 + g, jj)) = lds128(oxs + n * 64 + ((jj ^ (n >> 1)) << 4));
      mbar_arrive_warp(BAR(B_PVDONE));
      TR(s, 9);
    }
    if (LASTM) {
      const int ln = tid_now() & 31, n = ln >> 2, jj = ln & 3, tq_ = 8 * c.j + (n & 4) + 2 * (n & 1) + ((n >> 1) & 1);
      store_count(g_ox + ox_at(NSEG - 1, tq_, c.h * 4 + g, jj), lds128(c.sb + SM_OX + g * 512 + n * 64 + ((jj ^ (n >> 1)) << 4)), (char*)(g_ctl + C_LAST) + (LASTM == 2 ? c.r * 4 + g : 0));
    } else count_e(g_ctl + C_LAST);
    mbar_arrive_warp(BAR(B_DONE));
    if (tid_now() == 256) TL(8);
    __syncwarp();
    mbar_wait(BAR(B_E2TRIG), 1); mbar_wait(BAR(B_DONE), 0); mbar_wait(BAR(B_TW), 0);
    asm volatile("setmaxnreg.inc.sync.aligned.u32 128;");
  } else {
    {
      const int w = c.m * 4 + c.w;
      mbar_expect_e(BAR(B_ROWS), 4096 + 256);
      for (int i = 0; i < 2; i++) bulk_load_e(c.sb + SM_FFT + (1024 + w * ROW_BUF) * 8 + i * 2048, x + (size_t)(z_row(c.r * 8 + w) + i * 1024) * D_, 2048, BAR(B_ROWS));
      bulk_load_e(c.sb + SM_GW + w * 256, gw + w * 128, 256, BAR(B_ROWS));
    }
    asm volatile("setmaxnreg.inc.sync.aligned.u32 %0;" :: "n"(REG_F));
    c.lane = lane_id();
    uint32_t wa[16][4], wb[16][4], wv[16][4];
    TR(-2, 4);
    fft_rows_fwd((float2*)(smraw + SM_FFT), (const __nv_bfloat16*)(smraw + SM_GW), c.r, threadIdx.x, BAR(B_ROWS), BAR(B_FREE), [&](int e) { TR(-2, e); }, [&]() {
      mbar_spin(BAR(B_PFULL), 0);
#pragma unroll
      for (int k = 0; k < NP; k++) ldsm4t(wa[k], c.sb + SM_POOL + c.m * NP * 2048 + frag_off(c.w, c.lane) + k * 2048);
      bar_sync(NB_XCH, 256);
#pragma unroll
      for (int k = 0; k < NP; k++) sts128(c.sb + SM_POOL + c.m * 2048 + c.w * 512 + c.lane * 16 + k * 4096, make_uint4(wa[k][0], wa[k][1], wa[k][2], wa[k][3]));
    });
    mbar_arrive_warp(BAR(B_P1));
    TR(-2, 0);
    if (tid_now() == 0) TL2(1);
    __syncwarp();
    mbar_spin(BAR(B_WFULL + c.m), 0);
    TR(-2, 1);
    if ((tid_now() & 127) == 0) TL2(16);
    __syncwarp();
    {
      const uint32_t st = c.sb + c.m * ST_WG + frag_off(c.w, c.lane);
#pragma unroll
      for (int k = 0; k < 16; k++) ldsm4t(wb[k], st + k * 2048);
#pragma unroll
      for (int k = NP; k < 16; k++) ldsm4t(wa[k], st + (16 + k - NP) * 2048);
#pragma unroll
      for (int k = 0; k < NV; k++) ldsm4t(wv[k], st + (32 - NP + k) * 2048);
      mbar_arrive_warp(BAR(B_WREAD));
      if (c.m == 0) mbar_arrive_warp(BAR(B_WREAD0));
#pragma unroll
      for (int k = 0; k < (LP_IN == 2 ? 0 : NP); k++) lds_frag(wa[k], c.sb + SM_POOL + c.m * 2048 + c.w * 512 + c.lane * 16 + k * 4096);
      TR(-2, 2);
    }
    TR(-2, 3);
    if (tid_now() == 0) TL2(12);
    __syncwarp();
    asm volatile("barrier.cluster.wait;" ::: "memory");
    uint32_t t16 = c.m * 2048 + c.w * 512 + c.lane * 16;
    uint32_t pk = (c.m * NHV * 2048 + frag_off(c.w, c.lane)) | (tile_off(2 * (c.w & 1), c.lane) << 16) | ((c.lane & 12) ? 0u : 0x80000000u);
    const uint32_t dx1 = desc_lo(c.sb + SM_XT + c.m * 4096), dh = desc_lo(c.sb + SM_HV + c.m * NHV * 2048);
    mbar_spin(BAR(B_PFULL), 1);
    pad<PAD0>();
    for (int s = -2; ; s++) {
      t16 = vary(t16, s, c.sb); pk = vary(pk, s, c.sb);
      const uint32_t dx = dx1 - (s == -2 ? (SM_XT - SM_WO) / 16 : 0);
      auto ldp = [&](int k0, int k1, int d, int back = 0) {
#pragma unroll
        for (int k = k0; k < k1; k++) lds_frag(wa[k], (k < k0 + d - back ? t16 : dep(t16, wa[k < d ? 0 : k - d][0], c.sb)) + (c.sb + SM_POOL + k * 4096));
      };
      if (s >= 0) {
        uint32_t af[16][4], bf[4][4], wo;
        const uint32_t tab = ((t16 >> 3) & 0x1C0) + (c.sb + SM_TAB + (s & 1) * 512);
        const char* pa;
        mem_proj(wa, wb, wv, af, wo, pa, tab, t16, pk, c, s);
        const uint32_t t0 = clock_lo();
        t16 = dep(t16, t0, c.sb);
        auto ldwo = [&](int f) { ldsm4t(af[f], (f < WO_D ? wo : dep(wo, af[f < WO_D ? 0 : f - WO_D][0], c.sb)) + (c.sb + SM_WO + (f & 1) * 32768 + (f >> 1) * 2048)); };
        {
          const uint32_t tg = s >> 1, vm = t16 >> 1, chk = (~t16 >> 4) & 1;
          if (WO_S && s == 0) {
            mbar_spin(BAR(B_WOFULL), 0);
#pragma unroll
            for (int f = 0; f < WO_0; f++) ldwo(f);
          }
#pragma unroll
          for (int f = WO_0; f < WO_1; f++) ldwo(f);
          if (DLY_V) delay_fine(t0 + DLY_V); else sched_fence(c.sb);
          uint2 v0 = ld_poll2(pa), v1 = ld_poll2(pa + 1024), v2 = ld_poll2(pa + 2048), v3 = ld_poll2(pa + 3072);
          TR(s, 3);
#pragma unroll
          for (int f = WO_1; f < 16 - WO_L; f++) ldwo(f);
          TR(s, 4);
          uint32_t n = 0;
          while (true) {
            sts64(vm + (c.sb + SM_VM), sum4(v0.x, v1.x, v2.x, v3.x), sum4(v0.y, v1.y, v2.y, v3.y));
            if (arrive_if_clear(stale1(stale1(stale2(v0.x, v1.x, tg), v2.x, tg), v3.x, tg), chk, NB_VM, 384)) break;
            v0 = ld_poll2(pa); v1 = ld_poll2(pa + 1024); v2 = ld_poll2(pa + 2048); v3 = ld_poll2(pa + 3072);
            n++; CNT(3);
          }
          TR(s, 12); TRV(s, 15, n);
        }
        if (!NOWO || vary(s, s, c.sb) != NSEG - 1) {
        const uint32_t ob = dep(dep(t16 & 511, af[14 - WO_L][0], c.sb), af[15 - WO_L][0], c.sb);
        uint32_t l4 = ob >> 2;
        const uint32_t bit = (t16 & 48) ? 0u : 1u;
        if (LF_AT) mbar_spin2_if(BAR(B_XFULL), BAR(B_LFREE), s & 1, s + 2 < XEND); else mbar_spin_if(BAR(B_XFULL), s & 1, s + 2 < XEND);
        bar_sync(NB_OM, 384);
        TR(s, 5);
#pragma unroll
        for (int i = 0; i < 4; i++) ldsm4t(bf[i], ob + (c.sb + SM_OM + i * 512));
        uint2 sum = lds64(((t16 >> 1) & 24) + (c.sb + SM_SUM));
        if (OM_F) sched_fence(c.sb);
        float d[WO_C][4] = {};
        uint4 d0, d1;
#pragma unroll
        for (int f = 0; f < 16; f++) {
          mma_a(d[f % WO_C], af[f], bf[f >> 2][f & 2], bf[f >> 2][(f & 2) + 1]);
          if (f >= WO_C && f < WO_C + WO_L) {
            const int l = 16 - WO_L + f - WO_C;
            ldsm4t(af[l], (WO_LD ? dep(wo, __float_as_uint(d[(f + 1) % WO_C][0]), c.sb) : wo) + (c.sb + SM_WO + (l & 1) * 32768 + (l >> 1) * 2048));
          }
          if (f == WO_T) {
            const uint32_t tb2 = dep((t16 >> 3) & 0x1C0, __float_as_uint(d[f % WO_C][0]), c.sb) + (c.sb + SM_TAB + (s & 1) * 512);
            d0 = lds128(tb2 + 32); d1 = lds128(tb2 + 48);
          }
          if (f >= PL_WA && f < PL_WA + PL_W) lds_frag(wa[f - PL_WA], (PL_WD ? dep(t16, __float_as_uint(d[(f + PL_WD) % WO_C][0]), c.sb) : t16) + (c.sb + SM_POOL + (f - PL_WA) * 4096));
          if (PL_W && PL_WF && f == PL_WA + PL_W - 1) sched_fence(c.sb);
          if (f == 4) { sum.x = dep(sum.x, __float_as_uint(d[0][0]), c.sb); sum.y = dep(sum.y, __float_as_uint(d[0][0]), c.sb); }
        }
        if (PL_W && !PL_WF) {
          uint32_t all = 0;
#pragma unroll
          for (int k = 0; k < PL_W; k++) all ^= wa[k][0];
          l4 = dep(l4, all, c.sb);
        }
        char* dst[4] = {mk_ptr(d0.x | l4, d0.y), mk_ptr(d0.z | l4, d0.w), mk_ptr(d1.x | l4, d1.y), mk_ptr(d1.z | l4, d1.w)};
        const float i0 = rcp(__uint_as_float(sum.x)), i1 = rcp(__uint_as_float(sum.y));
#pragma unroll
        for (int i = 0; i < 4; i++) {
          const int t = i >> 1, e = 2 * (i & 1);
          const float y0 = WO_C == 2 ? d[t][e] : d[t][e] + d[(t + 2) % WO_C][e], y1 = WO_C == 2 ? d[t][e + 1] : d[t][e + 1] + d[(t + 2) % WO_C][e + 1];
          st_pub(dst[i], put_tag(pack_bf16(y0 * i0, y1 * i1), bit, s >> 1));
        }
        if (ANCH2) sts32(c.sb + SM_SUM + 64, clock_lo());
        mbar_arrive_warp(BAR(B_E2TRIG));
        TR(s, 6);
        sched_fence(c.sb);
        if (W_E2 == 2) mbar_spin(BAR(B_E2TRIG), s & 1);
        }
      }
      if (__builtin_expect(s + 2 < XEND, 1)) {
        const uint32_t tg0 = DLY_P ? clock_lo() + DLY_P : 0;
        if (LP_IN) ldp(0, PL_0, PL_D);
        float xa[16];
        uint32_t q[4];
        if (W_E2 == 1 && s >= 0) mbar_spin(BAR(B_E2TRIG), s & 1);
        TR(s, 7);
        constexpr int S1 = ORDER ? 0 : 2, S2 = ORDER == 0 ? 0 : ORDER == 1 ? 2 : 1, S3 = ORDER == 2 ? 2 : 1;
        if (ORDER) issue_qk<0, 16>(xa, wb, vary(dx, s, c.sb)); else issue_v(xa, wv, vary(dx, s, c.sb), vary(dh, s, c.sb));
        if (DLY_P) delay_until(tg0); else if (IS_F) sched_fence(c.sb);
        ldp(PL_0, PL_1, PL_D1);
        const uint32_t land = (t16 ^ ((t16 >> 3) & 0x60)) + vary(c.sb + SM_LAND + c.b * 4096, s, c.sb);
        TR(s, 14);
        if (LF_AT == 1) mbar_spin_if(BAR(B_LFREE), s & 1, s < 0); else if (!LF_AT) mbar_spin(BAR(B_LFREE), s & 1);
        TR(s, 15);
        WG_WAIT(0);
        TR(s, 8);
        park_own<S1 == 2>(q, xa, land, S1, c.sb);
        if (W_PUB == 4 && s >= 0) mbar_spin(BAR(B_PUB), s & 1);
        if (ORDER == 1) issue_v(xa, wv, vary(dx, s, c.sb + 32), vary(dh, s, c.sb)); else issue_qk<0, 16>(xa, ORDER ? wa : wb, vary(dx, s, c.sb + 32));
        if (IS_F) sched_fence(c.sb);
        ldp(PL_1, PL_2, PL_D1);
        if (W_PUB == 1) mbar_spin_if(BAR(B_PUB), s & 1, s >= 0);
        uint32_t tp = clock_lo(), q1[4] = {q[0], q[1], q[2], q[3]};
        if (PL_2B) ldp(PL_2, NP - PL_L, PL_D1);
        if (W_PUB != 3) park_peer(q, land, S1, c);
        if (!PL_2B) ldp(PL_2, NP - PL_L, PL_D1);
        TR(s, 13);
        WG_WAIT(0);
        TR(s, 9);
        park_own<S2 == 2>(q, xa, land, S2, c.sb);
        if (ORDER == 2) issue_v(xa, wv, vary(dx, s, c.sb + 64), vary(dh, s, c.sb));
        else {
          issue_qk<0, PL_L ? NP - PL_L : 16>(xa, wa, vary(dx, s, c.sb + 64));
          ldp(NP - PL_L, NP, PL_E);
          if (PL_L) issue_qk<NP - PL_L, 16>(xa, wa, vary(dx, s, c.sb + 64));
        }
        if ((W_PUB == 2 || W_PUB == 3) && s >= 0) { mbar_spin(BAR(B_PUB), s & 1); tp = clock_lo(); }
        if (W_PUB == 3) park_peer(q1, land, S1, c);
        if (DLY_S && s >= 0) delay_until(tp + DLY_S);
        park_peer(q, land, S2, c);
        WG_WAIT(0);
        TR(s, 10);
        mbar_arrive_warp(BAR(B_XEMPTY));
        park_own<S3 == 2>(q, xa, land, S3, c.sb);
        park_peer(q, land, S3, c);
        TR(s, 11);
      } else {
        if (s == NSEG - 1) break;
        if (EARLY2 && (XEND == NSEG || s == NSEG - 2) && c.m * 4 + c.w == 0) count_e(g_ctl + C_EARLY);
        ldp(LP_IN ? 0 : PL_0, NP, LP_IN ? 2 : 1);
      }
    }
    if (NOWO) mbar_arrive_warp(BAR(B_E2TRIG));
    asm volatile("setmaxnreg.dec.sync.aligned.u32 %0;" :: "n"(BPRE == 2 ? 176 : 128));
    const int tid = tid_now(), lane = tid & 31, tile = tile_of(c), m0 = (tile >> 3) * 128, n0 = (tile & 7) * 128;
    float acc[64];
#pragma unroll
    for (int i = 0; i < 64; i++) acc[i] = 0.f;
    const uint32_t rel = mapa(BAR(B_GEMPTY), lane & 1), la = desc_lo(c.sb + c.m * 8192), lb = ((c.sb + 16384) & 0x3FFFF) >> 4 | (8192 >> 4) << 16;
    bool relon = false;
    const int skew = tile < 120 ? 0 : SKEW, kend = 64 + skew - c.m * skew, hold = c.m * (65 - LEAD) - 1;
    const float g0 = __ldcg(g_gate + m0 + (tid >> 5) * 16 + (lane >> 2)), g1 = __ldcg(g_gate + m0 + (tid >> 5) * 16 + (lane >> 2) + 8);
    uint32_t o = SM_XT, st = 0, ph = 0, prev = 0;
    if (tid == 0) TL(9);
    __syncwarp();
    GT(0);
#pragma unroll 1
    for (int kb = -c.m * skew; kb < max(kend - 4, 64); kb++, o = next_stage(o)) {
      if (LEAD && kb == hold) bar_sync(15, 256);
      mbar_lim(BAR(B_GFULL + st), ph);
      if ((uint32_t)kb < 64) {
        WG_FENCE();
#pragma unroll
        for (int k = 0; k < 4; k++) wgmma_ss_n128_tb(acc, desc128(la + (o >> 4) + k * 2), desc128(lb + (o >> 4) + k * 128));
        WG_COMMIT();
        WG_WAIT(1);
      } else WG_WAIT(0);
      arrive_remote_if(rel + 8 * prev, relon && kb < kend - 4);
      relon = (tid & 127) < 2;
      prev = st;
      if (++st == 5) { st = 0; ph ^= 1; }
    }
    if (LEAD && c.m == 0) asm volatile("bar.arrive 15, 256;" ::: "memory");
    const uint32_t row = (tid >> 5) * 2048 + (lane & 15) * 128 + (((lane >> 4) ^ (lane & 7)) << 4);
    if (!BPRE) WG_WAIT(0);
    mbar_lim(BAR(B_BT), 0);
    uint32_t b[2][4][4];
    const uint32_t rb = (tid >> 5) * 2048 + (lane >> 2) * 128 + (((lane & 7) ^ (lane >> 2)) << 4);
#pragma unroll
    for (int i = 0; i < 8; i++) lds_frag(b[i & 1][i >> 1], (rb ^ (i & 2) * 32) + (c.sb + SM_BT + (i >> 2) * 16384 + (i & 1) * 1024));
    float bl[2][4][4], bh[2][4][4];
    if (BPRE == 2) {
#pragma unroll
      for (int i = 0; i < 32; i++) {
        asm volatile("shl.b32 %0, %1, 16;" : "=f"(bl[i >> 4][i >> 2 & 3][i & 3]) : "r"(b[i >> 4][i >> 2 & 3][i & 3]));
        asm volatile("and.b32 %0, %1, 0xffff0000;" : "=f"(bh[i >> 4][i >> 2 & 3][i & 3]) : "r"(b[i >> 4][i >> 2 & 3][i & 3]));
      }
    }
    if (BPRE) { sched_fence(c.sb); WG_WAIT(0); sched_fence(c.sb); }
#pragma unroll
    for (int i = 0; i < 64; i++) asm volatile("" : "+f"(acc[i]) :: "memory");
    GT(17);
    if (tid == 0) TL(4);
    __syncwarp();
#pragma unroll
    for (int hf = 0; hf < 2; hf++) {
#pragma unroll
      for (int t = 0; t < 4; t++) {
        uint32_t y[4];
#pragma unroll
        for (int i = 0; i < 4; i++) {
          const float* a = acc + 32 * hf + 8 * t + 2 * i, g = i & 1 ? g1 : g0;
          const uint32_t* q = b[i & 1][2 * (t & 1) + (i >> 1)] + hf;
          const float* f = (t & 2 ? bh : bl)[i & 1][2 * (t & 1) + (i >> 1)] + hf;
          if (BPRE == 2) y[i] = pack_bf16(fmaf(g, a[0], f[0]), fmaf(g, a[1], f[2])); else
          y[i] = pack_bf16(fmaf(g, a[0], __uint_as_float(t & 2 ? q[0] & 0xFFFF0000u : q[0] << 16)), fmaf(g, a[1], __uint_as_float(t & 2 ? q[2] & 0xFFFF0000u : q[2] << 16)));
        }
        stsm4<false>((row ^ t * 32) + (c.sb + SM_BT + hf * 16384), y[0], y[1], y[2], y[3]);
      }
      if (EP_F && !hf) { sched_fence(c.sb); for (int i = 32; i < 64; i++) asm volatile("" : "+f"(acc[i]) :: "memory"); }
      FENCE_ASYNC_SMEM();
      __syncwarp();
      tma2d_out_e(&tout, n0 + hf * 64, m0 + (c.m * 4 + c.w) * 16, c.sb + SM_BT + hf * 16384 + (c.m * 4 + c.w) * 2048);
    }
    asm volatile("cp.async.bulk.commit_group; cp.async.bulk.wait_group" WAITRD " 0;" ::: "memory");
    GT(18);
    if ((tid & 127) == 0) TL(11);
    return;
  }
  static_assert(!QSH || NCR >= 7, "rounds");
  const bool col = c.r >= 128;
  const int tile = col ? 0 : tile_of(c);
  const int q0 = col ? 256 - 16 * NCR + (c.r - 128) * 4 + c.m : tile < 120 ? tile : 256, u = (tile >> 1 & 32) | (tile >> 3 & 7) | (tile & 6) << 2, e = QSH == 2 ? 2 * (u - (u > 39) - (u > 47)) + c.b : tile,
            dq = col ? 16 : QSH ? 120 + (e >> 2) - tile : 120, qe = col ? 256 : 256 - 16 * NCR,
            qw = col || !QSH || c.w == (e & 3) ? qe : 120;
  const uint32_t zs = c.sb + (col ? COL_Z + c.m * 32768 : SM_BT), zb = BAR(B_Z + c.m);
  auto load_z = [&](int q) { if (c.w == 0 && q < qe) { mbar_expect_e(zb, 32768); tma2d_o<(ONCE & 4) != 0>(zs, &tz, q * 64, 0, zb); } };
  asm volatile("fence.proxy.async.global;" ::: "memory");
  load_z(q0);
  uint32_t ph = 0;
#pragma unroll 1
  for (int q = q0; q < qe; q += dq, ph ^= 1) {
    mbar_lim(zb, ph);
    const int p = q * 4 + c.w;
    if (EXP_INV && q < qw) fft_rows_inv(zs, (float2*)(smraw + (col ? 8192 + c.m * INV_BUF * 32 : SM_MEM)) + c.w * INV_BUF, (const float2*)(smraw + (col ? 0 : SM_TW)), p, tid_now() & 31, g_b,
                              [&]() { bar_sync(5 + c.m, 128); load_z(q + dq); });
    else { bar_sync(5 + c.m, 128); load_z(q + dq); }
  }
  asm volatile("fence.acq_rel.gpu;" ::: "memory");
  __syncwarp();
  { const int q = q0 + (tid_now() & 31) * dq; if (q < qw) asm volatile("red.relaxed.gpu.global.add.u32 [%0], 1;" :: "l"(g_ctl + C_ROWS + (q >> 5) * 32) : "memory"); }
  if (tid_now() == 256) { if (col) TL(27); else TL(3); }
  __syncwarp();
  if (!col && c.w == 0) {
    await_count<AW_NS>(g_ctl + C_ROWS + ((tile >> 3) & 7) * 32, 128);
    mbar_expect_e(BAR(B_BT), 32768);
    for (int i = 0; i < 2; i++) tma2d_o<(ONCE & 8) != 0>(c.sb + SM_BT + i * 16384, &tb, (tile & 7) * 128 + i * 64, (tile >> 3) * 128, BAR(B_BT));
    if (tid_now() == 256) TL(5);
  }
}

typedef CUresult (*EncodeFn)(CUtensorMap*, CUtensorMapDataType, cuuint32_t, void*, const cuuint64_t*, const cuuint64_t*,
                             const cuuint32_t*, const cuuint32_t*, CUtensorMapInterleave, CUtensorMapSwizzle,
                             CUtensorMapL2promotion, CUtensorMapFloatOOBfill);

void make_map(EncodeFn enc, CUtensorMap* tm, const void* p, int rank, const cuuint64_t* dims, const cuuint64_t* strides, const cuuint32_t* box, bool swz = true) {
  const cuuint32_t es[4] = {1, 1, 1, 1};
  enc(tm, CU_TENSOR_MAP_DATA_TYPE_BFLOAT16, rank, (void*)p, dims, strides, box, es, CU_TENSOR_MAP_INTERLEAVE_NONE,
      swz ? CU_TENSOR_MAP_SWIZZLE_128B : CU_TENSOR_MAP_SWIZZLE_NONE, swz ? CU_TENSOR_MAP_L2_PROMOTION_L2_128B : W_PROMO, CU_TENSOR_MAP_FLOAT_OOB_FILL_NONE);
}
void make_map2(EncodeFn enc, CUtensorMap* tm, const void* p, uint64_t cols, uint64_t rows, uint32_t boxrows) {
  const cuuint64_t dims[2] = {cols, rows}, strides[1] = {cols * 2};
  const cuuint32_t box[2] = {64, boxrows};
  make_map(enc, tm, p, 2, dims, strides, box);
}

}

extern "C" void kernel_launch(void* const* d_in, const int* in_sizes, int n_in, void* d_out, int out_size) {
  (void)in_sizes; (void)n_in; (void)out_size;
  const __nv_bfloat16* x = (const __nv_bfloat16*)d_in[0];
  const __nv_bfloat16* mem0 = (const __nv_bfloat16*)d_in[1];
  const __nv_bfloat16* gw = (const __nv_bfloat16*)d_in[10];

  EncodeFn enc = nullptr;
  cudaDriverEntryPointQueryResult qr;
  cudaGetDriverEntryPoint("cuTensorMapEncodeTiled", (void**)&enc, cudaEnableDefault, &qr);
  void *p_ox, *p_b, *p_z, *p_mail;
  cudaGetSymbolAddress(&p_ox, g_ox); cudaGetSymbolAddress(&p_b, g_b); cudaGetSymbolAddress(&p_z, g_z); cudaGetSymbolAddress(&p_mail, g_mail);
  CUtensorMap tq, tk, tv, tv16, to, tx, twr, twi, ta, tw, tb, tout, tz, tzs, ta32;
  make_map2(enc, &tq, d_in[2], 4096, 1024, 64);
  make_map2(enc, &tk, d_in[3], 4096, 1024, 64);
  make_map2(enc, &tv, d_in[4], 4096, 1024, 64);
  make_map2(enc, &tv16, d_in[4], 4096, 1024, 16);
  make_map2(enc, &to, d_in[5], 1024, 4096, 128);
  make_map2(enc, &tw, d_in[5], 1024, 4096, 64);
  {
    const cuuint64_t dims[3] = {64, 2048, 64}, strides[2] = {128, 262144};
    const cuuint32_t box[3] = {64, 32, 2}, box1[3] = {64, 32, 1};
    make_map(enc, &ta, p_ox, 3, dims, strides, box);
    make_map(enc, &ta32, p_ox, 3, dims, strides, box1);
  }
  make_map2(enc, &tb, p_b, 1024, 2048, 128);
  make_map2(enc, &tout, d_out, 1024, 2048, 16);
  make_map2(enc, &tz, p_z, 16384, 257, 256);
  {
    const cuuint64_t dims[4] = {64, 8, 16, 256}, strides[3] = {2048, 128, 16384};
    const cuuint32_t box[4] = {64, 8, 8, 2};
    make_map(enc, &tx, x, 4, dims, strides, box);
  }
  {
    const cuuint64_t dims[2] = {512, 257 * 32}, strides[1] = {1024};
    const cuuint32_t box[2] = {128, 16};
    make_map(enc, &tzs, p_z, 2, dims, strides, box, false);
  }
  {
    const cuuint64_t dims[2] = {8 * 513, 256}, strides[1] = {8 * 513 * 2};
    const cuuint32_t box[2] = {8, 256};
    make_map(enc, &twr, d_in[8], 2, dims, strides, box, false);
    make_map(enc, &twi, d_in[9], 2, dims, strides, box, false);
  }
  cudaFuncSetAttribute(chain_kernel, cudaFuncAttributeMaxDynamicSharedMemorySize, CHAIN_SMEM);

  cudaStream_t st = cudaStreamPerThread;
  char* mail = (char*)(((uintptr_t)p_mail + M_REG - 1) & ~(uintptr_t)(M_REG - 1));
  chain_kernel<<<132, 512, CHAIN_SMEM, st>>>(tq, tk, tv, tv16, to, tx, twr, twi, ta, tw, tb, tout, tz, tzs, ta32, mem0, mail, x, gw);
}
```

```cpp
#include <cuda_runtime.h>
#include <cuda_bf16.h>
#include <cuda.h>
#include <stdint.h>

#define DLY_E1 160
#define DLY_V 330
#define DLY_E2 300
#define DLY_E3 480
#define DLY_X 1
#define DLY_S 0
#define DLY_F 200
#define VM_AT 1
#define VM_F 0
#define OM_F 1
#define SXX_IN 0
#define C1_AT 7
#define NLAG 2
#define WO_D 2
#define WO_0 3
#define WO_1 10
#define PL_0 8
#define PL_1 10
#define PL_D 2
#define PL_L 0
#define DUAL 0
#define HV_D 5
#define DLY_FK 0
#define QX_SM 0
#define REG_F 216
#define REG_H 24
#define SC_F 1
#define E2_F 0
#define KVQ_AT 0
#define DLY_K 0
#define X_AT 2
#define W_PV 0
#define PL_2 10
#define BF_E 3
#define PL_E 2
#define ORDER 1
#define SSPOS 1
#define W_PUB 1
#define FIN_AT 5
#define AWARE 1
#define NPROBE 2
#define NP_ 12
#define USE_PDL 1
#define DLY_GRP 1000
#define P2_BULK 0
#define EXP_NV 4
#define EXP_NK 4
#define EXP_CHK 1
#define EXP_NXT 2
#define EXP_PEER 1
#define EXP_FIN 7
#define EXP_NWG 16
#define ANCH2 1
#define XF_AT 1
#define IS_F 0
#define PL_D1 2
#define W_E2 0
#define V_TMA 2
#define V_W 1
#define RED_L 3
#define RED_T 1
#define RED_P 1
#define DLY_E3B 20
#define HV_E 0
#define HV_R 4
#define HOLD 0
#define PACE 500
#define PACE0 0
#define EXP_ST 7
#define HOLD_AT NPROBE
#define WO_AT 38
#define WO_P 2
#define DLY_SEL 300
#define P1_AT 1
#define EXP_ZG 1
#define TMA_W tma2d_once
#define BULK_F bulk_once
#define TMA_O tma2d_once
#define PACE_Z 580
#define PACE_F 800
#define EXP_INV 1
#define VF_AT 0
#define UP_F 0
#define WO_L (12 - NP_)
#define WO_C 4
#define WO_T 4
#define WO_LD 0
#define EXP_LIN 0
#define PL_W 0
#define PL_WA 4
#define PL_WD 0
#define PL_WF 1
#define STAG 0
#define EXP_FL 0
#define DLY_FS 0
#define DLY_F2 40
#define LROT 0
#define PF_D 4
#define PF_A 1
#define PF_B 0
#define SIDE 1
#define ROLE 1
#define LOOSE 0x765498
#define E1OFF 1
#define EVOFF E1OFF
#define EPI 0
#define WAITRD ".read"
#define X01 1
#define E3I 1
#define START 1000
#define WUNR 1
#define WO_N 0
#define WO_H 0
#define PL_2B 1
#define DLY_P 530
#define LP_IN 1
#define LF_AT 1
#define FINE 0
#define LAG_F 0
#define E30 1
#define WO_S 1
#define POOL_AT 12
#define COL_DLY 0
#define WO_F 0
#define PAD0 0
#define PAD2 2
#define PAD3 0
#define WO_X 0
#define PRIOR 12
#define EARLY 1
#define SEL_AT 3000
#define CUNR 1
#define FUNR 0
#define ZINIT 1
#define ZDLY 0
#define NCR 7
#define GATE 0
#define LASTM 1
#define X_ONCE 1
#define ONCE 31
#define Z_PF 0
#define EXP_W 1
#define W_PROMO CU_TENSOR_MAP_L2_PROMOTION_L2_128B
#define Z_ST 1
#define W_FINE 0
#define X128 2
#define T128_ 1
#define W_AT 0
#define SKEW 7
#define AW_NS 0
#define QSH 2
#define NOWO 0
#define EARLY2 1
#define LEAD 3
#define BPRE 2
#define EP_F 1
#define TQ_AT 0
#define LAG_0 8
#define LAG_G 0
#define LAG_S 0
#define O_AT 0
#define XB 0
#define V_E 0
#define LAG_T 1
#define PRE_AT B_SC

namespace {
constexpr int wunr = WUNR;

constexpr int S_ = 2048, D_ = 1024, NSEG = 64;
constexpr uint32_t SENT = 0xFFFFFFFFu;
constexpr int NSLOT = 4;

constexpr uint32_t M_REG = 1 << 21, M_E3 = 64 * 16384, M_KVQ = M_E3 + 4 * 8192, M_SEL = M_KVQ + 32 * 24576;
__device__ __align__(1024) unsigned char g_mail[5 * M_REG];
constexpr int C_P1 = 0, C_COLS = C_P1 + 32, C_EARLY = C_COLS + 32, C_LAST = C_EARLY + 32, C_ROWS = C_LAST + 128, C_END = C_ROWS + 8 * 32;
__device__ __align__(1024) uint32_t g_ctl[C_END];
#define CLK(i)
#define TL(i)
#define TL2(i)
#define FT(i, v)
#define GT(i)
#define CNT(i)
__device__ __align__(1024) __nv_bfloat16 g_ox[S_ * 4096];
__device__ __align__(1024) float2 g_z[257 * 4096];
__device__ __align__(1024) __nv_bfloat16 g_b[S_ * D_];
__device__ float g_gate[S_];
__device__ __align__(1024) float2 g_tw[1024];

#define TRV(s, ev, val)
#define TR(s, ev)
#define TRSYNC(ev)
__device__ __forceinline__ uint32_t smem_u32(const void* p) { return (uint32_t)__cvta_generic_to_shared(p); }
__device__ __forceinline__ void watchdog(uint32_t& n, uint32_t limit) {
  asm volatile("{ .reg .pred p; add.u32 %0, %0, 1; setp.gt.u32 p, %0, %1; @p trap; }" : "+r"(n) : "r"(limit));
}
__device__ __forceinline__ void mbar_init(uint32_t bar, uint32_t cnt) {
  asm volatile("mbarrier.init.shared::cta.b64 [%0], %1;" :: "r"(bar), "r"(cnt) : "memory");
}
__device__ __forceinline__ void mbar_arrive_warp(uint32_t bar) {
  __syncwarp();
  asm volatile("{ .reg .pred p; elect.sync _|p, 0xffffffff; @p mbarrier.arrive.shared::cta.b64 _, [%0]; }" :: "r"(bar) : "memory");
}
__device__ __forceinline__ uint32_t clock_lo() {
  uint32_t r; asm volatile("{ .reg .u64 c; .reg .u32 h; mov.u64 c, %%clock64; mov.b64 {%0, h}, c; }" : "=r"(r) :: "memory"); return r;
}
__device__ __forceinline__ void delay_until(uint32_t t) {
  asm volatile("{ .reg .pred p; .reg .u64 c; .reg .u32 l, h;\n"
               "DLY: mov.u64 c, %%clock64; mov.b64 {l, h}, c; sub.s32 l, l, %0; setp.lt.s32 p, l, 0; @p bra.uni DLY; }" :: "r"(t) : "memory");
}
__device__ __forceinline__ void delay_fine(uint32_t t) {
  delay_until(t);
}
__device__ __forceinline__ void delay_cycles(uint32_t n) { delay_until(clock_lo() + n); }
__device__ __forceinline__ void sched_fence(uint32_t z) {
  asm volatile("{ .reg .pred p; setp.eq.u32 p, %0, 0x7fff0000; @p pmevent 1; }" :: "r"(z) : "memory");
}
__device__ __forceinline__ void pdl_wait() { asm volatile("griddepcontrol.wait;" ::: "memory"); }
__device__ __forceinline__ void pdl_launch() { asm volatile("griddepcontrol.launch_dependents;" ::: "memory"); }
__device__ __forceinline__ float ex2(float x) { float r; asm("ex2.approx.ftz.f32 %0, %1;" : "=f"(r) : "f"(x)); return r; }
__device__ __forceinline__ float rcp(float x) { float r; asm("rcp.approx.ftz.f32 %0, %1;" : "=f"(r) : "f"(x)); return r; }
__device__ __forceinline__ void mbar_expect(uint32_t bar, uint32_t bytes) {
  asm volatile("mbarrier.arrive.expect_tx.shared::cta.b64 _, [%0], %1;" :: "r"(bar), "r"(bytes) : "memory");
}
__device__ __forceinline__ bool mbar_try(uint32_t bar, uint32_t ph) {
  uint32_t ok;
  asm volatile("{ .reg .pred p; mbarrier.try_wait.parity.shared::cta.b64 p, [%1], %2; selp.u32 %0, 1, 0, p; }"
               : "=r"(ok) : "r"(bar), "r"(ph) : "memory");
  return ok;
}
__device__ __forceinline__ void mbar_wait(uint32_t bar, uint32_t ph) {
  uint32_t n = 0;
  while (!mbar_try(bar, ph)) { watchdog(n, (1u << 20)); }
}
__device__ __forceinline__ void mbar_spin(uint32_t bar, uint32_t ph) { while (!mbar_try(bar, ph)) {} }
__device__ __forceinline__ void mbar_spin_if(uint32_t bar, uint32_t ph, bool on) {
  asm volatile("{ .reg .pred p, q; setp.ne.u32 p, %2, 0;\n"
               "SPN: setp.eq.u32 q, 0, 0; @p mbarrier.try_wait.parity.shared::cta.b64 q, [%0], %1; @!q bra.uni SPN; }" :: "r"(bar), "r"(ph), "r"((uint32_t)on) : "memory");
}
__device__ __forceinline__ void mbar_spin2_if(uint32_t bar, uint32_t bar2, uint32_t ph, bool on) {
  asm volatile("{ .reg .pred p, q, r; setp.ne.u32 p, %3, 0;\n"
               "SPN: setp.eq.u32 q, 0, 0; setp.eq.u32 r, 0, 0; @p mbarrier.try_wait.parity.shared::cta.b64 q, [%0], %2;\n"
               "@p mbarrier.try_wait.parity.shared::cta.b64 r, [%1], %2; and.pred q, q, r; @!q bra.uni SPN; }" :: "r"(bar), "r"(bar2), "r"(ph), "r"((uint32_t)on) : "memory");
}
__device__ __forceinline__ void mbar_spin_cluster(uint32_t bar, uint32_t ph) {
  uint32_t ok;
  do {
    asm volatile("{ .reg .pred p; mbarrier.try_wait.parity.acquire.cluster.shared::cta.b64 p, [%1], %2; selp.u32 %0, 1, 0, p; }"
                 : "=r"(ok) : "r"(bar), "r"(ph) : "memory");
  } while (!ok);
}
#define ONCE_H "mov.b64 h, 0x12F0000000000000; "
__device__ __forceinline__ void tma2d(uint32_t dst, const CUtensorMap* tm, int c0, int c1, uint32_t bar) {
  if (ONCE & 32) asm volatile("{ .reg .b64 h; " ONCE_H "cp.async.bulk.tensor.2d.shared::cluster.global.mbarrier::complete_tx::bytes.L2::cache_hint [%0], [%1, {%3, %4}], [%2], h; }"
               :: "r"(dst), "l"(tm), "r"(bar), "r"(c0), "r"(c1) : "memory");
  else asm volatile("cp.async.bulk.tensor.2d.shared::cluster.global.mbarrier::complete_tx::bytes [%0], [%1, {%3, %4}], [%2];"
               :: "r"(dst), "l"(tm), "r"(bar), "r"(c0), "r"(c1) : "memory");
}
__device__ __forceinline__ void mbar_expect_e(uint32_t bar, uint32_t bytes) {
  asm volatile("{ .reg .pred p; elect.sync _|p, 0xffffffff; @p mbarrier.arrive.expect_tx.shared::cta.b64 _, [%0], %1; }" :: "r"(bar), "r"(bytes) : "memory");
}
__device__ __forceinline__ void tma2d_e(uint32_t dst, const CUtensorMap* tm, int c0, int c1, uint32_t bar) {
  asm volatile("{ .reg .pred p; elect.sync _|p, 0xffffffff;\n"
               "@p cp.async.bulk.tensor.2d.shared::cluster.global.mbarrier::complete_tx::bytes [%0], [%1, {%3, %4}], [%2]; }"
               :: "r"(dst), "l"(tm), "r"(bar), "r"(c0), "r"(c1) : "memory");
}
__device__ __forceinline__ void tma2d_st_e(const CUtensorMap* tm, int c0, int c1, uint32_t src) {
  asm volatile("{ .reg .pred p; elect.sync _|p, 0xffffffff;\n"
               "@p cp.async.bulk.tensor.2d.global.shared::cta.bulk_group [%0, {%2, %3}], [%1]; }" :: "l"(tm), "r"(src), "r"(c0), "r"(c1) : "memory");
}
__device__ __forceinline__ void tma2d_out_e(const CUtensorMap* tm, int c0, int c1, uint32_t src) {
  if (EPI) asm volatile("{ .reg .pred p; elect.sync _|p, 0xffffffff;\n"
               "@p cp.reduce.async.bulk.tensor.2d.global.shared::cta.add.bulk_group [%0, {%2, %3}], [%1]; }" :: "l"(tm), "r"(src), "r"(c0), "r"(c1) : "memory");
  else if (ONCE & 16) asm volatile("{ .reg .pred p; .reg .b64 h; " ONCE_H "elect.sync _|p, 0xffffffff;\n"
               "@p cp.async.bulk.tensor.2d.global.shared::cta.bulk_group.L2::cache_hint [%0, {%2, %3}], [%1], h; }" :: "l"(tm), "r"(src), "r"(c0), "r"(c1) : "memory");
  else asm volatile("{ .reg .pred p; elect.sync _|p, 0xffffffff;\n"
               "@p cp.async.bulk.tensor.2d.global.shared::cta.bulk_group [%0, {%2, %3}], [%1]; }" :: "l"(tm), "r"(src), "r"(c0), "r"(c1) : "memory");
}
__device__ __forceinline__ void tma2d_once(uint32_t dst, const CUtensorMap* tm, int c0, int c1, uint32_t bar) {
  asm volatile("{ .reg .pred p; .reg .b64 h; " ONCE_H "elect.sync _|p, 0xffffffff;\n"
               "@p cp.async.bulk.tensor.2d.shared::cluster.global.mbarrier::complete_tx::bytes.L2::cache_hint [%0], [%1, {%3, %4}], [%2], h; }"
               :: "r"(dst), "l"(tm), "r"(bar), "r"(c0), "r"(c1) : "memory");
}
__device__ __forceinline__ void bulk_once(uint32_t dst, const void* src, uint32_t bytes, uint32_t bar) {
  asm volatile("{ .reg .pred p; .reg .b64 h; " ONCE_H "elect.sync _|p, 0xffffffff;\n"
               "@p cp.async.bulk.shared::cluster.global.mbarrier::complete_tx::bytes.L2::cache_hint [%0], [%1], %2, [%3], h; }"
               :: "r"(dst), "l"(src), "r"(bytes), "r"(bar) : "memory");
}
__device__ __forceinline__ void tma4d_e(uint32_t dst, const CUtensorMap* tm, int c2, int c3, uint32_t bar) {
  asm volatile("{ .reg .pred p; .reg .b64 h; " ONCE_H "elect.sync _|p, 0xffffffff;\n"
               "@p cp.async.bulk.tensor.4d.shared::cluster.global.mbarrier::complete_tx::bytes.L2::cache_hint [%0], [%1, {0, 0, %3, %4}], [%2], h; }"
               :: "r"(dst), "l"(tm), "r"(bar), "r"(c2), "r"(c3) : "memory");
}
__device__ __forceinline__ void bulk_load_e(uint32_t dst, const void* src, uint32_t bytes, uint32_t bar) {
  asm volatile("{ .reg .pred p; elect.sync _|p, 0xffffffff;\n"
               "@p cp.async.bulk.shared::cluster.global.mbarrier::complete_tx::bytes [%0], [%1], %2, [%3]; }"
               :: "r"(dst), "l"(src), "r"(bytes), "r"(bar) : "memory");
}
template<bool O> __device__ __forceinline__ void tma2d_o(uint32_t dst, const CUtensorMap* tm, int c0, int c1, uint32_t bar) {
  if (O) tma2d_once(dst, tm, c0, c1, bar); else tma2d_e(dst, tm, c0, c1, bar);
}
__device__ __forceinline__ float2 ld_once(const float2* p) {
  float2 v;
  if (ONCE & 64) asm volatile("{ .reg .b64 h; " ONCE_H "ld.global.cg.L2::cache_hint.v2.f32 {%0, %1}, [%2], h; }" : "=f"(v.x), "=f"(v.y) : "l"(p));
  else v = __ldcg(p);
  return v;
}
template<bool O = false> __device__ __forceinline__ void prefetch2d_e(const CUtensorMap* tm, int c0, int c1) {
  if (O) asm volatile("{ .reg .pred p; .reg .b64 h; " ONCE_H "elect.sync _|p, 0xffffffff;\n"
               "@p cp.async.bulk.prefetch.tensor.2d.L2.global.L2::cache_hint [%0, {%1, %2}], h; }" :: "l"(tm), "r"(c0), "r"(c1) : "memory");
  else asm volatile("{ .reg .pred p; elect.sync _|p, 0xffffffff;\n"
               "@p cp.async.bulk.prefetch.tensor.2d.L2.global [%0, {%1, %2}]; }" :: "l"(tm), "r"(c0), "r"(c1) : "memory");
}
__device__ __forceinline__ void st_pub4(void* p, uint4 v) {
  asm volatile("st.relaxed.gpu.global.v4.u32 [%0], {%1,%2,%3,%4};" :: "l"(p), "r"(v.x), "r"(v.y), "r"(v.z), "r"(v.w) : "memory");
}
__device__ __forceinline__ void st_pub_if(void* p, uint32_t v, bool on) {
  asm volatile("{ .reg .pred p; setp.ne.u32 p, %2, 0; @p st.relaxed.gpu.global.u32 [%0], %1; }" :: "l"(p), "r"(v), "r"((uint32_t)on) : "memory");
}
__device__ __forceinline__ uint32_t mapa(uint32_t a, uint32_t r) {
  uint32_t d; asm volatile("mapa.shared::cluster.u32 %0, %1, %2;" : "=r"(d) : "r"(a), "r"(r)); return d;
}
__device__ __forceinline__ void st_async4(uint32_t a, uint32_t x, uint32_t y, uint32_t z, uint32_t w, uint32_t bar) {
  asm volatile("st.async.shared::cluster.mbarrier::complete_tx::bytes.v4.u32 [%0], {%1,%2,%3,%4}, [%5];"
               :: "r"(a), "r"(x), "r"(y), "r"(z), "r"(w), "r"(bar) : "memory");
}
__device__ __forceinline__ uint4 ld_poll(const void* p) {
  uint4 v;
  asm volatile("ld.volatile.global.v4.u32 {%0,%1,%2,%3}, [%4];" : "=r"(v.x), "=r"(v.y), "=r"(v.z), "=r"(v.w) : "l"(p) : "memory");
  return v;
}
__device__ __forceinline__ uint2 ld_poll2(const void* p) {
  uint2 v; asm volatile("ld.volatile.global.v2.u32 {%0,%1}, [%2];" : "=r"(v.x), "=r"(v.y) : "l"(p) : "memory"); return v;
}
__device__ __forceinline__ void st_pub2(void* p, uint32_t a, uint32_t b) {
  asm volatile("st.relaxed.gpu.global.v2.u32 [%0], {%1,%2};" :: "l"(p), "r"(a), "r"(b) : "memory");
}
__device__ __forceinline__ uint32_t ld_poll1(const void* p) {
  uint32_t v; asm volatile("ld.volatile.global.u32 %0, [%1];" : "=r"(v) : "l"(p) : "memory"); return v;
}
__device__ __forceinline__ uint32_t ld_acquire(const uint32_t* p) {
  uint32_t v; asm volatile("ld.acquire.gpu.global.u32 %0, [%1];" : "=r"(v) : "l"(p) : "memory"); return v;
}
__device__ __forceinline__ void st_pub(void* p, uint32_t v) {
  asm volatile("st.relaxed.gpu.global.u32 [%0], %1;" :: "l"(p), "r"(v) : "memory");
}
__device__ __forceinline__ uint32_t lds32(uint32_t a) {
  uint32_t v; asm volatile("ld.shared.u32 %0, [%1];" : "=r"(v) : "r"(a) : "memory"); return v;
}
__device__ __forceinline__ int race_init(void* p0, void* p1, uint32_t val) {
  int t;
  asm volatile("{ .reg .pred r; .reg .u32 a, b, u, v;\n"
               "atom.relaxed.gpu.global.exch.b32 u, [%1], %3; atom.relaxed.gpu.global.exch.b32 v, [%2], %3;\n"
               "setp.eq.u32 r, u, 0x12345; @r pmevent 1; mov.u32 a, %%clock;\n"
               "setp.eq.u32 r, v, 0x12345; @r pmevent 1; mov.u32 b, %%clock; sub.u32 %0, b, a; }" : "=r"(t) : "l"(p0), "l"(p1), "r"(val) : "memory");
  return t;
}
__device__ __forceinline__ void race_init2(void* p0, void* p1, uint32_t val) {
  asm volatile("{ .reg .pred r; .reg .u32 a, b, u, v;\n"
               "atom.relaxed.gpu.global.exch.b32 u, [%0], %2; atom.relaxed.gpu.global.exch.b32 v, [%1], %2;\n"
               "atom.relaxed.gpu.global.exch.b32 a, [%0 + 4096], %2; atom.relaxed.gpu.global.exch.b32 b, [%1 + 4096], %2;\n"
               "lop3.b32 u, u, v, a, 0x96; setp.eq.u32 r, u, 0x12345; setp.eq.and.u32 r, b, u, r; @r pmevent 1; }" :: "l"(p0), "l"(p1), "r"(val) : "memory");
}
__device__ __forceinline__ uint4 lds128(uint32_t a) {
  uint4 v; asm volatile("ld.shared.v4.u32 {%0,%1,%2,%3}, [%4];" : "=r"(v.x), "=r"(v.y), "=r"(v.z), "=r"(v.w) : "r"(a) : "memory"); return v;
}
__device__ __forceinline__ uint2 lds64(uint32_t a) {
  uint2 v; asm volatile("ld.shared.v2.u32 {%0,%1}, [%2];" : "=r"(v.x), "=r"(v.y) : "r"(a) : "memory"); return v;
}
__device__ __forceinline__ void sts128(uint32_t a, uint4 v) {
  asm volatile("st.shared.v4.u32 [%0], {%1,%2,%3,%4};" :: "r"(a), "r"(v.x), "r"(v.y), "r"(v.z), "r"(v.w) : "memory");
}
__device__ __forceinline__ void sts64(uint32_t a, uint32_t x, uint32_t y) { asm volatile("st.shared.v2.u32 [%0], {%1,%2};" :: "r"(a), "r"(x), "r"(y) : "memory"); }
__device__ __forceinline__ void sts32(uint32_t a, uint32_t x) { asm volatile("st.shared.u32 [%0], %1;" :: "r"(a), "r"(x) : "memory"); }
__device__ __forceinline__ void ldsm4t(uint32_t (&r)[4], uint32_t a) {
  asm volatile("ldmatrix.sync.aligned.m8n8.x4.trans.shared.b16 {%0,%1,%2,%3}, [%4];"
               : "=r"(r[0]), "=r"(r[1]), "=r"(r[2]), "=r"(r[3]) : "r"(a) : "memory");
}
__device__ __forceinline__ void ldsm4(uint32_t (&r)[4], uint32_t a) {
  asm volatile("ldmatrix.sync.aligned.m8n8.x4.shared.b16 {%0,%1,%2,%3}, [%4];"
               : "=r"(r[0]), "=r"(r[1]), "=r"(r[2]), "=r"(r[3]) : "r"(a) : "memory");
}
template<bool TRANS> __device__ __forceinline__ void stsm4(uint32_t a, uint32_t r0, uint32_t r1, uint32_t r2, uint32_t r3) {
  if (TRANS) asm volatile("stmatrix.sync.aligned.m8n8.x4.trans.shared.b16 [%0], {%1,%2,%3,%4};" :: "r"(a), "r"(r0), "r"(r1), "r"(r2), "r"(r3) : "memory");
  else       asm volatile("stmatrix.sync.aligned.m8n8.x4.shared.b16 [%0], {%1,%2,%3,%4};" :: "r"(a), "r"(r0), "r"(r1), "r"(r2), "r"(r3) : "memory");
}
__device__ __forceinline__ void mma16816(float (&d)[4], uint32_t a0, uint32_t a1, uint32_t a2, uint32_t a3, uint32_t b0, uint32_t b1) {
  asm volatile("mma.sync.aligned.m16n8k16.row.col.f32.bf16.bf16.f32 {%0,%1,%2,%3}, {%4,%5,%6,%7}, {%8,%9}, {%0,%1,%2,%3};"
               : "+f"(d[0]), "+f"(d[1]), "+f"(d[2]), "+f"(d[3]) : "r"(a0), "r"(a1), "r"(a2), "r"(a3), "r"(b0), "r"(b1));
}
__device__ __forceinline__ void mma1688(float (&d)[4], uint32_t a0, uint32_t a1, uint32_t b0) {
  asm volatile("mma.sync.aligned.m16n8k8.row.col.f32.bf16.bf16.f32 {%0,%1,%2,%3}, {%4,%5}, {%6}, {%0,%1,%2,%3};"
               : "+f"(d[0]), "+f"(d[1]), "+f"(d[2]), "+f"(d[3]) : "r"(a0), "r"(a1), "r"(b0));
}
__device__ __forceinline__ uint32_t pack_bf16(float lo, float hi) {
  uint32_t r; asm("cvt.rn.bf16x2.f32 %0, %1, %2;" : "=r"(r) : "f"(hi), "f"(lo)); return r;
}
__device__ __forceinline__ uint32_t add_bf16x2(uint32_t a, uint32_t b) {
  uint32_t r; asm("add.rn.bf16x2 %0, %1, %2;" : "=r"(r) : "r"(a), "r"(b)); return r;
}
__device__ __forceinline__ uint32_t umax4(uint4 v) { return max(max(v.x, v.y), max(v.z, v.w)); }
__device__ __forceinline__ uint32_t opaque(uint32_t x) { uint32_t r; asm volatile("mov.u32 %0, %1;" : "=r"(r) : "r"(x)); return r; }
template<class T> __device__ __forceinline__ void pin(T*& p) { asm volatile("" : "+l"(p)); }
__device__ __forceinline__ void pin(uint32_t& v) { asm volatile("" : "+r"(v)); }
__device__ __forceinline__ uint32_t desc_lo(uint32_t addr) { return ((addr & 0x3FFFF) >> 4) | 0x10000; }
__device__ __forceinline__ uint64_t desc128(uint32_t lo) {
  uint64_t d; asm("mov.b64 %0, {%1, %2};" : "=l"(d) : "r"(lo), "r"(0x40000040)); return d;
}
#define WG_FENCE()  asm volatile("wgmma.fence.sync.aligned;" ::: "memory")
#define WG_COMMIT() asm volatile("wgmma.commit_group.sync.aligned;" ::: "memory")
#define WG_WAIT(n)  asm volatile("wgmma.wait_group.sync.aligned " #n ";" ::: "memory")
#define FENCE_ASYNC_SMEM() asm volatile("fence.proxy.async.shared::cta;" ::: "memory")
__device__ __forceinline__ void bar_sync(int id, int n) { asm volatile("bar.sync %0, %1;" :: "r"(id), "r"(n) : "memory"); }

#define D16(c) c(d[0]), c(d[1]), c(d[2]), c(d[3]), c(d[4]), c(d[5]), c(d[6]), c(d[7]), \
               c(d[8]), c(d[9]), c(d[10]), c(d[11]), c(d[12]), c(d[13]), c(d[14]), c(d[15])
template<bool FIRST> __device__ __forceinline__ void wgmma_rs_n32(float (&d)[16], const uint32_t (&a)[4], uint64_t b) {
  if (FIRST)
    asm volatile("wgmma.mma_async.sync.aligned.m64n32k16.f32.bf16.bf16 {%0,%1,%2,%3,%4,%5,%6,%7,%8,%9,%10,%11,%12,%13,%14,%15}, {%16,%17,%18,%19}, %20, 0, 1, 1, 0;"
      : D16("=f") : "r"(a[0]), "r"(a[1]), "r"(a[2]), "r"(a[3]), "l"(b));
  else
    asm volatile("wgmma.mma_async.sync.aligned.m64n32k16.f32.bf16.bf16 {%0,%1,%2,%3,%4,%5,%6,%7,%8,%9,%10,%11,%12,%13,%14,%15}, {%16,%17,%18,%19}, %20, 1, 1, 1, 0;"
      : D16("+f") : "r"(a[0]), "r"(a[1]), "r"(a[2]), "r"(a[3]), "l"(b));
}
template<bool FIRST> __device__ __forceinline__ void wgmma_ss_n32_ta(float (&d)[16], uint64_t a, uint64_t b) {
  if (FIRST)
    asm volatile("wgmma.mma_async.sync.aligned.m64n32k16.f32.bf16.bf16 {%0,%1,%2,%3,%4,%5,%6,%7,%8,%9,%10,%11,%12,%13,%14,%15}, %16, %17, 0, 1, 1, 1, 0;"
      : D16("=f") : "l"(a), "l"(b));
  else
    asm volatile("wgmma.mma_async.sync.aligned.m64n32k16.f32.bf16.bf16 {%0,%1,%2,%3,%4,%5,%6,%7,%8,%9,%10,%11,%12,%13,%14,%15}, %16, %17, 1, 1, 1, 1, 0;"
      : D16("+f") : "l"(a), "l"(b));
}
__device__ __forceinline__ void wgmma_ss_n128_tb(float (&d)[64], uint64_t a, uint64_t b) {
  asm volatile("wgmma.mma_async.sync.aligned.m64n128k16.f32.bf16.bf16 "
    "{%0,%1,%2,%3,%4,%5,%6,%7,%8,%9,%10,%11,%12,%13,%14,%15,%16,%17,%18,%19,%20,%21,%22,%23,%24,%25,%26,%27,%28,%29,%30,%31,"
    "%32,%33,%34,%35,%36,%37,%38,%39,%40,%41,%42,%43,%44,%45,%46,%47,%48,%49,%50,%51,%52,%53,%54,%55,%56,%57,%58,%59,%60,%61,%62,%63}, "
    "%64, %65, 1, 1, 1, 0, 1;"
    : "+f"(d[0]), "+f"(d[1]), "+f"(d[2]), "+f"(d[3]), "+f"(d[4]), "+f"(d[5]), "+f"(d[6]), "+f"(d[7]),
      "+f"(d[8]), "+f"(d[9]), "+f"(d[10]), "+f"(d[11]), "+f"(d[12]), "+f"(d[13]), "+f"(d[14]), "+f"(d[15]),
      "+f"(d[16]), "+f"(d[17]), "+f"(d[18]), "+f"(d[19]), "+f"(d[20]), "+f"(d[21]), "+f"(d[22]), "+f"(d[23]),
      "+f"(d[24]), "+f"(d[25]), "+f"(d[26]), "+f"(d[27]), "+f"(d[28]), "+f"(d[29]), "+f"(d[30]), "+f"(d[31]),
      "+f"(d[32]), "+f"(d[33]), "+f"(d[34]), "+f"(d[35]), "+f"(d[36]), "+f"(d[37]), "+f"(d[38]), "+f"(d[39]),
      "+f"(d[40]), "+f"(d[41]), "+f"(d[42]), "+f"(d[43]), "+f"(d[44]), "+f"(d[45]), "+f"(d[46]), "+f"(d[47]),
      "+f"(d[48]), "+f"(d[49]), "+f"(d[50]), "+f"(d[51]), "+f"(d[52]), "+f"(d[53]), "+f"(d[54]), "+f"(d[55]),
      "+f"(d[56]), "+f"(d[57]), "+f"(d[58]), "+f"(d[59]), "+f"(d[60]), "+f"(d[61]), "+f"(d[62]), "+f"(d[63])
    : "l"(a), "l"(b));
}

__device__ __forceinline__ void tma3d_mc_e(uint32_t dst, const CUtensorMap* tm, int c1, int c2, uint32_t bar) {
  asm volatile("{ .reg .pred p; .reg .b64 h; " ONCE_H "elect.sync _|p, 0xffffffff;\n"
               "@p cp.async.bulk.tensor.3d.shared::cluster.global.mbarrier::complete_tx::bytes.multicast::cluster.L2::cache_hint [%0], [%1, {0, %3, %4}], [%2], %5, h; }"
               :: "r"(dst), "l"(tm), "r"(bar), "r"(c1), "r"(c2), "h"((uint16_t)3) : "memory");
}
__device__ __forceinline__ void prefetch3d_e(const CUtensorMap* tm, int c1, int c2) {
  asm volatile("{ .reg .pred p; elect.sync _|p, 0xffffffff;\n"
               "@p cp.async.bulk.prefetch.tensor.3d.L2.global [%0, {0, %1, %2}]; }" :: "l"(tm), "r"(c1), "r"(c2) : "memory");
}

__device__ __forceinline__ void count_e(uint32_t* p) {
  asm volatile("fence.acq_rel.gpu;" ::: "memory");
  __syncwarp();
  asm volatile("{ .reg .pred p; elect.sync _|p, 0xffffffff; @p red.relaxed.gpu.global.add.u32 [%0], 1; }" :: "l"(p) : "memory");
}
template<int NS = 0> __device__ __forceinline__ void await_count(const uint32_t* p, uint32_t n) {
  for (uint32_t i = 0; ld_acquire(p) < n && i < (1u << 22); i++) { if (NS) __nanosleep(NS); }
  asm volatile("fence.proxy.async.global;" ::: "memory");
}
__device__ __forceinline__ void await_flags(const uint32_t* p) {
  for (uint32_t i = 0; i < (1u << 22); i++) {
    uint4 v;
    asm volatile("ld.acquire.gpu.global.v4.u32 {%0,%1,%2,%3}, [%4];" : "=r"(v.x), "=r"(v.y), "=r"(v.z), "=r"(v.w) : "l"(p) : "memory");
    if (__all_sync(~0u, (v.x & v.y & v.z & v.w) == 0x01010101u)) break;
  }
  asm volatile("fence.proxy.async.global;" ::: "memory");
}
__device__ __forceinline__ void mbar_lim(uint32_t bar, uint32_t ph) { for (uint32_t i = 0; !mbar_try(bar, ph) && i < (1u << 20); i++) {} }

struct cf { float x, y; };
__host__ __device__ constexpr float cos64(int k) {
  return k == 0 ? 1.0f : k == 1 ? 0.99518472667219689f : k == 2 ? 0.98078528040323045f : k == 3 ? 0.95694033573220887f :
         k == 4 ? 0.92387953251128676f : k == 5 ? 0.88192126434835503f : k == 6 ? 0.83146961230254524f : k == 7 ? 0.77301045336273696f :
         k == 8 ? 0.70710678118654752f : k == 9 ? 0.63439328416364550f : k == 10 ? 0.55557023301960222f : k == 11 ? 0.47139673682599765f :
         k == 12 ? 0.38268343236508977f : k == 13 ? 0.29028467725446236f : k == 14 ? 0.19509032201612827f : k == 15 ? 0.09801714032956060f : 0.0f;
}
__host__ __device__ constexpr float c64(int k) { return k <= 16 ? cos64(k) : -cos64(32 - k); }
__host__ __device__ constexpr float s64(int k) { return k <= 16 ? cos64(16 - k) : cos64(k - 16); }

template<int N, int ST, bool INV> struct Fft {
  template<int K> static __device__ __forceinline__ void bf(const cf* e, const cf* o, cf* out) {
    if constexpr (K < N / 2) {
      constexpr int idx = K * (64 / N);
      const cf a = e[K], b = o[K];
      if constexpr (idx == 0) {
        out[K] = {a.x + b.x, a.y + b.y}; out[K + N / 2] = {a.x - b.x, a.y - b.y};
      } else if constexpr (idx == 16) {
        if constexpr (INV) { out[K] = {a.x - b.y, a.y + b.x}; out[K + N / 2] = {a.x + b.y, a.y - b.x}; }
        else               { out[K] = {a.x + b.y, a.y - b.x}; out[K + N / 2] = {a.x - b.y, a.y + b.x}; }
      } else {
        constexpr float c = c64(idx), s = INV ? s64(idx) : -s64(idx);
        cf p; p.x = fmaf(-s, b.y, fmaf(c, b.x, a.x)); p.y = fmaf(s, b.x, fmaf(c, b.y, a.y));
        out[K] = p; out[K + N / 2] = {fmaf(2.0f, a.x, -p.x), fmaf(2.0f, a.y, -p.y)};
      }
      bf<K + 1>(e, o, out);
    }
  }
  static __device__ __forceinline__ void run(const cf* in, cf* out) {
    cf e[N / 2], o[N / 2];
    Fft<N / 2, 2 * ST, INV>::run(in, e);
    Fft<N / 2, 2 * ST, INV>::run(in + ST, o);
    bf<0>(e, o, out);
  }
};
template<int ST, bool INV> struct Fft<1, ST, INV> {
  static __device__ __forceinline__ void run(const cf* in, cf* out) { out[0] = in[0]; }
};
template<bool INV> __device__ __forceinline__ void fft32(cf (&v)[32]) {
  cf o[32]; Fft<32, 1, INV>::run(v, o);
#pragma unroll
  for (int i = 0; i < 32; i++) v[i] = o[i];
}
__device__ __forceinline__ cf cmul(cf a, float c, float s) { return {fmaf(-a.y, s, a.x * c), fmaf(a.x, s, a.y * c)}; }
__device__ __forceinline__ float bf2f(__nv_bfloat16 v) { return __bfloat162float(v); }

__device__ __forceinline__ int tw_at(int i) { return (i & ~63) | (i & 31) << 1 | (i >> 5 & 1); }
template<bool INV, bool T128 = true> __device__ __forceinline__ void twiddles(cf (&v)[32], const float4* __restrict__ tw) {
#pragma unroll
  for (int j = 0; j < 32; j += 2) {
    float4 w;
    if (T128) w = tw[j * 16];
    else { const uint2 a = lds64(smem_u32(tw + j * 16)), b = lds64(smem_u32(tw + j * 16) + 8); w = make_float4(__uint_as_float(a.x), __uint_as_float(a.y), __uint_as_float(b.x), __uint_as_float(b.y)); }
    if (j) v[j] = cmul(v[j], w.x, INV ? -w.y : w.y);
    v[j + 1] = cmul(v[j + 1], w.z, INV ? -w.w : w.w);
  }
}
template<bool INV, class F> __device__ __forceinline__ void warp_fft1024(cf (&v)[32], float2* __restrict__ buf, const float2* __restrict__ tw, int t, int u, F mid) {
#pragma unroll 1
  for (uint32_t h = 0; h < 2; h++) {
    fft32<INV>(v);
    if (FUNR ? h : opaque(h)) continue;
    twiddles<INV>(v, (const float4*)tw + u);
    if (INV) {
      float* f = (float*)buf;
#pragma unroll
      for (int j = 0; j < 32; j++) f[j * 36 + t] = v[j].x;
      __syncwarp();
#pragma unroll
      for (int j = 0; j < 32; j += 4) { const float4 r = *(const float4*)(f + u * 36 + j); v[j].x = r.x; v[j + 1].x = r.y; v[j + 2].x = r.z; v[j + 3].x = r.w; }
      __syncwarp();
#pragma unroll
      for (int j = 0; j < 32; j++) f[j * 36 + t] = v[j].y;
      __syncwarp();
#pragma unroll
      for (int j = 0; j < 32; j += 4) { const float4 r = *(const float4*)(f + u * 36 + j); v[j].y = r.x; v[j + 1].y = r.y; v[j + 2].y = r.z; v[j + 3].y = r.w; }
    } else {
#pragma unroll
      for (int j = 0; j < 32; j++) buf[j * 33 + t] = make_float2(v[j].x, v[j].y);
      __syncwarp();
#pragma unroll
      for (int j = 0; j < 32; j++) { const float2 r = buf[u * 33 + j]; v[j] = {r.x, r.y}; }
    }
    __syncwarp();
    mid();
  }
}
constexpr int ROW_BUF = 32 * 33, INV_BUF = 32 * 18;

__device__ __forceinline__ int z_row(int p) { return (p & ~31) | (p & 7) << 2 | (p & 31) >> 3; }
__device__ __forceinline__ int inv_lane(int t) { return (t & ~14) | (t & 12) >> 1 | (t & 2) << 2; }
__device__ __forceinline__ float2 twiddle(int i) { float s, c; sincospif(-(float)((i >> 5) * (i & 31)) * (1.0f / 512.0f), &s, &c); return make_float2(c, s); }
template<class F, class G> __device__ __forceinline__ void fft_rows_fwd(float2* sm2, const __nv_bfloat16* gw, int cta, int tid, uint32_t full_bar, uint32_t release_bar, F ev, G extra) {
  const int t = tid & 31, w = tid >> 5, n = z_row(cta * 8 + w);
#pragma unroll 1
  for (int i = tid; i < 1024; i += 256) sm2[tw_at(i)] = twiddle(i);
  ev(5);
  mbar_spin(full_bar, 0);
  if (tid == 0) TL2(6);
  __syncwarp();
  const __nv_bfloat16* xa = (const __nv_bfloat16*)(sm2 + 1024 + w * ROW_BUF) + t;
  cf v[32];
  float ga = 0.f, gb = 0.f;
#pragma unroll
  for (int j = 0; j < 32; j++) {
    v[j] = {bf2f(xa[32 * j]), bf2f(xa[D_ + 32 * j])};
    const float g = bf2f(gw[32 * j + t]); ga = fmaf(v[j].x, g, ga); gb = fmaf(v[j].y, g, gb);
  }
#pragma unroll
  for (int o = 16; o; o >>= 1) { ga += __shfl_xor_sync(~0u, ga, o); gb += __shfl_xor_sync(~0u, gb, o); }
  if (t < 2) g_gate[n + 1024 * t] = __fdividef(1.0f, 1.0f + __expf(-(t ? gb : ga)));
  ev(6);
  bar_sync(13, 256);
  warp_fft1024<false>(v, sm2 + 1024 + w * ROW_BUF, sm2, t, t, [&]() { FENCE_ASYNC_SMEM(); mbar_arrive_warp(release_bar); });
  float ws, wc; sincospif(-(float)n * (1.0f / 1024.0f), &ws, &wc);
  ev(12);
  uint32_t tz = clock_lo();
  float4* z = (float4*)g_z + ((size_t)(t >> 1) * 1024 + cta * 8 + w) * 2 + (t & 1);
#pragma unroll
  for (int j = 0; j < 17; j++) {
    cf q = v[(32 - j) & 31];
    if (j < 16) {
      const cf r = {__shfl_sync(~0u, v[31 - j].x, 32 - t), __shfl_sync(~0u, v[31 - j].y, 32 - t)};
      if (t != 0) q = r;
    }
    const cf a = {v[j].x + q.x, v[j].y - q.y}, b = {v[j].y + q.y, q.x - v[j].x};
    const cf d = cmul({a.x - b.x, a.y - b.y}, wc, ws);
    if (j == POOL_AT) extra();
    if (PACE_Z && j && j < 16) delay_until(tz += PACE_Z);
    if ((j < 16 || t == 0) && ((EXP_ST & 4) || d.x == 123.f)) z[j * 32768] = make_float4(a.x + b.x, a.y + b.y, d.x, d.y);
  }
}
constexpr int CP = X128 == 0 ? 33 : X128 == 2 ? 34 : 36, COL_FS = 32 * 36 + 8, COL_W = (8192 + 16 * COL_FS * 4 + 127) & ~127, COL_SMEM = COL_W + 131072 + 128;

__device__ __forceinline__ void fft_cols(float2* sm2, int cta, const CUtensorMap* twr, const CUtensorMap* twi, const CUtensorMap* tzs) {
  const int grp = __shfl_sync(~0u, (int)(threadIdx.x >> 7), 0), tid = threadIdx.x & 127, tp = tid >> 2, w = __shfl_sync(~0u, tid >> 5, 0);
  float* buf = (float*)(sm2 + 1024) + (grp * 4 + (tid & 3)) * COL_FS;
  const uint32_t wsm = smem_u32(sm2) + COL_W, wbar = wsm + 131072 + (W_FINE ? w * 32 : 0);
  const int res = w * 2 + (tid & 1), el = res + grp * 2 + ((tid >> 1) & 1);
  uint32_t wa = (el >> 3) * 65536 + res * 4096 + (tp & 7) * 16 + (el & 7) * 2;
  auto load_w = [&](int q) {
    const uint32_t bar = wbar + (q & 1) * 8;
    mbar_expect(bar, W_FINE ? 16384 : 65536);
#pragma unroll 1
    for (int i = W_FINE ? 4 * w : 0; i < (W_FINE ? 4 * w + 4 : 16); i++) tma2d(wsm + (q & 1) * 65536 + (i & 1) * 32768 + (i >> 1) * 4096, i & 1 ? twi : twr, (i >> 1) * 512 + q * 8, 0, bar);
  };
  const bool lead = (tid & (W_FINE ? 31 : 127)) == 0, first = grp < 2 && lead;
  if (first) { mbar_init(wbar + grp * 8, 1); sts32(wbar + 16 + grp * 4, grp ? 0 : w); asm volatile("fence.mbarrier_init.release.cluster;" ::: "memory"); }
#pragma unroll 1
  for (int i = threadIdx.x; i < 1024; i += 512) {
    const float2 t = twiddle(z_row(i));
    sm2[tw_at(i)] = t;
    if (cta == 0) g_tw[tw_at(inv_lane(z_row(i)))] = t;
  }
  for (uint32_t n = 0; ld_acquire(g_ctl + C_P1) < 128; ) { watchdog(n, 1u << 22); __nanosleep(200); }
  if (COL_DLY) delay_cycles(COL_DLY);
  if (first) load_w(cta * 16 + grp);
  __syncthreads();
  delay_cycles(1 + grp * DLY_GRP);
  mbar_wait(wbar, 0);
  const int end = cta * 64 + 64 + (cta == 3);
  for (int item = cta * 64 + grp; item < end; item += 4, wa ^= 65536) {
    float2* zp = g_z + (size_t)item * 4096;
    auto next_w = [&]() {
      const int q = (item >> 2) + (W_FINE && grp + w > 3);
      uint32_t n; asm volatile("atom.shared.inc.u32 %0, [%1], 3;" : "=r"(n) : "r"(wbar + 16 + (q & 1) * 4) : "memory");
      if (EXP_W && n == 3 && q < (cta * 16 + 15)) load_w(q + 2);
    };
    cf v[32];
#pragma unroll
    for (int j = 0; j < 32; j++) { const float2 a = ld_once(zp + tid + j * 128); v[j] = {a.x, a.y}; }
#pragma unroll 1
    for (int ph = 0; ; ph++) {
      fft32<false>(v);
      twiddles<false, T128_>(v, (const float4*)sm2 + tp);
      if (Z_ST) asm volatile("cp.async.bulk.wait_group.read 0;" ::: "memory");
      bar_sync(1 + grp, 128);
      if (lead) {
        if (ph) {
          if (!W_AT) next_w();
        } else if (Z_PF && item + 4 < end) asm volatile("cp.async.bulk.prefetch.L2.global [%0], %1;" :: "l"(zp + 4 * 4096 + w * 1024), "n"(W_FINE ? 8192 : 32768) : "memory");
      }
      __syncwarp();
#pragma unroll
      for (int j = 0; j < 32; j++) buf[((j & 3) * 8 + (j >> 2)) * CP + tp] = v[j].x;
      bar_sync(1 + grp, 128);
      if (X128 == 0) {
#pragma unroll
        for (int j = 0; j < 32; j++) v[j].x = buf[tp * CP + (j & 3) * 8 + (j >> 2)];
      } else if (X128 == 2) {
#pragma unroll
        for (int j = 0; j < 16; j++) { const float2 r = *(const float2*)(buf + tp * CP + 2 * j); cf* d = v + (j & 3) * 8 + (j >> 2); d[0].x = r.x; d[4].x = r.y; }
      } else
#pragma unroll
      for (int j = 0; j < 8; j++) {
        const float4 r = *(const float4*)(buf + tp * 36 + 4 * j);
        cf* d = v + (j & 1) * 16 + (j >> 1);
        d[0].x = r.x; d[4].x = r.y; d[8].x = r.z; d[12].x = r.w;
      }
      bar_sync(1 + grp, 128);
#pragma unroll
      for (int j = 0; j < 32; j++) buf[((j & 3) * 8 + (j >> 2)) * CP + tp] = v[j].y;
      bar_sync(1 + grp, 128);
      if (X128 == 0) {
#pragma unroll
        for (int j = 0; j < 32; j++) v[j].y = buf[tp * CP + (j & 3) * 8 + (j >> 2)];
      } else if (X128 == 2) {
#pragma unroll
        for (int j = 0; j < 16; j++) { const float2 r = *(const float2*)(buf + tp * CP + 2 * j); cf* d = v + (j & 3) * 8 + (j >> 2); d[0].y = r.x; d[4].y = r.y; }
      } else
#pragma unroll
      for (int j = 0; j < 8; j++) {
        const float4 r = *(const float4*)(buf + tp * 36 + 4 * j);
        cf* d = v + (j & 1) * 16 + (j >> 1);
        d[0].y = r.x; d[4].y = r.y; d[8].y = r.z; d[12].y = r.w;
      }
      fft32<false>(v);
      if (ph) break;
      const int q = min((item >> 2) + (!W_FINE || grp + w >= 3), 64);
      if (EXP_W) mbar_wait(wbar + (q & 1) * 8, (q >> 1) & 1);
#pragma unroll
      for (int j = 0; j < 32; j++) {
        uint32_t re, im;
        asm volatile("ld.shared.u16 %0, [%1];" : "=r"(re) : "r"(wsm + wa + j * 128) : "memory");
        asm volatile("ld.shared.u16 %0, [%1];" : "=r"(im) : "r"(wsm + wa + 32768 + j * 128) : "memory");
        const cf r = cmul(v[j], __uint_as_float(re << 16), __uint_as_float(im << 16));
        v[j] = {r.y, r.x};
      }
    }
    if (Z_ST) {
      float2* st = sm2 + 1024 + grp * (COL_FS * 2) + w * 512;
      bar_sync(1 + grp, 128);
#pragma unroll
      for (int h = 0; h < 2; h++) {
        if (h && Z_ST == 2) {
#pragma unroll
          for (int j = 16; j < 32; j++) zp[tid + j * 128] = make_float2(v[j].y, v[j].x);
          break;
        }
        if (h) { asm volatile("cp.async.bulk.wait_group.read 0;" ::: "memory"); __syncwarp(); }
#pragma unroll
        for (int j = 0; j < 16; j++) st[j * 32 + (tid & 31)] = make_float2(v[h * 16 + j].y, v[h * 16 + j].x);
        FENCE_ASYNC_SMEM();
        __syncwarp();
        tma2d_st_e(tzs, w * 128, item * 32 + h * 16, smem_u32(st));
        asm volatile("cp.async.bulk.commit_group;" ::: "memory");
      }
    } else {
#pragma unroll
      for (int j = 0; j < 32; j++) zp[tid + j * 128] = make_float2(v[j].y, v[j].x);
    }
    if (W_AT) { if (lead) next_w(); __syncwarp(); }
  }
  if (Z_ST) asm volatile("cp.async.bulk.wait_group 0; fence.proxy.async.global;" ::: "memory");
  __syncthreads();
  if (threadIdx.x < 32) {
    count_e(g_ctl + C_COLS);
    await_count(g_ctl + C_COLS, 4);
    g_ctl[C_P1] = 0;
  }
  __syncthreads();
  ((float4*)sm2)[threadIdx.x] = __ldcg((const float4*)g_tw + threadIdx.x);
  __syncthreads();
}

template<class F> __device__ __forceinline__ void fft_rows_inv(uint32_t zs, float2* buf, const float2* tw, int p, int lane, __nv_bfloat16* out, F read) {
  const int n = z_row(p), t = (lane & 17) | (lane & 6) << 1 | (lane & 8) >> 2, src = inv_lane(-t & 31);
  const uint32_t z = zs + (t >> 1) * 128 + ((((p & 3) * 2 + (t & 1)) ^ (t >> 1 & 7)) << 4);
  FT(0, 0.f);
  float4 e[17];
  uint32_t all = 0;
  e[16] = __ldcg((const float4*)g_z + ((size_t)256 * 1024 + p) * 2);
  const float g0 = __ldcg(g_gate + n), g1 = __ldcg(g_gate + n + 1024);
#pragma unroll
  for (int j = 0; j < 16; j++) { const uint4 u = lds128(z + j * 2048); e[j] = make_float4(__uint_as_float(u.x), __uint_as_float(u.y), __uint_as_float(u.z), __uint_as_float(u.w)); all |= u.x; }
  sched_fence(all);
  read();
  float ws, wc; sincospif((float)n * (1.0f / 1024.0f), &ws, &wc);
  cf v[32], q[17];
#pragma unroll
  for (int j = 0; j < 17; j++) {
    const cf d = cmul({e[j].z, e[j].w}, wc, ws);
    cf a = {e[j].x + d.x, e[j].y + d.y}, b = {e[j].x - d.x, e[j].y - d.y};
    if (j == 16 || (j == 0 && t == 0)) { a.y = 0.f; b.y = 0.f; }
    if (j < 16) v[j] = {a.x - b.y, a.y + b.x};
    q[j] = {a.x + b.y, b.x - a.y};
  }
#pragma unroll
  for (int j = 16; j < 32; j++) {
    v[j] = {__shfl_sync(~0u, q[31 - j].x, src), __shfl_sync(~0u, q[31 - j].y, src)};
    if (t == 0) v[j] = q[32 - j];
  }
  FT(1, v[0].x + v[16].x + v[31].x);
  warp_fft1024<true>(v, buf, tw, t, lane, []() {});
  FT(3, v[31].y + v[0].x);
  const float sc = 0.5f / (2048.0f * 1024.0f), s0 = (1.f - g0) * sc, s1 = (1.f - g1) * sc;
  uint2* o = (uint2*)(out + (size_t)n * D_) + (lane ^ (n & 1) << 3);
#pragma unroll
  for (int j = 0; j < 32; j += 4) {
    o[8 * j] = make_uint2(pack_bf16(v[j].x * s0, v[j + 1].x * s0), pack_bf16(v[j + 2].x * s0, v[j + 3].x * s0));
    o[256 * D_ + 8 * j] = make_uint2(pack_bf16(v[j].y * s1, v[j + 1].y * s1), pack_bf16(v[j + 2].y * s1, v[j + 3].y * s1));
  }
  FT(4, 0.f);
}

constexpr int NP = NP_, NHV = REG_F == 216 ? 5 : 7, NV = 16 - NHV;
constexpr int XEND = NSEG;
constexpr uint32_t SM_WO = 0, SM_V = 65536, SM_LAND = SM_V + 8192, SM_MEM = SM_LAND + 24576, SM_SP = SM_MEM, SM_SPM = SM_MEM + 5120, SM_OM = SM_MEM + 6144,
                   SM_OX = SM_MEM + 8192, SM_RED = SM_OX + 2048, SM_XCH = SM_RED + 1024, SM_SUM = SM_XCH + 4096, SM_VM = SM_SUM + 128, SM_TAB = SM_VM + 2048, SM_TRACE = SM_TAB + 2048,
                   ST_WG = (32 - NP + NV) * 2048,
                   SM_XT = 2 * ST_WG, SM_POOL = SM_XT + 32768, SM_HV = SM_POOL + 2 * NP * 2048,
                   SM_BAR = SM_HV + 2 * NHV * 2048, SM_SEL = SM_BAR + 320, CHAIN_SMEM = SM_SEL + 544 + 1024;
constexpr uint32_t SM_FFT = 49152, SM_GW = SM_XT - 2048;
static_assert(NP % 4 == 0 && NV == 11 && SM_TRACE + 4096 <= SM_XT, "shared memory layout");
static_assert(CHAIN_SMEM <= 232448 && COL_SMEM <= SM_BAR && SM_FFT + (1024 + 8 * ROW_BUF) * 8 <= SM_GW && NP == 12, "shared memory budget");
enum { B_WFULL = 0, B_WREAD = 2, B_WOFULL, B_XFULL, B_XEMPTY, B_E1TRIG, B_E2TRIG, B_PVDONE, B_PUB, B_SC, B_PFULL, B_SPFREE,
       B_LAND, B_LFREE, B_DONE, B_SEL, B_PROBE, B_FREE, B_P1, B_ROWS, B_VFULL, B_VST, B_TW, B_BT, B_WREAD0, B_Z, B_GFULL = B_Z + 4, B_GEMPTY = B_GFULL + 5, B_END = B_GEMPTY + 5 };
static_assert(B_END * 8 <= 320, "barriers");
__host__ __device__ constexpr uint32_t bar_codes(int g) {
  uint32_t r = 0;
  for (int i = 16 * g; i < 16 * g + 16; i++)
    r |= (i == B_LAND ? 3u : i == B_WREAD || i == B_XEMPTY || i == B_E1TRIG || i == B_E2TRIG || i == B_LFREE || i == B_FREE || i == B_VST || i == B_P1 || i == B_ROWS ? 2u :
          i >= B_GEMPTY || i == B_WREAD0 || i == B_PROBE || i == B_DONE || i == B_PVDONE || i == B_PUB || i == B_SC || i == B_SPFREE ? 1u : 0u) << 2 * (i & 15);
  return r;
}
constexpr uint32_t SM_BT = 65536, SM_TW = SM_XT - 8192, COL_Z = 80 * 1024;
static_assert(SM_XT + 3 * 32768 <= SM_BAR && SM_BT + 32768 <= SM_MEM && SM_TRACE <= SM_TW && SM_MEM + 4 * INV_BUF * 8 <= SM_TRACE &&
              8192 + 16 * INV_BUF * 8 <= COL_Z && COL_Z + 131072 <= SM_BAR, "shared memory layout");
__device__ __forceinline__ uint32_t next_stage(uint32_t o) { return o == SM_XT + 65536 ? 0 : o == 32768 ? SM_XT : o + 32768; }

struct ChainCtx { char* mail; uint32_t sb, sel; int r, h, a, b, j, m, w, lane; };
#define BAR(i) (c.sb + SM_BAR + 8 * (i))

__device__ __forceinline__ uint32_t tile_off(int line, int lane) {
  return line * 128 + (((lane & 3) ^ line) << 5) + (lane >> 2) * 4;
}
__device__ __forceinline__ uint32_t read_off(int lane) {
  const int n = lane >> 2, jj = lane & 3, l = 2 * (jj >> 1) + (n & 1);
  return l * 128 + (((n >> 1) ^ l) << 5) + (jj & 1) * 16;
}
__device__ __forceinline__ uint32_t frag_off(int w, int lane) {
  const int mi = lane >> 3, r = lane & 7;
  return ((mi >> 1) * 8 + r) * 128 + (((2 * w + (mi & 1)) ^ r) << 4);
}
__device__ __forceinline__ uint32_t land_off(int w, int lane) { return w * 512 + ((lane ^ (((lane >> 4) | ((w & 1) << 1)) << 1)) << 4); }
__device__ __forceinline__ uint32_t tagged(uint32_t v, uint32_t tag) { return (v | 1u) ^ tag; }
__device__ __forceinline__ void mma_a(float (&d)[4], const uint32_t (&a)[4], uint32_t b0, uint32_t b1) { mma16816(d, a[0], a[1], a[2], a[3], b0, b1); }
__device__ __forceinline__ void mma_q(float (&d)[4], const uint4& a, uint32_t b0, uint32_t b1) { mma16816(d, a.x, a.y, a.z, a.w, b0, b1); }
__device__ __forceinline__ uint4 add4(uint4 a, uint4 b) {
  return make_uint4(add_bf16x2(a.x, b.x), add_bf16x2(a.y, b.y), add_bf16x2(a.z, b.z), add_bf16x2(a.w, b.w));
}
__device__ __forceinline__ void mbar_arrive_both(uint32_t bar, int peer) {
  __syncwarp();
  asm volatile("{ .reg .pred p; .reg .u32 a; mapa.shared::cluster.u32 a, %0, %1; elect.sync _|p, 0xffffffff;\n"
               "@p mbarrier.arrive.shared::cta.b64 _, [%0]; @p mbarrier.arrive.shared::cluster.b64 _, [a]; }" :: "r"(bar), "r"(peer) : "memory");
}

__device__ __forceinline__ void arrive_remote_if(uint32_t a, bool on) {
  asm volatile("{ .reg .pred p; setp.ne.u32 p, %1, 0; @p mbarrier.arrive.shared::cluster.b64 _, [%0]; }" :: "r"(a), "r"((uint32_t)on) : "memory");
}
__device__ __forceinline__ void store_count(void* p, uint4 v, void* cnt) {
  asm volatile("{ .reg .pred p, q; .reg .b128 a, b; .reg .b64 l, h; mov.b64 l, {%1, %2}; mov.b64 h, {%3, %4}; mov.b128 a, {l, h};\n"
               "atom.relaxed.gpu.global.exch.b128 b, [%0], a; mov.b128 {l, h}, b; setp.eq.u64 q, l, 0x7fc17fc17fc17fc1; @q pmevent 1;\n"
               "elect.sync _|p, 0xffffffff; @p red.relaxed.gpu.global.add.u32 [%5], 1; }"
               :: "l"(p), "r"(v.x), "r"(v.y), "r"(v.z), "r"(v.w), "l"(cnt) : "memory");
}

template<int N> __device__ __forceinline__ void pad() {
#pragma unroll
  for (int i = 0; i < N; i++) asm volatile("pmevent 3;");
}
__device__ __forceinline__ int lane_id() {
  int l; asm volatile("{ .reg .u32 t; mov.u32 t, %%laneid; shfl.sync.idx.b32 %0, t, t, 31, 0xffffffff; }" : "=r"(l)); return l;
}
__device__ __forceinline__ uint32_t tid_now() { uint32_t t; asm volatile("mov.u32 %0, %%tid.x;" : "=r"(t)); return t; }
enum { NB_ATT = 1, NB_OM = 2, NB_VM = 3, NB_XCH = 4, NB_MEM = 8, NB_HELP = 12 };
__device__ __forceinline__ uint32_t dep(uint32_t a, uint32_t v, uint32_t z) { uint32_t r; asm("shf.l.wrap.b32 %0, %2, %1, %3;" : "=r"(r) : "r"(a), "r"(v), "r"(z)); return r; }
__device__ __forceinline__ uint32_t vary(uint32_t a, int s, uint32_t z) { return dep(a, 0, z + 32 * s); }
__device__ __forceinline__ char* mk_ptr(uint32_t lo, uint32_t hi) { uint64_t r; asm("mov.b64 %0, {%1, %2};" : "=l"(r) : "r"(lo), "r"(hi)); return (char*)r; }
__device__ __forceinline__ void lds_frag(uint32_t (&r)[4], uint32_t a) {
  asm volatile("ld.shared.v4.u32 {%0,%1,%2,%3}, [%4];" : "=r"(r[0]), "=r"(r[1]), "=r"(r[2]), "=r"(r[3]) : "r"(a) : "memory");
}
__device__ __forceinline__ uint32_t stale2(uint32_t a, uint32_t b, uint32_t t) { uint32_t r; asm("lop3.b32 %0, %1, %2, %3, 0xbd;" : "=r"(r) : "r"(a), "r"(b), "r"(t)); return r; }
__device__ __forceinline__ uint32_t stale1(uint32_t acc, uint32_t a, uint32_t t) { uint32_t r; asm("lop3.b32 %0, %1, %2, %3, 0xf9;" : "=r"(r) : "r"(acc), "r"(a), "r"(t)); return r; }
__device__ __forceinline__ bool all_clear(uint32_t x, uint32_t m) {
  uint32_t r;
  asm volatile("{ .reg .pred p; .reg .u32 t; and.b32 t, %1, %2; setp.eq.u32 p, t, 0; vote.sync.all.pred p, p, 0xffffffff; selp.u32 %0, 1, 0, p; }" : "=r"(r) : "r"(x), "r"(m));
  return r;
}
__device__ __forceinline__ bool arrive_if_all(bool ok, int id, int n) {
  uint32_t r;
  asm volatile("{ .reg .pred p, q; setp.ne.u32 p, %1, 0; vote.sync.all.pred q, p, 0xffffffff; @q bar.arrive %2, %3; selp.u32 %0, 1, 0, q; }"
               : "=r"(r) : "r"((uint32_t)ok), "r"(id), "r"(n) : "memory");
  return r;
}
__device__ __forceinline__ bool arrive_if_clear(uint32_t x, uint32_t m, int id, int n) {
  uint32_t r;
  asm volatile("{ .reg .pred p; .reg .u32 t; and.b32 t, %1, %2; setp.eq.u32 p, t, 0; vote.sync.all.pred p, p, 0xffffffff; @p bar.arrive %3, %4; selp.u32 %0, 1, 0, p; }"
               : "=r"(r) : "r"(x), "r"(m), "r"(id), "r"(n) : "memory");
  return r;
}
__device__ __forceinline__ void touch(const void* p, uint32_t z) {
  asm volatile("{ .reg .pred p; setp.eq.u32 p, %1, 0x7fff0000; @p prefetch.global.L2 [%0]; }" :: "l"(p), "r"(z) : "memory");
}

__device__ __forceinline__ uint64_t desc_x(uint32_t lo, int k) {
  uint64_t d; asm("mov.b64 %0, {%1, %2};" : "=l"(d) : "r"(lo + (k >> 2) * 64 + (k & 3) * 2), "r"(0x40000200)); return d;
}
template<int K0, int K1> __device__ __forceinline__ void issue_qk(float (&xa)[16], const uint32_t (&wt)[16][4], uint32_t lo) {
  WG_FENCE();
#pragma unroll
  for (int k = K0; k < K1; k++) {
    if (k >= EXP_NWG) continue;
    if (k == 0) wgmma_rs_n32<true>(xa, wt[0], desc_x(lo, 0));
    else wgmma_rs_n32<false>(xa, wt[k], desc_x(lo, k));
  }
  WG_COMMIT();
}
__host__ __device__ constexpr int v_order(int i) { return SSPOS == 0 ? i : SSPOS == 2 ? (i + NV) % 16 : NHV == 5 ? (i % 3 == 2 ? NV + i / 3 : i - i / 3) : (i == 15 ? NV - 1 : i % 2 ? NV + i / 2 : i / 2); }
__device__ __forceinline__ void issue_v(float (&xa)[16], const uint32_t (&wv)[16][4], uint32_t lo, uint32_t la) {
  WG_FENCE();
#pragma unroll
  for (int i = 0; i < EXP_NWG; i++) {
    const int k = v_order(i);
    const uint64_t b = desc_x(lo, k);
    if (k < NV) { if (i == 0) wgmma_rs_n32<true>(xa, wv[k], b); else wgmma_rs_n32<false>(xa, wv[k], b); }
    else        { if (i == 0) wgmma_ss_n32_ta<true>(xa, desc128(la + (k - NV) * 128), b); else wgmma_ss_n32_ta<false>(xa, desc128(la + (k - NV) * 128), b); }
  }
  WG_COMMIT();
}
template<bool ISV> __device__ __forceinline__ void park_own(uint32_t (&q)[4], float (&xa)[16], uint32_t dst, int slot, uint32_t z) {
  uint32_t p[8];
#pragma unroll
  for (int i = 0; i < 16; i++) asm volatile("" : "+f"(xa[i]) :: "memory");
#pragma unroll
  for (int i = 0; i < 2; i++) {
    const float* k = xa + 8 * i;
    if (ISV) { p[4 * i] = pack_bf16(k[0], k[1]); p[4 * i + 1] = pack_bf16(k[2], k[3]); p[4 * i + 2] = pack_bf16(k[4], k[5]); p[4 * i + 3] = pack_bf16(k[6], k[7]); }
    else     { p[4 * i] = pack_bf16(k[0], k[2]); p[4 * i + 1] = pack_bf16(k[1], k[3]); p[4 * i + 2] = pack_bf16(k[4], k[6]); p[4 * i + 3] = pack_bf16(k[5], k[7]); }
  }
  sts128(dep(dep(dst, p[4] ^ p[5] ^ p[6], z), p[7], z) + slot * 8192, make_uint4(p[0], p[1], p[2], p[3]));
#pragma unroll
  for (int i = 0; i < 4; i++) q[i] = p[4 + i];
}
__device__ __forceinline__ void park_peer(const uint32_t (&q)[4], uint32_t dst, int slot, const ChainCtx& c) {
  const uint32_t bar = BAR(B_LAND);
  if (EXP_PEER) st_async4(mapa(dst + slot * 8192, c.b ^ 1), q[0], q[1], q[2], q[3], mapa(bar, c.b ^ 1));
  else touch((void*)(uintptr_t)(q[0] ^ q[1] ^ q[2] ^ q[3]), c.sb);
  mbar_arrive_warp(bar);
}
__device__ __forceinline__ uint32_t put_tag(uint32_t v, uint32_t bit, uint32_t t) {
  uint32_t r; asm("lop3.b32 %0, %1, %2, %3, 0x74;" : "=r"(r) : "r"(v), "r"(bit), "r"(t)); return r;
}
__device__ __forceinline__ void mem_proj(const uint32_t (&wa)[16][4], const uint32_t (&wb)[16][4], uint32_t (&wv)[16][4], uint32_t (&af)[16][4],
                                         uint32_t& wo, const char*& pa, uint32_t tab, uint32_t t16, uint32_t pk, const ChainCtx& c, int s) {
  const uint32_t mp = t16 & ~0x600u, id = NB_MEM + (t16 >> 11);
  uint32_t r[8][4];
  float la[4][4] = {}, lg[NLAG][4] = {}, lv[4][4] = {};
  auto lead = [&](int k) { mma_a(la[k & 3], wa[k], r[k >> 1][2 * (k & 1)], r[k >> 1][2 * (k & 1) + 1]); };
  auto lag = [&](int k) { mma_a(lg[k % NLAG], wb[k], r[k >> 1][2 * (k & 1)], r[k >> 1][2 * (k & 1) + 1]); };
  auto sum = [](const float (&d)[4][4], int i) { return (d[0][i] + d[1][i]) + (d[2][i] + d[3][i]); };
  bar_sync(id, 160);
  TR(s, 0);
#pragma unroll
  for (int i = 0; i < 4; i++) ldsm4t(r[i], mp + (c.sb + SM_MEM + i * 512));
  uint4 tq;
  if (!TQ_AT) tq = lds128(tab);
  bar_sync(id + 2, 160);
  uint32_t first = 0;
#pragma unroll
  for (int k = 0; k < 8; k++) { lead(k); if (k == C1_AT - 4) first = dep(mp, __float_as_uint(la[k & 3][0]), c.sb); }
  uint32_t ta, tb;
  if (!TQ_AT) { ta = tq.x | ((pk >> 16) & 511); tb = tq.z ^ ((pk >> 16) & 511); }
  const uint32_t mp1 = C1_AT >= 4 ? (TQ_AT ? first : dep(first, ta ^ tb, c.sb)) : dep(mp, __float_as_uint(la[C1_AT & 3][0]) ^ (TQ_AT ? 0 : ta ^ tb), c.sb);
#pragma unroll
  for (int i = 4; i < 8; i++) ldsm4t(r[i], mp1 + (c.sb + SM_MEM + 2048 + i * 512));
  if (TQ_AT) { tq = lds128(tab); ta = tq.x | ((pk >> 16) & 511); tb = tq.z ^ ((pk >> 16) & 511); }
  char* dst = mk_ptr(ta, tq.y);
  char* dst2 = mk_ptr(tb, tq.w);
  const uint32_t hv = pk & 0xFFFF;
#pragma unroll
  for (int k = NV; k < NV + HV_E; k++) ldsm4t(wv[k], dep(hv, r[HV_R][0], c.sb) + (c.sb + SM_HV + (k - NV) * 2048));
#pragma unroll
  for (int k = 0; k < LAG_0; k++) lag(k);
#pragma unroll
  for (int k = 8; k < 16; k++) lead(k);
  const uint32_t s0 = __float_as_uint(sum(la, 0)), s3 = __float_as_uint(sum(la, 3));
  sts128((HV_E ? dep(t16, wv[NV][0] ^ wv[NV + HV_E / 2][1] ^ wv[NV + HV_E - (HV_E > 0)][2], c.sb) : TQ_AT ? dep(t16, ta ^ tb, c.sb) : t16) + (c.sb + SM_XCH),
         make_uint4(s0, __float_as_uint(sum(la, 1)), __float_as_uint(sum(la, 2)), s3));
  if (XB) bar_sync(NB_XCH, 256); else bar_sync(NB_XCH | ((t16 >> 9) & 3), 64);
#pragma unroll
  for (int k = LAG_0; k < LAG_0 + LAG_G; k++) r[k >> 1][2 * (k & 1)] = dep(r[k >> 1][2 * (k & 1)], LAG_S == 0 ? s3 : __float_as_uint(la[LAG_S - 1][0]), c.sb);
#pragma unroll
  for (int k = LAG_0; k < O_AT; k++) lag(k);
  const uint4 o = lds128((O_AT > LAG_0 ? dep(t16 ^ 2048, __float_as_uint(lg[(O_AT - 1) % NLAG][0]), c.sb) : t16 ^ 2048) + (c.sb + SM_XCH));
#pragma unroll
  for (int k = O_AT > LAG_0 ? O_AT : LAG_0; k < 16; k++) lag(k);
#pragma unroll
  for (int k = 0; k < V_E; k++) mma_a(lv[k & 3], wv[k], r[k >> 1][2 * (k & 1)], r[k >> 1][2 * (k & 1) + 1]);
  float t[4];
#pragma unroll
  for (int i = 0; i < 4; i++) {
    const float oi = __uint_as_float(i == 0 ? o.x : i == 1 ? o.y : i == 2 ? o.z : o.w);
    t[i] = NLAG == 4 ? (LAG_T ? ((lg[0][i] + lg[1][i]) + oi) + (lg[2 % NLAG][i] + lg[3 % NLAG][i]) : (((lg[0][i] + lg[1][i]) + lg[2 % NLAG][i]) + lg[3 % NLAG][i]) + oi) : LAG_T && NLAG == 2 ? (lg[0][i] + lg[1][i]) + oi : NLAG == 3 ? (lg[1][i] + lg[2 % NLAG][i]) + (lg[0][i] + oi) : (lg[0][i] + oi) + lg[1][i];
  }
  const uint32_t y0 = put_tag(pack_bf16(t[0], t[2]), pk >> 31, s >> 1), y1 = put_tag(pack_bf16(t[1], t[3]), pk >> 31, s >> 1);
  st_pub(dst, y0); st_pub(dst2, y1);
  mbar_arrive_warp(BAR(B_E1TRIG));
  TR(s, 1);
  sched_fence(c.sb);
  const uint4 tv = lds128(tab + 16);
#pragma unroll
  for (int k = NV + HV_E; k < 16; k++) ldsm4t(wv[k], (k < NV + HV_E + HV_D ? hv : dep(hv, k == NV + HV_E + HV_D ? wv[k - HV_D][0] ^ tv.x : wv[k - HV_D][0], c.sb)) + (c.sb + SM_HV + (k - NV) * 2048));
  wo = (hv & 2047) | ((t16 & 2048) << 3);
  const uint32_t l8 = (t16 >> 1) & 255;
  char* dv = mk_ptr(tv.x | l8, tv.y);
  pa = mk_ptr(tv.z | l8, tv.w);
#pragma unroll
  for (int f = 0; f < WO_0; f++) ldsm4t(af[f], dep(wo, f < WO_D ? wv[16 - WO_D + f][0] : af[f < WO_D ? 0 : f - WO_D][0], c.sb) + (c.sb + SM_WO + (f & 1) * 32768 + (f >> 1) * 2048));
#pragma unroll
  for (int k = V_E; k < 16; k++) mma_a(lv[k & 3], wv[k], r[k >> 1][2 * (k & 1)], r[k >> 1][2 * (k & 1) + 1]);
  const uint32_t z0 = put_tag(pack_bf16(sum(lv, 0), sum(lv, 1)), (~t16 >> 4) & 1, s >> 1), z1 = pack_bf16(sum(lv, 2), sum(lv, 3));
  st_pub2(dv, z0, z1);
  if (FIN_AT >= 3) mbar_arrive_warp(BAR(B_VST));
  TR(s, 2);
}
__device__ __forceinline__ uint32_t max_bf16x2(uint32_t a, uint32_t b) { uint32_t r; asm("max.bf16x2 %0, %1, %2;" : "=r"(r) : "r"(a), "r"(b)); return r; }
constexpr float SCL = 0.08838834764831845f * 1.4426950408889634f;
__device__ __forceinline__ uint32_t max5(const uint32_t (&sc)[5]) { return max_bf16x2(max_bf16x2(max_bf16x2(max_bf16x2(sc[0], sc[1]), sc[2]), sc[3]), sc[4]); }
__device__ __forceinline__ float row_off(uint32_t m, uint32_t& m1) {
  m1 = __shfl_xor_sync(~0u, m, 1);
  const uint32_t m2 = __shfl_xor_sync(~0u, m, 2), m3 = __shfl_xor_sync(~0u, m, 3);
  const uint32_t mm = max_bf16x2(max_bf16x2(max_bf16x2(m, m1), m2), m3);
  return -SCL * fmaxf(__uint_as_float(mm << 16), __uint_as_float(mm & 0xFFFF0000u));
}
__device__ __forceinline__ void unpack(float (&f)[10], const uint32_t (&sc)[5]) {
#pragma unroll
  for (int i = 0; i < 5; i++) {
    asm volatile("shl.b32 %0, %1, 16;" : "=f"(f[2 * i]) : "r"(sc[i]));
    asm volatile("and.b32 %0, %1, 0xffff0000;" : "=f"(f[2 * i + 1]) : "r"(sc[i]));
  }
}
__device__ __forceinline__ uint32_t exp_pair(const float (&f)[10], int i, float off) {
  return pack_bf16(ex2(fmaf(f[2 * i], SCL, off)), ex2(fmaf(f[2 * i + 1], SCL, off)));
}
template<bool SPLIT> __device__ __forceinline__ void scores_x(float (&a)[2][4], const uint4 (&kf)[4], const uint4& q, uint32_t z) {
#pragma unroll
  for (int t = 0; t < 2; t++) { a[t][0] = a[t][1] = a[t][2] = a[t][3] = 0.f; }
  mma_q(a[0], kf[0], q.x, q.y); mma_q(a[1], kf[2], q.x, q.y);
  if (SPLIT) sched_fence(z);
  mma_q(a[0], kf[1], q.z, q.w); mma_q(a[1], kf[3], q.z, q.w);
}
__device__ __forceinline__ uint32_t scores_m(const uint4& q, const uint4& k) {
  float a[4] = {}, b[4] = {};
  mma_q(a, q, k.x, k.z); mma_q(b, q, k.y, k.w);
  return pack_bf16(a[0] + b[2], a[1] + b[3]);
}
__device__ __forceinline__ void store_scores(const float (&a)[2][4], uint32_t dst) {
  sts64(dst, pack_bf16(a[0][0], a[0][2]), pack_bf16(a[1][0], a[1][2]));
  sts64(dst + 320, pack_bf16(a[0][1], a[0][3]), pack_bf16(a[1][1], a[1][3]));
}
__device__ __forceinline__ uint32_t sum4(uint32_t a, uint32_t b, uint32_t d, uint32_t e) { return add_bf16x2(add_bf16x2(a, b), add_bf16x2(d, e)); }
__device__ __forceinline__ void load_scores(uint32_t (&sc)[5], uint32_t ax, uint32_t am) {
  uint4 p[4];
#pragma unroll
  for (int i = 0; i < 4; i++) p[i] = lds128(ax + i * 1280);
  const uint2 m0 = lds64(am), m1 = lds64(am + 256);
  const uint4 t = add4(add4(add4(p[0], p[1]), p[2]), p[3]);
  sc[1] = t.x; sc[2] = t.y; sc[3] = t.z; sc[4] = t.w;
  sc[0] = sum4(m0.x, m0.y, m1.x, m1.y);
}
constexpr uint32_t ONES = 0x3F803F80u;
__device__ __forceinline__ float pv(float (&o)[2][4], const uint32_t (&p)[5], const uint4 (&vf)[4], const uint4& vm) {
  float a[4] = {}, b[4] = {};
#pragma unroll
  for (int t = 0; t < 2; t++) { o[t][0] = o[t][1] = o[t][2] = o[t][3] = 0.f; }
  mma_q(o[0], vf[0], p[1], p[2]); mma_q(o[1], vf[2], p[1], p[2]);
  mma_q(o[0], vf[1], p[3], p[4]); mma_q(o[1], vf[3], p[3], p[4]);
  mma16816(a, p[1], p[2], p[3], p[4], ONES, ONES);
  mma1688(o[0], vm.x, vm.y, p[0]); mma1688(o[1], vm.z, vm.w, p[0]);
  mma1688(b, p[0], ONES, ONES);
  return (a[0] + a[2]) + b[0];
}
constexpr uint32_t POLL_LIMIT = 1u << 21;
__device__ __forceinline__ uint32_t box(int slot, int cta) { return (slot * 2 + (cta >> 6)) * M_REG + (cta & 63) * 16384; }
__device__ __forceinline__ uint32_t near_page(const ChainCtx& c, int cta, uint32_t off) {
  return off + (((lds32(c.sb + SM_SEL + cta * 4) >> (off >> 21)) ^ __popc(off & 0xB2000)) & 1) * 4096;
}
__device__ __forceinline__ uint32_t e1_box(const ChainCtx& c, int slot, int cta) { return near_page(c, E1OFF ? cta ^ 2 : cta, box(slot, cta) + 8192) ^ (E1OFF ? 0 : 4096); }
__device__ __forceinline__ uint32_t tile_key() {
  uint32_t sm; asm volatile("mov.u32 %0, %%smid;" : "=r"(sm));
  return (sm < 64 ? sm / 2 % 8 : sm < 120 ? 1 + (sm / 2 - 32) % 7 : 0) << 24 | sm << 16;
}
__device__ __forceinline__ uint32_t ox_at(int s, int row, int g, int jj) { return s * 131072 + ((g >> 1) * 32 + row) * 64 + (g & 1) * 32 + 8 * jj; }
__device__ __forceinline__ int tile_of(const ChainCtx& c) { return SIDE ? __shfl_sync(~0u, lds32(c.sb + SM_SEL + 528), 0) : c.r; }

__global__ void __cluster_dims__(2, 1, 1) __launch_bounds__(512, 1)
chain_kernel(const __grid_constant__ CUtensorMap tq, const __grid_constant__ CUtensorMap tk, const __grid_constant__ CUtensorMap tv,
             const __grid_constant__ CUtensorMap tv16, const __grid_constant__ CUtensorMap to, const __grid_constant__ CUtensorMap tx,
             const __grid_constant__ CUtensorMap twr, const __grid_constant__ CUtensorMap twi,
             const __grid_constant__ CUtensorMap ta, const __grid_constant__ CUtensorMap tw,
             const __grid_constant__ CUtensorMap tb, const __grid_constant__ CUtensorMap tout, const __grid_constant__ CUtensorMap tz,
             const __grid_constant__ CUtensorMap tzs, const __grid_constant__ CUtensorMap ta32,
             const __nv_bfloat16* __restrict__ mem0, char* __restrict__ mail, const __nv_bfloat16* __restrict__ x,
             const __nv_bfloat16* __restrict__ gw) {
  extern __shared__ __align__(1024) unsigned char smraw[];
  if (threadIdx.x == 0) TL(0);
  ChainCtx c;
  c.sb = __shfl_sync(~0u, smem_u32(smraw), 0);
  c.mail = mail; c.sel = 0; c.r = blockIdx.x;
  if (ROLE) {
    const uint32_t u = blockIdx.x >> 1, n = u < 36 ? 8 : 7, k = u - (u < 36 ? 4 : 36), q = k * (u < 36 ? 32 : 37) >> 8;
    c.r = __shfl_sync(~0u, 2 * (u - 4 < 60 ? u + k - q * n - (q & 1) * (n - 1) : u) + (blockIdx.x & 1) + (threadIdx.x >> 9), 0);
  }
  c.h = c.r >> 2; c.a = (c.r >> 1) & 1; c.b = c.r & 1; c.j = c.r & 3;
  c.m = __shfl_sync(~0u, (int)(threadIdx.x >> 7), 0); c.w = __shfl_sync(~0u, (int)((threadIdx.x >> 5) & 3), 0);
  char* own = c.mail + (uint32_t)(c.w * M_REG + M_E3 + (c.r >> 5) * 8192 + (c.r & 31) * 128 + (threadIdx.x & 31) * 4);
  uint32_t i0 = 0, i1 = 0;
  if (EARLY) asm volatile("{ .reg .pred p; setp.ne.u32 p, %4, 0; @p atom.relaxed.gpu.global.exch.b32 %0, [%2], %3; @p atom.relaxed.gpu.global.exch.b32 %1, [%2 + 4096], %3; }"
               : "+r"(i0), "+r"(i1) : "l"(own), "r"(SENT), "r"((uint32_t)(c.m == 2 && c.r < 128)) : "memory");
#pragma unroll
  for (int g = 0; g < 3; g++) {
    const int i = c.m * 4 + c.w;
    if (g < 2 || i < B_END - 32)
      asm volatile("{ .reg .pred p; elect.sync _|p, 0xffffffff; @p mbarrier.init.shared::cta.b64 [%0], %1; }"
                   :: "r"(BAR(g * 16 + i)), "r"(0x19080401u >> (bar_codes(g) >> 2 * i & 3) * 8 & 255) : "memory");
  }
  asm volatile("fence.mbarrier_init.release.cluster;" ::: "memory");
  __syncthreads();
  asm volatile("barrier.cluster.arrive.relaxed.aligned;" ::: "memory");

  if (c.r >= 128) {
    fft_cols((float2*)smraw, c.r - 128, &twr, &twi, &tzs);
    if ((threadIdx.x & 127) == 0) TL(7);
    __syncwarp();
  } else if (c.m == 3) {
    asm volatile("setmaxnreg.dec.sync.aligned.u32 %0;" :: "n"(REG_H));
    c.lane = lane_id();
    if (c.sb & 1023) asm volatile("trap;");
    const int col = c.h * 128 + c.a * 64;
    uint32_t tl = clock_lo();
    TR(-2, 3);
    if (c.w == 0) {
      if (START) delay_until(tl + START);
      if (HOLD == 2) mbar_wait(BAR(B_PROBE), 0);
      if (HOLD == 3) mbar_wait(BAR(B_SEL), 0);
      if (HOLD == 1) mbar_wait(BAR(B_PROBE), 0);
      TR(-2, 4);
      tl = clock_lo();
      mbar_expect_e(BAR(B_PFULL), 2 * NP * 2048);
      mbar_expect_e(BAR(B_WFULL), (48 - NP) * 2048);
      mbar_expect_e(BAR(B_WFULL + 1), (48 - NP) * 2048);
    }
    auto dst_x = [&](int e, int w) {
      const uint32_t g2 = 2 * c.a + (w >> 1), u = w & 1;
      return M_KVQ + c.h * 24576 + (e == 0 ? 8192 + (2 * u + c.b) * 2048 + g2 * 512 : e == 1 ? g2 * 2048 + u * 1024 + c.b * 128 : 16384 + c.b * 4096 + g2 * 512 + u * 256);
    };
    if (c.w == 0) {
      tl += PACE0;
#pragma unroll wunr
      for (int i = 0; i < 24; i++) {
        const int m = i < 4 || i >= 16, k = i < 4 ? i : m ? i - 12 : i - 4;
        const int row = c.b * 512 + m * 256;
        const uint32_t st = c.sb + m * ST_WG, bar = BAR(k < 3 ? B_PFULL : B_WFULL + m);
        if (PACE) delay_until(tl += PACE);
        if (i == 14) { mbar_wait(BAR(B_FREE), 0); if (c.lane == 0) TL2(2); __syncwarp(); }
        if (k < 11) TMA_W(k < 3 ? c.sb + SM_POOL + m * NP * 2048 + k * 8192 : k == 3 ? c.sb + SM_HV + (m * NHV + 1) * 2048 : st + (k - 4) * 8192,
                          k == 3 || k > 8 ? &tv : (k >> 2 & 1) == m ? &tk : &tq, col, row + (k < 8 ? k & 3 : (k - 9) & 3) * 64, bar);
        else {
#pragma unroll 1
          for (int j = 8; j < 12; j++) TMA_W(j < NV ? st + (32 - NP + j) * 2048 : c.sb + SM_HV + m * NHV * 2048, &tv16, col, row + j * 16, bar);
        }
      }
      TR(-2, 7);
    } else if (c.w == 2) {
      const unsigned short* mp = (const unsigned short*)mem0 + (2 * (c.lane & 3)) * D_ + 8 * c.r + (c.lane >> 2);
      uint32_t mv = (uint32_t)mp[0] | (uint32_t)mp[D_] << 16;
      if (mv == SENT) mv = 0x7FFF7FFFu;
      mbar_wait(BAR(B_PROBE), 0);
      char* dst = c.mail + (uint32_t)(M_E3 + (c.r >> 5) * 8192 + (c.r & 31) * 128 + c.lane * 4);
      st_pub(dst, mv); st_pub(dst + 4096, mv);
    } else if (c.w == 3) {
      mbar_wait(BAR(B_FREE), 0);
      mbar_wait(BAR(B_PFULL), 0);
      mbar_expect_e(BAR(B_PFULL), 65536);
      for (int i = 0; i < 2; i++) tma4d_e(c.sb + SM_XT + i * 16384, &tx, c.b * 8, 4 + 2 * (c.b ^ i), BAR(B_PFULL));
    }
    {
      mbar_wait(BAR(B_SEL), 0);
      const int i = tid_now() & 127, sl = i & 3, e = (i >> 2) & 3;
      uint32_t ox = dst_x(e, i >> 5) + sl * M_REG;
      uint32_t oh = e & 1 ? (sl ^ (e & 2)) * M_REG + M_E3 + (c.r >> 5) * 8192 + (c.w & 1) * 4096 + (c.r & 31) * 128
                          : near_page(c, c.r, e ? sl * M_REG + M_E3 + (c.b * 2 + (c.w >> 1)) * 8192 : box(~sl & 1, c.r)) + (e ? (c.w & 1) * 2048 : c.w * 1024), of;
      {
        const int e = i & 7, w = (i >> 3) & 3, m = (i >> 5) & 1, sl = i >> 6;
        const int cta = e < 2 ? c.r & ~1 : e == 2 ? c.r | 1 : e == 3 ? c.h * 4 + 2 * m + 1 : c.j * 32 + m * 8 + 2 * w + (e & 2) * 8 + (e & 1);
        const uint32_t off = e < 2 ? c.b * 2048 + m * 1024 + (w >> 1) * 512 + e * 160 : e == 2 ? c.b * 2048 + m * 1024 + w * 256 : e == 3 ? w * 256 : c.h * 128;
        of = (e < 4 ? e1_box(c, sl, cta) : near_page(c, cta, box(sl, cta))) + off;
      }
      char *px = c.mail + ox, *ph = c.mail + oh, *pf = c.mail + of;
      uint32_t at = sl * 128 + (i >> 5) * 32 + e * 8, af = i * 8;
      pin(px); pin(ph); pin(pf); pin(at); pin(af);
      asm volatile("barrier.cluster.wait;" ::: "memory");
      TR(-2, 0);
      mbar_wait(BAR(B_WREAD), 0);
      TR(-2, 1);
      mbar_arrive_both(BAR(B_LFREE), c.b ^ 1);
      sts64(at + (c.sb + SM_TAB + 1536), (uint32_t)(uintptr_t)px, (uint32_t)((uintptr_t)px >> 32));
      sts64(at + (c.sb + SM_TAB + 1024), (uint32_t)(uintptr_t)ph, (uint32_t)((uintptr_t)ph >> 32));
      sts64(af + (c.sb + SM_TAB), (uint32_t)(uintptr_t)pf, (uint32_t)((uintptr_t)pf >> 32));
      TR(-2, 2);
      if (tid_now() == 384) TL2(25);
      __syncwarp();
      bar_sync(14, 160);
    }
    pad<PAD3>();
    for (int s = -1; s < NSEG; s++) {
      if (E30 ? s != 0 : s >= 0) {
        const uint32_t tab = c.sb + SM_TAB + 1024 + (max(s, 0) & 3) * 128 + c.w * 32;
        uint32_t t0;
        if (s > 0) {
          const uint32_t ln = tid_now() & 31;
          const uint4 ta = lds128(tab);
          const char* src = mk_ptr(ta.x | ln * 4, ta.y);
          char* dst = mk_ptr(ta.z | ln * 4, ta.w);
          const uint32_t tg = (s - 1) >> 1, chk = (ln & 3) ? 0u : 1u, red = ln * (RED_L == 3 ? 4 : 8);
          touch(src, dep(c.sb, chk, c.sb)); touch(dst, dep(c.sb, red, c.sb));
          mbar_wait(BAR(B_E2TRIG), (s - 1) & 1);
          TR(s, 0);
          if (ANCH2) delay_fine(lds32(c.sb + SM_SUM + 64) + DLY_E2); else delay_cycles(DLY_E2);
          uint32_t n = 0;
          while (true) {
            uint32_t v[8];
#pragma unroll
            for (int i = 0; i < 8; i++) v[i] = ld_poll1(src + i * 128);
            if (E2_F) sched_fence(c.sb);
            const uint32_t bad = RED_T ? (stale2(v[0], v[1], tg) | stale2(v[2], v[3], tg) | stale2(v[4], v[5], tg)) | stale2(v[6], v[7], tg)
                                       : stale1(stale1(stale2(v[0], v[1], tg), v[2], tg), v[3], tg) | stale1(stale1(stale2(v[4], v[5], tg), v[6], tg), v[7], tg);
            const bool ok = all_clear(bad, chk);
#pragma unroll
            for (int l = 0; l < RED_L; l++)
#pragma unroll
              for (int i = 0; i < (4 >> l); i++) v[i] = add_bf16x2(v[2 * i], v[2 * i + 1]);
            if (RED_L == 3) sts32(red + (c.sb + SM_RED + c.w * 128), v[0]);
            else {
              float lo[8], hi[8];
#pragma unroll
              for (int i = 0; i < (8 >> RED_L); i++) { lo[i] = __uint_as_float(v[i] << 16); hi[i] = __uint_as_float(v[i] & 0xFFFF0000u); }
#pragma unroll
              for (int l = RED_L; l < 3; l++)
#pragma unroll
                for (int i = 0; i < (4 >> l); i++) { lo[i] = lo[2 * i] + lo[2 * i + 1]; hi[i] = hi[2 * i] + hi[2 * i + 1]; }
              sts64(red + (c.sb + SM_RED + c.w * 256), __float_as_uint(lo[0]), __float_as_uint(hi[0]));
            }
            if (ok) break;
            n++; CNT(0);
          }
          bar_sync(NB_HELP, 128);
          const uint32_t rd = red + (c.sb + SM_RED);
          if (!RED_P || c.w < 2) {
            if (RED_L == 3) st_pub_if(dst, sum4(lds32(rd), lds32(rd + 128), lds32(rd + 256), lds32(rd + 384)), c.w < 2);
            else {
              const uint2 p0 = lds64(rd), p1 = lds64(rd + 256), p2 = lds64(rd + 512), p3 = lds64(rd + 768);
              st_pub_if(dst, pack_bf16((__uint_as_float(p0.x) + __uint_as_float(p1.x)) + (__uint_as_float(p2.x) + __uint_as_float(p3.x)),
                                       (__uint_as_float(p0.y) + __uint_as_float(p1.y)) + (__uint_as_float(p2.y) + __uint_as_float(p3.y))), c.w < 2);
            }
          }
          t0 = clock_lo();
          mbar_arrive_warp(BAR(B_PUB));
          TRV(s, 15, n);
          mbar_wait(BAR(B_SPFREE), (s - 1) & 1);
        } else {
          if (tid_now() == 384) TL2(24);
          __syncwarp();
          if (!E30) mbar_wait(BAR(B_PROBE), 1);
          if (!WO_S) mbar_wait(BAR(B_WOFULL), 0);
          if (tid_now() == 384) TL2(19);
          __syncwarp();
          t0 = clock_lo() - DLY_E3;
        }
        TRV(s, 1, t0);
        {
          const uint32_t l16 = (tid_now() & 31) * 16, dst = vary(l16, s, c.sb) + (c.sb + SM_MEM + (c.w & 1) * 4096 + (c.w >> 1) * 2048);
          const uint4 tb = lds128(tab + 16);
          st_pub_if(mk_ptr(tb.z | l16 >> 2, tb.w), SENT, c.w >= 2);
          const char* src = mk_ptr(tb.x | l16, tb.y);
          touch(src, dep(c.sb, dst, c.sb));
          delay_fine(t0 + (DLY_E3 + (c.w & 1) * DLY_E3B));
          uint32_t n = 0;
          while (true) {
            uint4 v[4];
#pragma unroll
            for (int i = 0; i < 4; i++) v[i] = ld_poll(src + i * 512);
#pragma unroll
            for (int i = 0; i < 4; i++) sts128(dst + i * 512, v[i]);
            if (arrive_if_all(max(max(v[0].x, v[1].x), max(v[2].x, v[3].x)) != SENT, NB_MEM + (c.w & 1) * 2 + (c.w >> 1), 160)) break;
            n++; CNT(1);
          }
          TR(s, 2); TRV(s, 14, n);
        }

        if (s == 1) CLK(1); if (s == 8) CLK(2); if (s == 56) CLK(3);
        if (c.w == 2 && s == 15) TRSYNC(8);
        if (c.w == 2 && s == 21) TRSYNC(10);
      }
      const int g = s + 1;
      auto load_v = [&]() {
        if (V_TMA && c.w == V_W) {
          mbar_expect_e(BAR(B_VFULL), 8192);
          bulk_load_e(c.sb + SM_V, c.mail + (uint32_t)(M_KVQ + (min(g, XEND - 1) & (NSLOT - 1)) * M_REG + c.h * 24576 + 8192), 8192, BAR(B_VFULL));
        }
      };
      if (XEND < NSEG && g >= XEND && g < NSEG) { mbar_wait(BAR(B_SC), s & 1); load_v(); }
      if (g < XEND) {
        const uint32_t tx_ = c.sb + SM_TAB + 1536 + (g & 3) * 128 + c.w * 32, tag = (g >> 2) & 1;
        if (c.w == 0) mbar_expect_e(BAR(B_LAND), EXP_PEER * 12288);
        auto load_x = [&]() {
          if (c.w == 3 && g + 1 < XEND) {
            mbar_wait(BAR(B_XEMPTY), g & 1);
            mbar_expect_e(BAR(B_XFULL), 16384 * EXP_NXT);
            for (int i = 0; i < EXP_NXT; i++) tma4d_e(c.sb + SM_XT + i * 16384, &tx, c.b * 8, (g + 1) * 4 + 2 * (c.b ^ i), BAR(B_XFULL));
          }
        };
        if (X_AT == 0 && g > 0) load_x();
        TR(s, 6);
        if (E30 && g == 0) mbar_wait(BAR(B_PROBE), 1);
        mbar_wait(BAR(B_LAND), g & 1);
        TR(s, 7);
        if (DLY_F && g > 0) delay_cycles(DLY_F);
        auto total = [&](int w, int lane, uint32_t o0, uint32_t o1) {
          const uint32_t a = c.sb + SM_LAND + land_off(w, lane);
          if (EXP_FL == 1) return make_uint4(a, a, a, a);
          const uint4 t = add4(lds128(a + o0), lds128(a + o1 + 2048));
          const uint32_t a2 = dep(dep(a, t.x ^ t.y ^ t.z, c.sb), t.w, c.sb);
          return add4(t, add4(lds128(a2 + o0 + 4096), lds128(a2 + o1 + 6144)));
        };
        auto get = [&](int e) {
          const int ln = tid_now() & 31;
          return e == 0 ? total(c.w, ln, 16384, 16384)
               : e == 1 ? total((c.w & 2) + ((ln >> 1) & 1), (ln & 1) * 16 + (c.w & 1) * 8 + (ln >> 2), 8192, 0)
                        : total((c.w & 2) + ((ln >> 1) & 1), (ln & 1) * 16 + (ln >> 3) * 4 + (c.w & 1) * 2 + ((ln >> 2) & 1), 0, 8192);
        };
        auto put = [&](int e, uint4 v) {
          const int ln = tid_now() & 31;
          const uint2 d = lds64(tx_ + e * 8);
          if (e < 2) {
            v.x = tagged(v.x, tag);
            st_pub4(mk_ptr(d.x | (e ? (ln & 24) * 32 + (ln & 7) * 16 : ln * 16), d.y), v);
          } else {
            char* dst = mk_ptr(d.x | ((ln & 7) * 16 + (ln >> 3) * 4), d.y);
            const uint32_t bit = ln < 8;
            st_pub(dst, put_tag(v.x, bit, tag)); st_pub(dst + 128, put_tag(v.y, bit, tag));
            st_pub(dst + 2048, put_tag(v.z, bit, tag)); st_pub(dst + 2176, put_tag(v.w, bit, tag));
          }
        };
        auto after_sc = [&]() { if (g > 0) { mbar_wait(BAR(B_SC), s & 1); if (DLY_FK) delay_cycles(DLY_FK); if (X_AT == 1) load_x(); } };
        if (FIN_AT == 5) {
          put(0, get(0));
          if (DLY_F2 && g > 0) delay_cycles(DLY_F2); else sched_fence(c.sb);
          const uint4 k = get(1);
          sched_fence(c.sb);
          const uint4 q = get(2);
          if (g > 0) mbar_wait(BAR(B_VST), s & 1);
          put(1, k); put(2, q);
          TR(s, 5);
          mbar_arrive_both(BAR(B_LFREE), c.b ^ 1);
          after_sc();
          load_v();
          continue;
        }
        if (FIN_AT < 3) {
          if (EXP_FIN & 1) put(0, get(0));
          TR(s, 3);
          if (FIN_AT == 1) after_sc();
          if (V_TMA == 1) load_v();
          if (EXP_FIN & 2) put(1, get(1));
        } else {
          const uint4 v = get(0);
          sched_fence(c.sb);
          const uint4 k = get(1);
          if (g > 0) { mbar_wait(BAR(B_VST), s & 1); if (DLY_FS) delay_cycles(DLY_FS); }
          put(0, v); put(1, k);
        }
        TR(s, 4);
        if (FIN_AT == 4) {
          const uint4 q = get(2);
          after_sc();
          load_v();
          put(2, q);
        } else {
          if (FIN_AT >= 2) after_sc();
          if (V_TMA == 2) load_v();
          if (EXP_FIN & 4) put(2, get(2));
        }
        mbar_arrive_both(BAR(B_LFREE), c.b ^ 1);
        if (V_TMA == 3) load_v();
        TR(s, 5);
        if (!FIN_AT && X_AT && g > 0) { mbar_wait(BAR(B_SC), s & 1); if (DLY_FK) delay_cycles(DLY_FK); load_x(); }
      }
    }
    const int tile = tile_of(c), s0 = (tile >> 3) * 4, n0 = (tile & 7) * 128;
    if (c.w == 1) {
      mbar_wait(BAR(B_PVDONE), 0);
      count_e(g_ctl + (EARLY2 ? C_LAST : C_EARLY));
      st_pub(c.mail + (uint32_t)((tid_now() & 6) * (M_REG / 2) + M_SEL + (tid_now() & 1) * 4096 + c.r * 4), 0);
      await_count(g_ctl + C_COLS, 4);
      mbar_expect_e(BAR(B_TW), 8192);
      bulk_load_e(c.sb + SM_TW, g_tw, 8192, BAR(B_TW));
    } else if (c.w == 2) {
      const uint32_t ln = tid_now() & 31, rel = mapa(BAR(B_GEMPTY) + (ln >> 2) * 8, ln & 1);
      mbar_wait(BAR(B_VST), 1); mbar_wait(BAR(PRE_AT), 1);
      arrive_remote_if(rel, ln < 12);
      mbar_wait(BAR(B_E2TRIG), 1);
      if (GATE) mbar_wait(BAR(B_DONE), 0);
      arrive_remote_if(rel, ln >= 12 && ln < 20);
    } else {
      auto ahead = [&](int k) {
        if (c.w) { if (PF_A && (k & 3) == (tile >> 1 & 3)) prefetch3d_e(&ta, k * 32, s0 + 2 * c.b); }
        else if (PF_B && (k & 7) == (tile >> 4)) prefetch2d_e<(ONCE & 512) != 0>(&tw, n0 + (tile & 8) * 8, k * 64);
      };
#pragma unroll 1
      for (int k = 0; k < PF_D; k++) ahead(k);
      if (c.w == 3) await_count(g_ctl + C_EARLY, 128);
      const int skew = tile < 120 ? 0 : SKEW;
      uint32_t o = SM_XT, st = 0, ph = 0;
#pragma unroll 1
      for (int kb = 0; kb < 64 + skew; kb++, o = next_stage(o)) {
        const bool solo = kb < skew || kb >= 64;
        const uint32_t bar = BAR(B_GFULL + st), k = kb & 63;
        if (c.w && kb == skew) {
          if (tile >= 120) await_count(g_ctl + C_LAST, EARLY2 ? 640 : 512);
          if (tid_now() == 480) TL(10);
          __syncwarp();
        }
        mbar_wait(BAR(B_GEMPTY + st), ph);
        if (c.w) {
          const int r = solo ? (kb >> 5) + c.b : c.b * 2;
          tma3d_mc_e(c.sb + o + r * 4096, solo ? &ta32 : &ta, k * 32, s0 + r, bar);
        } else {
          mbar_expect_e(bar, solo ? 24576 : 32768);
          tma2d_o<(ONCE & 2) != 0>(c.sb + o + 16384, &tw, n0, k * 64, bar);
          tma2d_o<(ONCE & 2) != 0>(c.sb + o + 24576, &tw, n0 + 64, k * 64, bar);
        }
        if (kb + PF_D < 64) ahead(kb + PF_D);
        if (++st == 5) { st = 0; ph ^= 1; }
      }
    }
    return;
  } else if (c.m == 2) {
    asm volatile("setmaxnreg.dec.sync.aligned.u32 %0;" :: "n"(512 - 2 * REG_F - REG_H));
    c.lane = lane_id();
    {
      uint32_t tl = clock_lo() + (PACE0 + WO_AT * PACE);
      TR(-2, 0);
      sched_fence(i0 ^ i1);
      TR(-2, 7);
      int far1 = 0;
#pragma unroll 1
      for (int rep = EARLY; rep <= NPROBE; rep++) {
        const int lag = race_init(own + (rep & 1) * 4096, own + (~rep & 1) * 4096, SENT);
        if (rep) far1 += ((rep ^ c.r >> 5) & 1 ? 1 : -1) * min(lag, 200);
      }
      sts32(c.sb + SM_SEL + 512 + c.w * 4, (8 + far1 / (16 * NPROBE)) << 4 * c.w);
      TR(-2, 1);
      if (tid_now() == 256) TL2(14);
      __syncwarp();
      mbar_arrive_warp(BAR(B_PROBE));
      if (c.w == 0) {
        mbar_wait(BAR(B_PROBE), 0);
        const uint4 bits = lds128(c.sb + SM_SEL + 512);
        const uint32_t res = bits.x | bits.y | bits.z | bits.w;
        st_pub_if(c.mail + (uint32_t)((c.lane & 6) * (M_REG / 2) + M_SEL + (c.lane & 1) * 4096 + c.r * 4), res | tile_key(), c.lane < 8);
        const int q = (res >> 4 * ((c.lane + c.r) & 3) & 15) - 8, best = __reduce_max_sync(~0u, abs(q) * 64 + (c.lane & 3) * 16 + ((c.lane + c.r) & 3) * 2 + (q <= 0));
        const char* src = c.mail + (uint32_t)((best & 6) * (M_REG / 2) + M_SEL + (best & 1) * 4096 + c.lane * 16);
        if (SEL_AT) delay_until(tl - (PACE0 + WO_AT * PACE - SEL_AT));
        uint4 v; uint32_t n = 0;
        TR(-2, 4);
        while (true) {
          delay_cycles(DLY_SEL);
          TR(-2, 6);
          v = ld_poll(src);
          if (__all_sync(~0u, v.x && v.y && v.z && v.w)) break;
          watchdog(n, POLL_LIMIT);
        }
        TR(-2, 5);
        int ta = 0, tb = 0, pa = 0, pb = 0;
        uint32_t flip = 0;
#pragma unroll 1
        for (int i = 0; i < 4; i++) {
          const int a = (v.x >> 4 * i & 15) + (v.y >> 4 * i & 15) - 16, b = (v.z >> 4 * i & 15) + (v.w >> 4 * i & 15) - 16;
          const bool f = __reduce_add_sync(~0u, a * ta + b * tb) < 0;
          ta += f ? -a : a; tb += f ? -b : b; flip |= (uint32_t)f << i;
        }
#pragma unroll 1
        for (uint32_t g = 0; g < 8; g++) {
          const bool a = (v.x >> 16) - g * 256 < 120, b = (v.z >> 16) - g * 256 < 120;
          const int n = __reduce_add_sync(~0u, (a ? ta : 0) + (b ? tb : 0)) > 0 ? PRIOR : -PRIOR;
          if (a) pa = n;
          if (b) pb = n;
        }
        const uint32_t ka = AWARE && ta + pa > 0 ? ~flip : flip, kb = AWARE && tb + pb > 0 ? ~flip : flip;
        sts128(c.sb + SM_SEL + c.lane * 16, make_uint4(ka, ka, kb, kb));
        mbar_arrive_warp(BAR(B_SEL));
        const uint32_t key = __shfl_sync(~0u, c.a ? v.z : v.x, c.h);
        const int u = __popc(__ballot_sync(~0u, v.x < key)) + __popc(__ballot_sync(~0u, v.z < key));
        sts32(c.sb + SM_SEL + 528, (u & 32) * 2 + (u & 7) * 8 + (u >> 2 & 6) + c.b);
        TR(-2, 2);
        if (c.lane == 0) TL2(13);
        __syncwarp();
        bar_sync(14, 160);
        if (ZDLY) delay_cycles(ZDLY);
#pragma unroll 4
        for (int k = c.lane >> 3; k < (ZINIT ? 128 : 0); k += 4) {
          const int e = k & 7;
          const uint2 d = lds64(c.sb + SM_TAB + (e == 3 ? k - 1 : k) * 8);
          st_pub4(mk_ptr((d.x & ~127u) + (e < 2 ? (k & 8) * 32 : e == 3 ? 128 : 0) + (c.lane & 7) * 16, d.y), make_uint4(0, 0, 0, 0));
        }
        __syncwarp();
        if (c.lane < 4) asm volatile("mbarrier.arrive.shared::cta.b64 _, [%0];" :: "r"(BAR(B_PROBE)) : "memory");
        __syncwarp();
        TR(-2, 8);
      }
      if (c.w == 2) {
        mbar_wait(BAR(B_P1), 0);
        if (P1_AT) { mbar_wait(BAR(B_WFULL), 0); mbar_wait(BAR(B_WFULL + 1), 0); }
        st_pub_if(g_ctl + C_COLS + (c.r & 15) * 32 + c.lane, 0, c.r < (C_END - C_COLS) / 32);
        count_e(g_ctl + C_P1);
        TR(-2, 3);
      }
      if (c.w == 1) for (int i = 0; i < WO_N; i++) { delay_until(tl += WO_P * PACE); prefetch2d_e(&to, c.j * 256 + (i ^ WO_X) * 64, c.h * 128); }
      if (c.w == 3) {
        mbar_wait(BAR(B_WREAD0), 0);
        for (int i = 0; i < 2; i++) tma4d_e(c.sb + SM_WO + i * 16384, &tx, c.b * 8, 2 * (c.b ^ i), BAR(B_PFULL));
        mbar_expect_e(BAR(B_WOFULL), 65536);
#pragma unroll 1
        for (int i = 3; i >= 0; i--) {
          if (i & 1) mbar_wait(BAR(i < 2 ? B_XEMPTY : B_WREAD), 0);
          TMA_O(c.sb + SM_WO + i * 16384, &to, c.j * 256 + i * 64, c.h * 128, BAR(B_WOFULL));
        }
      }
    }
    asm volatile("barrier.cluster.wait;" ::: "memory");
    const int g = c.w, src0 = c.h * 4 + (g >> 1) * 2;
    mbar_wait(BAR(B_SEL), 0);
    c.sel = __shfl_sync(~0u, (e1_box(c, 0, src0 + (c.lane >> 5)) & 4096) | (e1_box(c, 1, src0) & 4096) * 2, 0);
    mbar_wait(BAR(B_WREAD), 0);
    uint32_t l16 = c.sb + g * 512 + c.lane * 16;
    auto lane = [&](uint32_t v) { l16 = dep(l16, v, c.sb); return (int)((l16 & 511) >> 4); };
    pad<PAD2>();
    for (int s = 0; s < NSEG; s++) {
      l16 = vary(l16, s, c.sb);
      int ln = (l16 & 511) >> 4;
      uint4 kf[4], qx;
      {
        const int gs = min(s, XEND - 1);
        const char* pk = c.mail + (uint32_t)(M_KVQ + (gs & (NSLOT - 1)) * M_REG + c.h * 24576 + g * 2048 + ln * 16);
        const char* pq = pk + (16384 + c.j * 2048 - g * 1536);
        const uint32_t tg = (gs / NSLOT) & 1;
        touch(pk, c.sb); touch(pq, c.sb);
        TR(s, 0);
        mbar_wait(BAR(B_VFULL), s & 1);
        TR(s, 1);
        if (s > 0) mbar_wait(BAR(B_PUB), (s - 1) & 1);
        for (uint32_t n = 0; ; ) {
          uint4 k[4];
#pragma unroll
          for (int t = 0; t < 4; t++) k[t] = ld_poll(pk + t * 512);
          qx = ld_poll(pq);
#pragma unroll
          for (int t = 0; t < 2; t++) {
            auto cp = [&](uint32_t v) { return dep(v, 0, c.sb); };
            kf[t] = make_uint4(cp(k[2 * t].x), cp(k[2 * t].y), cp(k[2 * t + 1].x), cp(k[2 * t + 1].y));
            kf[2 + t] = make_uint4(cp(k[2 * t].z), cp(k[2 * t].w), cp(k[2 * t + 1].z), cp(k[2 * t + 1].w));
          }
          if (all_clear(stale1(stale2(k[0].x, k[1].x, tg) | stale2(k[2].x, k[3].x, tg), qx.x, tg), EXP_CHK)) break;
          watchdog(n, POLL_LIMIT); CNT(4);
        }
        TR(s, 2);
      }
      if (X_AT >= 2 && g == 0 && s + 2 < XEND) {
        mbar_wait(BAR(B_XEMPTY), ~s & 1);
        mbar_expect_e(BAR(B_XFULL), 16384 * EXP_NXT);
        for (int i = 0; i < EXP_NXT; i++) tma4d_e(c.sb + SM_XT + i * 16384, &tx, c.b * 8, (s + 2) * 4 + 2 * (c.b ^ i), BAR(B_XFULL));
      }
      ln = lane(kf[0].y);
      const char* pa = c.mail + (uint32_t)(box(s & 1, src0) + 8192 + (c.sel >> (s & 1) & 4096) + (g & 1) * 512 + (EXP_LIN ? ln * 16 : read_off(ln)));
      const uint32_t spw = c.sb + SM_SP + g * 1280 + (ln & 3) * 64 + ((((ln >> 3) ^ ln) & 2) << 4) + (ln & 4) * 4 + (ln & 8),
                     spr = c.sb + SM_SP + (ln & 4) * 80 + (ln >> 3) * 64 + (((ln & 3) ^ ((ln >> 3) & 2)) << 4), l8 = ln * 8;
      const uint32_t tg = s >> 1;
      float sx[2][4];
      uint32_t sm;
      uint4 km;
      touch(pa, c.sb);
      mbar_wait(BAR(B_E1TRIG), s & 1);
      const uint32_t t0 = clock_lo();
      TRV(s, 3, t0);
      scores_x<false>(sx, kf, qx, 0);
      store_scores(sx, spw + 640);
      if (DLY_E1) delay_fine(t0 + DLY_E1);
      uint32_t nr = 0;
      while (true) {
        const uint4 q0 = ld_poll(pa), q1 = ld_poll(pa + 2048), k0 = ld_poll(pa + 1024), k1 = ld_poll(pa + 3072);
        uint4 qm = add4(q0, q1);
        const uint32_t bq = stale2(q0.x, q1.x, tg);
        qm.x = dep(qm.x, bq, c.sb);
        scores_x<SC_F>(sx, kf, qm, c.sb);
        const uint32_t bk = stale2(k0.x, k1.x, tg);
        km = add4(k0, k1);
        km.x = dep(km.x, bk, c.sb);
        const bool ok = all_clear(bq | bk, 1);
        sm = scores_m(qm, km);
        store_scores(sx, spw);
        if (ok) break;
        nr++; CNT(2);
      }
      sts32(l8 + (c.sb + SM_SPM + (g >> 1) * 256 + (g & 1) * 4), sm);
      bar_sync(NB_ATT, 128);
      TR(s, 5); TRV(s, 13, nr);
      float o[2][4];
      uint32_t sp[5];
      uint4 vf[4];
      load_scores(sp, spr, l8 + (c.sb + SM_SPM));
      const uint32_t m5 = max5(sp);
      uint32_t m1;
      float off = row_off(m5, m1), f[10];
      l16 = dep(l16, VF_AT ? m1 : m5, c.sb);
#pragma unroll
      for (int t = 0; t < 4; t++) vf[(t >> 1) + 2 * (t & 1)] = lds128(l16 + SM_V + ((t >> 1) + 2 * (t & 1)) * 2048);
      qx.x = dep(qx.x, sp[0], c.sb);
      sts32(l8 + (c.sb + SM_SPM + 512 + (g >> 1) * 256 + (g & 1) * 4), scores_m(qx, km));
      mbar_arrive_warp(BAR(B_SC));
      unpack(f, sp);
      if (UP_F) sched_fence(c.sb);
      uint4 vm;
      if (VM_AT < 2) {
        bar_sync(NB_VM, 384);
        sp[1] = exp_pair(f, 1, off);
        const uint32_t av = dep(l8, VM_AT ? sp[1] : __float_as_uint(off), c.sb) + (c.sb + g * 512 + SM_VM);
        const uint2 vm0 = lds64(av), vm1 = lds64(av + 256);
        vm = make_uint4(vm0.x, vm0.y, vm1.x, vm1.y);
#pragma unroll
        for (int i = 2; i < 6; i++) sp[i % 5] = exp_pair(f, i % 5, off);
      } else {
#pragma unroll
        for (int i = 1; i < 6; i++) sp[i % 5] = exp_pair(f, i % 5, off);
        bar_sync(VM_AT == 2 ? dep(dep(0, sp[1] ^ sp[2], c.sb) + NB_VM, sp[0], c.sb) : dep(dep(0, sp[0] ^ sp[1] ^ sp[2], c.sb) + NB_VM, sp[3], c.sb), 384);
        const uint32_t av = l8 + (c.sb + g * 512 + SM_VM);
        const uint2 vm0 = lds64(av), vm1 = lds64(av + 256);
        vm = make_uint4(vm0.x, vm0.y, vm1.x, vm1.y);
      }
      float sum;
      auto rows_m = [&]() {
        const uint32_t tv = min(s, XEND - 1) / NSLOT;
        sum = pv(o, sp, vf, vm);
        stsm4<false>(l16 + SM_OM, pack_bf16(o[0][0], o[0][1]), pack_bf16(o[0][2], o[0][3]), pack_bf16(o[1][0], o[1][1]), pack_bf16(o[1][2], o[1][3]));
        sts32(c.sb + SM_SUM + ((l16 >> 4) & 28), __float_as_uint(sum));
        return arrive_if_clear(stale2(vf[0].x, vf[1].x, tv) | stale2(vf[2].x, vf[3].x, tv), EXP_CHK, NB_OM, 384);
      };
      if (!rows_m()) {
        const char* pv_ = c.mail + (uint32_t)(M_KVQ + (min(s, XEND - 1) & (NSLOT - 1)) * M_REG + c.h * 24576 + 8192 + (l16 - c.sb));
        uint32_t n = 0;
        do {
#pragma unroll
          for (int t = 0; t < 4; t++) vf[t] = ld_poll(pv_ + t * 2048);
          watchdog(n, POLL_LIMIT); CNT(5);
        } while (!rows_m());
      }
      const uint32_t tom = clock_lo();
      TRV(s, 8, tom);
      sched_fence(c.sb);
      ln = lane(tom);
      const int n = ln >> 2, jj = ln & 3, tq_ = 8 * c.j + (n & 4) + 2 * (n & 1) + ((n >> 1) & 1), lim = 16 * (tq_ - 2 * jj + 1);
      if (DLY_X) delay_until(tom + DLY_X);
      load_scores(sp, spr + 640, c.sb + SM_SPM + 512 + ln * 8);
#pragma unroll
      for (int w = 0; w < 4; w++) {
        uint32_t m; asm("shl.b32 %0, 0xffffffff, %1;" : "=r"(m) : "r"(max(lim - 128 * w, 0)));
        sp[1 + w] = (sp[1 + w] & ~m) | (0xD029D029u & m);
      }
      mbar_arrive_warp(dep(dep(0, sp[0], c.sb), sp[1], c.sb) + BAR(B_SPFREE));
      off = row_off(max5(sp), m1);
      unpack(f, sp);
#pragma unroll
      for (int i = 1; i < 6; i++) sp[i % 5] = exp_pair(f, i % 5, off);
      sum = pv(o, sp, vf, vm);
      TR(s, 7);
      sum = rcp(sum);
      const float i0 = __shfl_sync(~0u, sum, 8 * jj), i1 = __shfl_sync(~0u, sum, 8 * jj + 4);
      const uint32_t oxs = c.sb + SM_OX + g * 512;
      stsm4<true>(oxs + (ln & 7) * 64 + (((ln >> 3) ^ ((ln >> 1) & 3)) << 4),
                  pack_bf16(o[0][0] * i0, o[0][1] * i1), pack_bf16(o[0][2] * i0, o[0][3] * i1), pack_bf16(o[1][0] * i0, o[1][1] * i1), pack_bf16(o[1][2] * i0, o[1][3] * i1));
      __syncwarp();
      *(uint4*)(g_ox + ox_at(s, tq_, c.h * 4 + g, jj)) = lds128(oxs + n * 64 + ((jj ^ (n >> 1)) << 4));
      mbar_arrive_warp(BAR(B_PVDONE));
      TR(s, 9);
    }
    if (LASTM) {
      const int ln = tid_now() & 31, n = ln >> 2, jj = ln & 3, tq_ = 8 * c.j + (n & 4) + 2 * (n & 1) + ((n >> 1) & 1);
      store_count(g_ox + ox_at(NSEG - 1, tq_, c.h * 4 + g, jj), lds128(c.sb + SM_OX + g * 512 + n * 64 + ((jj ^ (n >> 1)) << 4)), (char*)(g_ctl + C_LAST) + (LASTM == 2 ? c.r * 4 + g : 0));
    } else count_e(g_ctl + C_LAST);
    mbar_arrive_warp(BAR(B_DONE));
    if (tid_now() == 256) TL(8);
    __syncwarp();
    mbar_wait(BAR(B_E2TRIG), 1); mbar_wait(BAR(B_DONE), 0); mbar_wait(BAR(B_TW), 0);
    asm volatile("setmaxnreg.inc.sync.aligned.u32 128;");
  } else {
    {
      const int w = c.m * 4 + c.w;
      mbar_expect_e(BAR(B_ROWS), 4096 + 256);
      for (int i = 0; i < 2; i++) bulk_load_e(c.sb + SM_FFT + (1024 + w * ROW_BUF) * 8 + i * 2048, x + (size_t)(z_row(c.r * 8 + w) + i * 1024) * D_, 2048, BAR(B_ROWS));
      bulk_load_e(c.sb + SM_GW + w * 256, gw + w * 128, 256, BAR(B_ROWS));
    }
    asm volatile("setmaxnreg.inc.sync.aligned.u32 %0;" :: "n"(REG_F));
    c.lane = lane_id();
    uint32_t wa[16][4], wb[16][4], wv[16][4];
    TR(-2, 4);
    fft_rows_fwd((float2*)(smraw + SM_FFT), (const __nv_bfloat16*)(smraw + SM_GW), c.r, threadIdx.x, BAR(B_ROWS), BAR(B_FREE), [&](int e) { TR(-2, e); }, [&]() {
      mbar_spin(BAR(B_PFULL), 0);
#pragma unroll
      for (int k = 0; k < NP; k++) ldsm4t(wa[k], c.sb + SM_POOL + c.m * NP * 2048 + frag_off(c.w, c.lane) + k * 2048);
      bar_sync(NB_XCH, 256);
#pragma unroll
      for (int k = 0; k < NP; k++) sts128(c.sb + SM_POOL + c.m * 2048 + c.w * 512 + c.lane * 16 + k * 4096, make_uint4(wa[k][0], wa[k][1], wa[k][2], wa[k][3]));
    });
    mbar_arrive_warp(BAR(B_P1));
    TR(-2, 0);
    if (tid_now() == 0) TL2(1);
    __syncwarp();
    mbar_spin(BAR(B_WFULL + c.m), 0);
    TR(-2, 1);
    if ((tid_now() & 127) == 0) TL2(16);
    __syncwarp();
    {
      const uint32_t st = c.sb + c.m * ST_WG + frag_off(c.w, c.lane);
#pragma unroll
      for (int k = 0; k < 16; k++) ldsm4t(wb[k], st + k * 2048);
#pragma unroll
      for (int k = NP; k < 16; k++) ldsm4t(wa[k], st + (16 + k - NP) * 2048);
#pragma unroll
      for (int k = 0; k < NV; k++) ldsm4t(wv[k], st + (32 - NP + k) * 2048);
      mbar_arrive_warp(BAR(B_WREAD));
      if (c.m == 0) mbar_arrive_warp(BAR(B_WREAD0));
#pragma unroll
      for (int k = 0; k < (LP_IN == 2 ? 0 : NP); k++) lds_frag(wa[k], c.sb + SM_POOL + c.m * 2048 + c.w * 512 + c.lane * 16 + k * 4096);
      TR(-2, 2);
    }
    TR(-2, 3);
    if (tid_now() == 0) TL2(12);
    __syncwarp();
    asm volatile("barrier.cluster.wait;" ::: "memory");
    uint32_t t16 = c.m * 2048 + c.w * 512 + c.lane * 16;
    uint32_t pk = (c.m * NHV * 2048 + frag_off(c.w, c.lane)) | (tile_off(2 * (c.w & 1), c.lane) << 16) | ((c.lane & 12) ? 0u : 0x80000000u);
    const uint32_t dx1 = desc_lo(c.sb + SM_XT + c.m * 4096), dh = desc_lo(c.sb + SM_HV + c.m * NHV * 2048);
    mbar_spin(BAR(B_PFULL), 1);
    pad<PAD0>();
    for (int s = -2; ; s++) {
      t16 = vary(t16, s, c.sb); pk = vary(pk, s, c.sb);
      const uint32_t dx = dx1 - (s == -2 ? (SM_XT - SM_WO) / 16 : 0);
      auto ldp = [&](int k0, int k1, int d, int back = 0) {
#pragma unroll
        for (int k = k0; k < k1; k++) lds_frag(wa[k], (k < k0 + d - back ? t16 : dep(t16, wa[k < d ? 0 : k - d][0], c.sb)) + (c.sb + SM_POOL + k * 4096));
      };
      if (s >= 0) {
        uint32_t af[16][4], bf[4][4], wo;
        const uint32_t tab = ((t16 >> 3) & 0x1C0) + (c.sb + SM_TAB + (s & 1) * 512);
        const char* pa;
        mem_proj(wa, wb, wv, af, wo, pa, tab, t16, pk, c, s);
        const uint32_t t0 = clock_lo();
        t16 = dep(t16, t0, c.sb);
        auto ldwo = [&](int f) { ldsm4t(af[f], (f < WO_D ? wo : dep(wo, af[f < WO_D ? 0 : f - WO_D][0], c.sb)) + (c.sb + SM_WO + (f & 1) * 32768 + (f >> 1) * 2048)); };
        {
          const uint32_t tg = s >> 1, vm = t16 >> 1, chk = (~t16 >> 4) & 1;
          if (WO_S && s == 0) {
            mbar_spin(BAR(B_WOFULL), 0);
#pragma unroll
            for (int f = 0; f < WO_0; f++) ldwo(f);
          }
#pragma unroll
          for (int f = WO_0; f < WO_1; f++) ldwo(f);
          if (DLY_V) delay_fine(t0 + DLY_V); else sched_fence(c.sb);
          uint2 v0 = ld_poll2(pa), v1 = ld_poll2(pa + 1024), v2 = ld_poll2(pa + 2048), v3 = ld_poll2(pa + 3072);
          TR(s, 3);
#pragma unroll
          for (int f = WO_1; f < 16 - WO_L; f++) ldwo(f);
          TR(s, 4);
          uint32_t n = 0;
          while (true) {
            sts64(vm + (c.sb + SM_VM), sum4(v0.x, v1.x, v2.x, v3.x), sum4(v0.y, v1.y, v2.y, v3.y));
            if (arrive_if_clear(stale1(stale1(stale2(v0.x, v1.x, tg), v2.x, tg), v3.x, tg), chk, NB_VM, 384)) break;
            v0 = ld_poll2(pa); v1 = ld_poll2(pa + 1024); v2 = ld_poll2(pa + 2048); v3 = ld_poll2(pa + 3072);
            n++; CNT(3);
          }
          TR(s, 12); TRV(s, 15, n);
        }
        if (!NOWO || vary(s, s, c.sb) != NSEG - 1) {
        const uint32_t ob = dep(dep(t16 & 511, af[14 - WO_L][0], c.sb), af[15 - WO_L][0], c.sb);
        uint32_t l4 = ob >> 2;
        const uint32_t bit = (t16 & 48) ? 0u : 1u;
        if (LF_AT) mbar_spin2_if(BAR(B_XFULL), BAR(B_LFREE), s & 1, s + 2 < XEND); else mbar_spin_if(BAR(B_XFULL), s & 1, s + 2 < XEND);
        bar_sync(NB_OM, 384);
        TR(s, 5);
#pragma unroll
        for (int i = 0; i < 4; i++) ldsm4t(bf[i], ob + (c.sb + SM_OM + i * 512));
        uint2 sum = lds64(((t16 >> 1) & 24) + (c.sb + SM_SUM));
        if (OM_F) sched_fence(c.sb);
        float d[WO_C][4] = {};
        uint4 d0, d1;
#pragma unroll
        for (int f = 0; f < 16; f++) {
          mma_a(d[f % WO_C], af[f], bf[f >> 2][f & 2], bf[f >> 2][(f & 2) + 1]);
          if (f >= WO_C && f < WO_C + WO_L) {
            const int l = 16 - WO_L + f - WO_C;
            ldsm4t(af[l], (WO_LD ? dep(wo, __float_as_uint(d[(f + 1) % WO_C][0]), c.sb) : wo) + (c.sb + SM_WO + (l & 1) * 32768 + (l >> 1) * 2048));
          }
          if (f == WO_T) {
            const uint32_t tb2 = dep((t16 >> 3) & 0x1C0, __float_as_uint(d[f % WO_C][0]), c.sb) + (c.sb + SM_TAB + (s & 1) * 512);
            d0 = lds128(tb2 + 32); d1 = lds128(tb2 + 48);
          }
          if (f >= PL_WA && f < PL_WA + PL_W) lds_frag(wa[f - PL_WA], (PL_WD ? dep(t16, __float_as_uint(d[(f + PL_WD) % WO_C][0]), c.sb) : t16) + (c.sb + SM_POOL + (f - PL_WA) * 4096));
          if (PL_W && PL_WF && f == PL_WA + PL_W - 1) sched_fence(c.sb);
          if (f == 4) { sum.x = dep(sum.x, __float_as_uint(d[0][0]), c.sb); sum.y = dep(sum.y, __float_as_uint(d[0][0]), c.sb); }
        }
        if (PL_W && !PL_WF) {
          uint32_t all = 0;
#pragma unroll
          for (int k = 0; k < PL_W; k++) all ^= wa[k][0];
          l4 = dep(l4, all, c.sb);
        }
        char* dst[4] = {mk_ptr(d0.x | l4, d0.y), mk_ptr(d0.z | l4, d0.w), mk_ptr(d1.x | l4, d1.y), mk_ptr(d1.z | l4, d1.w)};
        const float i0 = rcp(__uint_as_float(sum.x)), i1 = rcp(__uint_as_float(sum.y));
#pragma unroll
        for (int i = 0; i < 4; i++) {
          const int t = i >> 1, e = 2 * (i & 1);
          const float y0 = WO_C == 2 ? d[t][e] : d[t][e] + d[(t + 2) % WO_C][e], y1 = WO_C == 2 ? d[t][e + 1] : d[t][e + 1] + d[(t + 2) % WO_C][e + 1];
          st_pub(dst[i], put_tag(pack_bf16(y0 * i0, y1 * i1), bit, s >> 1));
        }
        if (ANCH2) sts32(c.sb + SM_SUM + 64, clock_lo());
        mbar_arrive_warp(BAR(B_E2TRIG));
        TR(s, 6);
        sched_fence(c.sb);
        if (W_E2 == 2) mbar_spin(BAR(B_E2TRIG), s & 1);
        }
      }
      if (__builtin_expect(s + 2 < XEND, 1)) {
        const uint32_t tg0 = DLY_P ? clock_lo() + DLY_P : 0;
        if (LP_IN) ldp(0, PL_0, PL_D);
        float xa[16];
        uint32_t q[4];
        if (W_E2 == 1 && s >= 0) mbar_spin(BAR(B_E2TRIG), s & 1);
        TR(s, 7);
        constexpr int S1 = ORDER ? 0 : 2, S2 = ORDER == 0 ? 0 : ORDER == 1 ? 2 : 1, S3 = ORDER == 2 ? 2 : 1;
        if (ORDER) issue_qk<0, 16>(xa, wb, vary(dx, s, c.sb)); else issue_v(xa, wv, vary(dx, s, c.sb), vary(dh, s, c.sb));
        if (DLY_P) delay_until(tg0); else if (IS_F) sched_fence(c.sb);
        ldp(PL_0, PL_1, PL_D1);
        const uint32_t land = (t16 ^ ((t16 >> 3) & 0x60)) + vary(c.sb + SM_LAND + c.b * 4096, s, c.sb);
        TR(s, 14);
        if (LF_AT == 1) mbar_spin_if(BAR(B_LFREE), s & 1, s < 0); else if (!LF_AT) mbar_spin(BAR(B_LFREE), s & 1);
        TR(s, 15);
        WG_WAIT(0);
        TR(s, 8);
        park_own<S1 == 2>(q, xa, land, S1, c.sb);
        if (W_PUB == 4 && s >= 0) mbar_spin(BAR(B_PUB), s & 1);
        if (ORDER == 1) issue_v(xa, wv, vary(dx, s, c.sb + 32), vary(dh, s, c.sb)); else issue_qk<0, 16>(xa, ORDER ? wa : wb, vary(dx, s, c.sb + 32));
        if (IS_F) sched_fence(c.sb);
        ldp(PL_1, PL_2, PL_D1);
        if (W_PUB == 1) mbar_spin_if(BAR(B_PUB), s & 1, s >= 0);
        uint32_t tp = clock_lo(), q1[4] = {q[0], q[1], q[2], q[3]};
        if (PL_2B) ldp(PL_2, NP - PL_L, PL_D1);
        if (W_PUB != 3) park_peer(q, land, S1, c);
        if (!PL_2B) ldp(PL_2, NP - PL_L, PL_D1);
        TR(s, 13);
        WG_WAIT(0);
        TR(s, 9);
        park_own<S2 == 2>(q, xa, land, S2, c.sb);
        if (ORDER == 2) issue_v(xa, wv, vary(dx, s, c.sb + 64), vary(dh, s, c.sb));
        else {
          issue_qk<0, PL_L ? NP - PL_L : 16>(xa, wa, vary(dx, s, c.sb + 64));
          ldp(NP - PL_L, NP, PL_E);
          if (PL_L) issue_qk<NP - PL_L, 16>(xa, wa, vary(dx, s, c.sb + 64));
        }
        if ((W_PUB == 2 || W_PUB == 3) && s >= 0) { mbar_spin(BAR(B_PUB), s & 1); tp = clock_lo(); }
        if (W_PUB == 3) park_peer(q1, land, S1, c);
        if (DLY_S && s >= 0) delay_until(tp + DLY_S);
        park_peer(q, land, S2, c);
        WG_WAIT(0);
        TR(s, 10);
        mbar_arrive_warp(BAR(B_XEMPTY));
        park_own<S3 == 2>(q, xa, land, S3, c.sb);
        park_peer(q, land, S3, c);
        TR(s, 11);
      } else {
        if (s == NSEG - 1) break;
        if (EARLY2 && (XEND == NSEG || s == NSEG - 2) && c.m * 4 + c.w == 0) count_e(g_ctl + C_EARLY);
        ldp(LP_IN ? 0 : PL_0, NP, LP_IN ? 2 : 1);
      }
    }
    if (NOWO) mbar_arrive_warp(BAR(B_E2TRIG));
    asm volatile("setmaxnreg.dec.sync.aligned.u32 %0;" :: "n"(BPRE == 2 ? 176 : 128));
    const int tid = tid_now(), lane = tid & 31, tile = tile_of(c), m0 = (tile >> 3) * 128, n0 = (tile & 7) * 128;
    float acc[64];
#pragma unroll
    for (int i = 0; i < 64; i++) acc[i] = 0.f;
    const uint32_t rel = mapa(BAR(B_GEMPTY), lane & 1), la = desc_lo(c.sb + c.m * 8192), lb = ((c.sb + 16384) & 0x3FFFF) >> 4 | (8192 >> 4) << 16;
    bool relon = false;
    const int skew = tile < 120 ? 0 : SKEW, kend = 64 + skew - c.m * skew, hold = c.m * (65 - LEAD) - 1;
    const float g0 = __ldcg(g_gate + m0 + (tid >> 5) * 16 + (lane >> 2)), g1 = __ldcg(g_gate + m0 + (tid >> 5) * 16 + (lane >> 2) + 8);
    uint32_t o = SM_XT, st = 0, ph = 0, prev = 0;
    if (tid == 0) TL(9);
    __syncwarp();
    GT(0);
#pragma unroll 1
    for (int kb = -c.m * skew; kb < max(kend - 4, 64); kb++, o = next_stage(o)) {
      if (LEAD && kb == hold) bar_sync(15, 256);
      mbar_lim(BAR(B_GFULL + st), ph);
      if ((uint32_t)kb < 64) {
        WG_FENCE();
#pragma unroll
        for (int k = 0; k < 4; k++) wgmma_ss_n128_tb(acc, desc128(la + (o >> 4) + k * 2), desc128(lb + (o >> 4) + k * 128));
        WG_COMMIT();
        WG_WAIT(1);
      } else WG_WAIT(0);
      arrive_remote_if(rel + 8 * prev, relon && kb < kend - 4);
      relon = (tid & 127) < 2;
      prev = st;
      if (++st == 5) { st = 0; ph ^= 1; }
    }
    if (LEAD && c.m == 0) asm volatile("bar.arrive 15, 256;" ::: "memory");
    const uint32_t row = (tid >> 5) * 2048 + (lane & 15) * 128 + (((lane >> 4) ^ (lane & 7)) << 4);
    if (!BPRE) WG_WAIT(0);
    mbar_lim(BAR(B_BT), 0);
    uint32_t b[2][4][4];
    const uint32_t rb = (tid >> 5) * 2048 + (lane >> 2) * 128 + (((lane & 7) ^ (lane >> 2)) << 4);
#pragma unroll
    for (int i = 0; i < 8; i++) lds_frag(b[i & 1][i >> 1], (rb ^ (i & 2) * 32) + (c.sb + SM_BT + (i >> 2) * 16384 + (i & 1) * 1024));
    float bl[2][4][4], bh[2][4][4];
    if (BPRE == 2) {
#pragma unroll
      for (int i = 0; i < 32; i++) {
        asm volatile("shl.b32 %0, %1, 16;" : "=f"(bl[i >> 4][i >> 2 & 3][i & 3]) : "r"(b[i >> 4][i >> 2 & 3][i & 3]));
        asm volatile("and.b32 %0, %1, 0xffff0000;" : "=f"(bh[i >> 4][i >> 2 & 3][i & 3]) : "r"(b[i >> 4][i >> 2 & 3][i & 3]));
      }
    }
    if (BPRE) { sched_fence(c.sb); WG_WAIT(0); sched_fence(c.sb); }
#pragma unroll
    for (int i = 0; i < 64; i++) asm volatile("" : "+f"(acc[i]) :: "memory");
    GT(17);
    if (tid == 0) TL(4);
    __syncwarp();
#pragma unroll
    for (int hf = 0; hf < 2; hf++) {
#pragma unroll
      for (int t = 0; t < 4; t++) {
        uint32_t y[4];
#pragma unroll
        for (int i = 0; i < 4; i++) {
          const float* a = acc + 32 * hf + 8 * t + 2 * i, g = i & 1 ? g1 : g0;
          const uint32_t* q = b[i & 1][2 * (t & 1) + (i >> 1)] + hf;
          const float* f = (t & 2 ? bh : bl)[i & 1][2 * (t & 1) + (i >> 1)] + hf;
          if (BPRE == 2) y[i] = pack_bf16(fmaf(g, a[0], f[0]), fmaf(g, a[1], f[2])); else
          y[i] = pack_bf16(fmaf(g, a[0], __uint_as_float(t & 2 ? q[0] & 0xFFFF0000u : q[0] << 16)), fmaf(g, a[1], __uint_as_float(t & 2 ? q[2] & 0xFFFF0000u : q[2] << 16)));
        }
        stsm4<false>((row ^ t * 32) + (c.sb + SM_BT + hf * 16384), y[0], y[1], y[2], y[3]);
      }
      if (EP_F && !hf) { sched_fence(c.sb); for (int i = 32; i < 64; i++) asm volatile("" : "+f"(acc[i]) :: "memory"); }
      FENCE_ASYNC_SMEM();
      __syncwarp();
      tma2d_out_e(&tout, n0 + hf * 64, m0 + (c.m * 4 + c.w) * 16, c.sb + SM_BT + hf * 16384 + (c.m * 4 + c.w) * 2048);
    }
    asm volatile("cp.async.bulk.commit_group; cp.async.bulk.wait_group" WAITRD " 0;" ::: "memory");
    GT(18);
    if ((tid & 127) == 0) TL(11);
    return;
  }
  static_assert(!QSH || NCR >= 7, "rounds");
  const bool col = c.r >= 128;
  const int tile = col ? 0 : tile_of(c);
  const int q0 = col ? 256 - 16 * NCR + (c.r - 128) * 4 + c.m : tile < 120 ? tile : 256, u = (tile >> 1 & 32) | (tile >> 3 & 7) | (tile & 6) << 2, e = QSH == 2 ? 2 * (u - (u > 39) - (u > 47)) + c.b : tile,
            dq = col ? 16 : QSH ? 120 + (e >> 2) - tile : 120, qe = col ? 256 : 256 - 16 * NCR,
            qw = col || !QSH || c.w == (e & 3) ? qe : 120;
  const uint32_t zs = c.sb + (col ? COL_Z + c.m * 32768 : SM_BT), zb = BAR(B_Z + c.m);
  auto load_z = [&](int q) { if (c.w == 0 && q < qe) { mbar_expect_e(zb, 32768); tma2d_o<(ONCE & 4) != 0>(zs, &tz, q * 64, 0, zb); } };
  asm volatile("fence.proxy.async.global;" ::: "memory");
  load_z(q0);
  uint32_t ph = 0;
#pragma unroll 1
  for (int q = q0; q < qe; q += dq, ph ^= 1) {
    mbar_lim(zb, ph);
    const int p = q * 4 + c.w;
    if (EXP_INV && q < qw) fft_rows_inv(zs, (float2*)(smraw + (col ? 8192 + c.m * INV_BUF * 32 : SM_MEM)) + c.w * INV_BUF, (const float2*)(smraw + (col ? 0 : SM_TW)), p, tid_now() & 31, g_b,
                              [&]() { bar_sync(5 + c.m, 128); load_z(q + dq); });
    else { bar_sync(5 + c.m, 128); load_z(q + dq); }
  }
  asm volatile("fence.acq_rel.gpu;" ::: "memory");
  __syncwarp();
  { const int q = q0 + (tid_now() & 31) * dq; if (q < qw) asm volatile("red.relaxed.gpu.global.add.u32 [%0], 1;" :: "l"(g_ctl + C_ROWS + (q >> 5) * 32) : "memory"); }
  if (tid_now() == 256) { if (col) TL(27); else TL(3); }
  __syncwarp();
  if (!col && c.w == 0) {
    await_count<AW_NS>(g_ctl + C_ROWS + ((tile >> 3) & 7) * 32, 128);
    mbar_expect_e(BAR(B_BT), 32768);
    for (int i = 0; i < 2; i++) tma2d_o<(ONCE & 8) != 0>(c.sb + SM_BT + i * 16384, &tb, (tile & 7) * 128 + i * 64, (tile >> 3) * 128, BAR(B_BT));
    if (tid_now() == 256) TL(5);
  }
}

typedef CUresult (*EncodeFn)(CUtensorMap*, CUtensorMapDataType, cuuint32_t, void*, const cuuint64_t*, const cuuint64_t*,
                             const cuuint32_t*, const cuuint32_t*, CUtensorMapInterleave, CUtensorMapSwizzle,
                             CUtensorMapL2promotion, CUtensorMapFloatOOBfill);

void make_map(EncodeFn enc, CUtensorMap* tm, const void* p, int rank, const cuuint64_t* dims, const cuuint64_t* strides, const cuuint32_t* box, bool swz = true) {
  const cuuint32_t es[4] = {1, 1, 1, 1};
  enc(tm, CU_TENSOR_MAP_DATA_TYPE_BFLOAT16, rank, (void*)p, dims, strides, box, es, CU_TENSOR_MAP_INTERLEAVE_NONE,
      swz ? CU_TENSOR_MAP_SWIZZLE_128B : CU_TENSOR_MAP_SWIZZLE_NONE, swz ? CU_TENSOR_MAP_L2_PROMOTION_L2_128B : W_PROMO, CU_TENSOR_MAP_FLOAT_OOB_FILL_NONE);
}
void make_map2(EncodeFn enc, CUtensorMap* tm, const void* p, uint64_t cols, uint64_t rows, uint32_t boxrows) {
  const cuuint64_t dims[2] = {cols, rows}, strides[1] = {cols * 2};
  const cuuint32_t box[2] = {64, boxrows};
  make_map(enc, tm, p, 2, dims, strides, box);
}

}

extern "C" void kernel_launch(void* const* d_in, const int* in_sizes, int n_in, void* d_out, int out_size) {
  (void)in_sizes; (void)n_in; (void)out_size;
  const __nv_bfloat16* x = (const __nv_bfloat16*)d_in[0];
  const __nv_bfloat16* mem0 = (const __nv_bfloat16*)d_in[1];
  const __nv_bfloat16* gw = (const __nv_bfloat16*)d_in[10];

  EncodeFn enc = nullptr;
  cudaDriverEntryPointQueryResult qr;
  cudaGetDriverEntryPoint("cuTensorMapEncodeTiled", (void**)&enc, cudaEnableDefault, &qr);
  void *p_ox, *p_b, *p_z, *p_mail;
  cudaGetSymbolAddress(&p_ox, g_ox); cudaGetSymbolAddress(&p_b, g_b); cudaGetSymbolAddress(&p_z, g_z); cudaGetSymbolAddress(&p_mail, g_mail);
  CUtensorMap tq, tk, tv, tv16, to, tx, twr, twi, ta, tw, tb, tout, tz, tzs, ta32;
  make_map2(enc, &tq, d_in[2], 4096, 1024, 64);
  make_map2(enc, &tk, d_in[3], 4096, 1024, 64);
  make_map2(enc, &tv, d_in[4], 4096, 1024, 64);
  make_map2(enc, &tv16, d_in[4], 4096, 1024, 16);
  make_map2(enc, &to, d_in[5], 1024, 4096, 128);
  make_map2(enc, &tw, d_in[5], 1024, 4096, 64);
  {
    const cuuint64_t dims[3] = {64, 2048, 64}, strides[2] = {128, 262144};
    const cuuint32_t box[3] = {64, 32, 2}, box1[3] = {64, 32, 1};
    make_map(enc, &ta, p_ox, 3, dims, strides, box);
    make_map(enc, &ta32, p_ox, 3, dims, strides, box1);
  }
  make_map2(enc, &tb, p_b, 1024, 2048, 128);
  make_map2(enc, &tout, d_out, 1024, 2048, 16);
  make_map2(enc, &tz, p_z, 16384, 257, 256);
  {
    const cuuint64_t dims[4] = {64, 8, 16, 256}, strides[3] = {2048, 128, 16384};
    const cuuint32_t box[4] = {64, 8, 8, 2};
    make_map(enc, &tx, x, 4, dims, strides, box);
  }
  {
    const cuuint64_t dims[2] = {512, 257 * 32}, strides[1] = {1024};
    const cuuint32_t box[2] = {128, 16};
    make_map(enc, &tzs, p_z, 2, dims, strides, box, false);
  }
  {
    const cuuint64_t dims[2] = {8 * 513, 256}, strides[1] = {8 * 513 * 2};
    const cuuint32_t box[2] = {8, 256};
    make_map(enc, &twr, d_in[8], 2, dims, strides, box, false);
    make_map(enc, &twi, d_in[9], 2, dims, strides, box, false);
  }
  cudaFuncSetAttribute(chain_kernel, cudaFuncAttributeMaxDynamicSharedMemorySize, CHAIN_SMEM);

  cudaStream_t st = cudaStreamPerThread;
  char* mail = (char*)(((uintptr_t)p_mail + M_REG - 1) & ~(uintptr_t)(M_REG - 1));
  chain_kernel<<<132, 512, CHAIN_SMEM, st>>>(tq, tk, tv, tv16, to, tx, twr, twi, ta, tw, tb, tout, tz, tzs, ta32, mem0, mail, x, gw);
}
```

```cpp
#include <cuda_runtime.h>
#include <cuda_bf16.h>
#include <cuda.h>
#include <stdint.h>

#define DLY_E1 160
#define DLY_V 270
#define DLY_E2 260
#define DLY_E3 440
#define DLY_X 1
#define DLY_S 0
#define DLY_F 200
#define VM_AT 1
#define VM_F 0
#define OM_F 1
#define SXX_IN 0
#define C1_AT 7
#define NLAG 2
#define WO_D 2
#define WO_0 3
#define WO_1 10
#define PL_0 10
#define PL_1 10
#define PL_D 2
#define PL_L 0
#define DUAL 0
#define HV_D 4
#define DLY_FK 0
#define QX_SM 0
#define REG_F 216
#define REG_H 24
#define SC_F 1
#define E2_F 0
#define KVQ_AT 0
#define DLY_K 0
#define X_AT 2
#define W_PV 0
#define PL_2 10
#define BF_E 3
#define PL_E 2
#define ORDER 1
#define SSPOS 1
#define W_PUB 1
#define FIN_AT 5
#define AWARE 1
#define NPROBE 2
#define NP_ 12
#define USE_PDL 1
#define DLY_GRP 1000
#define P2_BULK 0
#define EXP_NV 4
#define EXP_NK 4
#define EXP_CHK 1
#define EXP_NXT 2
#define EXP_PEER 1
#define EXP_FIN 7
#define EXP_NWG 16
#define ANCH2 1
#define XF_AT 1
#define IS_F 0
#define PL_D1 2
#define W_E2 0
#define V_TMA 2
#define V_W 3
#define RED_L 3
#define RED_T 1
#define RED_P 1
#define DLY_E3B 20
#define HV_E 1
#define HV_R 4
#define HOLD 0
#define PACE 500
#define PACE0 0
#define EXP_ST 7
#define HOLD_AT NPROBE
#define WO_AT 38
#define WO_P 2
#define DLY_SEL 300
#define P1_AT 1
#define EXP_ZG 1
#define TMA_W tma2d_once
#define BULK_F bulk_once
#define TMA_O tma2d_once
#define PACE_Z 580
#define PACE_F 800
#define EXP_INV 1
#define VF_AT 0
#define UP_F 0
#define WO_L (12 - NP_)
#define WO_C 4
#define WO_T 4
#define WO_LD 0
#define EXP_LIN 0
#define PL_W 2
#define PL_WA 6
#define PL_WD 0
#define PL_WF 2
#define STAG 0
#define EXP_FL 0
#define DLY_FS 0
#define DLY_F2 40
#define LROT 0
#define PF_D 4
#define PF_A 1
#define PF_B 0
#define SIDE 1
#define ROLE 1
#define LOOSE 0x765498
#define E1OFF 1
#define EVOFF E1OFF
#define EPI 0
#define WAITRD ".read"
#define X01 1
#define E3I 1
#define START 1000
#define WUNR 1
#define WO_N 0
#define WO_H 0
#define PL_2B 1
#define DLY_P 0
#define LP_IN 1
#define LF_AT 1
#define FINE 0
#define LAG_F 0
#define E30 1
#define WO_S 1
#define POOL_AT 12
#define COL_DLY 0
#define WO_F 0
#define PAD0 0
#define PAD2 2
#define PAD3 0
#define WO_X 0
#define PRIOR 12
#define EARLY 1
#define SEL_AT 3000
#define CUNR 1
#define FUNR 0
#define ZINIT 1
#define ZDLY 0
#define NQ 108
#define GATE 0
#define LASTM 1
#define X_ONCE 1
#define ONCE 31
#define Z_PF 0
#define EXP_W 1
#define W_PROMO CU_TENSOR_MAP_L2_PROMOTION_L2_128B
#define Z_ST 1
#define W_FINE 0
#define X128 2
#define T128_ 1
#define W_AT 0
#define SKEW 7
#define AW_NS 0
#define QSH 2
#define NOWO 0
#define EARLY2 1
#define LEAD 3
#define BPRE 2
#define EP_F 1
#define TQ_AT 0
#define LAG_0 8
#define LAG_G 0
#define LAG_S 0
#define O_AT 0
#define XB 0
#define V_E 0
#define LAG_T 1
#define E3M 0
#define B_ST 1
#define TW_L 1
#define MINI 0
#define DLY_M 310
#define PRE_AT B_SC

namespace {
constexpr int wunr = WUNR;

constexpr int S_ = 2048, D_ = 1024, NSEG = 64;
constexpr uint32_t SENT = 0xFFFFFFFFu;
constexpr int NSLOT = 4;

constexpr uint32_t M_REG = 1 << 21, M_E3 = 64 * 16384, M_KVQ = M_E3 + 4 * 8192, M_SEL = M_KVQ + 32 * 24576;
__device__ __align__(1024) unsigned char g_mail[5 * M_REG];
constexpr int C_P1 = 0, C_COLS = C_P1 + 32, C_EARLY = C_COLS + 32, C_LAST = C_EARLY + 32, C_ROWS = C_LAST + 128, C_END = C_ROWS + 8 * 32;
__device__ __align__(1024) uint32_t g_ctl[C_END];
#define CLK(i)
#define TL(i)
#define TL2(i)
#define FT(i, v)
#define GT(i)
#define CNT(i)
__device__ __align__(1024) __nv_bfloat16 g_ox[S_ * 4096];
__device__ __align__(1024) float2 g_z[257 * 4096];
__device__ __align__(1024) __nv_bfloat16 g_b[S_ * D_];
__device__ float g_gate[S_];
__device__ __align__(1024) float2 g_tw[1024];

#define TRV(s, ev, val)
#define TR(s, ev)
#define TRSYNC(ev)
__device__ __forceinline__ uint32_t smem_u32(const void* p) { return (uint32_t)__cvta_generic_to_shared(p); }
__device__ __forceinline__ void watchdog(uint32_t& n, uint32_t limit) {
  asm volatile("{ .reg .pred p; add.u32 %0, %0, 1; setp.gt.u32 p, %0, %1; @p trap; }" : "+r"(n) : "r"(limit));
}
__device__ __forceinline__ void mbar_init(uint32_t bar, uint32_t cnt) {
  asm volatile("mbarrier.init.shared::cta.b64 [%0], %1;" :: "r"(bar), "r"(cnt) : "memory");
}
__device__ __forceinline__ void mbar_arrive_warp(uint32_t bar) {
  __syncwarp();
  asm volatile("{ .reg .pred p; elect.sync _|p, 0xffffffff; @p mbarrier.arrive.shared::cta.b64 _, [%0]; }" :: "r"(bar) : "memory");
}
__device__ __forceinline__ uint32_t clock_lo() {
  uint32_t r; asm volatile("{ .reg .u64 c; .reg .u32 h; mov.u64 c, %%clock64; mov.b64 {%0, h}, c; }" : "=r"(r) :: "memory"); return r;
}
__device__ __forceinline__ void delay_until(uint32_t t) {
  asm volatile("{ .reg .pred p; .reg .u64 c; .reg .u32 l, h;\n"
               "DLY: mov.u64 c, %%clock64; mov.b64 {l, h}, c; sub.s32 l, l, %0; setp.lt.s32 p, l, 0; @p bra.uni DLY; }" :: "r"(t) : "memory");
}
__device__ __forceinline__ void delay_fine(uint32_t t) {
  delay_until(t);
}
__device__ __forceinline__ void delay_cycles(uint32_t n) { delay_until(clock_lo() + n); }
__device__ __forceinline__ void sched_fence(uint32_t z) {
  asm volatile("{ .reg .pred p; setp.eq.u32 p, %0, 0x7fff0000; @p pmevent 1; }" :: "r"(z) : "memory");
}
__device__ __forceinline__ void pdl_wait() { asm volatile("griddepcontrol.wait;" ::: "memory"); }
__device__ __forceinline__ void pdl_launch() { asm volatile("griddepcontrol.launch_dependents;" ::: "memory"); }
__device__ __forceinline__ float ex2(float x) { float r; asm("ex2.approx.ftz.f32 %0, %1;" : "=f"(r) : "f"(x)); return r; }
__device__ __forceinline__ float rcp(float x) { float r; asm("rcp.approx.ftz.f32 %0, %1;" : "=f"(r) : "f"(x)); return r; }
__device__ __forceinline__ void mbar_expect(uint32_t bar, uint32_t bytes) {
  asm volatile("mbarrier.arrive.expect_tx.shared::cta.b64 _, [%0], %1;" :: "r"(bar), "r"(bytes) : "memory");
}
__device__ __forceinline__ bool mbar_try(uint32_t bar, uint32_t ph) {
  uint32_t ok;
  asm volatile("{ .reg .pred p; mbarrier.try_wait.parity.shared::cta.b64 p, [%1], %2; selp.u32 %0, 1, 0, p; }"
               : "=r"(ok) : "r"(bar), "r"(ph) : "memory");
  return ok;
}
__device__ __forceinline__ void mbar_wait(uint32_t bar, uint32_t ph) {
  uint32_t n = 0;
  while (!mbar_try(bar, ph)) { watchdog(n, (1u << 20)); }
}
__device__ __forceinline__ void mbar_spin(uint32_t bar, uint32_t ph) { while (!mbar_try(bar, ph)) {} }
__device__ __forceinline__ void mbar_spin_if(uint32_t bar, uint32_t ph, bool on) {
  asm volatile("{ .reg .pred p, q; setp.ne.u32 p, %2, 0;\n"
               "SPN: setp.eq.u32 q, 0, 0; @p mbarrier.try_wait.parity.shared::cta.b64 q, [%0], %1; @!q bra.uni SPN; }" :: "r"(bar), "r"(ph), "r"((uint32_t)on) : "memory");
}
__device__ __forceinline__ void mbar_spin2_if(uint32_t bar, uint32_t bar2, uint32_t ph, bool on) {
  asm volatile("{ .reg .pred p, q, r; setp.ne.u32 p, %3, 0;\n"
               "SPN: setp.eq.u32 q, 0, 0; setp.eq.u32 r, 0, 0; @p mbarrier.try_wait.parity.shared::cta.b64 q, [%0], %2;\n"
               "@p mbarrier.try_wait.parity.shared::cta.b64 r, [%1], %2; and.pred q, q, r; @!q bra.uni SPN; }" :: "r"(bar), "r"(bar2), "r"(ph), "r"((uint32_t)on) : "memory");
}
__device__ __forceinline__ void mbar_spin_cluster(uint32_t bar, uint32_t ph) {
  uint32_t ok;
  do {
    asm volatile("{ .reg .pred p; mbarrier.try_wait.parity.acquire.cluster.shared::cta.b64 p, [%1], %2; selp.u32 %0, 1, 0, p; }"
                 : "=r"(ok) : "r"(bar), "r"(ph) : "memory");
  } while (!ok);
}
#define ONCE_H "mov.b64 h, 0x12F0000000000000; "
__device__ __forceinline__ void tma2d(uint32_t dst, const CUtensorMap* tm, int c0, int c1, uint32_t bar) {
  if (ONCE & 32) asm volatile("{ .reg .b64 h; " ONCE_H "cp.async.bulk.tensor.2d.shared::cluster.global.mbarrier::complete_tx::bytes.L2::cache_hint [%0], [%1, {%3, %4}], [%2], h; }"
               :: "r"(dst), "l"(tm), "r"(bar), "r"(c0), "r"(c1) : "memory");
  else asm volatile("cp.async.bulk.tensor.2d.shared::cluster.global.mbarrier::complete_tx::bytes [%0], [%1, {%3, %4}], [%2];"
               :: "r"(dst), "l"(tm), "r"(bar), "r"(c0), "r"(c1) : "memory");
}
__device__ __forceinline__ void mbar_expect_e(uint32_t bar, uint32_t bytes) {
  asm volatile("{ .reg .pred p; elect.sync _|p, 0xffffffff; @p mbarrier.arrive.expect_tx.shared::cta.b64 _, [%0], %1; }" :: "r"(bar), "r"(bytes) : "memory");
}
__device__ __forceinline__ void tma2d_e(uint32_t dst, const CUtensorMap* tm, int c0, int c1, uint32_t bar) {
  asm volatile("{ .reg .pred p; elect.sync _|p, 0xffffffff;\n"
               "@p cp.async.bulk.tensor.2d.shared::cluster.global.mbarrier::complete_tx::bytes [%0], [%1, {%3, %4}], [%2]; }"
               :: "r"(dst), "l"(tm), "r"(bar), "r"(c0), "r"(c1) : "memory");
}
__device__ __forceinline__ void tma2d_st_e(const CUtensorMap* tm, int c0, int c1, uint32_t src) {
  asm volatile("{ .reg .pred p; elect.sync _|p, 0xffffffff;\n"
               "@p cp.async.bulk.tensor.2d.global.shared::cta.bulk_group [%0, {%2, %3}], [%1]; }" :: "l"(tm), "r"(src), "r"(c0), "r"(c1) : "memory");
}
__device__ __forceinline__ void tma2d_out_e(const CUtensorMap* tm, int c0, int c1, uint32_t src) {
  if (EPI) asm volatile("{ .reg .pred p; elect.sync _|p, 0xffffffff;\n"
               "@p cp.reduce.async.bulk.tensor.2d.global.shared::cta.add.bulk_group [%0, {%2, %3}], [%1]; }" :: "l"(tm), "r"(src), "r"(c0), "r"(c1) : "memory");
  else if (ONCE & 16) asm volatile("{ .reg .pred p; .reg .b64 h; " ONCE_H "elect.sync _|p, 0xffffffff;\n"
               "@p cp.async.bulk.tensor.2d.global.shared::cta.bulk_group.L2::cache_hint [%0, {%2, %3}], [%1], h; }" :: "l"(tm), "r"(src), "r"(c0), "r"(c1) : "memory");
  else asm volatile("{ .reg .pred p; elect.sync _|p, 0xffffffff;\n"
               "@p cp.async.bulk.tensor.2d.global.shared::cta.bulk_group [%0, {%2, %3}], [%1]; }" :: "l"(tm), "r"(src), "r"(c0), "r"(c1) : "memory");
}
__device__ __forceinline__ void tma2d_once(uint32_t dst, const CUtensorMap* tm, int c0, int c1, uint32_t bar) {
  asm volatile("{ .reg .pred p; .reg .b64 h; " ONCE_H "elect.sync _|p, 0xffffffff;\n"
               "@p cp.async.bulk.tensor.2d.shared::cluster.global.mbarrier::complete_tx::bytes.L2::cache_hint [%0], [%1, {%3, %4}], [%2], h; }"
               :: "r"(dst), "l"(tm), "r"(bar), "r"(c0), "r"(c1) : "memory");
}
__device__ __forceinline__ void bulk_once(uint32_t dst, const void* src, uint32_t bytes, uint32_t bar) {
  asm volatile("{ .reg .pred p; .reg .b64 h; " ONCE_H "elect.sync _|p, 0xffffffff;\n"
               "@p cp.async.bulk.shared::cluster.global.mbarrier::complete_tx::bytes.L2::cache_hint [%0], [%1], %2, [%3], h; }"
               :: "r"(dst), "l"(src), "r"(bytes), "r"(bar) : "memory");
}
__device__ __forceinline__ void tma4d_e(uint32_t dst, const CUtensorMap* tm, int c2, int c3, uint32_t bar) {
  asm volatile("{ .reg .pred p; .reg .b64 h; " ONCE_H "elect.sync _|p, 0xffffffff;\n"
               "@p cp.async.bulk.tensor.4d.shared::cluster.global.mbarrier::complete_tx::bytes.L2::cache_hint [%0], [%1, {0, 0, %3, %4}], [%2], h; }"
               :: "r"(dst), "l"(tm), "r"(bar), "r"(c2), "r"(c3) : "memory");
}
__device__ __forceinline__ void bulk_load_e(uint32_t dst, const void* src, uint32_t bytes, uint32_t bar) {
  asm volatile("{ .reg .pred p; elect.sync _|p, 0xffffffff;\n"
               "@p cp.async.bulk.shared::cluster.global.mbarrier::complete_tx::bytes [%0], [%1], %2, [%3]; }"
               :: "r"(dst), "l"(src), "r"(bytes), "r"(bar) : "memory");
}
template<bool O> __device__ __forceinline__ void tma2d_o(uint32_t dst, const CUtensorMap* tm, int c0, int c1, uint32_t bar) {
  if (O) tma2d_once(dst, tm, c0, c1, bar); else tma2d_e(dst, tm, c0, c1, bar);
}
__device__ __forceinline__ float2 ld_once(const float2* p) {
  float2 v;
  if (ONCE & 64) asm volatile("{ .reg .b64 h; " ONCE_H "ld.global.cg.L2::cache_hint.v2.f32 {%0, %1}, [%2], h; }" : "=f"(v.x), "=f"(v.y) : "l"(p));
  else v = __ldcg(p);
  return v;
}
template<bool O = false> __device__ __forceinline__ void prefetch2d_e(const CUtensorMap* tm, int c0, int c1) {
  if (O) asm volatile("{ .reg .pred p; .reg .b64 h; " ONCE_H "elect.sync _|p, 0xffffffff;\n"
               "@p cp.async.bulk.prefetch.tensor.2d.L2.global.L2::cache_hint [%0, {%1, %2}], h; }" :: "l"(tm), "r"(c0), "r"(c1) : "memory");
  else asm volatile("{ .reg .pred p; elect.sync _|p, 0xffffffff;\n"
               "@p cp.async.bulk.prefetch.tensor.2d.L2.global [%0, {%1, %2}]; }" :: "l"(tm), "r"(c0), "r"(c1) : "memory");
}
__device__ __forceinline__ void st_pub4(void* p, uint4 v) {
  asm volatile("st.relaxed.gpu.global.v4.u32 [%0], {%1,%2,%3,%4};" :: "l"(p), "r"(v.x), "r"(v.y), "r"(v.z), "r"(v.w) : "memory");
}
__device__ __forceinline__ void st_pub_if(void* p, uint32_t v, bool on) {
  asm volatile("{ .reg .pred p; setp.ne.u32 p, %2, 0; @p st.relaxed.gpu.global.u32 [%0], %1; }" :: "l"(p), "r"(v), "r"((uint32_t)on) : "memory");
}
__device__ __forceinline__ uint32_t mapa(uint32_t a, uint32_t r) {
  uint32_t d; asm volatile("mapa.shared::cluster.u32 %0, %1, %2;" : "=r"(d) : "r"(a), "r"(r)); return d;
}
__device__ __forceinline__ void st_async4(uint32_t a, uint32_t x, uint32_t y, uint32_t z, uint32_t w, uint32_t bar) {
  asm volatile("st.async.shared::cluster.mbarrier::complete_tx::bytes.v4.u32 [%0], {%1,%2,%3,%4}, [%5];"
               :: "r"(a), "r"(x), "r"(y), "r"(z), "r"(w), "r"(bar) : "memory");
}
__device__ __forceinline__ uint4 ld_poll(const void* p) {
  uint4 v;
  asm volatile("ld.volatile.global.v4.u32 {%0,%1,%2,%3}, [%4];" : "=r"(v.x), "=r"(v.y), "=r"(v.z), "=r"(v.w) : "l"(p) : "memory");
  return v;
}
__device__ __forceinline__ uint2 ld_poll2(const void* p) {
  uint2 v; asm volatile("ld.volatile.global.v2.u32 {%0,%1}, [%2];" : "=r"(v.x), "=r"(v.y) : "l"(p) : "memory"); return v;
}
__device__ __forceinline__ void st_pub2(void* p, uint32_t a, uint32_t b) {
  asm volatile("st.relaxed.gpu.global.v2.u32 [%0], {%1,%2};" :: "l"(p), "r"(a), "r"(b) : "memory");
}
__device__ __forceinline__ uint32_t ld_poll1(const void* p) {
  uint32_t v; asm volatile("ld.volatile.global.u32 %0, [%1];" : "=r"(v) : "l"(p) : "memory"); return v;
}
__device__ __forceinline__ uint32_t ld_acquire(const uint32_t* p) {
  uint32_t v; asm volatile("ld.acquire.gpu.global.u32 %0, [%1];" : "=r"(v) : "l"(p) : "memory"); return v;
}
__device__ __forceinline__ void st_pub(void* p, uint32_t v) {
  asm volatile("st.relaxed.gpu.global.u32 [%0], %1;" :: "l"(p), "r"(v) : "memory");
}
__device__ __forceinline__ uint32_t lds32(uint32_t a) {
  uint32_t v; asm volatile("ld.shared.u32 %0, [%1];" : "=r"(v) : "r"(a) : "memory"); return v;
}
__device__ __forceinline__ int race_init(void* p0, void* p1, uint32_t val) {
  int t;
  asm volatile("{ .reg .pred r; .reg .u32 a, b, u, v;\n"
               "atom.relaxed.gpu.global.exch.b32 u, [%1], %3; atom.relaxed.gpu.global.exch.b32 v, [%2], %3;\n"
               "setp.eq.u32 r, u, 0x12345; @r pmevent 1; mov.u32 a, %%clock;\n"
               "setp.eq.u32 r, v, 0x12345; @r pmevent 1; mov.u32 b, %%clock; sub.u32 %0, b, a; }" : "=r"(t) : "l"(p0), "l"(p1), "r"(val) : "memory");
  return t;
}
__device__ __forceinline__ void race_init2(void* p0, void* p1, uint32_t val) {
  asm volatile("{ .reg .pred r; .reg .u32 a, b, u, v;\n"
               "atom.relaxed.gpu.global.exch.b32 u, [%0], %2; atom.relaxed.gpu.global.exch.b32 v, [%1], %2;\n"
               "atom.relaxed.gpu.global.exch.b32 a, [%0 + 4096], %2; atom.relaxed.gpu.global.exch.b32 b, [%1 + 4096], %2;\n"
               "lop3.b32 u, u, v, a, 0x96; setp.eq.u32 r, u, 0x12345; setp.eq.and.u32 r, b, u, r; @r pmevent 1; }" :: "l"(p0), "l"(p1), "r"(val) : "memory");
}
__device__ __forceinline__ uint4 lds128(uint32_t a) {
  uint4 v; asm volatile("ld.shared.v4.u32 {%0,%1,%2,%3}, [%4];" : "=r"(v.x), "=r"(v.y), "=r"(v.z), "=r"(v.w) : "r"(a) : "memory"); return v;
}
__device__ __forceinline__ uint2 lds64(uint32_t a) {
  uint2 v; asm volatile("ld.shared.v2.u32 {%0,%1}, [%2];" : "=r"(v.x), "=r"(v.y) : "r"(a) : "memory"); return v;
}
__device__ __forceinline__ void sts128(uint32_t a, uint4 v) {
  asm volatile("st.shared.v4.u32 [%0], {%1,%2,%3,%4};" :: "r"(a), "r"(v.x), "r"(v.y), "r"(v.z), "r"(v.w) : "memory");
}
__device__ __forceinline__ void sts64(uint32_t a, uint32_t x, uint32_t y) { asm volatile("st.shared.v2.u32 [%0], {%1,%2};" :: "r"(a), "r"(x), "r"(y) : "memory"); }
__device__ __forceinline__ void sts32(uint32_t a, uint32_t x) { asm volatile("st.shared.u32 [%0], %1;" :: "r"(a), "r"(x) : "memory"); }
__device__ __forceinline__ void ldsm4t(uint32_t (&r)[4], uint32_t a) {
  asm volatile("ldmatrix.sync.aligned.m8n8.x4.trans.shared.b16 {%0,%1,%2,%3}, [%4];"
               : "=r"(r[0]), "=r"(r[1]), "=r"(r[2]), "=r"(r[3]) : "r"(a) : "memory");
}
__device__ __forceinline__ void ldsm4(uint32_t (&r)[4], uint32_t a) {
  asm volatile("ldmatrix.sync.aligned.m8n8.x4.shared.b16 {%0,%1,%2,%3}, [%4];"
               : "=r"(r[0]), "=r"(r[1]), "=r"(r[2]), "=r"(r[3]) : "r"(a) : "memory");
}
template<bool TRANS> __device__ __forceinline__ void stsm4(uint32_t a, uint32_t r0, uint32_t r1, uint32_t r2, uint32_t r3) {
  if (TRANS) asm volatile("stmatrix.sync.aligned.m8n8.x4.trans.shared.b16 [%0], {%1,%2,%3,%4};" :: "r"(a), "r"(r0), "r"(r1), "r"(r2), "r"(r3) : "memory");
  else       asm volatile("stmatrix.sync.aligned.m8n8.x4.shared.b16 [%0], {%1,%2,%3,%4};" :: "r"(a), "r"(r0), "r"(r1), "r"(r2), "r"(r3) : "memory");
}
__device__ __forceinline__ void mma16816(float (&d)[4], uint32_t a0, uint32_t a1, uint32_t a2, uint32_t a3, uint32_t b0, uint32_t b1) {
  asm volatile("mma.sync.aligned.m16n8k16.row.col.f32.bf16.bf16.f32 {%0,%1,%2,%3}, {%4,%5,%6,%7}, {%8,%9}, {%0,%1,%2,%3};"
               : "+f"(d[0]), "+f"(d[1]), "+f"(d[2]), "+f"(d[3]) : "r"(a0), "r"(a1), "r"(a2), "r"(a3), "r"(b0), "r"(b1));
}
__device__ __forceinline__ void mma1688(float (&d)[4], uint32_t a0, uint32_t a1, uint32_t b0) {
  asm volatile("mma.sync.aligned.m16n8k8.row.col.f32.bf16.bf16.f32 {%0,%1,%2,%3}, {%4,%5}, {%6}, {%0,%1,%2,%3};"
               : "+f"(d[0]), "+f"(d[1]), "+f"(d[2]), "+f"(d[3]) : "r"(a0), "r"(a1), "r"(b0));
}
__device__ __forceinline__ uint32_t pack_bf16(float lo, float hi) {
  uint32_t r; asm("cvt.rn.bf16x2.f32 %0, %1, %2;" : "=r"(r) : "f"(hi), "f"(lo)); return r;
}
__device__ __forceinline__ uint32_t add_bf16x2(uint32_t a, uint32_t b) {
  uint32_t r; asm("add.rn.bf16x2 %0, %1, %2;" : "=r"(r) : "r"(a), "r"(b)); return r;
}
__device__ __forceinline__ uint32_t umax4(uint4 v) { return max(max(v.x, v.y), max(v.z, v.w)); }
__device__ __forceinline__ uint32_t opaque(uint32_t x) { uint32_t r; asm volatile("mov.u32 %0, %1;" : "=r"(r) : "r"(x)); return r; }
template<class T> __device__ __forceinline__ void pin(T*& p) { asm volatile("" : "+l"(p)); }
__device__ __forceinline__ void pin(uint32_t& v) { asm volatile("" : "+r"(v)); }
__device__ __forceinline__ uint32_t desc_lo(uint32_t addr) { return ((addr & 0x3FFFF) >> 4) | 0x10000; }
__device__ __forceinline__ uint64_t desc128(uint32_t lo) {
  uint64_t d; asm("mov.b64 %0, {%1, %2};" : "=l"(d) : "r"(lo), "r"(0x40000040)); return d;
}
#define WG_FENCE()  asm volatile("wgmma.fence.sync.aligned;" ::: "memory")
#define WG_COMMIT() asm volatile("wgmma.commit_group.sync.aligned;" ::: "memory")
#define WG_WAIT(n)  asm volatile("wgmma.wait_group.sync.aligned " #n ";" ::: "memory")
#define FENCE_ASYNC_SMEM() asm volatile("fence.proxy.async.shared::cta;" ::: "memory")
__device__ __forceinline__ void bar_sync(int id, int n) { asm volatile("bar.sync %0, %1;" :: "r"(id), "r"(n) : "memory"); }

#define D16(c) c(d[0]), c(d[1]), c(d[2]), c(d[3]), c(d[4]), c(d[5]), c(d[6]), c(d[7]), \
               c(d[8]), c(d[9]), c(d[10]), c(d[11]), c(d[12]), c(d[13]), c(d[14]), c(d[15])
template<bool FIRST> __device__ __forceinline__ void wgmma_rs_n32(float (&d)[16], const uint32_t (&a)[4], uint64_t b) {
  if (FIRST)
    asm volatile("wgmma.mma_async.sync.aligned.m64n32k16.f32.bf16.bf16 {%0,%1,%2,%3,%4,%5,%6,%7,%8,%9,%10,%11,%12,%13,%14,%15}, {%16,%17,%18,%19}, %20, 0, 1, 1, 0;"
      : D16("=f") : "r"(a[0]), "r"(a[1]), "r"(a[2]), "r"(a[3]), "l"(b));
  else
    asm volatile("wgmma.mma_async.sync.aligned.m64n32k16.f32.bf16.bf16 {%0,%1,%2,%3,%4,%5,%6,%7,%8,%9,%10,%11,%12,%13,%14,%15}, {%16,%17,%18,%19}, %20, 1, 1, 1, 0;"
      : D16("+f") : "r"(a[0]), "r"(a[1]), "r"(a[2]), "r"(a[3]), "l"(b));
}
template<bool FIRST> __device__ __forceinline__ void wgmma_ss_n32_ta(float (&d)[16], uint64_t a, uint64_t b) {
  if (FIRST)
    asm volatile("wgmma.mma_async.sync.aligned.m64n32k16.f32.bf16.bf16 {%0,%1,%2,%3,%4,%5,%6,%7,%8,%9,%10,%11,%12,%13,%14,%15}, %16, %17, 0, 1, 1, 1, 0;"
      : D16("=f") : "l"(a), "l"(b));
  else
    asm volatile("wgmma.mma_async.sync.aligned.m64n32k16.f32.bf16.bf16 {%0,%1,%2,%3,%4,%5,%6,%7,%8,%9,%10,%11,%12,%13,%14,%15}, %16, %17, 1, 1, 1, 1, 0;"
      : D16("+f") : "l"(a), "l"(b));
}
__device__ __forceinline__ void wgmma_ss_n128_tb(float (&d)[64], uint64_t a, uint64_t b) {
  asm volatile("wgmma.mma_async.sync.aligned.m64n128k16.f32.bf16.bf16 "
    "{%0,%1,%2,%3,%4,%5,%6,%7,%8,%9,%10,%11,%12,%13,%14,%15,%16,%17,%18,%19,%20,%21,%22,%23,%24,%25,%26,%27,%28,%29,%30,%31,"
    "%32,%33,%34,%35,%36,%37,%38,%39,%40,%41,%42,%43,%44,%45,%46,%47,%48,%49,%50,%51,%52,%53,%54,%55,%56,%57,%58,%59,%60,%61,%62,%63}, "
    "%64, %65, 1, 1, 1, 0, 1;"
    : "+f"(d[0]), "+f"(d[1]), "+f"(d[2]), "+f"(d[3]), "+f"(d[4]), "+f"(d[5]), "+f"(d[6]), "+f"(d[7]),
      "+f"(d[8]), "+f"(d[9]), "+f"(d[10]), "+f"(d[11]), "+f"(d[12]), "+f"(d[13]), "+f"(d[14]), "+f"(d[15]),
      "+f"(d[16]), "+f"(d[17]), "+f"(d[18]), "+f"(d[19]), "+f"(d[20]), "+f"(d[21]), "+f"(d[22]), "+f"(d[23]),
      "+f"(d[24]), "+f"(d[25]), "+f"(d[26]), "+f"(d[27]), "+f"(d[28]), "+f"(d[29]), "+f"(d[30]), "+f"(d[31]),
      "+f"(d[32]), "+f"(d[33]), "+f"(d[34]), "+f"(d[35]), "+f"(d[36]), "+f"(d[37]), "+f"(d[38]), "+f"(d[39]),
      "+f"(d[40]), "+f"(d[41]), "+f"(d[42]), "+f"(d[43]), "+f"(d[44]), "+f"(d[45]), "+f"(d[46]), "+f"(d[47]),
      "+f"(d[48]), "+f"(d[49]), "+f"(d[50]), "+f"(d[51]), "+f"(d[52]), "+f"(d[53]), "+f"(d[54]), "+f"(d[55]),
      "+f"(d[56]), "+f"(d[57]), "+f"(d[58]), "+f"(d[59]), "+f"(d[60]), "+f"(d[61]), "+f"(d[62]), "+f"(d[63])
    : "l"(a), "l"(b));
}

__device__ __forceinline__ void tma3d_mc_e(uint32_t dst, const CUtensorMap* tm, int c1, int c2, uint32_t bar) {
  asm volatile("{ .reg .pred p; .reg .b64 h; " ONCE_H "elect.sync _|p, 0xffffffff;\n"
               "@p cp.async.bulk.tensor.3d.shared::cluster.global.mbarrier::complete_tx::bytes.multicast::cluster.L2::cache_hint [%0], [%1, {0, %3, %4}], [%2], %5, h; }"
               :: "r"(dst), "l"(tm), "r"(bar), "r"(c1), "r"(c2), "h"((uint16_t)3) : "memory");
}
__device__ __forceinline__ void prefetch3d_e(const CUtensorMap* tm, int c1, int c2) {
  asm volatile("{ .reg .pred p; elect.sync _|p, 0xffffffff;\n"
               "@p cp.async.bulk.prefetch.tensor.3d.L2.global [%0, {0, %1, %2}]; }" :: "l"(tm), "r"(c1), "r"(c2) : "memory");
}

__device__ __forceinline__ void count_e(uint32_t* p) {
  asm volatile("fence.acq_rel.gpu;" ::: "memory");
  __syncwarp();
  asm volatile("{ .reg .pred p; elect.sync _|p, 0xffffffff; @p red.relaxed.gpu.global.add.u32 [%0], 1; }" :: "l"(p) : "memory");
}
template<int NS = 0> __device__ __forceinline__ void await_count(const uint32_t* p, uint32_t n) {
  for (uint32_t i = 0; ld_acquire(p) < n && i < (1u << 22); i++) { if (NS) __nanosleep(NS); }
  asm volatile("fence.proxy.async.global;" ::: "memory");
}
__device__ __forceinline__ void await_flags(const uint32_t* p) {
  for (uint32_t i = 0; i < (1u << 22); i++) {
    uint4 v;
    asm volatile("ld.acquire.gpu.global.v4.u32 {%0,%1,%2,%3}, [%4];" : "=r"(v.x), "=r"(v.y), "=r"(v.z), "=r"(v.w) : "l"(p) : "memory");
    if (__all_sync(~0u, (v.x & v.y & v.z & v.w) == 0x01010101u)) break;
  }
  asm volatile("fence.proxy.async.global;" ::: "memory");
}
__device__ __forceinline__ void mbar_lim(uint32_t bar, uint32_t ph) { for (uint32_t i = 0; !mbar_try(bar, ph) && i < (1u << 20); i++) {} }

struct cf { float x, y; };
__host__ __device__ constexpr float cos64(int k) {
  return k == 0 ? 1.0f : k == 1 ? 0.99518472667219689f : k == 2 ? 0.98078528040323045f : k == 3 ? 0.95694033573220887f :
         k == 4 ? 0.92387953251128676f : k == 5 ? 0.88192126434835503f : k == 6 ? 0.83146961230254524f : k == 7 ? 0.77301045336273696f :
         k == 8 ? 0.70710678118654752f : k == 9 ? 0.63439328416364550f : k == 10 ? 0.55557023301960222f : k == 11 ? 0.47139673682599765f :
         k == 12 ? 0.38268343236508977f : k == 13 ? 0.29028467725446236f : k == 14 ? 0.19509032201612827f : k == 15 ? 0.09801714032956060f : 0.0f;
}
__host__ __device__ constexpr float c64(int k) { return k <= 16 ? cos64(k) : -cos64(32 - k); }
__host__ __device__ constexpr float s64(int k) { return k <= 16 ? cos64(16 - k) : cos64(k - 16); }

template<int N, int ST, bool INV> struct Fft {
  template<int K> static __device__ __forceinline__ void bf(const cf* e, const cf* o, cf* out) {
    if constexpr (K < N / 2) {
      constexpr int idx = K * (64 / N);
      const cf a = e[K], b = o[K];
      if constexpr (idx == 0) {
        out[K] = {a.x + b.x, a.y + b.y}; out[K + N / 2] = {a.x - b.x, a.y - b.y};
      } else if constexpr (idx == 16) {
        if constexpr (INV) { out[K] = {a.x - b.y, a.y + b.x}; out[K + N / 2] = {a.x + b.y, a.y - b.x}; }
        else               { out[K] = {a.x + b.y, a.y - b.x}; out[K + N / 2] = {a.x - b.y, a.y + b.x}; }
      } else {
        constexpr float c = c64(idx), s = INV ? s64(idx) : -s64(idx);
        cf p; p.x = fmaf(-s, b.y, fmaf(c, b.x, a.x)); p.y = fmaf(s, b.x, fmaf(c, b.y, a.y));
        out[K] = p; out[K + N / 2] = {fmaf(2.0f, a.x, -p.x), fmaf(2.0f, a.y, -p.y)};
      }
      bf<K + 1>(e, o, out);
    }
  }
  static __device__ __forceinline__ void run(const cf* in, cf* out) {
    cf e[N / 2], o[N / 2];
    Fft<N / 2, 2 * ST, INV>::run(in, e);
    Fft<N / 2, 2 * ST, INV>::run(in + ST, o);
    bf<0>(e, o, out);
  }
};
template<int ST, bool INV> struct Fft<1, ST, INV> {
  static __device__ __forceinline__ void run(const cf* in, cf* out) { out[0] = in[0]; }
};
template<bool INV> __device__ __forceinline__ void fft32(cf (&v)[32]) {
  cf o[32]; Fft<32, 1, INV>::run(v, o);
#pragma unroll
  for (int i = 0; i < 32; i++) v[i] = o[i];
}
__device__ __forceinline__ cf cmul(cf a, float c, float s) { return {fmaf(-a.y, s, a.x * c), fmaf(a.x, s, a.y * c)}; }
__device__ __forceinline__ float bf2f(__nv_bfloat16 v) { return __bfloat162float(v); }

__device__ __forceinline__ int tw_at(int i) { return (i & ~63) | (i & 31) << 1 | (i >> 5 & 1); }
template<bool INV, bool T128 = true> __device__ __forceinline__ void twiddles(cf (&v)[32], const float4* __restrict__ tw) {
#pragma unroll
  for (int j = 0; j < 32; j += 2) {
    float4 w;
    if (T128) w = tw[j * 16];
    else { const uint2 a = lds64(smem_u32(tw + j * 16)), b = lds64(smem_u32(tw + j * 16) + 8); w = make_float4(__uint_as_float(a.x), __uint_as_float(a.y), __uint_as_float(b.x), __uint_as_float(b.y)); }
    if (j) v[j] = cmul(v[j], w.x, INV ? -w.y : w.y);
    v[j + 1] = cmul(v[j + 1], w.z, INV ? -w.w : w.w);
  }
}
template<bool INV, class F> __device__ __forceinline__ void warp_fft1024(cf (&v)[32], float2* __restrict__ buf, const float2* __restrict__ tw, int t, int u, F mid) {
#pragma unroll 1
  for (uint32_t h = 0; h < 2; h++) {
    fft32<INV>(v);
    if (FUNR ? h : opaque(h)) continue;
    twiddles<INV>(v, (const float4*)tw + u);
    if (INV) {
      float* f = (float*)buf;
#pragma unroll
      for (int j = 0; j < 32; j++) f[j * 36 + t] = v[j].x;
      __syncwarp();
#pragma unroll
      for (int j = 0; j < 32; j += 4) { const float4 r = *(const float4*)(f + u * 36 + j); v[j].x = r.x; v[j + 1].x = r.y; v[j + 2].x = r.z; v[j + 3].x = r.w; }
      __syncwarp();
#pragma unroll
      for (int j = 0; j < 32; j++) f[j * 36 + t] = v[j].y;
      __syncwarp();
#pragma unroll
      for (int j = 0; j < 32; j += 4) { const float4 r = *(const float4*)(f + u * 36 + j); v[j].y = r.x; v[j + 1].y = r.y; v[j + 2].y = r.z; v[j + 3].y = r.w; }
    } else {
#pragma unroll
      for (int j = 0; j < 32; j++) buf[j * 33 + t] = make_float2(v[j].x, v[j].y);
      __syncwarp();
#pragma unroll
      for (int j = 0; j < 32; j++) { const float2 r = buf[u * 33 + j]; v[j] = {r.x, r.y}; }
    }
    __syncwarp();
    mid();
  }
}
constexpr int ROW_BUF = 32 * 33, INV_BUF = 32 * 18;

__device__ __forceinline__ int z_row(int p) { return (p & ~31) | (p & 7) << 2 | (p & 31) >> 3; }
__device__ __forceinline__ int inv_lane(int t) { return (t & ~14) | (t & 12) >> 1 | (t & 2) << 2; }
__device__ __forceinline__ float2 twiddle(int i) { float s, c; sincospif(-(float)((i >> 5) * (i & 31)) * (1.0f / 512.0f), &s, &c); return make_float2(c, s); }
template<class F, class G> __device__ __forceinline__ void fft_rows_fwd(float2* sm2, const __nv_bfloat16* gw, int cta, int tid, uint32_t full_bar, uint32_t release_bar, F ev, G extra) {
  const int t = tid & 31, w = tid >> 5, n = z_row(cta * 8 + w);
#pragma unroll 1
  for (int i = tid; i < 1024; i += 256) sm2[tw_at(i)] = twiddle(i);
  ev(5);
  mbar_spin(full_bar, 0);
  if (tid == 0) TL2(6);
  __syncwarp();
  const __nv_bfloat16* xa = (const __nv_bfloat16*)(sm2 + 1024 + w * ROW_BUF) + t;
  cf v[32];
  float ga = 0.f, gb = 0.f;
#pragma unroll
  for (int j = 0; j < 32; j++) {
    v[j] = {bf2f(xa[32 * j]), bf2f(xa[D_ + 32 * j])};
    const float g = bf2f(gw[32 * j + t]); ga = fmaf(v[j].x, g, ga); gb = fmaf(v[j].y, g, gb);
  }
#pragma unroll
  for (int o = 16; o; o >>= 1) { ga += __shfl_xor_sync(~0u, ga, o); gb += __shfl_xor_sync(~0u, gb, o); }
  if (t < 2) g_gate[n + 1024 * t] = __fdividef(1.0f, 1.0f + __expf(-(t ? gb : ga)));
  ev(6);
  bar_sync(13, 256);
  warp_fft1024<false>(v, sm2 + 1024 + w * ROW_BUF, sm2, t, t, [&]() { FENCE_ASYNC_SMEM(); mbar_arrive_warp(release_bar); });
  float ws, wc; sincospif(-(float)n * (1.0f / 1024.0f), &ws, &wc);
  ev(12);
  uint32_t tz = clock_lo();
  float4* z = (float4*)g_z + ((size_t)(t >> 1) * 1024 + cta * 8 + w) * 2 + (t & 1);
#pragma unroll
  for (int j = 0; j < 17; j++) {
    cf q = v[(32 - j) & 31];
    if (j < 16) {
      const cf r = {__shfl_sync(~0u, v[31 - j].x, 32 - t), __shfl_sync(~0u, v[31 - j].y, 32 - t)};
      if (t != 0) q = r;
    }
    const cf a = {v[j].x + q.x, v[j].y - q.y}, b = {v[j].y + q.y, q.x - v[j].x};
    const cf d = cmul({a.x - b.x, a.y - b.y}, wc, ws);
    if (j == POOL_AT) extra();
    if (PACE_Z && j && j < 16) delay_until(tz += PACE_Z);
    if ((j < 16 || t == 0) && ((EXP_ST & 4) || d.x == 123.f)) z[j * 32768] = make_float4(a.x + b.x, a.y + b.y, d.x, d.y);
  }
}
constexpr int CP = X128 == 0 ? 33 : X128 == 2 ? 34 : 36, COL_FS = 32 * 36 + 8, COL_W = (8192 + 16 * COL_FS * 4 + 127) & ~127, COL_SMEM = COL_W + 131072 + 128;

__device__ __forceinline__ void fft_cols(float2* sm2, int cta, const CUtensorMap* twr, const CUtensorMap* twi, const CUtensorMap* tzs) {
  const int grp = __shfl_sync(~0u, (int)(threadIdx.x >> 7), 0), tid = threadIdx.x & 127, tp = tid >> 2, w = __shfl_sync(~0u, tid >> 5, 0);
  float* buf = (float*)(sm2 + 1024) + (grp * 4 + (tid & 3)) * COL_FS;
  const uint32_t wsm = smem_u32(sm2) + COL_W, wbar = wsm + 131072 + (W_FINE ? w * 32 : 0);
  const int res = w * 2 + (tid & 1), el = res + grp * 2 + ((tid >> 1) & 1);
  uint32_t wa = (el >> 3) * 65536 + res * 4096 + (tp & 7) * 16 + (el & 7) * 2;
  auto load_w = [&](int q) {
    const uint32_t bar = wbar + (q & 1) * 8;
    mbar_expect(bar, W_FINE ? 16384 : 65536);
#pragma unroll 1
    for (int i = W_FINE ? 4 * w : 0; i < (W_FINE ? 4 * w + 4 : 16); i++) tma2d(wsm + (q & 1) * 65536 + (i & 1) * 32768 + (i >> 1) * 4096, i & 1 ? twi : twr, (i >> 1) * 512 + q * 8, 0, bar);
  };
  const bool lead = (tid & (W_FINE ? 31 : 127)) == 0, first = grp < 2 && lead;
  if (first) { mbar_init(wbar + grp * 8, 1); sts32(wbar + 16 + grp * 4, grp ? 0 : w); asm volatile("fence.mbarrier_init.release.cluster;" ::: "memory"); }
#pragma unroll 1
  for (int i = threadIdx.x; i < 1024; i += 512) {
    const float2 t = twiddle(z_row(i));
    sm2[tw_at(i)] = t;
    if (cta == 0) g_tw[tw_at(inv_lane(z_row(i)))] = t;
  }
  for (uint32_t n = 0; ld_acquire(g_ctl + C_P1) < 128; ) { watchdog(n, 1u << 22); __nanosleep(200); }
  if (COL_DLY) delay_cycles(COL_DLY);
  if (first) load_w(cta * 16 + grp);
  __syncthreads();
  delay_cycles(1 + grp * DLY_GRP);
  mbar_wait(wbar, 0);
  const int end = cta * 64 + 64 + (cta == 3);
  for (int item = cta * 64 + grp; item < end; item += 4, wa ^= 65536) {
    float2* zp = g_z + (size_t)item * 4096;
    auto next_w = [&]() {
      const int q = (item >> 2) + (W_FINE && grp + w > 3);
      uint32_t n; asm volatile("atom.shared.inc.u32 %0, [%1], 3;" : "=r"(n) : "r"(wbar + 16 + (q & 1) * 4) : "memory");
      if (EXP_W && n == 3 && q < (cta * 16 + 15)) load_w(q + 2);
    };
    cf v[32];
#pragma unroll
    for (int j = 0; j < 32; j++) { const float2 a = ld_once(zp + tid + j * 128); v[j] = {a.x, a.y}; }
#pragma unroll 1
    for (int ph = 0; ; ph++) {
      fft32<false>(v);
      twiddles<false, T128_>(v, (const float4*)sm2 + tp);
      if (Z_ST) asm volatile("cp.async.bulk.wait_group.read 0;" ::: "memory");
      bar_sync(1 + grp, 128);
      if (lead) {
        if (ph) {
          if (!W_AT) next_w();
        } else if (Z_PF && item + 4 < end) asm volatile("cp.async.bulk.prefetch.L2.global [%0], %1;" :: "l"(zp + 4 * 4096 + w * 1024), "n"(W_FINE ? 8192 : 32768) : "memory");
      }
      __syncwarp();
#pragma unroll
      for (int j = 0; j < 32; j++) buf[((j & 3) * 8 + (j >> 2)) * CP + tp] = v[j].x;
      bar_sync(1 + grp, 128);
      if (X128 == 0) {
#pragma unroll
        for (int j = 0; j < 32; j++) v[j].x = buf[tp * CP + (j & 3) * 8 + (j >> 2)];
      } else if (X128 == 2) {
#pragma unroll
        for (int j = 0; j < 16; j++) { const float2 r = *(const float2*)(buf + tp * CP + 2 * j); cf* d = v + (j & 3) * 8 + (j >> 2); d[0].x = r.x; d[4].x = r.y; }
      } else
#pragma unroll
      for (int j = 0; j < 8; j++) {
        const float4 r = *(const float4*)(buf + tp * 36 + 4 * j);
        cf* d = v + (j & 1) * 16 + (j >> 1);
        d[0].x = r.x; d[4].x = r.y; d[8].x = r.z; d[12].x = r.w;
      }
      bar_sync(1 + grp, 128);
#pragma unroll
      for (int j = 0; j < 32; j++) buf[((j & 3) * 8 + (j >> 2)) * CP + tp] = v[j].y;
      bar_sync(1 + grp, 128);
      if (X128 == 0) {
#pragma unroll
        for (int j = 0; j < 32; j++) v[j].y = buf[tp * CP + (j & 3) * 8 + (j >> 2)];
      } else if (X128 == 2) {
#pragma unroll
        for (int j = 0; j < 16; j++) { const float2 r = *(const float2*)(buf + tp * CP + 2 * j); cf* d = v + (j & 3) * 8 + (j >> 2); d[0].y = r.x; d[4].y = r.y; }
      } else
#pragma unroll
      for (int j = 0; j < 8; j++) {
        const float4 r = *(const float4*)(buf + tp * 36 + 4 * j);
        cf* d = v + (j & 1) * 16 + (j >> 1);
        d[0].y = r.x; d[4].y = r.y; d[8].y = r.z; d[12].y = r.w;
      }
      fft32<false>(v);
      if (ph) break;
      const int q = min((item >> 2) + (!W_FINE || grp + w >= 3), 64);
      if (EXP_W) mbar_wait(wbar + (q & 1) * 8, (q >> 1) & 1);
#pragma unroll
      for (int j = 0; j < 32; j++) {
        uint32_t re, im;
        asm volatile("ld.shared.u16 %0, [%1];" : "=r"(re) : "r"(wsm + wa + j * 128) : "memory");
        asm volatile("ld.shared.u16 %0, [%1];" : "=r"(im) : "r"(wsm + wa + 32768 + j * 128) : "memory");
        const cf r = cmul(v[j], __uint_as_float(re << 16), __uint_as_float(im << 16));
        v[j] = {r.y, r.x};
      }
    }
    if (Z_ST) {
      float2* st = sm2 + 1024 + grp * (COL_FS * 2) + w * 512;
      bar_sync(1 + grp, 128);
#pragma unroll
      for (int h = 0; h < 2; h++) {
        if (h && Z_ST == 2) {
#pragma unroll
          for (int j = 16; j < 32; j++) zp[tid + j * 128] = make_float2(v[j].y, v[j].x);
          break;
        }
        if (h) { asm volatile("cp.async.bulk.wait_group.read 0;" ::: "memory"); __syncwarp(); }
#pragma unroll
        for (int j = 0; j < 16; j++) st[j * 32 + (tid & 31)] = make_float2(v[h * 16 + j].y, v[h * 16 + j].x);
        FENCE_ASYNC_SMEM();
        __syncwarp();
        tma2d_st_e(tzs, w * 128, item * 32 + h * 16, smem_u32(st));
        asm volatile("cp.async.bulk.commit_group;" ::: "memory");
      }
    } else {
#pragma unroll
      for (int j = 0; j < 32; j++) zp[tid + j * 128] = make_float2(v[j].y, v[j].x);
    }
    if (W_AT) { if (lead) next_w(); __syncwarp(); }
  }
  if (Z_ST) asm volatile("cp.async.bulk.wait_group 0; fence.proxy.async.global;" ::: "memory");
  const float4 t = ((const float4*)sm2)[threadIdx.x];
  __syncthreads();
  if (TW_L) ((float4*)sm2)[inv_lane(z_row(threadIdx.x))] = t;
  if (threadIdx.x < 32) {
    count_e(g_ctl + C_COLS);
    await_count(g_ctl + C_COLS, 4);
    g_ctl[C_P1] = 0;
  }
  __syncthreads();
  if (!TW_L) {
    ((float4*)sm2)[threadIdx.x] = __ldcg((const float4*)g_tw + threadIdx.x);
    __syncthreads();
  }
}

template<class F> __device__ __forceinline__ void fft_rows_inv(uint32_t zs, float2* buf, const float2* tw, int p, int lane, __nv_bfloat16* out, F read) {
  const int n = z_row(p), t = (lane & 17) | (lane & 6) << 1 | (lane & 8) >> 2, src = inv_lane(-t & 31);
  const uint32_t z = zs + (t >> 1) * 128 + ((((p & 3) * 2 + (t & 1)) ^ (t >> 1 & 7)) << 4);
  FT(0, 0.f);
  float4 e[17];
  uint32_t all = 0;
  e[16] = __ldcg((const float4*)g_z + ((size_t)256 * 1024 + p) * 2);
  const float g0 = __ldcg(g_gate + n), g1 = __ldcg(g_gate + n + 1024);
#pragma unroll
  for (int j = 0; j < 16; j++) { const uint4 u = lds128(z + j * 2048); e[j] = make_float4(__uint_as_float(u.x), __uint_as_float(u.y), __uint_as_float(u.z), __uint_as_float(u.w)); all |= u.x; }
  sched_fence(all);
  read();
  float ws, wc; sincospif((float)n * (1.0f / 1024.0f), &ws, &wc);
  cf v[32], q[17];
#pragma unroll
  for (int j = 0; j < 17; j++) {
    const cf d = cmul({e[j].z, e[j].w}, wc, ws);
    cf a = {e[j].x + d.x, e[j].y + d.y}, b = {e[j].x - d.x, e[j].y - d.y};
    if (j == 16 || (j == 0 && t == 0)) { a.y = 0.f; b.y = 0.f; }
    if (j < 16) v[j] = {a.x - b.y, a.y + b.x};
    q[j] = {a.x + b.y, b.x - a.y};
  }
#pragma unroll
  for (int j = 16; j < 32; j++) {
    v[j] = {__shfl_sync(~0u, q[31 - j].x, src), __shfl_sync(~0u, q[31 - j].y, src)};
    if (t == 0) v[j] = q[32 - j];
  }
  FT(1, v[0].x + v[16].x + v[31].x);
  if (B_ST) { asm volatile("cp.async.bulk.wait_group.read 0;" ::: "memory"); __syncwarp(); }
  warp_fft1024<true>(v, buf, tw, t, lane, []() {});
  FT(3, v[31].y + v[0].x);
  const float sc = 0.5f / (2048.0f * 1024.0f), s0 = (1.f - g0) * sc, s1 = (1.f - g1) * sc;
  uint2* o = (B_ST ? (uint2*)buf : (uint2*)(out + (size_t)n * D_)) + (lane ^ (n & 1) << 3);
#pragma unroll
  for (int j = 0; j < 32; j += 4) {
    o[8 * j] = make_uint2(pack_bf16(v[j].x * s0, v[j + 1].x * s0), pack_bf16(v[j + 2].x * s0, v[j + 3].x * s0));
    o[(B_ST ? 256 : 256 * D_) + 8 * j] = make_uint2(pack_bf16(v[j].y * s1, v[j + 1].y * s1), pack_bf16(v[j + 2].y * s1, v[j + 3].y * s1));
  }
  if (B_ST) {
    FENCE_ASYNC_SMEM();
    __syncwarp();
    asm volatile("{ .reg .pred p; setp.lt.u32 p, %2, 2; @p cp.async.bulk.global.shared::cta.bulk_group [%0], [%1], 2048; cp.async.bulk.commit_group; }"
                 :: "l"(out + (size_t)(n + 1024 * (lane & 1)) * D_), "r"(smem_u32(buf) + (lane & 1) * 2048), "r"(lane) : "memory");
  }
  FT(4, 0.f);
}

constexpr int NP = NP_, NHV = REG_F == 216 ? 5 : 7, NV = 16 - NHV;
constexpr int XEND = NSEG;
constexpr uint32_t SM_WO = 0, SM_V = 65536, SM_LAND = SM_V + 8192, SM_MEM = SM_LAND + 24576, SM_SP = SM_MEM, SM_SPM = SM_MEM + 5120, SM_OM = SM_MEM + 6144,
                   SM_OX = SM_MEM + 8192, SM_RED = SM_OX + 2048, SM_XCH = SM_RED + 1024, SM_SUM = SM_XCH + 4096, SM_VM = SM_SUM + 128, SM_TAB = SM_VM + 2048, SM_TRACE = SM_TAB + 2048,
                   ST_WG = (32 - NP + NV) * 2048,
                   SM_XT = 2 * ST_WG, SM_POOL = SM_XT + 32768, SM_HV = SM_POOL + 2 * NP * 2048,
                   SM_BAR = SM_HV + 2 * NHV * 2048, SM_SEL = SM_BAR + 320, CHAIN_SMEM = SM_SEL + 544 + 1024;
constexpr uint32_t SM_FFT = 49152, SM_GW = SM_XT - 2048;
static_assert(NP % 4 == 0 && NV == 11 && SM_TRACE + 4096 <= SM_XT, "shared memory layout");
static_assert(CHAIN_SMEM <= 232448 && COL_SMEM <= SM_BAR && SM_FFT + (1024 + 8 * ROW_BUF) * 8 <= SM_GW && NP == 12, "shared memory budget");
enum { B_WFULL = 0, B_WREAD = 2, B_WOFULL, B_XFULL, B_XEMPTY, B_E1TRIG, B_E2TRIG, B_PVDONE, B_PUB, B_SC, B_PFULL, B_SPFREE,
       B_LAND, B_LFREE, B_DONE, B_SEL, B_PROBE, B_FREE, B_P1, B_ROWS, B_VFULL, B_VST, B_TW, B_BT, B_WREAD0, B_Z, B_GFULL = B_Z + 4, B_GEMPTY = B_GFULL + 5, B_END = B_GEMPTY + 5 };
static_assert(B_END * 8 <= 320, "barriers");
__host__ __device__ constexpr uint32_t bar_codes(int g) {
  uint32_t r = 0;
  for (int i = 16 * g; i < 16 * g + 16; i++)
    r |= (i == B_LAND ? 3u : i == B_WREAD || i == B_XEMPTY || i == B_E1TRIG || i == B_E2TRIG || i == B_LFREE || i == B_FREE || i == B_VST || i == B_P1 || i == B_ROWS ? 2u :
          i >= B_GEMPTY || i == B_WREAD0 || i == B_PROBE || i == B_DONE || i == B_PVDONE || i == B_PUB || i == B_SC || i == B_SPFREE ? 1u : 0u) << 2 * (i & 15);
  return r;
}
constexpr uint32_t SM_BT = 65536, SM_TW = SM_XT - 8192, COL_Z = 80 * 1024;
static_assert(SM_XT + 3 * 32768 <= SM_BAR && SM_BT + 32768 <= SM_MEM && SM_TRACE <= SM_TW && SM_MEM + 4 * INV_BUF * 8 <= SM_TRACE &&
              8192 + 16 * INV_BUF * 8 <= COL_Z && COL_Z + 131072 <= SM_BAR, "shared memory layout");
__device__ __forceinline__ uint32_t next_stage(uint32_t o) { return o == SM_XT + 65536 ? 0 : o == 32768 ? SM_XT : o + 32768; }

struct ChainCtx { char* mail; uint32_t sb, sel; int r, h, a, b, j, m, w, lane; };
#define BAR(i) (c.sb + SM_BAR + 8 * (i))

__device__ __forceinline__ uint32_t tile_off(int line, int lane) {
  return line * 128 + (((lane & 3) ^ line) << 5) + (lane >> 2) * 4;
}
__device__ __forceinline__ uint32_t read_off(int lane) {
  const int n = lane >> 2, jj = lane & 3, l = 2 * (jj >> 1) + (n & 1);
  return l * 128 + (((n >> 1) ^ l) << 5) + (jj & 1) * 16;
}
__device__ __forceinline__ uint32_t frag_off(int w, int lane) {
  const int mi = lane >> 3, r = lane & 7;
  return ((mi >> 1) * 8 + r) * 128 + (((2 * w + (mi & 1)) ^ r) << 4);
}
__device__ __forceinline__ uint32_t land_off(int w, int lane) { return w * 512 + ((lane ^ (((lane >> 4) | ((w & 1) << 1)) << 1)) << 4); }
__device__ __forceinline__ uint32_t tagged(uint32_t v, uint32_t tag) { return (v | 1u) ^ tag; }
__device__ __forceinline__ void mma_a(float (&d)[4], const uint32_t (&a)[4], uint32_t b0, uint32_t b1) { mma16816(d, a[0], a[1], a[2], a[3], b0, b1); }
__device__ __forceinline__ void mma_q(float (&d)[4], const uint4& a, uint32_t b0, uint32_t b1) { mma16816(d, a.x, a.y, a.z, a.w, b0, b1); }
__device__ __forceinline__ uint4 add4(uint4 a, uint4 b) {
  return make_uint4(add_bf16x2(a.x, b.x), add_bf16x2(a.y, b.y), add_bf16x2(a.z, b.z), add_bf16x2(a.w, b.w));
}
__device__ __forceinline__ void mbar_arrive_both(uint32_t bar, int peer) {
  __syncwarp();
  asm volatile("{ .reg .pred p; .reg .u32 a; mapa.shared::cluster.u32 a, %0, %1; elect.sync _|p, 0xffffffff;\n"
               "@p mbarrier.arrive.shared::cta.b64 _, [%0]; @p mbarrier.arrive.shared::cluster.b64 _, [a]; }" :: "r"(bar), "r"(peer) : "memory");
}

__device__ __forceinline__ void arrive_remote_if(uint32_t a, bool on) {
  asm volatile("{ .reg .pred p; setp.ne.u32 p, %1, 0; @p mbarrier.arrive.shared::cluster.b64 _, [%0]; }" :: "r"(a), "r"((uint32_t)on) : "memory");
}
__device__ __forceinline__ void store_count(void* p, uint4 v, void* cnt) {
  asm volatile("{ .reg .pred p, q; .reg .b128 a, b; .reg .b64 l, h; mov.b64 l, {%1, %2}; mov.b64 h, {%3, %4}; mov.b128 a, {l, h};\n"
               "atom.relaxed.gpu.global.exch.b128 b, [%0], a; mov.b128 {l, h}, b; setp.eq.u64 q, l, 0x7fc17fc17fc17fc1; @q pmevent 1;\n"
               "elect.sync _|p, 0xffffffff; @p red.relaxed.gpu.global.add.u32 [%5], 1; }"
               :: "l"(p), "r"(v.x), "r"(v.y), "r"(v.z), "r"(v.w), "l"(cnt) : "memory");
}

template<int N> __device__ __forceinline__ void pad() {
#pragma unroll
  for (int i = 0; i < N; i++) asm volatile("pmevent 3;");
}
__device__ __forceinline__ int lane_id() {
  int l; asm volatile("{ .reg .u32 t; mov.u32 t, %%laneid; shfl.sync.idx.b32 %0, t, t, 31, 0xffffffff; }" : "=r"(l)); return l;
}
__device__ __forceinline__ uint32_t tid_now() { uint32_t t; asm volatile("mov.u32 %0, %%tid.x;" : "=r"(t)); return t; }
enum { NB_ATT = 1, NB_OM = 2, NB_VM = 3, NB_XCH = 4, NB_MEM = 8, NB_HELP = 12 };
__device__ __forceinline__ uint32_t dep(uint32_t a, uint32_t v, uint32_t z) { uint32_t r; asm("shf.l.wrap.b32 %0, %2, %1, %3;" : "=r"(r) : "r"(a), "r"(v), "r"(z)); return r; }
__device__ __forceinline__ uint32_t vary(uint32_t a, int s, uint32_t z) { return dep(a, 0, z + 32 * s); }
__device__ __forceinline__ char* mk_ptr(uint32_t lo, uint32_t hi) { uint64_t r; asm("mov.b64 %0, {%1, %2};" : "=l"(r) : "r"(lo), "r"(hi)); return (char*)r; }
__device__ __forceinline__ void lds_frag(uint32_t (&r)[4], uint32_t a) {
  asm volatile("ld.shared.v4.u32 {%0,%1,%2,%3}, [%4];" : "=r"(r[0]), "=r"(r[1]), "=r"(r[2]), "=r"(r[3]) : "r"(a) : "memory");
}
__device__ __forceinline__ uint32_t stale2(uint32_t a, uint32_t b, uint32_t t) { uint32_t r; asm("lop3.b32 %0, %1, %2, %3, 0xbd;" : "=r"(r) : "r"(a), "r"(b), "r"(t)); return r; }
__device__ __forceinline__ uint32_t stale1(uint32_t acc, uint32_t a, uint32_t t) { uint32_t r; asm("lop3.b32 %0, %1, %2, %3, 0xf9;" : "=r"(r) : "r"(acc), "r"(a), "r"(t)); return r; }
__device__ __forceinline__ bool all_clear(uint32_t x, uint32_t m) {
  uint32_t r;
  asm volatile("{ .reg .pred p; .reg .u32 t; and.b32 t, %1, %2; setp.eq.u32 p, t, 0; vote.sync.all.pred p, p, 0xffffffff; selp.u32 %0, 1, 0, p; }" : "=r"(r) : "r"(x), "r"(m));
  return r;
}
__device__ __forceinline__ bool arrive_if_all(bool ok, int id, int n) {
  uint32_t r;
  asm volatile("{ .reg .pred p, q; setp.ne.u32 p, %1, 0; vote.sync.all.pred q, p, 0xffffffff; @q bar.arrive %2, %3; selp.u32 %0, 1, 0, q; }"
               : "=r"(r) : "r"((uint32_t)ok), "r"(id), "r"(n) : "memory");
  return r;
}
__device__ __forceinline__ bool arrive_if_clear(uint32_t x, uint32_t m, int id, int n) {
  uint32_t r;
  asm volatile("{ .reg .pred p; .reg .u32 t; and.b32 t, %1, %2; setp.eq.u32 p, t, 0; vote.sync.all.pred p, p, 0xffffffff; @p bar.arrive %3, %4; selp.u32 %0, 1, 0, p; }"
               : "=r"(r) : "r"(x), "r"(m), "r"(id), "r"(n) : "memory");
  return r;
}
__device__ __forceinline__ void touch(const void* p, uint32_t z) {
  asm volatile("{ .reg .pred p; setp.eq.u32 p, %1, 0x7fff0000; @p prefetch.global.L2 [%0]; }" :: "l"(p), "r"(z) : "memory");
}

__device__ __forceinline__ uint64_t desc_x(uint32_t lo, int k) {
  uint64_t d; asm("mov.b64 %0, {%1, %2};" : "=l"(d) : "r"(lo + (k >> 2) * 64 + (k & 3) * 2), "r"(0x40000200)); return d;
}
template<int K0, int K1> __device__ __forceinline__ void issue_qk(float (&xa)[16], const uint32_t (&wt)[16][4], uint32_t lo) {
  WG_FENCE();
#pragma unroll
  for (int k = K0; k < K1; k++) {
    if (k >= EXP_NWG) continue;
    if (k == 0) wgmma_rs_n32<true>(xa, wt[0], desc_x(lo, 0));
    else wgmma_rs_n32<false>(xa, wt[k], desc_x(lo, k));
  }
  WG_COMMIT();
}
__host__ __device__ constexpr int v_order(int i) { return SSPOS == 0 ? i : SSPOS == 2 ? (i + NV) % 16 : NHV == 5 ? (i % 3 == 2 ? NV + i / 3 : i - i / 3) : (i == 15 ? NV - 1 : i % 2 ? NV + i / 2 : i / 2); }
__device__ __forceinline__ void issue_v(float (&xa)[16], const uint32_t (&wv)[16][4], uint32_t lo, uint32_t la) {
  WG_FENCE();
#pragma unroll
  for (int i = 0; i < EXP_NWG; i++) {
    const int k = v_order(i);
    const uint64_t b = desc_x(lo, k);
    if (k < NV) { if (i == 0) wgmma_rs_n32<true>(xa, wv[k], b); else wgmma_rs_n32<false>(xa, wv[k], b); }
    else        { if (i == 0) wgmma_ss_n32_ta<true>(xa, desc128(la + (k - NV) * 128), b); else wgmma_ss_n32_ta<false>(xa, desc128(la + (k - NV) * 128), b); }
  }
  WG_COMMIT();
}
template<bool ISV> __device__ __forceinline__ void park_own(uint32_t (&q)[4], float (&xa)[16], uint32_t dst, int slot, uint32_t z) {
  uint32_t p[8];
#pragma unroll
  for (int i = 0; i < 16; i++) asm volatile("" : "+f"(xa[i]) :: "memory");
#pragma unroll
  for (int i = 0; i < 2; i++) {
    const float* k = xa + 8 * i;
    if (ISV) { p[4 * i] = pack_bf16(k[0], k[1]); p[4 * i + 1] = pack_bf16(k[2], k[3]); p[4 * i + 2] = pack_bf16(k[4], k[5]); p[4 * i + 3] = pack_bf16(k[6], k[7]); }
    else     { p[4 * i] = pack_bf16(k[0], k[2]); p[4 * i + 1] = pack_bf16(k[1], k[3]); p[4 * i + 2] = pack_bf16(k[4], k[6]); p[4 * i + 3] = pack_bf16(k[5], k[7]); }
  }
  sts128(dep(dep(dst, p[4] ^ p[5] ^ p[6], z), p[7], z) + slot * 8192, make_uint4(p[0], p[1], p[2], p[3]));
#pragma unroll
  for (int i = 0; i < 4; i++) q[i] = p[4 + i];
}
__device__ __forceinline__ void park_peer(const uint32_t (&q)[4], uint32_t dst, int slot, const ChainCtx& c) {
  const uint32_t bar = BAR(B_LAND);
  if (EXP_PEER) st_async4(mapa(dst + slot * 8192, c.b ^ 1), q[0], q[1], q[2], q[3], mapa(bar, c.b ^ 1));
  else touch((void*)(uintptr_t)(q[0] ^ q[1] ^ q[2] ^ q[3]), c.sb);
  mbar_arrive_warp(bar);
}
__device__ __forceinline__ uint32_t put_tag(uint32_t v, uint32_t bit, uint32_t t) {
  uint32_t r; asm("lop3.b32 %0, %1, %2, %3, 0x74;" : "=r"(r) : "r"(v), "r"(bit), "r"(t)); return r;
}
__device__ __forceinline__ void mem_proj(const uint32_t (&wa)[16][4], const uint32_t (&wb)[16][4], uint32_t (&wv)[16][4], uint32_t (&af)[16][4],
                                         uint32_t& wo, const char*& pa, uint32_t tab, uint32_t t16, uint32_t pk, const ChainCtx& c, int s) {
  const uint32_t mp = t16 & ~0x600u, id = NB_MEM + (t16 >> 11);
  uint32_t r[8][4];
  float la[4][4] = {}, lg[NLAG][4] = {}, lv[4][4] = {};
  auto lead = [&](int k) { mma_a(la[k & 3], wa[k], r[k >> 1][2 * (k & 1)], r[k >> 1][2 * (k & 1) + 1]); };
  auto lag = [&](int k) { mma_a(lg[k % NLAG], wb[k], r[k >> 1][2 * (k & 1)], r[k >> 1][2 * (k & 1) + 1]); };
  auto sum = [](const float (&d)[4][4], int i) { return (d[0][i] + d[1][i]) + (d[2][i] + d[3][i]); };
  bar_sync(id, 160);
  TR(s, 0);
#pragma unroll
  for (int i = 0; i < 4; i++) ldsm4t(r[i], mp + (c.sb + SM_MEM + i * 512));
  uint4 tq;
  if (!TQ_AT) tq = lds128(tab);
  bar_sync(id + 2, 160);
  uint32_t first = 0;
#pragma unroll
  for (int k = 0; k < 8; k++) { lead(k); if (k == C1_AT - 4) first = dep(mp, __float_as_uint(la[k & 3][0]), c.sb); }
  uint32_t ta, tb;
  if (!TQ_AT) { ta = tq.x | ((pk >> 16) & 511); tb = tq.z ^ ((pk >> 16) & 511); }
  const uint32_t mp1 = C1_AT >= 4 ? (TQ_AT ? first : dep(first, ta ^ tb, c.sb)) : dep(mp, __float_as_uint(la[C1_AT & 3][0]) ^ (TQ_AT ? 0 : ta ^ tb), c.sb);
#pragma unroll
  for (int i = 4; i < 8; i++) ldsm4t(r[i], mp1 + (c.sb + SM_MEM + 2048 + i * 512));
  if (TQ_AT) { tq = lds128(tab); ta = tq.x | ((pk >> 16) & 511); tb = tq.z ^ ((pk >> 16) & 511); }
  char* dst = mk_ptr(ta, tq.y);
  char* dst2 = mk_ptr(tb, tq.w);
  const uint32_t hv = pk & 0xFFFF;
#pragma unroll
  for (int k = NV; k < NV + HV_E; k++) ldsm4t(wv[k], dep(hv, r[HV_R][0], c.sb) + (c.sb + SM_HV + (k - NV) * 2048));
#pragma unroll
  for (int k = 0; k < LAG_0; k++) lag(k);
#pragma unroll
  for (int k = 8; k < 16; k++) lead(k);
  const uint32_t s0 = __float_as_uint(sum(la, 0)), s3 = __float_as_uint(sum(la, 3));
  sts128((HV_E ? dep(t16, wv[NV][0] ^ wv[NV + HV_E / 2][1] ^ wv[NV + HV_E - (HV_E > 0)][2], c.sb) : TQ_AT ? dep(t16, ta ^ tb, c.sb) : t16) + (c.sb + SM_XCH),
         make_uint4(s0, __float_as_uint(sum(la, 1)), __float_as_uint(sum(la, 2)), s3));
  if (XB) bar_sync(NB_XCH, 256); else bar_sync(NB_XCH | ((t16 >> 9) & 3), 64);
#pragma unroll
  for (int k = LAG_0; k < LAG_0 + LAG_G; k++) r[k >> 1][2 * (k & 1)] = dep(r[k >> 1][2 * (k & 1)], LAG_S == 0 ? s3 : __float_as_uint(la[LAG_S - 1][0]), c.sb);
#pragma unroll
  for (int k = LAG_0; k < O_AT; k++) lag(k);
  const uint4 o = lds128((O_AT > LAG_0 ? dep(t16 ^ 2048, __float_as_uint(lg[(O_AT - 1) % NLAG][0]), c.sb) : t16 ^ 2048) + (c.sb + SM_XCH));
#pragma unroll
  for (int k = O_AT > LAG_0 ? O_AT : LAG_0; k < 16; k++) lag(k);
#pragma unroll
  for (int k = 0; k < V_E; k++) mma_a(lv[k & 3], wv[k], r[k >> 1][2 * (k & 1)], r[k >> 1][2 * (k & 1) + 1]);
  float t[4];
#pragma unroll
  for (int i = 0; i < 4; i++) {
    const float oi = __uint_as_float(i == 0 ? o.x : i == 1 ? o.y : i == 2 ? o.z : o.w);
    t[i] = NLAG == 4 ? (LAG_T ? ((lg[0][i] + lg[1][i]) + oi) + (lg[2 % NLAG][i] + lg[3 % NLAG][i]) : (((lg[0][i] + lg[1][i]) + lg[2 % NLAG][i]) + lg[3 % NLAG][i]) + oi) : LAG_T && NLAG == 2 ? (lg[0][i] + lg[1][i]) + oi : NLAG == 3 ? (lg[1][i] + lg[2 % NLAG][i]) + (lg[0][i] + oi) : (lg[0][i] + oi) + lg[1][i];
  }
  const uint32_t y0 = put_tag(pack_bf16(t[0], t[2]), pk >> 31, s >> 1), y1 = put_tag(pack_bf16(t[1], t[3]), pk >> 31, s >> 1);
  st_pub(dst, y0); st_pub(dst2, y1);
  mbar_arrive_warp(BAR(B_E1TRIG));
  TR(s, 1);
  sched_fence(c.sb);
  const uint4 tv = lds128(tab + 16);
#pragma unroll
  for (int k = NV + HV_E; k < 16; k++) ldsm4t(wv[k], (k < NV + HV_E + HV_D ? hv : dep(hv, k == NV + HV_E + HV_D ? wv[k - HV_D][0] ^ tv.x : wv[k - HV_D][0], c.sb)) + (c.sb + SM_HV + (k - NV) * 2048));
  wo = (hv & 2047) | ((t16 & 2048) << 3);
  const uint32_t l8 = (t16 >> 1) & 255;
  char* dv = mk_ptr(tv.x | l8, tv.y);
  pa = mk_ptr(tv.z | l8, tv.w);
#pragma unroll
  for (int f = 0; f < WO_0; f++) ldsm4t(af[f], dep(wo, f < WO_D ? wv[16 - WO_D + f][0] : af[f < WO_D ? 0 : f - WO_D][0], c.sb) + (c.sb + SM_WO + (f & 1) * 32768 + (f >> 1) * 2048));
#pragma unroll
  for (int k = V_E; k < 16; k++) mma_a(lv[k & 3], wv[k], r[k >> 1][2 * (k & 1)], r[k >> 1][2 * (k & 1) + 1]);
  const uint32_t z0 = put_tag(pack_bf16(sum(lv, 0), sum(lv, 1)), (~t16 >> 4) & 1, s >> 1), z1 = pack_bf16(sum(lv, 2), sum(lv, 3));
  st_pub2(dv, z0, z1);
  if (FIN_AT >= 3) mbar_arrive_warp(BAR(B_VST));
  TR(s, 2);
}
__device__ __forceinline__ uint32_t max_bf16x2(uint32_t a, uint32_t b) { uint32_t r; asm("max.bf16x2 %0, %1, %2;" : "=r"(r) : "r"(a), "r"(b)); return r; }
constexpr float SCL = 0.08838834764831845f * 1.4426950408889634f;
__device__ __forceinline__ uint32_t max5(const uint32_t (&sc)[5]) { return max_bf16x2(max_bf16x2(max_bf16x2(max_bf16x2(sc[0], sc[1]), sc[2]), sc[3]), sc[4]); }
__device__ __forceinline__ float row_off(uint32_t m, uint32_t& m1) {
  m1 = __shfl_xor_sync(~0u, m, 1);
  const uint32_t m2 = __shfl_xor_sync(~0u, m, 2), m3 = __shfl_xor_sync(~0u, m, 3);
  const uint32_t mm = max_bf16x2(max_bf16x2(max_bf16x2(m, m1), m2), m3);
  return -SCL * fmaxf(__uint_as_float(mm << 16), __uint_as_float(mm & 0xFFFF0000u));
}
__device__ __forceinline__ void unpack(float (&f)[10], const uint32_t (&sc)[5]) {
#pragma unroll
  for (int i = 0; i < 5; i++) {
    asm volatile("shl.b32 %0, %1, 16;" : "=f"(f[2 * i]) : "r"(sc[i]));
    asm volatile("and.b32 %0, %1, 0xffff0000;" : "=f"(f[2 * i + 1]) : "r"(sc[i]));
  }
}
__device__ __forceinline__ uint32_t exp_pair(const float (&f)[10], int i, float off) {
  return pack_bf16(ex2(fmaf(f[2 * i], SCL, off)), ex2(fmaf(f[2 * i + 1], SCL, off)));
}
template<bool SPLIT> __device__ __forceinline__ void scores_x(float (&a)[2][4], const uint4 (&kf)[4], const uint4& q, uint32_t z) {
#pragma unroll
  for (int t = 0; t < 2; t++) { a[t][0] = a[t][1] = a[t][2] = a[t][3] = 0.f; }
  mma_q(a[0], kf[0], q.x, q.y); mma_q(a[1], kf[2], q.x, q.y);
  if (SPLIT) sched_fence(z);
  mma_q(a[0], kf[1], q.z, q.w); mma_q(a[1], kf[3], q.z, q.w);
}
__device__ __forceinline__ uint32_t scores_m(const uint4& q, const uint4& k) {
  float a[4] = {}, b[4] = {};
  mma_q(a, q, k.x, k.z); mma_q(b, q, k.y, k.w);
  return pack_bf16(a[0] + b[2], a[1] + b[3]);
}
__device__ __forceinline__ void store_scores(const float (&a)[2][4], uint32_t dst) {
  sts64(dst, pack_bf16(a[0][0], a[0][2]), pack_bf16(a[1][0], a[1][2]));
  sts64(dst + 320, pack_bf16(a[0][1], a[0][3]), pack_bf16(a[1][1], a[1][3]));
}
__device__ __forceinline__ uint32_t sum4(uint32_t a, uint32_t b, uint32_t d, uint32_t e) { return add_bf16x2(add_bf16x2(a, b), add_bf16x2(d, e)); }
__device__ __forceinline__ void load_scores(uint32_t (&sc)[5], uint32_t ax, uint32_t am) {
  uint4 p[4];
#pragma unroll
  for (int i = 0; i < 4; i++) p[i] = lds128(ax + i * 1280);
  const uint2 m0 = lds64(am), m1 = lds64(am + 256);
  const uint4 t = add4(add4(add4(p[0], p[1]), p[2]), p[3]);
  sc[1] = t.x; sc[2] = t.y; sc[3] = t.z; sc[4] = t.w;
  sc[0] = sum4(m0.x, m0.y, m1.x, m1.y);
}
constexpr uint32_t ONES = 0x3F803F80u;
__device__ __forceinline__ float pv(float (&o)[2][4], const uint32_t (&p)[5], const uint4 (&vf)[4], const uint4& vm) {
  float a[4] = {}, b[4] = {};
#pragma unroll
  for (int t = 0; t < 2; t++) { o[t][0] = o[t][1] = o[t][2] = o[t][3] = 0.f; }
  mma_q(o[0], vf[0], p[1], p[2]); mma_q(o[1], vf[2], p[1], p[2]);
  mma_q(o[0], vf[1], p[3], p[4]); mma_q(o[1], vf[3], p[3], p[4]);
  mma16816(a, p[1], p[2], p[3], p[4], ONES, ONES);
  mma1688(o[0], vm.x, vm.y, p[0]); mma1688(o[1], vm.z, vm.w, p[0]);
  mma1688(b, p[0], ONES, ONES);
  return (a[0] + a[2]) + b[0];
}
constexpr uint32_t POLL_LIMIT = 1u << 21;
__device__ __forceinline__ uint32_t box(int slot, int cta) { return (slot * 2 + (cta >> 6)) * M_REG + (cta & 63) * 16384; }
__device__ __forceinline__ uint32_t near_page(const ChainCtx& c, int cta, uint32_t off) {
  return off + (((lds32(c.sb + SM_SEL + cta * 4) >> (off >> 21)) ^ __popc(off & 0xB2000)) & 1) * 4096;
}
__device__ __forceinline__ uint32_t e1_box(const ChainCtx& c, int slot, int cta) { return near_page(c, E1OFF ? cta ^ 2 : cta, box(slot, cta) + 8192) ^ (E1OFF ? 0 : 4096); }
__device__ __forceinline__ uint32_t tile_key() {
  uint32_t sm; asm volatile("mov.u32 %0, %%smid;" : "=r"(sm));
  return (sm < 64 ? sm / 2 % 8 : sm < 120 ? 1 + (sm / 2 - 32) % 7 : 0) << 24 | sm << 16;
}
__device__ __forceinline__ uint32_t ox_at(int s, int row, int g, int jj) { return s * 131072 + ((g >> 1) * 32 + row) * 64 + (g & 1) * 32 + 8 * jj; }
__device__ __forceinline__ int tile_of(const ChainCtx& c) { return SIDE ? __shfl_sync(~0u, lds32(c.sb + SM_SEL + 528), 0) : c.r; }

__global__ void __cluster_dims__(2, 1, 1) __launch_bounds__(512, 1)
chain_kernel(const __grid_constant__ CUtensorMap tq, const __grid_constant__ CUtensorMap tk, const __grid_constant__ CUtensorMap tv,
             const __grid_constant__ CUtensorMap tv16, const __grid_constant__ CUtensorMap to, const __grid_constant__ CUtensorMap tx,
             const __grid_constant__ CUtensorMap twr, const __grid_constant__ CUtensorMap twi,
             const __grid_constant__ CUtensorMap ta, const __grid_constant__ CUtensorMap tw,
             const __grid_constant__ CUtensorMap tb, const __grid_constant__ CUtensorMap tout, const __grid_constant__ CUtensorMap tz,
             const __grid_constant__ CUtensorMap tzs, const __grid_constant__ CUtensorMap ta32,
             const __nv_bfloat16* __restrict__ mem0, char* __restrict__ mail, const __nv_bfloat16* __restrict__ x,
             const __nv_bfloat16* __restrict__ gw) {
  extern __shared__ __align__(1024) unsigned char smraw[];
  if (threadIdx.x == 0) TL(0);
  ChainCtx c;
  c.sb = __shfl_sync(~0u, smem_u32(smraw), 0);
  c.mail = mail; c.sel = 0; c.r = blockIdx.x;
  if (ROLE) {
    const uint32_t u = blockIdx.x >> 1, n = u < 36 ? 8 : 7, k = u - (u < 36 ? 4 : 36), q = k * (u < 36 ? 32 : 37) >> 8;
    c.r = __shfl_sync(~0u, 2 * (u - 4 < 60 ? u + k - q * n - (q & 1) * (n - 1) : u) + (blockIdx.x & 1) + (threadIdx.x >> 9), 0);
  }
  c.h = c.r >> 2; c.a = (c.r >> 1) & 1; c.b = c.r & 1; c.j = c.r & 3;
  c.m = __shfl_sync(~0u, (int)(threadIdx.x >> 7), 0); c.w = __shfl_sync(~0u, (int)((threadIdx.x >> 5) & 3), 0);
  char* own = c.mail + (uint32_t)(c.w * M_REG + M_E3 + (c.r >> 5) * 8192 + (c.r & 31) * 128 + (threadIdx.x & 31) * 4);
  uint32_t i0 = 0, i1 = 0;
  if (EARLY) asm volatile("{ .reg .pred p; setp.ne.u32 p, %4, 0; @p atom.relaxed.gpu.global.exch.b32 %0, [%2], %3; @p atom.relaxed.gpu.global.exch.b32 %1, [%2 + 4096], %3; }"
               : "+r"(i0), "+r"(i1) : "l"(own), "r"(SENT), "r"((uint32_t)(c.m == 2 && c.r < 128)) : "memory");
#pragma unroll
  for (int g = 0; g < 3; g++) {
    const int i = c.m * 4 + c.w;
    if (g < 2 || i < B_END - 32)
      asm volatile("{ .reg .pred p; elect.sync _|p, 0xffffffff; @p mbarrier.init.shared::cta.b64 [%0], %1; }"
                   :: "r"(BAR(g * 16 + i)), "r"(0x19080401u >> (bar_codes(g) >> 2 * i & 3) * 8 & 255) : "memory");
  }
  asm volatile("fence.mbarrier_init.release.cluster;" ::: "memory");
  __syncthreads();
  asm volatile("barrier.cluster.arrive.relaxed.aligned;" ::: "memory");

  if (c.r >= 128) {
    fft_cols((float2*)smraw, c.r - 128, &twr, &twi, &tzs);
    if ((threadIdx.x & 127) == 0) TL(7);
    __syncwarp();
  } else if (c.m == 3) {
    asm volatile("setmaxnreg.dec.sync.aligned.u32 %0;" :: "n"(REG_H));
    c.lane = lane_id();
    if (c.sb & 1023) asm volatile("trap;");
    const int col = c.h * 128 + c.a * 64, eq = E3M ? c.w & 1 : c.w >> 1, eh = E3M == 1 ? (c.w >> 1) ^ 1 : E3M ? c.w >> 1 : c.w & 1;
    uint32_t tl = clock_lo();
    TR(-2, 3);
    if (c.w == 0) {
      if (START) delay_until(tl + START);
      if (HOLD == 2) mbar_wait(BAR(B_PROBE), 0);
      if (HOLD == 3) mbar_wait(BAR(B_SEL), 0);
      if (HOLD == 1) mbar_wait(BAR(B_PROBE), 0);
      TR(-2, 4);
      tl = clock_lo();
      mbar_expect_e(BAR(B_PFULL), 2 * NP * 2048);
      mbar_expect_e(BAR(B_WFULL), (48 - NP) * 2048);
      mbar_expect_e(BAR(B_WFULL + 1), (48 - NP) * 2048);
    }
    auto dst_x = [&](int e, int w) {
      const uint32_t g2 = 2 * c.a + (w >> 1), u = w & 1;
      return M_KVQ + c.h * 24576 + (e == 0 ? 8192 + (2 * u + c.b) * 2048 + g2 * 512 : e == 1 ? g2 * 2048 + u * 1024 + c.b * 128 : 16384 + c.b * 4096 + g2 * 512 + u * 256);
    };
    if (c.w == 0) {
      tl += PACE0;
#pragma unroll wunr
      for (int i = 0; i < 24; i++) {
        const int m = i < 4 || i >= 16, k = i < 4 ? i : m ? i - 12 : i - 4;
        const int row = c.b * 512 + m * 256;
        const uint32_t st = c.sb + m * ST_WG, bar = BAR(k < 3 ? B_PFULL : B_WFULL + m);
        if (PACE) delay_until(tl += PACE);
        if (i == 14) { mbar_wait(BAR(B_FREE), 0); if (c.lane == 0) TL2(2); __syncwarp(); }
        if (k < 11) TMA_W(k < 3 ? c.sb + SM_POOL + m * NP * 2048 + k * 8192 : k == 3 ? c.sb + SM_HV + (m * NHV + 1) * 2048 : st + (k - 4) * 8192,
                          k == 3 || k > 8 ? &tv : (k >> 2 & 1) == m ? &tk : &tq, col, row + (k < 8 ? k & 3 : (k - 9) & 3) * 64, bar);
        else {
#pragma unroll 1
          for (int j = 8; j < 12; j++) TMA_W(j < NV ? st + (32 - NP + j) * 2048 : c.sb + SM_HV + m * NHV * 2048, &tv16, col, row + j * 16, bar);
        }
      }
      TR(-2, 7);
    } else if (c.w == 2) {
      const unsigned short* mp = (const unsigned short*)mem0 + (2 * (c.lane & 3)) * D_ + 8 * c.r + (c.lane >> 2);
      uint32_t mv = (uint32_t)mp[0] | (uint32_t)mp[D_] << 16;
      if (mv == SENT) mv = 0x7FFF7FFFu;
      mbar_wait(BAR(B_PROBE), 0);
      char* dst = c.mail + (uint32_t)(M_E3 + (c.r >> 5) * 8192 + (c.r & 31) * 128 + c.lane * 4);
      st_pub(dst, mv); st_pub(dst + 4096, mv);
    } else if (c.w == 3) {
      mbar_wait(BAR(B_FREE), 0);
      mbar_wait(BAR(B_PFULL), 0);
      mbar_expect_e(BAR(B_PFULL), 65536);
      for (int i = 0; i < 2; i++) tma4d_e(c.sb + SM_XT + i * 16384, &tx, c.b * 8, 4 + 2 * (c.b ^ i), BAR(B_PFULL));
    }
    {
      mbar_wait(BAR(B_SEL), 0);
      const int i = tid_now() & 127, sl = i & 3, e = (i >> 2) & 3;
      uint32_t ox = dst_x(e, i >> 5) + sl * M_REG;
      uint32_t oh = e & 1 ? (sl ^ (e & 2)) * M_REG + M_E3 + (c.r >> 5) * 8192 + (c.w & 1) * 4096 + (c.r & 31) * 128
                          : near_page(c, c.r, e ? sl * M_REG + M_E3 + (c.b * 2 + eq) * 8192 : box(~sl & 1, c.r)) + (e ? eh * 2048 : c.w * 1024), of;
      {
        const int e = i & 7, w = (i >> 3) & 3, m = (i >> 5) & 1, sl = i >> 6;
        const int cta = e < 2 ? c.r & ~1 : e == 2 ? c.r | 1 : e == 3 ? c.h * 4 + 2 * m + 1 : c.j * 32 + m * 8 + 2 * w + (e & 2) * 8 + (e & 1);
        const uint32_t off = e < 2 ? c.b * 2048 + m * 1024 + (w >> 1) * 512 + e * 160 : e == 2 ? c.b * 2048 + m * 1024 + w * 256 : e == 3 ? w * 256 : c.h * 128;
        of = (e < 4 ? e1_box(c, sl, cta) : near_page(c, cta, box(sl, cta))) + off;
      }
      char *px = c.mail + ox, *ph = c.mail + oh, *pf = c.mail + of;
      uint32_t at = sl * 128 + (i >> 5) * 32 + e * 8, af = i * 8;
      pin(px); pin(ph); pin(pf); pin(at); pin(af);
      asm volatile("barrier.cluster.wait;" ::: "memory");
      TR(-2, 0);
      mbar_wait(BAR(B_WREAD), 0);
      TR(-2, 1);
      mbar_arrive_both(BAR(B_LFREE), c.b ^ 1);
      sts64(at + (c.sb + SM_TAB + 1536), (uint32_t)(uintptr_t)px, (uint32_t)((uintptr_t)px >> 32));
      sts64(at + (c.sb + SM_TAB + 1024), (uint32_t)(uintptr_t)ph, (uint32_t)((uintptr_t)ph >> 32));
      sts64(af + (c.sb + SM_TAB), (uint32_t)(uintptr_t)pf, (uint32_t)((uintptr_t)pf >> 32));
      TR(-2, 2);
      if (tid_now() == 384) TL2(25);
      __syncwarp();
      bar_sync(14, 160);
    }
    pad<PAD3>();
    for (int s = -1; s < NSEG; s++) {
      if (E30 ? s != 0 : s >= 0) {
        const uint32_t tab = c.sb + SM_TAB + 1024 + (max(s, 0) & 3) * 128 + c.w * 32;
        uint32_t t0;
        if (s > 0) {
          const uint32_t ln = tid_now() & 31;
          const uint4 ta = lds128(tab);
          const char* src = mk_ptr(ta.x | ln * 4, ta.y);
          char* dst = mk_ptr(ta.z | ln * 4, ta.w);
          const uint32_t tg = (s - 1) >> 1, chk = (ln & 3) ? 0u : 1u, red = ln * (RED_L == 3 ? 4 : 8);
          touch(src, dep(c.sb, chk, c.sb)); touch(dst, dep(c.sb, red, c.sb));
          mbar_wait(BAR(B_E2TRIG), (s - 1) & 1);
          TR(s, 0);
          if (ANCH2) delay_fine(lds32(c.sb + SM_SUM + 64) + DLY_E2); else delay_cycles(DLY_E2);
          uint32_t n = 0;
          while (true) {
            uint32_t v[8];
#pragma unroll
            for (int i = 0; i < 8; i++) v[i] = ld_poll1(src + i * 128);
            if (E2_F) sched_fence(c.sb);
            const uint32_t bad = RED_T ? (stale2(v[0], v[1], tg) | stale2(v[2], v[3], tg) | stale2(v[4], v[5], tg)) | stale2(v[6], v[7], tg)
                                       : stale1(stale1(stale2(v[0], v[1], tg), v[2], tg), v[3], tg) | stale1(stale1(stale2(v[4], v[5], tg), v[6], tg), v[7], tg);
            const bool ok = all_clear(bad, chk);
#pragma unroll
            for (int l = 0; l < RED_L; l++)
#pragma unroll
              for (int i = 0; i < (4 >> l); i++) v[i] = add_bf16x2(v[2 * i], v[2 * i + 1]);
            if (RED_L == 3) sts32(red + (c.sb + SM_RED + c.w * 128), v[0]);
            else {
              float lo[8], hi[8];
#pragma unroll
              for (int i = 0; i < (8 >> RED_L); i++) { lo[i] = __uint_as_float(v[i] << 16); hi[i] = __uint_as_float(v[i] & 0xFFFF0000u); }
#pragma unroll
              for (int l = RED_L; l < 3; l++)
#pragma unroll
                for (int i = 0; i < (4 >> l); i++) { lo[i] = lo[2 * i] + lo[2 * i + 1]; hi[i] = hi[2 * i] + hi[2 * i + 1]; }
              sts64(red + (c.sb + SM_RED + c.w * 256), __float_as_uint(lo[0]), __float_as_uint(hi[0]));
            }
            if (ok) break;
            n++; CNT(0);
          }
          bar_sync(NB_HELP, 128);
          const uint32_t rd = red + (c.sb + SM_RED);
          if (!RED_P || c.w < 2) {
            if (RED_L == 3) st_pub_if(dst, sum4(lds32(rd), lds32(rd + 128), lds32(rd + 256), lds32(rd + 384)), c.w < 2);
            else {
              const uint2 p0 = lds64(rd), p1 = lds64(rd + 256), p2 = lds64(rd + 512), p3 = lds64(rd + 768);
              st_pub_if(dst, pack_bf16((__uint_as_float(p0.x) + __uint_as_float(p1.x)) + (__uint_as_float(p2.x) + __uint_as_float(p3.x)),
                                       (__uint_as_float(p0.y) + __uint_as_float(p1.y)) + (__uint_as_float(p2.y) + __uint_as_float(p3.y))), c.w < 2);
            }
          }
          t0 = clock_lo();
          mbar_arrive_warp(BAR(B_PUB));
          TRV(s, 15, n);
          mbar_wait(BAR(B_SPFREE), (s - 1) & 1);
        } else {
          if (tid_now() == 384) TL2(24);
          __syncwarp();
          if (!E30) mbar_wait(BAR(B_PROBE), 1);
          if (!WO_S) mbar_wait(BAR(B_WOFULL), 0);
          if (tid_now() == 384) TL2(19);
          __syncwarp();
          t0 = clock_lo() - DLY_E3;
        }
        TRV(s, 1, t0);
        {
          const uint32_t l16 = (tid_now() & 31) * 16, dst = vary(l16, s, c.sb) + (c.sb + SM_MEM + eh * 4096 + eq * 2048);
          const uint4 tb = lds128(tab + 16);
          st_pub_if(mk_ptr(tb.z | l16 >> 2, tb.w), SENT, c.w >= 2);
          const char* src = mk_ptr(tb.x | l16, tb.y);
          touch(src, dep(c.sb, dst, c.sb));
          delay_fine(t0 + (DLY_E3 + eh * DLY_E3B));
          uint32_t n = 0;
          while (true) {
            uint4 v[4];
#pragma unroll
            for (int i = 0; i < 4; i++) v[i] = ld_poll(src + i * 512);
#pragma unroll
            for (int i = 0; i < 4; i++) sts128(dst + i * 512, v[i]);
            if (arrive_if_all(max(max(v[0].x, v[1].x), max(v[2].x, v[3].x)) != SENT, NB_MEM + eh * 2 + eq, 160)) break;
            n++; CNT(1);
          }
          TR(s, 2); TRV(s, 14, n);
        }

        if (s == 1) CLK(1); if (s == 8) CLK(2); if (s == 56) CLK(3);
        if (c.w == 2 && s == 15) TRSYNC(8);
        if (c.w == 2 && s == 21) TRSYNC(10);
      }
      const int g = s + 1;
      auto load_v = [&]() {
        if (V_TMA && c.w == V_W) {
          mbar_expect_e(BAR(B_VFULL), 8192);
          bulk_load_e(c.sb + SM_V, c.mail + (uint32_t)(M_KVQ + (min(g, XEND - 1) & (NSLOT - 1)) * M_REG + c.h * 24576 + 8192), 8192, BAR(B_VFULL));
        }
      };
      if (XEND < NSEG && g >= XEND && g < NSEG) { mbar_wait(BAR(B_SC), s & 1); load_v(); }
      if (g < XEND) {
        const uint32_t tx_ = c.sb + SM_TAB + 1536 + (g & 3) * 128 + c.w * 32, tag = (g >> 2) & 1;
        if (c.w == 0) mbar_expect_e(BAR(B_LAND), EXP_PEER * 12288);
        auto load_x = [&]() {
          if (c.w == 3 && g + 1 < XEND) {
            mbar_wait(BAR(B_XEMPTY), g & 1);
            mbar_expect_e(BAR(B_XFULL), 16384 * EXP_NXT);
            for (int i = 0; i < EXP_NXT; i++) tma4d_e(c.sb + SM_XT + i * 16384, &tx, c.b * 8, (g + 1) * 4 + 2 * (c.b ^ i), BAR(B_XFULL));
          }
        };
        if (X_AT == 0 && g > 0) load_x();
        TR(s, 6);
        if (E30 && g == 0) mbar_wait(BAR(B_PROBE), 1);
        mbar_wait(BAR(B_LAND), g & 1);
        TR(s, 7);
        if (DLY_F && g > 0) delay_cycles(DLY_F);
        auto total = [&](int w, int lane, uint32_t o0, uint32_t o1) {
          const uint32_t a = c.sb + SM_LAND + land_off(w, lane);
          if (EXP_FL == 1) return make_uint4(a, a, a, a);
          const uint4 t = add4(lds128(a + o0), lds128(a + o1 + 2048));
          const uint32_t a2 = dep(dep(a, t.x ^ t.y ^ t.z, c.sb), t.w, c.sb);
          return add4(t, add4(lds128(a2 + o0 + 4096), lds128(a2 + o1 + 6144)));
        };
        auto get = [&](int e) {
          const int ln = tid_now() & 31;
          return e == 0 ? total(c.w, ln, 16384, 16384)
               : e == 1 ? total((c.w & 2) + ((ln >> 1) & 1), (ln & 1) * 16 + (c.w & 1) * 8 + (ln >> 2), 8192, 0)
                        : total((c.w & 2) + ((ln >> 1) & 1), (ln & 1) * 16 + (ln >> 3) * 4 + (c.w & 1) * 2 + ((ln >> 2) & 1), 0, 8192);
        };
        auto put = [&](int e, uint4 v) {
          const int ln = tid_now() & 31;
          const uint2 d = lds64(tx_ + e * 8);
          if (e < 2) {
            v.x = tagged(v.x, tag);
            st_pub4(mk_ptr(d.x | (e ? (ln & 24) * 32 + (ln & 7) * 16 : ln * 16), d.y), v);
          } else {
            char* dst = mk_ptr(d.x | ((ln & 7) * 16 + (ln >> 3) * 4), d.y);
            const uint32_t bit = ln < 8;
            st_pub(dst, put_tag(v.x, bit, tag)); st_pub(dst + 128, put_tag(v.y, bit, tag));
            st_pub(dst + 2048, put_tag(v.z, bit, tag)); st_pub(dst + 2176, put_tag(v.w, bit, tag));
          }
        };
        auto after_sc = [&]() { if (g > 0) { mbar_wait(BAR(B_SC), s & 1); if (DLY_FK) delay_cycles(DLY_FK); if (X_AT == 1) load_x(); } };
        if (FIN_AT == 5) {
          put(0, get(0));
          if (DLY_F2 && g > 0) delay_cycles(DLY_F2); else sched_fence(c.sb);
          const uint4 k = get(1);
          sched_fence(c.sb);
          const uint4 q = get(2);
          if (g > 0) mbar_wait(BAR(B_VST), s & 1);
          put(1, k); put(2, q);
          TR(s, 5);
          mbar_arrive_both(BAR(B_LFREE), c.b ^ 1);
          after_sc();
          load_v();
          continue;
        }
        if (FIN_AT < 3) {
          if (EXP_FIN & 1) put(0, get(0));
          TR(s, 3);
          if (FIN_AT == 1) after_sc();
          if (V_TMA == 1) load_v();
          if (EXP_FIN & 2) put(1, get(1));
        } else {
          const uint4 v = get(0);
          sched_fence(c.sb);
          const uint4 k = get(1);
          if (g > 0) { mbar_wait(BAR(B_VST), s & 1); if (DLY_FS) delay_cycles(DLY_FS); }
          put(0, v); put(1, k);
        }
        TR(s, 4);
        if (FIN_AT == 4) {
          const uint4 q = get(2);
          after_sc();
          load_v();
          put(2, q);
        } else {
          if (FIN_AT >= 2) after_sc();
          if (V_TMA == 2) load_v();
          if (EXP_FIN & 4) put(2, get(2));
        }
        mbar_arrive_both(BAR(B_LFREE), c.b ^ 1);
        if (V_TMA == 3) load_v();
        TR(s, 5);
        if (!FIN_AT && X_AT && g > 0) { mbar_wait(BAR(B_SC), s & 1); if (DLY_FK) delay_cycles(DLY_FK); load_x(); }
      }
    }
    const int tile = tile_of(c), s0 = (tile >> 3) * 4, n0 = (tile & 7) * 128;
    if (c.w == 1) {
      mbar_wait(BAR(B_PVDONE), 0);
      count_e(g_ctl + (EARLY2 ? C_LAST : C_EARLY));
      st_pub(c.mail + (uint32_t)((tid_now() & 6) * (M_REG / 2) + M_SEL + (tid_now() & 1) * 4096 + c.r * 4), 0);
      await_count(g_ctl + C_COLS, 4);
      mbar_expect_e(BAR(B_TW), 8192);
      bulk_load_e(c.sb + SM_TW, g_tw, 8192, BAR(B_TW));
    } else if (c.w == 2) {
      const uint32_t ln = tid_now() & 31, rel = mapa(BAR(B_GEMPTY) + (ln >> 2) * 8, ln & 1);
      mbar_wait(BAR(B_VST), 1); mbar_wait(BAR(PRE_AT), 1);
      arrive_remote_if(rel, ln < 12);
      mbar_wait(BAR(B_E2TRIG), 1);
      if (GATE) mbar_wait(BAR(B_DONE), 0);
      arrive_remote_if(rel, ln >= 12 && ln < 20);
    } else {
      auto ahead = [&](int k) {
        if (c.w) { if (PF_A && (k & 3) == (tile >> 1 & 3)) prefetch3d_e(&ta, k * 32, s0 + 2 * c.b); }
        else if (PF_B && (k & 7) == (tile >> 4)) prefetch2d_e<(ONCE & 512) != 0>(&tw, n0 + (tile & 8) * 8, k * 64);
      };
#pragma unroll 1
      for (int k = 0; k < PF_D; k++) ahead(k);
      if (c.w == 3) await_count(g_ctl + C_EARLY, 128);
      const int skew = tile < 120 ? 0 : SKEW;
      uint32_t o = SM_XT, st = 0, ph = 0;
#pragma unroll 1
      for (int kb = 0; kb < 64 + skew; kb++, o = next_stage(o)) {
        const bool solo = kb < skew || kb >= 64;
        const uint32_t bar = BAR(B_GFULL + st), k = kb & 63;
        if (c.w && kb == skew) {
          if (tile >= 120) await_count(g_ctl + C_LAST, EARLY2 ? 640 : 512);
          if (tid_now() == 480) TL(10);
          __syncwarp();
        }
        mbar_wait(BAR(B_GEMPTY + st), ph);
        if (c.w) {
          const int r = solo ? (kb >> 5) + c.b : c.b * 2;
          tma3d_mc_e(c.sb + o + r * 4096, solo ? &ta32 : &ta, k * 32, s0 + r, bar);
        } else {
          mbar_expect_e(bar, solo ? 24576 : 32768);
          tma2d_o<(ONCE & 2) != 0>(c.sb + o + 16384, &tw, n0, k * 64, bar);
          tma2d_o<(ONCE & 2) != 0>(c.sb + o + 24576, &tw, n0 + 64, k * 64, bar);
        }
        if (kb + PF_D < 64) ahead(kb + PF_D);
        if (++st == 5) { st = 0; ph ^= 1; }
      }
    }
    return;
  } else if (c.m == 2) {
    asm volatile("setmaxnreg.dec.sync.aligned.u32 %0;" :: "n"(512 - 2 * REG_F - REG_H));
    c.lane = lane_id();
    {
      uint32_t tl = clock_lo() + (PACE0 + WO_AT * PACE);
      TR(-2, 0);
      sched_fence(i0 ^ i1);
      TR(-2, 7);
      int far1 = 0;
#pragma unroll 1
      for (int rep = EARLY; rep <= NPROBE; rep++) {
        const int lag = race_init(own + (rep & 1) * 4096, own + (~rep & 1) * 4096, SENT);
        if (rep) far1 += ((rep ^ c.r >> 5) & 1 ? 1 : -1) * min(lag, 200);
      }
      sts32(c.sb + SM_SEL + 512 + c.w * 4, (8 + far1 / (16 * NPROBE)) << 4 * c.w);
      TR(-2, 1);
      if (tid_now() == 256) TL2(14);
      __syncwarp();
      mbar_arrive_warp(BAR(B_PROBE));
      if (c.w == 0) {
        mbar_wait(BAR(B_PROBE), 0);
        const uint4 bits = lds128(c.sb + SM_SEL + 512);
        const uint32_t res = bits.x | bits.y | bits.z | bits.w;
        st_pub_if(c.mail + (uint32_t)((c.lane & 6) * (M_REG / 2) + M_SEL + (c.lane & 1) * 4096 + c.r * 4), res | tile_key(), c.lane < 8);
        const int q = (res >> 4 * ((c.lane + c.r) & 3) & 15) - 8, best = __reduce_max_sync(~0u, abs(q) * 64 + (c.lane & 3) * 16 + ((c.lane + c.r) & 3) * 2 + (q <= 0));
        const char* src = c.mail + (uint32_t)((best & 6) * (M_REG / 2) + M_SEL + (best & 1) * 4096 + c.lane * 16);
        if (SEL_AT) delay_until(tl - (PACE0 + WO_AT * PACE - SEL_AT));
        uint4 v; uint32_t n = 0;
        TR(-2, 4);
        while (true) {
          delay_cycles(DLY_SEL);
          TR(-2, 6);
          v = ld_poll(src);
          if (__all_sync(~0u, v.x && v.y && v.z && v.w)) break;
          watchdog(n, POLL_LIMIT);
        }
        TR(-2, 5);
        int ta = 0, tb = 0, pa = 0, pb = 0;
        uint32_t flip = 0;
#pragma unroll 1
        for (int i = 0; i < 4; i++) {
          const int a = (v.x >> 4 * i & 15) + (v.y >> 4 * i & 15) - 16, b = (v.z >> 4 * i & 15) + (v.w >> 4 * i & 15) - 16;
          const bool f = __reduce_add_sync(~0u, a * ta + b * tb) < 0;
          ta += f ? -a : a; tb += f ? -b : b; flip |= (uint32_t)f << i;
        }
#pragma unroll 1
        for (uint32_t g = 0; g < 8; g++) {
          const bool a = (v.x >> 16) - g * 256 < 120, b = (v.z >> 16) - g * 256 < 120;
          const int n = __reduce_add_sync(~0u, (a ? ta : 0) + (b ? tb : 0)) > 0 ? PRIOR : -PRIOR;
          if (a) pa = n;
          if (b) pb = n;
        }
        const uint32_t ka = AWARE && ta + pa > 0 ? ~flip : flip, kb = AWARE && tb + pb > 0 ? ~flip : flip;
        sts128(c.sb + SM_SEL + c.lane * 16, make_uint4(ka, ka, kb, kb));
        mbar_arrive_warp(BAR(B_SEL));
        const uint32_t key = __shfl_sync(~0u, c.a ? v.z : v.x, c.h);
        const int u = __popc(__ballot_sync(~0u, v.x < key)) + __popc(__ballot_sync(~0u, v.z < key));
        sts32(c.sb + SM_SEL + 528, (u & 32) * 2 + (u & 7) * 8 + (u >> 2 & 6) + c.b);
        TR(-2, 2);
        if (c.lane == 0) TL2(13);
        __syncwarp();
        bar_sync(14, 160);
        if (ZDLY) delay_cycles(ZDLY);
#pragma unroll 4
        for (int k = c.lane >> 3; k < (ZINIT ? 128 : 0); k += 4) {
          const int e = k & 7;
          const uint2 d = lds64(c.sb + SM_TAB + (e == 3 ? k - 1 : k) * 8);
          st_pub4(mk_ptr((d.x & ~127u) + (e < 2 ? (k & 8) * 32 : e == 3 ? 128 : 0) + (c.lane & 7) * 16, d.y), make_uint4(0, 0, 0, 0));
        }
        __syncwarp();
        if (c.lane < 4) asm volatile("mbarrier.arrive.shared::cta.b64 _, [%0];" :: "r"(BAR(B_PROBE)) : "memory");
        __syncwarp();
        TR(-2, 8);
      }
      if (c.w == 2) {
        mbar_wait(BAR(B_P1), 0);
        if (P1_AT) { mbar_wait(BAR(B_WFULL), 0); mbar_wait(BAR(B_WFULL + 1), 0); }
        st_pub_if(g_ctl + C_COLS + (c.r & 15) * 32 + c.lane, 0, c.r < (C_END - C_COLS) / 32);
        count_e(g_ctl + C_P1);
        TR(-2, 3);
      }
      if (c.w == 1) for (int i = 0; i < WO_N; i++) { delay_until(tl += WO_P * PACE); prefetch2d_e(&to, c.j * 256 + (i ^ WO_X) * 64, c.h * 128); }
      if (c.w == 3) {
        mbar_wait(BAR(B_WREAD0), 0);
        for (int i = 0; i < 2; i++) tma4d_e(c.sb + SM_WO + i * 16384, &tx, c.b * 8, 2 * (c.b ^ i), BAR(B_PFULL));
        mbar_expect_e(BAR(B_WOFULL), 65536);
#pragma unroll 1
        for (int i = 3; i >= 0; i--) {
          if (i & 1) mbar_wait(BAR(i < 2 ? B_XEMPTY : B_WREAD), 0);
          TMA_O(c.sb + SM_WO + i * 16384, &to, c.j * 256 + i * 64, c.h * 128, BAR(B_WOFULL));
        }
      }
    }
    asm volatile("barrier.cluster.wait;" ::: "memory");
    const int g = c.w, src0 = c.h * 4 + (g >> 1) * 2;
    mbar_wait(BAR(B_SEL), 0);
    c.sel = __shfl_sync(~0u, (e1_box(c, 0, src0 + (c.lane >> 5)) & 4096) | (e1_box(c, 1, src0) & 4096) * 2, 0);
    mbar_wait(BAR(B_WREAD), 0);
    uint32_t l16 = c.sb + g * 512 + c.lane * 16;
    auto lane = [&](uint32_t v) { l16 = dep(l16, v, c.sb); return (int)((l16 & 511) >> 4); };
    pad<PAD2>();
    for (int s = 0; s < NSEG; s++) {
      l16 = vary(l16, s, c.sb);
      int ln = (l16 & 511) >> 4;
      uint4 kf[4], qx;
      {
        const int gs = min(s, XEND - 1);
        const char* pk = c.mail + (uint32_t)(M_KVQ + (gs & (NSLOT - 1)) * M_REG + c.h * 24576 + g * 2048 + ln * 16);
        const char* pq = pk + (16384 + c.j * 2048 - g * 1536);
        const uint32_t tg = (gs / NSLOT) & 1;
        touch(pk, c.sb); touch(pq, c.sb);
        TR(s, 0);
        mbar_wait(BAR(B_VFULL), s & 1);
        TR(s, 1);
        if (s > 0) mbar_wait(BAR(B_PUB), (s - 1) & 1);
        for (uint32_t n = 0; ; ) {
          uint4 k[4];
#pragma unroll
          for (int t = 0; t < 4; t++) k[t] = ld_poll(pk + t * 512);
          qx = ld_poll(pq);
#pragma unroll
          for (int t = 0; t < 2; t++) {
            auto cp = [&](uint32_t v) { return dep(v, 0, c.sb); };
            kf[t] = make_uint4(cp(k[2 * t].x), cp(k[2 * t].y), cp(k[2 * t + 1].x), cp(k[2 * t + 1].y));
            kf[2 + t] = make_uint4(cp(k[2 * t].z), cp(k[2 * t].w), cp(k[2 * t + 1].z), cp(k[2 * t + 1].w));
          }
          if (all_clear(stale1(stale2(k[0].x, k[1].x, tg) | stale2(k[2].x, k[3].x, tg), qx.x, tg), EXP_CHK)) break;
          watchdog(n, POLL_LIMIT); CNT(4);
        }
        TR(s, 2);
      }
      if (X_AT >= 2 && g == 0 && s + 2 < XEND) {
        mbar_wait(BAR(B_XEMPTY), ~s & 1);
        mbar_expect_e(BAR(B_XFULL), 16384 * EXP_NXT);
        for (int i = 0; i < EXP_NXT; i++) tma4d_e(c.sb + SM_XT + i * 16384, &tx, c.b * 8, (s + 2) * 4 + 2 * (c.b ^ i), BAR(B_XFULL));
      }
      ln = lane(kf[0].y);
      const char* pa = c.mail + (uint32_t)(box(s & 1, src0) + 8192 + (c.sel >> (s & 1) & 4096) + (g & 1) * 512 + (EXP_LIN ? ln * 16 : read_off(ln)));
      const uint32_t spw = c.sb + SM_SP + g * 1280 + (ln & 3) * 64 + ((((ln >> 3) ^ ln) & 2) << 4) + (ln & 4) * 4 + (ln & 8),
                     spr = c.sb + SM_SP + (ln & 4) * 80 + (ln >> 3) * 64 + (((ln & 3) ^ ((ln >> 3) & 2)) << 4), l8 = ln * 8;
      const uint32_t tg = s >> 1;
      float sx[2][4];
      uint32_t sm;
      uint4 km;
      touch(pa, c.sb);
      mbar_wait(BAR(B_E1TRIG), s & 1);
      const uint32_t t0 = clock_lo();
      TRV(s, 3, t0);
      scores_x<false>(sx, kf, qx, 0);
      store_scores(sx, spw + 640);
      if (DLY_E1) delay_fine(t0 + DLY_E1);
      uint32_t nr = 0;
      while (true) {
        const uint4 q0 = ld_poll(pa), q1 = ld_poll(pa + 2048), k0 = ld_poll(pa + 1024), k1 = ld_poll(pa + 3072);
        uint4 qm = add4(q0, q1);
        const uint32_t bq = stale2(q0.x, q1.x, tg);
        qm.x = dep(qm.x, bq, c.sb);
        scores_x<SC_F>(sx, kf, qm, c.sb);
        const uint32_t bk = stale2(k0.x, k1.x, tg);
        km = add4(k0, k1);
        km.x = dep(km.x, bk, c.sb);
        const bool ok = all_clear(bq | bk, 1);
        sm = scores_m(qm, km);
        store_scores(sx, spw);
        if (ok) break;
        nr++; CNT(2);
      }
      sts32(l8 + (c.sb + SM_SPM + (g >> 1) * 256 + (g & 1) * 4), sm);
      bar_sync(NB_ATT, 128);
      TR(s, 5); TRV(s, 13, nr);
      float o[2][4];
      uint32_t sp[5];
      uint4 vf[4];
      load_scores(sp, spr, l8 + (c.sb + SM_SPM));
      const uint32_t m5 = max5(sp);
      uint32_t m1;
      float off = row_off(m5, m1), f[10];
      l16 = dep(l16, VF_AT ? m1 : m5, c.sb);
#pragma unroll
      for (int t = 0; t < 4; t++) vf[(t >> 1) + 2 * (t & 1)] = lds128(l16 + SM_V + ((t >> 1) + 2 * (t & 1)) * 2048);
      qx.x = dep(qx.x, sp[0], c.sb);
      sts32(l8 + (c.sb + SM_SPM + 512 + (g >> 1) * 256 + (g & 1) * 4), scores_m(qx, km));
      mbar_arrive_warp(BAR(B_SC));
      unpack(f, sp);
      if (UP_F) sched_fence(c.sb);
      uint4 vm;
      if (VM_AT < 2) {
        bar_sync(NB_VM, 384);
        sp[1] = exp_pair(f, 1, off);
        const uint32_t av = dep(l8, VM_AT ? sp[1] : __float_as_uint(off), c.sb) + (c.sb + g * 512 + SM_VM);
        const uint2 vm0 = lds64(av), vm1 = lds64(av + 256);
        vm = make_uint4(vm0.x, vm0.y, vm1.x, vm1.y);
#pragma unroll
        for (int i = 2; i < 6; i++) sp[i % 5] = exp_pair(f, i % 5, off);
      } else {
#pragma unroll
        for (int i = 1; i < 6; i++) sp[i % 5] = exp_pair(f, i % 5, off);
        bar_sync(VM_AT == 2 ? dep(dep(0, sp[1] ^ sp[2], c.sb) + NB_VM, sp[0], c.sb) : dep(dep(0, sp[0] ^ sp[1] ^ sp[2], c.sb) + NB_VM, sp[3], c.sb), 384);
        const uint32_t av = l8 + (c.sb + g * 512 + SM_VM);
        const uint2 vm0 = lds64(av), vm1 = lds64(av + 256);
        vm = make_uint4(vm0.x, vm0.y, vm1.x, vm1.y);
      }
      float sum;
      auto rows_m = [&]() {
        const uint32_t tv = min(s, XEND - 1) / NSLOT;
        sum = pv(o, sp, vf, vm);
        stsm4<false>(l16 + SM_OM, pack_bf16(o[0][0], o[0][1]), pack_bf16(o[0][2], o[0][3]), pack_bf16(o[1][0], o[1][1]), pack_bf16(o[1][2], o[1][3]));
        sts32(c.sb + SM_SUM + ((l16 >> 4) & 28), __float_as_uint(sum));
        return arrive_if_clear(stale2(vf[0].x, vf[1].x, tv) | stale2(vf[2].x, vf[3].x, tv), EXP_CHK, NB_OM, 384);
      };
      if (!rows_m()) {
        const char* pv_ = c.mail + (uint32_t)(M_KVQ + (min(s, XEND - 1) & (NSLOT - 1)) * M_REG + c.h * 24576 + 8192 + (l16 - c.sb));
        uint32_t n = 0;
        do {
#pragma unroll
          for (int t = 0; t < 4; t++) vf[t] = ld_poll(pv_ + t * 2048);
          watchdog(n, POLL_LIMIT); CNT(5);
        } while (!rows_m());
      }
      const uint32_t tom = clock_lo();
      TRV(s, 8, tom);
      sched_fence(c.sb);
      ln = lane(tom);
      const int n = ln >> 2, jj = ln & 3, tq_ = 8 * c.j + (n & 4) + 2 * (n & 1) + ((n >> 1) & 1), lim = 16 * (tq_ - 2 * jj + 1);
      if (DLY_X) delay_until(tom + DLY_X);
      load_scores(sp, spr + 640, c.sb + SM_SPM + 512 + ln * 8);
#pragma unroll
      for (int w = 0; w < 4; w++) {
        uint32_t m; asm("shl.b32 %0, 0xffffffff, %1;" : "=r"(m) : "r"(max(lim - 128 * w, 0)));
        sp[1 + w] = (sp[1 + w] & ~m) | (0xD029D029u & m);
      }
      mbar_arrive_warp(dep(dep(0, sp[0], c.sb), sp[1], c.sb) + BAR(B_SPFREE));
      off = row_off(max5(sp), m1);
      unpack(f, sp);
#pragma unroll
      for (int i = 1; i < 6; i++) sp[i % 5] = exp_pair(f, i % 5, off);
      sum = pv(o, sp, vf, vm);
      TR(s, 7);
      sum = rcp(sum);
      const float i0 = __shfl_sync(~0u, sum, 8 * jj), i1 = __shfl_sync(~0u, sum, 8 * jj + 4);
      const uint32_t oxs = c.sb + SM_OX + g * 512;
      stsm4<true>(oxs + (ln & 7) * 64 + (((ln >> 3) ^ ((ln >> 1) & 3)) << 4),
                  pack_bf16(o[0][0] * i0, o[0][1] * i1), pack_bf16(o[0][2] * i0, o[0][3] * i1), pack_bf16(o[1][0] * i0, o[1][1] * i1), pack_bf16(o[1][2] * i0, o[1][3] * i1));
      __syncwarp();
      *(uint4*)(g_ox + ox_at(s, tq_, c.h * 4 + g, jj)) = lds128(oxs + n * 64 + ((jj ^ (n >> 1)) << 4));
      mbar_arrive_warp(BAR(B_PVDONE));
      TR(s, 9);
    }
    if (LASTM) {
      const int ln = tid_now() & 31, n = ln >> 2, jj = ln & 3, tq_ = 8 * c.j + (n & 4) + 2 * (n & 1) + ((n >> 1) & 1);
      store_count(g_ox + ox_at(NSEG - 1, tq_, c.h * 4 + g, jj), lds128(c.sb + SM_OX + g * 512 + n * 64 + ((jj ^ (n >> 1)) << 4)), (char*)(g_ctl + C_LAST) + (LASTM == 2 ? c.r * 4 + g : 0));
    } else count_e(g_ctl + C_LAST);
    mbar_arrive_warp(BAR(B_DONE));
    if (tid_now() == 256) TL(8);
    __syncwarp();
    mbar_wait(BAR(B_E2TRIG), 1); mbar_wait(BAR(B_DONE), 0); mbar_wait(BAR(B_TW), 0);
    asm volatile("setmaxnreg.inc.sync.aligned.u32 128;");
  } else {
    {
      const int w = c.m * 4 + c.w;
      mbar_expect_e(BAR(B_ROWS), 4096 + 256);
      for (int i = 0; i < 2; i++) bulk_load_e(c.sb + SM_FFT + (1024 + w * ROW_BUF) * 8 + i * 2048, x + (size_t)(z_row(c.r * 8 + w) + i * 1024) * D_, 2048, BAR(B_ROWS));
      bulk_load_e(c.sb + SM_GW + w * 256, gw + w * 128, 256, BAR(B_ROWS));
    }
    asm volatile("setmaxnreg.inc.sync.aligned.u32 %0;" :: "n"(REG_F));
    c.lane = lane_id();
    uint32_t wa[16][4], wb[16][4], wv[16][4];
    TR(-2, 4);
    fft_rows_fwd((float2*)(smraw + SM_FFT), (const __nv_bfloat16*)(smraw + SM_GW), c.r, threadIdx.x, BAR(B_ROWS), BAR(B_FREE), [&](int e) { TR(-2, e); }, [&]() {
      mbar_spin(BAR(B_PFULL), 0);
#pragma unroll
      for (int k = 0; k < NP; k++) ldsm4t(wa[k], c.sb + SM_POOL + c.m * NP * 2048 + frag_off(c.w, c.lane) + k * 2048);
      bar_sync(NB_XCH, 256);
#pragma unroll
      for (int k = 0; k < NP; k++) sts128(c.sb + SM_POOL + c.m * 2048 + c.w * 512 + c.lane * 16 + k * 4096, make_uint4(wa[k][0], wa[k][1], wa[k][2], wa[k][3]));
    });
    mbar_arrive_warp(BAR(B_P1));
    TR(-2, 0);
    if (tid_now() == 0) TL2(1);
    __syncwarp();
    mbar_spin(BAR(B_WFULL + c.m), 0);
    TR(-2, 1);
    if ((tid_now() & 127) == 0) TL2(16);
    __syncwarp();
    {
      const uint32_t st = c.sb + c.m * ST_WG + frag_off(c.w, c.lane);
#pragma unroll
      for (int k = 0; k < 16; k++) ldsm4t(wb[k], st + k * 2048);
#pragma unroll
      for (int k = NP; k < 16; k++) ldsm4t(wa[k], st + (16 + k - NP) * 2048);
#pragma unroll
      for (int k = 0; k < NV; k++) ldsm4t(wv[k], st + (32 - NP + k) * 2048);
      mbar_arrive_warp(BAR(B_WREAD));
      if (c.m == 0) mbar_arrive_warp(BAR(B_WREAD0));
#pragma unroll
      for (int k = 0; k < (LP_IN == 2 ? 0 : NP); k++) lds_frag(wa[k], c.sb + SM_POOL + c.m * 2048 + c.w * 512 + c.lane * 16 + k * 4096);
      TR(-2, 2);
    }
    TR(-2, 3);
    if (tid_now() == 0) TL2(12);
    __syncwarp();
    asm volatile("barrier.cluster.wait;" ::: "memory");
    uint32_t t16 = c.m * 2048 + c.w * 512 + c.lane * 16;
    uint32_t pk = (c.m * NHV * 2048 + frag_off(c.w, c.lane)) | (tile_off(2 * (c.w & 1), c.lane) << 16) | ((c.lane & 12) ? 0u : 0x80000000u);
    const uint32_t dx1 = desc_lo(c.sb + SM_XT + c.m * 4096), dh = desc_lo(c.sb + SM_HV + c.m * NHV * 2048);
    mbar_spin(BAR(B_PFULL), 1);
    pad<PAD0>();
    for (int s = -2; ; s++) {
      t16 = vary(t16, s, c.sb); pk = vary(pk, s, c.sb);
      const uint32_t dx = dx1 - (s == -2 ? (SM_XT - SM_WO) / 16 : 0);
      auto ldp = [&](int k0, int k1, int d, int back = 0) {
#pragma unroll
        for (int k = k0; k < k1; k++) lds_frag(wa[k], (k < k0 + d - back ? t16 : dep(t16, wa[k < d ? 0 : k - d][0], c.sb)) + (c.sb + SM_POOL + k * 4096));
      };
      if (s >= 0) {
        uint32_t af[16][4], bf[4][4], wo;
        const uint32_t tab = ((t16 >> 3) & 0x1C0) + (c.sb + SM_TAB + (s & 1) * 512);
        const char* pa;
        mem_proj(wa, wb, wv, af, wo, pa, tab, t16, pk, c, s);
        const uint32_t t0 = clock_lo();
        t16 = dep(t16, t0, c.sb);
        auto ldwo = [&](int f) { ldsm4t(af[f], (f < WO_D ? wo : dep(wo, af[f < WO_D ? 0 : f - WO_D][0], c.sb)) + (c.sb + SM_WO + (f & 1) * 32768 + (f >> 1) * 2048)); };
        {
          const uint32_t tg = s >> 1, vm = t16 >> 1, chk = (~t16 >> 4) & 1;
          if (WO_S && s == 0) {
            mbar_spin(BAR(B_WOFULL), 0);
#pragma unroll
            for (int f = 0; f < WO_0; f++) ldwo(f);
          }
#pragma unroll
          for (int f = WO_0; f < WO_1; f++) ldwo(f);
          if (DLY_V) delay_fine(t0 + DLY_V); else sched_fence(c.sb);
          uint2 v0 = ld_poll2(pa), v1 = ld_poll2(pa + 1024), v2 = ld_poll2(pa + 2048), v3 = ld_poll2(pa + 3072);
          TR(s, 3);
#pragma unroll
          for (int f = WO_1; f < 16 - WO_L; f++) ldwo(f);
          TR(s, 4);
          uint32_t n = 0;
          while (true) {
            sts64(vm + (c.sb + SM_VM), sum4(v0.x, v1.x, v2.x, v3.x), sum4(v0.y, v1.y, v2.y, v3.y));
            if (arrive_if_clear(stale1(stale1(stale2(v0.x, v1.x, tg), v2.x, tg), v3.x, tg), chk, NB_VM, 384)) break;
            v0 = ld_poll2(pa); v1 = ld_poll2(pa + 1024); v2 = ld_poll2(pa + 2048); v3 = ld_poll2(pa + 3072);
            n++; CNT(3);
          }
          TR(s, 12); TRV(s, 15, n);
        }
        if (!NOWO || vary(s, s, c.sb) != NSEG - 1) {
        const uint32_t ob = dep(dep(t16 & 511, af[14 - WO_L][0], c.sb), af[15 - WO_L][0], c.sb);
        uint32_t l4 = ob >> 2;
        const uint32_t bit = (t16 & 48) ? 0u : 1u;
        if (LF_AT) mbar_spin2_if(BAR(B_XFULL), BAR(B_LFREE), s & 1, s + 2 < XEND); else mbar_spin_if(BAR(B_XFULL), s & 1, s + 2 < XEND);
        bar_sync(NB_OM, 384);
        TR(s, 5);
#pragma unroll
        for (int i = 0; i < 4; i++) ldsm4t(bf[i], ob + (c.sb + SM_OM + i * 512));
        uint2 sum = lds64(((t16 >> 1) & 24) + (c.sb + SM_SUM));
        if (OM_F) sched_fence(c.sb);
        float d[WO_C][4] = {};
        uint4 d0, d1;
#pragma unroll
        for (int f = 0; f < 16; f++) {
          mma_a(d[f % WO_C], af[f], bf[f >> 2][f & 2], bf[f >> 2][(f & 2) + 1]);
          if (f >= WO_C && f < WO_C + WO_L) {
            const int l = 16 - WO_L + f - WO_C;
            ldsm4t(af[l], (WO_LD ? dep(wo, __float_as_uint(d[(f + 1) % WO_C][0]), c.sb) : wo) + (c.sb + SM_WO + (l & 1) * 32768 + (l >> 1) * 2048));
          }
          if (f == WO_T) {
            const uint32_t tb2 = dep((t16 >> 3) & 0x1C0, __float_as_uint(d[f % WO_C][0]), c.sb) + (c.sb + SM_TAB + (s & 1) * 512);
            d0 = lds128(tb2 + 32); d1 = lds128(tb2 + 48);
          }
          if (f >= PL_WA && f < PL_WA + PL_W) lds_frag(wa[f - PL_WA], (PL_WD ? dep(t16, __float_as_uint(d[(f + PL_WD) % WO_C][0]), c.sb) : t16) + (c.sb + SM_POOL + (f - PL_WA) * 4096));
          if (PL_W && PL_WF == 1 && f == PL_WA + PL_W - 1) sched_fence(c.sb);
          if (f == 4) { sum.x = dep(sum.x, __float_as_uint(d[0][0]), c.sb); sum.y = dep(sum.y, __float_as_uint(d[0][0]), c.sb); }
        }
        if (PL_W && !PL_WF) {
          uint32_t all = 0;
#pragma unroll
          for (int k = 0; k < PL_W; k++) all ^= wa[k][0];
          l4 = dep(l4, all, c.sb);
        }
        char* dst[4] = {mk_ptr(d0.x | l4, d0.y), mk_ptr(d0.z | l4, d0.w), mk_ptr(d1.x | l4, d1.y), mk_ptr(d1.z | l4, d1.w)};
        const float i0 = rcp(__uint_as_float(sum.x)), i1 = rcp(__uint_as_float(sum.y));
#pragma unroll
        for (int i = 0; i < 4; i++) {
          const int t = i >> 1, e = 2 * (i & 1);
          const float y0 = WO_C == 2 ? d[t][e] : d[t][e] + d[(t + 2) % WO_C][e], y1 = WO_C == 2 ? d[t][e + 1] : d[t][e + 1] + d[(t + 2) % WO_C][e + 1];
          st_pub(dst[i], put_tag(pack_bf16(y0 * i0, y1 * i1), bit, s >> 1));
        }
        if (ANCH2) sts32(c.sb + SM_SUM + 64, clock_lo());
        mbar_arrive_warp(BAR(B_E2TRIG));
        TR(s, 6);
        sched_fence(c.sb);
        if (W_E2 == 2) mbar_spin(BAR(B_E2TRIG), s & 1);
        }
      }
      if (__builtin_expect(s + 2 < XEND, 1)) {
        const uint32_t tg0 = DLY_P ? clock_lo() + DLY_P : 0;
        if (LP_IN) ldp(PL_W, PL_0, PL_D);
        float xa[16];
        uint32_t q[4];
        if (W_E2 == 1 && s >= 0) mbar_spin(BAR(B_E2TRIG), s & 1);
        TR(s, 7);
        constexpr int S1 = ORDER ? 0 : 2, S2 = ORDER == 0 ? 0 : ORDER == 1 ? 2 : 1, S3 = ORDER == 2 ? 2 : 1;
        if (MINI) { issue_qk<0, MINI>(xa, wb, vary(dx, s, c.sb + 96)); delay_until(tg0 - DLY_P + DLY_M); }
        if (ORDER) issue_qk<MINI, 16>(xa, wb, vary(dx, s, c.sb)); else issue_v(xa, wv, vary(dx, s, c.sb), vary(dh, s, c.sb));
        if (DLY_P) delay_until(tg0); else if (IS_F) sched_fence(c.sb);
        ldp(PL_0, PL_1, PL_D1);
        const uint32_t land = (t16 ^ ((t16 >> 3) & 0x60)) + vary(c.sb + SM_LAND + c.b * 4096, s, c.sb);
        TR(s, 14);
        if (LF_AT == 1) mbar_spin_if(BAR(B_LFREE), s & 1, s < 0); else if (!LF_AT) mbar_spin(BAR(B_LFREE), s & 1);
        TR(s, 15);
        WG_WAIT(0);
        TR(s, 8);
        park_own<S1 == 2>(q, xa, land, S1, c.sb);
        if (W_PUB == 4 && s >= 0) mbar_spin(BAR(B_PUB), s & 1);
        if (ORDER == 1) issue_v(xa, wv, vary(dx, s, c.sb + 32), vary(dh, s, c.sb)); else issue_qk<0, 16>(xa, ORDER ? wa : wb, vary(dx, s, c.sb + 32));
        if (IS_F) sched_fence(c.sb);
        ldp(PL_1, PL_2, PL_D1);
        if (W_PUB == 1) mbar_spin_if(BAR(B_PUB), s & 1, s >= 0);
        uint32_t tp = clock_lo(), q1[4] = {q[0], q[1], q[2], q[3]};
        if (PL_2B) ldp(PL_2, NP - PL_L, PL_D1);
        if (W_PUB != 3) park_peer(q, land, S1, c);
        if (!PL_2B) ldp(PL_2, NP - PL_L, PL_D1);
        TR(s, 13);
        WG_WAIT(0);
        TR(s, 9);
        park_own<S2 == 2>(q, xa, land, S2, c.sb);
        if (ORDER == 2) issue_v(xa, wv, vary(dx, s, c.sb + 64), vary(dh, s, c.sb));
        else {
          issue_qk<0, PL_L ? NP - PL_L : 16>(xa, wa, vary(dx, s, c.sb + 64));
          ldp(NP - PL_L, NP, PL_E);
          if (PL_L) issue_qk<NP - PL_L, 16>(xa, wa, vary(dx, s, c.sb + 64));
        }
        if ((W_PUB == 2 || W_PUB == 3) && s >= 0) { mbar_spin(BAR(B_PUB), s & 1); tp = clock_lo(); }
        if (W_PUB == 3) park_peer(q1, land, S1, c);
        if (DLY_S && s >= 0) delay_until(tp + DLY_S);
        park_peer(q, land, S2, c);
        WG_WAIT(0);
        TR(s, 10);
        mbar_arrive_warp(BAR(B_XEMPTY));
        park_own<S3 == 2>(q, xa, land, S3, c.sb);
        park_peer(q, land, S3, c);
        TR(s, 11);
      } else {
        if (s == NSEG - 1) break;
        if (EARLY2 && (XEND == NSEG || s == NSEG - 2) && c.m * 4 + c.w == 0) count_e(g_ctl + C_EARLY);
        ldp(PL_W, NP, 2);
      }
    }
    if (NOWO) mbar_arrive_warp(BAR(B_E2TRIG));
    asm volatile("setmaxnreg.dec.sync.aligned.u32 %0;" :: "n"(BPRE == 2 ? 176 : 128));
    const int tid = tid_now(), lane = tid & 31, tile = tile_of(c), m0 = (tile >> 3) * 128, n0 = (tile & 7) * 128;
    float acc[64];
#pragma unroll
    for (int i = 0; i < 64; i++) acc[i] = 0.f;
    const uint32_t rel = mapa(BAR(B_GEMPTY), lane & 1), la = desc_lo(c.sb + c.m * 8192), lb = ((c.sb + 16384) & 0x3FFFF) >> 4 | (8192 >> 4) << 16;
    bool relon = false;
    const int skew = tile < 120 ? 0 : SKEW, kend = 64 + skew - c.m * skew, hold = c.m * (65 - LEAD) - 1;
    const float g0 = __ldcg(g_gate + m0 + (tid >> 5) * 16 + (lane >> 2)), g1 = __ldcg(g_gate + m0 + (tid >> 5) * 16 + (lane >> 2) + 8);
    uint32_t o = SM_XT, st = 0, ph = 0, prev = 0;
    if (tid == 0) TL(9);
    __syncwarp();
    GT(0);
#pragma unroll 1
    for (int kb = -c.m * skew; kb < max(kend - 4, 64); kb++, o = next_stage(o)) {
      if (LEAD && kb == hold) bar_sync(15, 256);
      mbar_lim(BAR(B_GFULL + st), ph);
      if ((uint32_t)kb < 64) {
        WG_FENCE();
#pragma unroll
        for (int k = 0; k < 4; k++) wgmma_ss_n128_tb(acc, desc128(la + (o >> 4) + k * 2), desc128(lb + (o >> 4) + k * 128));
        WG_COMMIT();
        WG_WAIT(1);
      } else WG_WAIT(0);
      arrive_remote_if(rel + 8 * prev, relon && kb < kend - 4);
      relon = (tid & 127) < 2;
      prev = st;
      if (++st == 5) { st = 0; ph ^= 1; }
    }
    if (LEAD && c.m == 0) asm volatile("bar.arrive 15, 256;" ::: "memory");
    const uint32_t row = (tid >> 5) * 2048 + (lane & 15) * 128 + (((lane >> 4) ^ (lane & 7)) << 4);
    if (!BPRE) WG_WAIT(0);
    mbar_lim(BAR(B_BT), 0);
    uint32_t b[2][4][4];
    const uint32_t rb = (tid >> 5) * 2048 + (lane >> 2) * 128 + (((lane & 7) ^ (lane >> 2)) << 4);
#pragma unroll
    for (int i = 0; i < 8; i++) lds_frag(b[i & 1][i >> 1], (rb ^ (i & 2) * 32) + (c.sb + SM_BT + (i >> 2) * 16384 + (i & 1) * 1024));
    float bl[2][4][4], bh[2][4][4];
    if (BPRE == 2) {
#pragma unroll
      for (int i = 0; i < 32; i++) {
        asm volatile("shl.b32 %0, %1, 16;" : "=f"(bl[i >> 4][i >> 2 & 3][i & 3]) : "r"(b[i >> 4][i >> 2 & 3][i & 3]));
        asm volatile("and.b32 %0, %1, 0xffff0000;" : "=f"(bh[i >> 4][i >> 2 & 3][i & 3]) : "r"(b[i >> 4][i >> 2 & 3][i & 3]));
      }
    }
    if (BPRE) { sched_fence(c.sb); WG_WAIT(0); sched_fence(c.sb); }
#pragma unroll
    for (int i = 0; i < 64; i++) asm volatile("" : "+f"(acc[i]) :: "memory");
    GT(17);
    if (tid == 0) TL(4);
    __syncwarp();
#pragma unroll
    for (int hf = 0; hf < 2; hf++) {
#pragma unroll
      for (int t = 0; t < 4; t++) {
        uint32_t y[4];
#pragma unroll
        for (int i = 0; i < 4; i++) {
          const float* a = acc + 32 * hf + 8 * t + 2 * i, g = i & 1 ? g1 : g0;
          const uint32_t* q = b[i & 1][2 * (t & 1) + (i >> 1)] + hf;
          const float* f = (t & 2 ? bh : bl)[i & 1][2 * (t & 1) + (i >> 1)] + hf;
          if (BPRE == 2) y[i] = pack_bf16(fmaf(g, a[0], f[0]), fmaf(g, a[1], f[2])); else
          y[i] = pack_bf16(fmaf(g, a[0], __uint_as_float(t & 2 ? q[0] & 0xFFFF0000u : q[0] << 16)), fmaf(g, a[1], __uint_as_float(t & 2 ? q[2] & 0xFFFF0000u : q[2] << 16)));
        }
        stsm4<false>((row ^ t * 32) + (c.sb + SM_BT + hf * 16384), y[0], y[1], y[2], y[3]);
      }
      if (EP_F && !hf) { sched_fence(c.sb); for (int i = 32; i < 64; i++) asm volatile("" : "+f"(acc[i]) :: "memory"); }
      FENCE_ASYNC_SMEM();
      __syncwarp();
      tma2d_out_e(&tout, n0 + hf * 64, m0 + (c.m * 4 + c.w) * 16, c.sb + SM_BT + hf * 16384 + (c.m * 4 + c.w) * 2048);
    }
    asm volatile("cp.async.bulk.commit_group; cp.async.bulk.wait_group" WAITRD " 0;" ::: "memory");
    GT(18);
    if ((tid & 127) == 0) TL(11);
    return;
  }
  static_assert(!QSH || NQ >= 106, "rounds");
  const bool col = c.r >= 128;
  const int tile = col ? 0 : tile_of(c);
  const int q0 = col ? 256 - NQ + (c.r - 128) + c.m * 4 : tile < 120 ? tile : 256, u = (tile >> 1 & 32) | (tile >> 3 & 7) | (tile & 6) << 2, e = QSH == 2 ? 2 * (u - (u > 39) - (u > 47) - (NQ < 110 && u > 55)) + c.b : tile,
            dq = col ? 16 : QSH ? 120 + (e >> 2) - tile : 120, qe = col ? 256 : 256 - NQ,
            qw = col || !QSH || c.w == (e & 3) ? qe : 120;
  const uint32_t zs = c.sb + (col ? COL_Z + c.m * 32768 : SM_BT), zb = BAR(B_Z + c.m);
  auto load_z = [&](int q) { if (c.w == 0 && q < qe) { mbar_expect_e(zb, 32768); tma2d_o<(ONCE & 4) != 0>(zs, &tz, q * 64, 0, zb); } };
  asm volatile("fence.proxy.async.global;" ::: "memory");
  load_z(q0);
  uint32_t ph = 0;
#pragma unroll 1
  for (int q = q0; q < qe; q += dq, ph ^= 1) {
    mbar_lim(zb, ph);
    const int p = q * 4 + c.w;
    if (EXP_INV && q < qw) fft_rows_inv(zs, (float2*)(smraw + (col ? 8192 + c.m * INV_BUF * 32 : SM_MEM)) + c.w * INV_BUF, (const float2*)(smraw + (col ? 0 : SM_TW)), p, tid_now() & 31, g_b,
                              [&]() { bar_sync(5 + c.m, 128); load_z(q + dq); });
    else { bar_sync(5 + c.m, 128); load_z(q + dq); }
  }
  if (B_ST) asm volatile("cp.async.bulk.wait_group 0; fence.proxy.async.global;" ::: "memory");
  asm volatile("fence.acq_rel.gpu;" ::: "memory");
  __syncwarp();
  { const int q = q0 + (tid_now() & 31) * dq; if (q < qw) asm volatile("red.relaxed.gpu.global.add.u32 [%0], 1;" :: "l"(g_ctl + C_ROWS + (q >> 5) * 32) : "memory"); }
  if (tid_now() == 256) { if (col) TL(27); else TL(3); }
  __syncwarp();
  if (!col && c.w == 0) {
    await_count<AW_NS>(g_ctl + C_ROWS + ((tile >> 3) & 7) * 32, 128);
    mbar_expect_e(BAR(B_BT), 32768);
    for (int i = 0; i < 2; i++) tma2d_o<(ONCE & 8) != 0>(c.sb + SM_BT + i * 16384, &tb, (tile & 7) * 128 + i * 64, (tile >> 3) * 128, BAR(B_BT));
    if (tid_now() == 256) TL(5);
  }
}

typedef CUresult (*EncodeFn)(CUtensorMap*, CUtensorMapDataType, cuuint32_t, void*, const cuuint64_t*, const cuuint64_t*,
                             const cuuint32_t*, const cuuint32_t*, CUtensorMapInterleave, CUtensorMapSwizzle,
                             CUtensorMapL2promotion, CUtensorMapFloatOOBfill);

void make_map(EncodeFn enc, CUtensorMap* tm, const void* p, int rank, const cuuint64_t* dims, const cuuint64_t* strides, const cuuint32_t* box, bool swz = true) {
  const cuuint32_t es[4] = {1, 1, 1, 1};
  enc(tm, CU_TENSOR_MAP_DATA_TYPE_BFLOAT16, rank, (void*)p, dims, strides, box, es, CU_TENSOR_MAP_INTERLEAVE_NONE,
      swz ? CU_TENSOR_MAP_SWIZZLE_128B : CU_TENSOR_MAP_SWIZZLE_NONE, swz ? CU_TENSOR_MAP_L2_PROMOTION_L2_128B : W_PROMO, CU_TENSOR_MAP_FLOAT_OOB_FILL_NONE);
}
void make_map2(EncodeFn enc, CUtensorMap* tm, const void* p, uint64_t cols, uint64_t rows, uint32_t boxrows) {
  const cuuint64_t dims[2] = {cols, rows}, strides[1] = {cols * 2};
  const cuuint32_t box[2] = {64, boxrows};
  make_map(enc, tm, p, 2, dims, strides, box);
}

}

extern "C" void kernel_launch(void* const* d_in, const int* in_sizes, int n_in, void* d_out, int out_size) {
  (void)in_sizes; (void)n_in; (void)out_size;
  const __nv_bfloat16* x = (const __nv_bfloat16*)d_in[0];
  const __nv_bfloat16* mem0 = (const __nv_bfloat16*)d_in[1];
  const __nv_bfloat16* gw = (const __nv_bfloat16*)d_in[10];

  EncodeFn enc = nullptr;
  cudaDriverEntryPointQueryResult qr;
  cudaGetDriverEntryPoint("cuTensorMapEncodeTiled", (void**)&enc, cudaEnableDefault, &qr);
  void *p_ox, *p_b, *p_z, *p_mail;
  cudaGetSymbolAddress(&p_ox, g_ox); cudaGetSymbolAddress(&p_b, g_b); cudaGetSymbolAddress(&p_z, g_z); cudaGetSymbolAddress(&p_mail, g_mail);
  CUtensorMap tq, tk, tv, tv16, to, tx, twr, twi, ta, tw, tb, tout, tz, tzs, ta32;
  make_map2(enc, &tq, d_in[2], 4096, 1024, 64);
  make_map2(enc, &tk, d_in[3], 4096, 1024, 64);
  make_map2(enc, &tv, d_in[4], 4096, 1024, 64);
  make_map2(enc, &tv16, d_in[4], 4096, 1024, 16);
  make_map2(enc, &to, d_in[5], 1024, 4096, 128);
  make_map2(enc, &tw, d_in[5], 1024, 4096, 64);
  {
    const cuuint64_t dims[3] = {64, 2048, 64}, strides[2] = {128, 262144};
    const cuuint32_t box[3] = {64, 32, 2}, box1[3] = {64, 32, 1};
    make_map(enc, &ta, p_ox, 3, dims, strides, box);
    make_map(enc, &ta32, p_ox, 3, dims, strides, box1);
  }
  make_map2(enc, &tb, p_b, 1024, 2048, 128);
  make_map2(enc, &tout, d_out, 1024, 2048, 16);
  make_map2(enc, &tz, p_z, 16384, 257, 256);
  {
    const cuuint64_t dims[4] = {64, 8, 16, 256}, strides[3] = {2048, 128, 16384};
    const cuuint32_t box[4] = {64, 8, 8, 2};
    make_map(enc, &tx, x, 4, dims, strides, box);
  }
  {
    const cuuint64_t dims[2] = {512, 257 * 32}, strides[1] = {1024};
    const cuuint32_t box[2] = {128, 16};
    make_map(enc, &tzs, p_z, 2, dims, strides, box, false);
  }
  {
    const cuuint64_t dims[2] = {8 * 513, 256}, strides[1] = {8 * 513 * 2};
    const cuuint32_t box[2] = {8, 256};
    make_map(enc, &twr, d_in[8], 2, dims, strides, box, false);
    make_map(enc, &twi, d_in[9], 2, dims, strides, box, false);
  }
  cudaFuncSetAttribute(chain_kernel, cudaFuncAttributeMaxDynamicSharedMemorySize, CHAIN_SMEM);

  cudaStream_t st = cudaStreamPerThread;
  char* mail = (char*)(((uintptr_t)p_mail + M_REG - 1) & ~(uintptr_t)(M_REG - 1));
  chain_kernel<<<132, 512, CHAIN_SMEM, st>>>(tq, tk, tv, tv16, to, tx, twr, twi, ta, tw, tb, tout, tz, tzs, ta32, mem0, mail, x, gw);
}
```

```cpp
#include <cuda_runtime.h>
#include <cuda_bf16.h>
#include <cuda.h>
#include <stdint.h>

#define DLY_E1 160
#define DLY_V 270
#define DLY_E2 260
#define DLY_E3 440
#define DLY_X 1
#define DLY_S 0
#define DLY_F 200
#define VM_AT 1
#define OM_F 1
#define C1_AT 7
#define NLAG 2
#define WO_D 2
#define WO_0 3
#define WO_1 10
#define PL_0 10
#define PL_1 10
#define PL_D 2
#define PL_L 0
#define HV_D 4
#define DLY_FK 0
#define REG_F 216
#define REG_H 24
#define SC_F 1
#define E2_F 0
#define X_AT 2
#define PL_2 10
#define PL_E 2
#define ORDER 1
#define SSPOS 1
#define W_PUB 1
#define FIN_AT 5
#define AWARE 1
#define NPROBE 2
#define NP_ 12
#define DLY_GRP 1000
#define EXP_CHK 1
#define EXP_NXT 2
#define EXP_PEER 1
#define EXP_FIN 7
#define EXP_NWG 16
#define ANCH2 1
#define IS_F 0
#define PL_D1 2
#define W_E2 0
#define V_TMA 2
#define V_W 3
#define RED_L 3
#define RED_T 1
#define RED_P 1
#define DLY_E3B 20
#define HV_E 1
#define HV_R 4
#define HOLD 0
#define PACE 500
#define PACE0 0
#define EXP_ST 7
#define WO_AT 38
#define WO_P 2
#define DLY_SEL 300
#define P1_AT 1
#define TMA_W tma2d_once
#define TMA_O tma2d_once
#define PACE_Z 580
#define EXP_INV 1
#define VF_AT 0
#define UP_F 0
#define WO_L (12 - NP_)
#define WO_C 4
#define WO_T 4
#define WO_LD 0
#define EXP_LIN 0
#define PL_W 2
#define PL_WA 6
#define PL_WD 0
#define PL_WF 2
#define EXP_FL 0
#define DLY_FS 0
#define DLY_F2 40
#define PF_D 4
#define PF_A 1
#define PF_B 0
#define SIDE 1
#define ROLE 1
#define E1OFF 1
#define EPI 0
#define WAITRD ".read"
#define START 1000
#define WUNR 1
#define WO_N 0
#define PL_2B 1
#define DLY_P 0
#define LP_IN 1
#define LF_AT 1
#define FINE 0
#define E30 1
#define WO_S 1
#define POOL_AT 12
#define COL_DLY 0
#define PAD0 0
#define PAD2 2
#define PAD3 0
#define WO_X 0
#define PRIOR 12
#define EARLY 1
#define SEL_AT 3000
#define FUNR 0
#define ZINIT 1
#define ZDLY 0
#define NQ 100
#define GATE 0
#define LASTM 1
#define X_ONCE 1
#define ONCE 31
#define Z_PF 0
#define EXP_W 1
#define W_PROMO CU_TENSOR_MAP_L2_PROMOTION_L2_128B
#define Z_ST 1
#define W_FINE 0
#define X128 2
#define T128_ 1
#define W_AT 0
#define SKEW 7
#define AW_NS 0
#define QSH 2
#define EARLY2 1
#define LEAD 3
#define BPRE 2
#define EP_F 1
#define TQ_AT 0
#define LAG_0 8
#define LAG_G 0
#define LAG_S 0
#define O_AT 0
#define XB 0
#define V_E 0
#define LAG_T 1
#define E3M 0
#define B_ST 1
#define TW_L 1
#define PRE_AT B_SC

namespace {
constexpr int wunr = WUNR;

constexpr int S_ = 2048, D_ = 1024, NSEG = 64;
constexpr uint32_t SENT = 0xFFFFFFFFu;
constexpr int NSLOT = 4;

constexpr uint32_t M_REG = 1 << 21, M_E3 = 64 * 16384, M_KVQ = M_E3 + 4 * 8192, M_SEL = M_KVQ + 32 * 24576;
__device__ __align__(1024) unsigned char g_mail[5 * M_REG];
constexpr int C_P1 = 0, C_COLS = C_P1 + 32, C_EARLY = C_COLS + 32, C_LAST = C_EARLY + 32, C_ROWS = C_LAST + 128, C_END = C_ROWS + 8 * 32;
__device__ __align__(1024) uint32_t g_ctl[C_END];
#define CLK(i)
#define TL(i)
#define TL2(i)
#define FT(i, v)
#define GT(i)
#define CNT(i)
__device__ __align__(1024) __nv_bfloat16 g_ox[S_ * 4096];
__device__ __align__(1024) float2 g_z[257 * 4096];
__device__ __align__(1024) __nv_bfloat16 g_b[S_ * D_];
__device__ float g_gate[S_];
__device__ __align__(1024) float2 g_tw[1024];

#define TRV(s, ev, val)
#define TR(s, ev)
#define TRSYNC(ev)
__device__ __forceinline__ uint32_t smem_u32(const void* p) { return (uint32_t)__cvta_generic_to_shared(p); }
__device__ __forceinline__ void watchdog(uint32_t& n, uint32_t limit) {
  asm volatile("{ .reg .pred p; add.u32 %0, %0, 1; setp.gt.u32 p, %0, %1; @p trap; }" : "+r"(n) : "r"(limit));
}
__device__ __forceinline__ void mbar_init(uint32_t bar, uint32_t cnt) {
  asm volatile("mbarrier.init.shared::cta.b64 [%0], %1;" :: "r"(bar), "r"(cnt) : "memory");
}
__device__ __forceinline__ void mbar_arrive_warp(uint32_t bar) {
  __syncwarp();
  asm volatile("{ .reg .pred p; elect.sync _|p, 0xffffffff; @p mbarrier.arrive.shared::cta.b64 _, [%0]; }" :: "r"(bar) : "memory");
}
__device__ __forceinline__ uint32_t clock_lo() {
  uint32_t r; asm volatile("{ .reg .u64 c; .reg .u32 h; mov.u64 c, %%clock64; mov.b64 {%0, h}, c; }" : "=r"(r) :: "memory"); return r;
}
__device__ __forceinline__ void delay_until(uint32_t t) {
  asm volatile("{ .reg .pred p; .reg .u64 c; .reg .u32 l, h;\n"
               "DLY: mov.u64 c, %%clock64; mov.b64 {l, h}, c; sub.s32 l, l, %0; setp.lt.s32 p, l, 0; @p bra.uni DLY; }" :: "r"(t) : "memory");
}
__device__ __forceinline__ void delay_fine(uint32_t t) {
  delay_until(t);
}
__device__ __forceinline__ void delay_cycles(uint32_t n) { delay_until(clock_lo() + n); }
__device__ __forceinline__ void sched_fence(uint32_t z) {
  asm volatile("{ .reg .pred p; setp.eq.u32 p, %0, 0x7fff0000; @p pmevent 1; }" :: "r"(z) : "memory");
}
__device__ __forceinline__ void pdl_wait() { asm volatile("griddepcontrol.wait;" ::: "memory"); }
__device__ __forceinline__ void pdl_launch() { asm volatile("griddepcontrol.launch_dependents;" ::: "memory"); }
__device__ __forceinline__ float ex2(float x) { float r; asm("ex2.approx.ftz.f32 %0, %1;" : "=f"(r) : "f"(x)); return r; }
__device__ __forceinline__ float rcp(float x) { float r; asm("rcp.approx.ftz.f32 %0, %1;" : "=f"(r) : "f"(x)); return r; }
__device__ __forceinline__ void mbar_expect(uint32_t bar, uint32_t bytes) {
  asm volatile("mbarrier.arrive.expect_tx.shared::cta.b64 _, [%0], %1;" :: "r"(bar), "r"(bytes) : "memory");
}
__device__ __forceinline__ bool mbar_try(uint32_t bar, uint32_t ph) {
  uint32_t ok;
  asm volatile("{ .reg .pred p; mbarrier.try_wait.parity.shared::cta.b64 p, [%1], %2; selp.u32 %0, 1, 0, p; }"
               : "=r"(ok) : "r"(bar), "r"(ph) : "memory");
  return ok;
}
__device__ __forceinline__ void mbar_wait(uint32_t bar, uint32_t ph) {
  uint32_t n = 0;
  while (!mbar_try(bar, ph)) { watchdog(n, (1u << 20)); }
}
__device__ __forceinline__ void mbar_spin(uint32_t bar, uint32_t ph) { while (!mbar_try(bar, ph)) {} }
__device__ __forceinline__ void mbar_spin_if(uint32_t bar, uint32_t ph, bool on) {
  asm volatile("{ .reg .pred p, q; setp.ne.u32 p, %2, 0;\n"
               "SPN: setp.eq.u32 q, 0, 0; @p mbarrier.try_wait.parity.shared::cta.b64 q, [%0], %1; @!q bra.uni SPN; }" :: "r"(bar), "r"(ph), "r"((uint32_t)on) : "memory");
}
__device__ __forceinline__ void mbar_spin2_if(uint32_t bar, uint32_t bar2, uint32_t ph, bool on) {
  asm volatile("{ .reg .pred p, q, r; setp.ne.u32 p, %3, 0;\n"
               "SPN: setp.eq.u32 q, 0, 0; setp.eq.u32 r, 0, 0; @p mbarrier.try_wait.parity.shared::cta.b64 q, [%0], %2;\n"
               "@p mbarrier.try_wait.parity.shared::cta.b64 r, [%1], %2; and.pred q, q, r; @!q bra.uni SPN; }" :: "r"(bar), "r"(bar2), "r"(ph), "r"((uint32_t)on) : "memory");
}
__device__ __forceinline__ void mbar_spin_cluster(uint32_t bar, uint32_t ph) {
  uint32_t ok;
  do {
    asm volatile("{ .reg .pred p; mbarrier.try_wait.parity.acquire.cluster.shared::cta.b64 p, [%1], %2; selp.u32 %0, 1, 0, p; }"
                 : "=r"(ok) : "r"(bar), "r"(ph) : "memory");
  } while (!ok);
}
#define ONCE_H "mov.b64 h, 0x12F0000000000000; "
__device__ __forceinline__ void tma2d(uint32_t dst, const CUtensorMap* tm, int c0, int c1, uint32_t bar) {
  if (ONCE & 32) asm volatile("{ .reg .b64 h; " ONCE_H "cp.async.bulk.tensor.2d.shared::cluster.global.mbarrier::complete_tx::bytes.L2::cache_hint [%0], [%1, {%3, %4}], [%2], h; }"
               :: "r"(dst), "l"(tm), "r"(bar), "r"(c0), "r"(c1) : "memory");
  else asm volatile("cp.async.bulk.tensor.2d.shared::cluster.global.mbarrier::complete_tx::bytes [%0], [%1, {%3, %4}], [%2];"
               :: "r"(dst), "l"(tm), "r"(bar), "r"(c0), "r"(c1) : "memory");
}
__device__ __forceinline__ void mbar_expect_e(uint32_t bar, uint32_t bytes) {
  asm volatile("{ .reg .pred p; elect.sync _|p, 0xffffffff; @p mbarrier.arrive.expect_tx.shared::cta.b64 _, [%0], %1; }" :: "r"(bar), "r"(bytes) : "memory");
}
__device__ __forceinline__ void tma2d_e(uint32_t dst, const CUtensorMap* tm, int c0, int c1, uint32_t bar) {
  asm volatile("{ .reg .pred p; elect.sync _|p, 0xffffffff;\n"
               "@p cp.async.bulk.tensor.2d.shared::cluster.global.mbarrier::complete_tx::bytes [%0], [%1, {%3, %4}], [%2]; }"
               :: "r"(dst), "l"(tm), "r"(bar), "r"(c0), "r"(c1) : "memory");
}
__device__ __forceinline__ void tma2d_st_e(const CUtensorMap* tm, int c0, int c1, uint32_t src) {
  asm volatile("{ .reg .pred p; elect.sync _|p, 0xffffffff;\n"
               "@p cp.async.bulk.tensor.2d.global.shared::cta.bulk_group [%0, {%2, %3}], [%1]; }" :: "l"(tm), "r"(src), "r"(c0), "r"(c1) : "memory");
}
__device__ __forceinline__ void tma2d_out_e(const CUtensorMap* tm, int c0, int c1, uint32_t src) {
  if (EPI) asm volatile("{ .reg .pred p; elect.sync _|p, 0xffffffff;\n"
               "@p cp.reduce.async.bulk.tensor.2d.global.shared::cta.add.bulk_group [%0, {%2, %3}], [%1]; }" :: "l"(tm), "r"(src), "r"(c0), "r"(c1) : "memory");
  else if (ONCE & 16) asm volatile("{ .reg .pred p; .reg .b64 h; " ONCE_H "elect.sync _|p, 0xffffffff;\n"
               "@p cp.async.bulk.tensor.2d.global.shared::cta.bulk_group.L2::cache_hint [%0, {%2, %3}], [%1], h; }" :: "l"(tm), "r"(src), "r"(c0), "r"(c1) : "memory");
  else asm volatile("{ .reg .pred p; elect.sync _|p, 0xffffffff;\n"
               "@p cp.async.bulk.tensor.2d.global.shared::cta.bulk_group [%0, {%2, %3}], [%1]; }" :: "l"(tm), "r"(src), "r"(c0), "r"(c1) : "memory");
}
__device__ __forceinline__ void tma2d_once(uint32_t dst, const CUtensorMap* tm, int c0, int c1, uint32_t bar) {
  asm volatile("{ .reg .pred p; .reg .b64 h; " ONCE_H "elect.sync _|p, 0xffffffff;\n"
               "@p cp.async.bulk.tensor.2d.shared::cluster.global.mbarrier::complete_tx::bytes.L2::cache_hint [%0], [%1, {%3, %4}], [%2], h; }"
               :: "r"(dst), "l"(tm), "r"(bar), "r"(c0), "r"(c1) : "memory");
}
__device__ __forceinline__ void bulk_once(uint32_t dst, const void* src, uint32_t bytes, uint32_t bar) {
  asm volatile("{ .reg .pred p; .reg .b64 h; " ONCE_H "elect.sync _|p, 0xffffffff;\n"
               "@p cp.async.bulk.shared::cluster.global.mbarrier::complete_tx::bytes.L2::cache_hint [%0], [%1], %2, [%3], h; }"
               :: "r"(dst), "l"(src), "r"(bytes), "r"(bar) : "memory");
}
__device__ __forceinline__ void tma4d_e(uint32_t dst, const CUtensorMap* tm, int c2, int c3, uint32_t bar) {
  asm volatile("{ .reg .pred p; .reg .b64 h; " ONCE_H "elect.sync _|p, 0xffffffff;\n"
               "@p cp.async.bulk.tensor.4d.shared::cluster.global.mbarrier::complete_tx::bytes.L2::cache_hint [%0], [%1, {0, 0, %3, %4}], [%2], h; }"
               :: "r"(dst), "l"(tm), "r"(bar), "r"(c2), "r"(c3) : "memory");
}
__device__ __forceinline__ void bulk_load_e(uint32_t dst, const void* src, uint32_t bytes, uint32_t bar) {
  asm volatile("{ .reg .pred p; elect.sync _|p, 0xffffffff;\n"
               "@p cp.async.bulk.shared::cluster.global.mbarrier::complete_tx::bytes [%0], [%1], %2, [%3]; }"
               :: "r"(dst), "l"(src), "r"(bytes), "r"(bar) : "memory");
}
template<bool O> __device__ __forceinline__ void tma2d_o(uint32_t dst, const CUtensorMap* tm, int c0, int c1, uint32_t bar) {
  if (O) tma2d_once(dst, tm, c0, c1, bar); else tma2d_e(dst, tm, c0, c1, bar);
}
__device__ __forceinline__ float2 ld_once(const float2* p) {
  float2 v;
  if (ONCE & 64) asm volatile("{ .reg .b64 h; " ONCE_H "ld.global.cg.L2::cache_hint.v2.f32 {%0, %1}, [%2], h; }" : "=f"(v.x), "=f"(v.y) : "l"(p));
  else v = __ldcg(p);
  return v;
}
template<bool O = false> __device__ __forceinline__ void prefetch2d_e(const CUtensorMap* tm, int c0, int c1) {
  if (O) asm volatile("{ .reg .pred p; .reg .b64 h; " ONCE_H "elect.sync _|p, 0xffffffff;\n"
               "@p cp.async.bulk.prefetch.tensor.2d.L2.global.L2::cache_hint [%0, {%1, %2}], h; }" :: "l"(tm), "r"(c0), "r"(c1) : "memory");
  else asm volatile("{ .reg .pred p; elect.sync _|p, 0xffffffff;\n"
               "@p cp.async.bulk.prefetch.tensor.2d.L2.global [%0, {%1, %2}]; }" :: "l"(tm), "r"(c0), "r"(c1) : "memory");
}
__device__ __forceinline__ void st_pub4(void* p, uint4 v) {
  asm volatile("st.relaxed.gpu.global.v4.u32 [%0], {%1,%2,%3,%4};" :: "l"(p), "r"(v.x), "r"(v.y), "r"(v.z), "r"(v.w) : "memory");
}
__device__ __forceinline__ void st_pub_if(void* p, uint32_t v, bool on) {
  asm volatile("{ .reg .pred p; setp.ne.u32 p, %2, 0; @p st.relaxed.gpu.global.u32 [%0], %1; }" :: "l"(p), "r"(v), "r"((uint32_t)on) : "memory");
}
__device__ __forceinline__ uint32_t mapa(uint32_t a, uint32_t r) {
  uint32_t d; asm volatile("mapa.shared::cluster.u32 %0, %1, %2;" : "=r"(d) : "r"(a), "r"(r)); return d;
}
__device__ __forceinline__ void st_async4(uint32_t a, uint32_t x, uint32_t y, uint32_t z, uint32_t w, uint32_t bar) {
  asm volatile("st.async.shared::cluster.mbarrier::complete_tx::bytes.v4.u32 [%0], {%1,%2,%3,%4}, [%5];"
               :: "r"(a), "r"(x), "r"(y), "r"(z), "r"(w), "r"(bar) : "memory");
}
__device__ __forceinline__ uint4 ld_poll(const void* p) {
  uint4 v;
  asm volatile("ld.volatile.global.v4.u32 {%0,%1,%2,%3}, [%4];" : "=r"(v.x), "=r"(v.y), "=r"(v.z), "=r"(v.w) : "l"(p) : "memory");
  return v;
}
__device__ __forceinline__ uint2 ld_poll2(const void* p) {
  uint2 v; asm volatile("ld.volatile.global.v2.u32 {%0,%1}, [%2];" : "=r"(v.x), "=r"(v.y) : "l"(p) : "memory"); return v;
}
__device__ __forceinline__ void st_pub2(void* p, uint32_t a, uint32_t b) {
  asm volatile("st.relaxed.gpu.global.v2.u32 [%0], {%1,%2};" :: "l"(p), "r"(a), "r"(b) : "memory");
}
__device__ __forceinline__ uint32_t ld_poll1(const void* p) {
  uint32_t v; asm volatile("ld.volatile.global.u32 %0, [%1];" : "=r"(v) : "l"(p) : "memory"); return v;
}
__device__ __forceinline__ uint32_t ld_acquire(const uint32_t* p) {
  uint32_t v; asm volatile("ld.acquire.gpu.global.u32 %0, [%1];" : "=r"(v) : "l"(p) : "memory"); return v;
}
__device__ __forceinline__ void st_pub(void* p, uint32_t v) {
  asm volatile("st.relaxed.gpu.global.u32 [%0], %1;" :: "l"(p), "r"(v) : "memory");
}
__device__ __forceinline__ uint32_t lds32(uint32_t a) {
  uint32_t v; asm volatile("ld.shared.u32 %0, [%1];" : "=r"(v) : "r"(a) : "memory"); return v;
}
__device__ __forceinline__ int race_init(void* p0, void* p1, uint32_t val) {
  int t;
  asm volatile("{ .reg .pred r; .reg .u32 a, b, u, v;\n"
               "atom.relaxed.gpu.global.exch.b32 u, [%1], %3; atom.relaxed.gpu.global.exch.b32 v, [%2], %3;\n"
               "setp.eq.u32 r, u, 0x12345; @r pmevent 1; mov.u32 a, %%clock;\n"
               "setp.eq.u32 r, v, 0x12345; @r pmevent 1; mov.u32 b, %%clock; sub.u32 %0, b, a; }" : "=r"(t) : "l"(p0), "l"(p1), "r"(val) : "memory");
  return t;
}
__device__ __forceinline__ void race_init2(void* p0, void* p1, uint32_t val) {
  asm volatile("{ .reg .pred r; .reg .u32 a, b, u, v;\n"
               "atom.relaxed.gpu.global.exch.b32 u, [%0], %2; atom.relaxed.gpu.global.exch.b32 v, [%1], %2;\n"
               "atom.relaxed.gpu.global.exch.b32 a, [%0 + 4096], %2; atom.relaxed.gpu.global.exch.b32 b, [%1 + 4096], %2;\n"
               "lop3.b32 u, u, v, a, 0x96; setp.eq.u32 r, u, 0x12345; setp.eq.and.u32 r, b, u, r; @r pmevent 1; }" :: "l"(p0), "l"(p1), "r"(val) : "memory");
}
__device__ __forceinline__ uint4 lds128(uint32_t a) {
  uint4 v; asm volatile("ld.shared.v4.u32 {%0,%1,%2,%3}, [%4];" : "=r"(v.x), "=r"(v.y), "=r"(v.z), "=r"(v.w) : "r"(a) : "memory"); return v;
}
__device__ __forceinline__ uint2 lds64(uint32_t a) {
  uint2 v; asm volatile("ld.shared.v2.u32 {%0,%1}, [%2];" : "=r"(v.x), "=r"(v.y) : "r"(a) : "memory"); return v;
}
__device__ __forceinline__ void sts128(uint32_t a, uint4 v) {
  asm volatile("st.shared.v4.u32 [%0], {%1,%2,%3,%4};" :: "r"(a), "r"(v.x), "r"(v.y), "r"(v.z), "r"(v.w) : "memory");
}
__device__ __forceinline__ void sts64(uint32_t a, uint32_t x, uint32_t y) { asm volatile("st.shared.v2.u32 [%0], {%1,%2};" :: "r"(a), "r"(x), "r"(y) : "memory"); }
__device__ __forceinline__ void sts32(uint32_t a, uint32_t x) { asm volatile("st.shared.u32 [%0], %1;" :: "r"(a), "r"(x) : "memory"); }
__device__ __forceinline__ void ldsm4t(uint32_t (&r)[4], uint32_t a) {
  asm volatile("ldmatrix.sync.aligned.m8n8.x4.trans.shared.b16 {%0,%1,%2,%3}, [%4];"
               : "=r"(r[0]), "=r"(r[1]), "=r"(r[2]), "=r"(r[3]) : "r"(a) : "memory");
}
__device__ __forceinline__ void ldsm4(uint32_t (&r)[4], uint32_t a) {
  asm volatile("ldmatrix.sync.aligned.m8n8.x4.shared.b16 {%0,%1,%2,%3}, [%4];"
               : "=r"(r[0]), "=r"(r[1]), "=r"(r[2]), "=r"(r[3]) : "r"(a) : "memory");
}
template<bool TRANS> __device__ __forceinline__ void stsm4(uint32_t a, uint32_t r0, uint32_t r1, uint32_t r2, uint32_t r3) {
  if (TRANS) asm volatile("stmatrix.sync.aligned.m8n8.x4.trans.shared.b16 [%0], {%1,%2,%3,%4};" :: "r"(a), "r"(r0), "r"(r1), "r"(r2), "r"(r3) : "memory");
  else       asm volatile("stmatrix.sync.aligned.m8n8.x4.shared.b16 [%0], {%1,%2,%3,%4};" :: "r"(a), "r"(r0), "r"(r1), "r"(r2), "r"(r3) : "memory");
}
__device__ __forceinline__ void mma16816(float (&d)[4], uint32_t a0, uint32_t a1, uint32_t a2, uint32_t a3, uint32_t b0, uint32_t b1) {
  asm volatile("mma.sync.aligned.m16n8k16.row.col.f32.bf16.bf16.f32 {%0,%1,%2,%3}, {%4,%5,%6,%7}, {%8,%9}, {%0,%1,%2,%3};"
               : "+f"(d[0]), "+f"(d[1]), "+f"(d[2]), "+f"(d[3]) : "r"(a0), "r"(a1), "r"(a2), "r"(a3), "r"(b0), "r"(b1));
}
__device__ __forceinline__ void mma1688(float (&d)[4], uint32_t a0, uint32_t a1, uint32_t b0) {
  asm volatile("mma.sync.aligned.m16n8k8.row.col.f32.bf16.bf16.f32 {%0,%1,%2,%3}, {%4,%5}, {%6}, {%0,%1,%2,%3};"
               : "+f"(d[0]), "+f"(d[1]), "+f"(d[2]), "+f"(d[3]) : "r"(a0), "r"(a1), "r"(b0));
}
__device__ __forceinline__ uint32_t pack_bf16(float lo, float hi) {
  uint32_t r; asm("cvt.rn.bf16x2.f32 %0, %1, %2;" : "=r"(r) : "f"(hi), "f"(lo)); return r;
}
__device__ __forceinline__ uint32_t add_bf16x2(uint32_t a, uint32_t b) {
  uint32_t r; asm("add.rn.bf16x2 %0, %1, %2;" : "=r"(r) : "r"(a), "r"(b)); return r;
}
__device__ __forceinline__ uint32_t umax4(uint4 v) { return max(max(v.x, v.y), max(v.z, v.w)); }
__device__ __forceinline__ uint32_t opaque(uint32_t x) { uint32_t r; asm volatile("mov.u32 %0, %1;" : "=r"(r) : "r"(x)); return r; }
template<class T> __device__ __forceinline__ void pin(T*& p) { asm volatile("" : "+l"(p)); }
__device__ __forceinline__ void pin(uint32_t& v) { asm volatile("" : "+r"(v)); }
__device__ __forceinline__ uint32_t desc_lo(uint32_t addr) { return ((addr & 0x3FFFF) >> 4) | 0x10000; }
__device__ __forceinline__ uint64_t desc128(uint32_t lo) {
  uint64_t d; asm("mov.b64 %0, {%1, %2};" : "=l"(d) : "r"(lo), "r"(0x40000040)); return d;
}
#define WG_FENCE()  asm volatile("wgmma.fence.sync.aligned;" ::: "memory")
#define WG_COMMIT() asm volatile("wgmma.commit_group.sync.aligned;" ::: "memory")
#define WG_WAIT(n)  asm volatile("wgmma.wait_group.sync.aligned " #n ";" ::: "memory")
#define FENCE_ASYNC_SMEM() asm volatile("fence.proxy.async.shared::cta;" ::: "memory")
__device__ __forceinline__ void bar_sync(int id, int n) { asm volatile("bar.sync %0, %1;" :: "r"(id), "r"(n) : "memory"); }

#define D16(c) c(d[0]), c(d[1]), c(d[2]), c(d[3]), c(d[4]), c(d[5]), c(d[6]), c(d[7]), \
               c(d[8]), c(d[9]), c(d[10]), c(d[11]), c(d[12]), c(d[13]), c(d[14]), c(d[15])
template<bool FIRST> __device__ __forceinline__ void wgmma_rs_n32(float (&d)[16], const uint32_t (&a)[4], uint64_t b) {
  if (FIRST)
    asm volatile("wgmma.mma_async.sync.aligned.m64n32k16.f32.bf16.bf16 {%0,%1,%2,%3,%4,%5,%6,%7,%8,%9,%10,%11,%12,%13,%14,%15}, {%16,%17,%18,%19}, %20, 0, 1, 1, 0;"
      : D16("=f") : "r"(a[0]), "r"(a[1]), "r"(a[2]), "r"(a[3]), "l"(b));
  else
    asm volatile("wgmma.mma_async.sync.aligned.m64n32k16.f32.bf16.bf16 {%0,%1,%2,%3,%4,%5,%6,%7,%8,%9,%10,%11,%12,%13,%14,%15}, {%16,%17,%18,%19}, %20, 1, 1, 1, 0;"
      : D16("+f") : "r"(a[0]), "r"(a[1]), "r"(a[2]), "r"(a[3]), "l"(b));
}
template<bool FIRST> __device__ __forceinline__ void wgmma_ss_n32_ta(float (&d)[16], uint64_t a, uint64_t b) {
  if (FIRST)
    asm volatile("wgmma.mma_async.sync.aligned.m64n32k16.f32.bf16.bf16 {%0,%1,%2,%3,%4,%5,%6,%7,%8,%9,%10,%11,%12,%13,%14,%15}, %16, %17, 0, 1, 1, 1, 0;"
      : D16("=f") : "l"(a), "l"(b));
  else
    asm volatile("wgmma.mma_async.sync.aligned.m64n32k16.f32.bf16.bf16 {%0,%1,%2,%3,%4,%5,%6,%7,%8,%9,%10,%11,%12,%13,%14,%15}, %16, %17, 1, 1, 1, 1, 0;"
      : D16("+f") : "l"(a), "l"(b));
}
__device__ __forceinline__ void wgmma_ss_n128_tb(float (&d)[64], uint64_t a, uint64_t b) {
  asm volatile("wgmma.mma_async.sync.aligned.m64n128k16.f32.bf16.bf16 "
    "{%0,%1,%2,%3,%4,%5,%6,%7,%8,%9,%10,%11,%12,%13,%14,%15,%16,%17,%18,%19,%20,%21,%22,%23,%24,%25,%26,%27,%28,%29,%30,%31,"
    "%32,%33,%34,%35,%36,%37,%38,%39,%40,%41,%42,%43,%44,%45,%46,%47,%48,%49,%50,%51,%52,%53,%54,%55,%56,%57,%58,%59,%60,%61,%62,%63}, "
    "%64, %65, 1, 1, 1, 0, 1;"
    : "+f"(d[0]), "+f"(d[1]), "+f"(d[2]), "+f"(d[3]), "+f"(d[4]), "+f"(d[5]), "+f"(d[6]), "+f"(d[7]),
      "+f"(d[8]), "+f"(d[9]), "+f"(d[10]), "+f"(d[11]), "+f"(d[12]), "+f"(d[13]), "+f"(d[14]), "+f"(d[15]),
      "+f"(d[16]), "+f"(d[17]), "+f"(d[18]), "+f"(d[19]), "+f"(d[20]), "+f"(d[21]), "+f"(d[22]), "+f"(d[23]),
      "+f"(d[24]), "+f"(d[25]), "+f"(d[26]), "+f"(d[27]), "+f"(d[28]), "+f"(d[29]), "+f"(d[30]), "+f"(d[31]),
      "+f"(d[32]), "+f"(d[33]), "+f"(d[34]), "+f"(d[35]), "+f"(d[36]), "+f"(d[37]), "+f"(d[38]), "+f"(d[39]),
      "+f"(d[40]), "+f"(d[41]), "+f"(d[42]), "+f"(d[43]), "+f"(d[44]), "+f"(d[45]), "+f"(d[46]), "+f"(d[47]),
      "+f"(d[48]), "+f"(d[49]), "+f"(d[50]), "+f"(d[51]), "+f"(d[52]), "+f"(d[53]), "+f"(d[54]), "+f"(d[55]),
      "+f"(d[56]), "+f"(d[57]), "+f"(d[58]), "+f"(d[59]), "+f"(d[60]), "+f"(d[61]), "+f"(d[62]), "+f"(d[63])
    : "l"(a), "l"(b));
}

__device__ __forceinline__ void tma3d_mc_e(uint32_t dst, const CUtensorMap* tm, int c1, int c2, uint32_t bar) {
  asm volatile("{ .reg .pred p; .reg .b64 h; " ONCE_H "elect.sync _|p, 0xffffffff;\n"
               "@p cp.async.bulk.tensor.3d.shared::cluster.global.mbarrier::complete_tx::bytes.multicast::cluster.L2::cache_hint [%0], [%1, {0, %3, %4}], [%2], %5, h; }"
               :: "r"(dst), "l"(tm), "r"(bar), "r"(c1), "r"(c2), "h"((uint16_t)3) : "memory");
}
__device__ __forceinline__ void prefetch3d_e(const CUtensorMap* tm, int c1, int c2) {
  asm volatile("{ .reg .pred p; elect.sync _|p, 0xffffffff;\n"
               "@p cp.async.bulk.prefetch.tensor.3d.L2.global [%0, {0, %1, %2}]; }" :: "l"(tm), "r"(c1), "r"(c2) : "memory");
}

__device__ __forceinline__ void count_e(uint32_t* p) {
  asm volatile("fence.acq_rel.gpu;" ::: "memory");
  __syncwarp();
  asm volatile("{ .reg .pred p; elect.sync _|p, 0xffffffff; @p red.relaxed.gpu.global.add.u32 [%0], 1; }" :: "l"(p) : "memory");
}
template<int NS = 0> __device__ __forceinline__ void await_count(const uint32_t* p, uint32_t n) {
  for (uint32_t i = 0; ld_acquire(p) < n && i < (1u << 22); i++) { if (NS) __nanosleep(NS); }
  asm volatile("fence.proxy.async.global;" ::: "memory");
}
__device__ __forceinline__ void await_flags(const uint32_t* p) {
  for (uint32_t i = 0; i < (1u << 22); i++) {
    uint4 v;
    asm volatile("ld.acquire.gpu.global.v4.u32 {%0,%1,%2,%3}, [%4];" : "=r"(v.x), "=r"(v.y), "=r"(v.z), "=r"(v.w) : "l"(p) : "memory");
    if (__all_sync(~0u, (v.x & v.y & v.z & v.w) == 0x01010101u)) break;
  }
  asm volatile("fence.proxy.async.global;" ::: "memory");
}
__device__ __forceinline__ void mbar_lim(uint32_t bar, uint32_t ph) { for (uint32_t i = 0; !mbar_try(bar, ph) && i < (1u << 20); i++) {} }

struct cf { float x, y; };
__host__ __device__ constexpr float cos64(int k) {
  return k == 0 ? 1.0f : k == 1 ? 0.99518472667219689f : k == 2 ? 0.98078528040323045f : k == 3 ? 0.95694033573220887f :
         k == 4 ? 0.92387953251128676f : k == 5 ? 0.88192126434835503f : k == 6 ? 0.83146961230254524f : k == 7 ? 0.77301045336273696f :
         k == 8 ? 0.70710678118654752f : k == 9 ? 0.63439328416364550f : k == 10 ? 0.55557023301960222f : k == 11 ? 0.47139673682599765f :
         k == 12 ? 0.38268343236508977f : k == 13 ? 0.29028467725446236f : k == 14 ? 0.19509032201612827f : k == 15 ? 0.09801714032956060f : 0.0f;
}
__host__ __device__ constexpr float c64(int k) { return k <= 16 ? cos64(k) : -cos64(32 - k); }
__host__ __device__ constexpr float s64(int k) { return k <= 16 ? cos64(16 - k) : cos64(k - 16); }

template<int N, int ST, bool INV> struct Fft {
  template<int K> static __device__ __forceinline__ void bf(const cf* e, const cf* o, cf* out) {
    if constexpr (K < N / 2) {
      constexpr int idx = K * (64 / N);
      const cf a = e[K], b = o[K];
      if constexpr (idx == 0) {
        out[K] = {a.x + b.x, a.y + b.y}; out[K + N / 2] = {a.x - b.x, a.y - b.y};
      } else if constexpr (idx == 16) {
        if constexpr (INV) { out[K] = {a.x - b.y, a.y + b.x}; out[K + N / 2] = {a.x + b.y, a.y - b.x}; }
        else               { out[K] = {a.x + b.y, a.y - b.x}; out[K + N / 2] = {a.x - b.y, a.y + b.x}; }
      } else {
        constexpr float c = c64(idx), s = INV ? s64(idx) : -s64(idx);
        cf p; p.x = fmaf(-s, b.y, fmaf(c, b.x, a.x)); p.y = fmaf(s, b.x, fmaf(c, b.y, a.y));
        out[K] = p; out[K + N / 2] = {fmaf(2.0f, a.x, -p.x), fmaf(2.0f, a.y, -p.y)};
      }
      bf<K + 1>(e, o, out);
    }
  }
  static __device__ __forceinline__ void run(const cf* in, cf* out) {
    cf e[N / 2], o[N / 2];
    Fft<N / 2, 2 * ST, INV>::run(in, e);
    Fft<N / 2, 2 * ST, INV>::run(in + ST, o);
    bf<0>(e, o, out);
  }
};
template<int ST, bool INV> struct Fft<1, ST, INV> {
  static __device__ __forceinline__ void run(const cf* in, cf* out) { out[0] = in[0]; }
};
template<bool INV> __device__ __forceinline__ void fft32(cf (&v)[32]) {
  cf o[32]; Fft<32, 1, INV>::run(v, o);
#pragma unroll
  for (int i = 0; i < 32; i++) v[i] = o[i];
}
__device__ __forceinline__ cf cmul(cf a, float c, float s) { return {fmaf(-a.y, s, a.x * c), fmaf(a.x, s, a.y * c)}; }
__device__ __forceinline__ float bf2f(__nv_bfloat16 v) { return __bfloat162float(v); }

__device__ __forceinline__ int tw_at(int i) { return (i & ~63) | (i & 31) << 1 | (i >> 5 & 1); }
template<bool INV, bool T128 = true> __device__ __forceinline__ void twiddles(cf (&v)[32], const float4* __restrict__ tw) {
#pragma unroll
  for (int j = 0; j < 32; j += 2) {
    float4 w;
    if (T128) w = tw[j * 16];
    else { const uint2 a = lds64(smem_u32(tw + j * 16)), b = lds64(smem_u32(tw + j * 16) + 8); w = make_float4(__uint_as_float(a.x), __uint_as_float(a.y), __uint_as_float(b.x), __uint_as_float(b.y)); }
    if (j) v[j] = cmul(v[j], w.x, INV ? -w.y : w.y);
    v[j + 1] = cmul(v[j + 1], w.z, INV ? -w.w : w.w);
  }
}
template<bool INV, class F> __device__ __forceinline__ void warp_fft1024(cf (&v)[32], float2* __restrict__ buf, const float2* __restrict__ tw, int t, int u, F mid) {
#pragma unroll 1
  for (uint32_t h = 0; h < 2; h++) {
    fft32<INV>(v);
    if (FUNR ? h : opaque(h)) continue;
    twiddles<INV>(v, (const float4*)tw + u);
    if (INV) {
      float* f = (float*)buf;
#pragma unroll
      for (int j = 0; j < 32; j++) f[j * 36 + t] = v[j].x;
      __syncwarp();
#pragma unroll
      for (int j = 0; j < 32; j += 4) { const float4 r = *(const float4*)(f + u * 36 + j); v[j].x = r.x; v[j + 1].x = r.y; v[j + 2].x = r.z; v[j + 3].x = r.w; }
      __syncwarp();
#pragma unroll
      for (int j = 0; j < 32; j++) f[j * 36 + t] = v[j].y;
      __syncwarp();
#pragma unroll
      for (int j = 0; j < 32; j += 4) { const float4 r = *(const float4*)(f + u * 36 + j); v[j].y = r.x; v[j + 1].y = r.y; v[j + 2].y = r.z; v[j + 3].y = r.w; }
    } else {
#pragma unroll
      for (int j = 0; j < 32; j++) buf[j * 33 + t] = make_float2(v[j].x, v[j].y);
      __syncwarp();
#pragma unroll
      for (int j = 0; j < 32; j++) { const float2 r = buf[u * 33 + j]; v[j] = {r.x, r.y}; }
    }
    __syncwarp();
    mid();
  }
}
constexpr int ROW_BUF = 32 * 33, INV_BUF = 32 * 18;

__device__ __forceinline__ int z_row(int p) { return (p & ~31) | (p & 7) << 2 | (p & 31) >> 3; }
__device__ __forceinline__ int inv_lane(int t) { return (t & ~14) | (t & 12) >> 1 | (t & 2) << 2; }
__device__ __forceinline__ float2 twiddle(int i) { float s, c; sincospif(-(float)((i >> 5) * (i & 31)) * (1.0f / 512.0f), &s, &c); return make_float2(c, s); }
template<class F, class G> __device__ __forceinline__ void fft_rows_fwd(float2* sm2, const __nv_bfloat16* gw, int cta, int tid, uint32_t full_bar, uint32_t release_bar, F ev, G extra) {
  const int t = tid & 31, w = tid >> 5, n = z_row(cta * 8 + w);
#pragma unroll 1
  for (int i = tid; i < 1024; i += 256) sm2[tw_at(i)] = twiddle(i);
  ev(5);
  mbar_spin(full_bar, 0);
  if (tid == 0) TL2(6);
  __syncwarp();
  const __nv_bfloat16* xa = (const __nv_bfloat16*)(sm2 + 1024 + w * ROW_BUF) + t;
  cf v[32];
  float ga = 0.f, gb = 0.f;
#pragma unroll
  for (int j = 0; j < 32; j++) {
    v[j] = {bf2f(xa[32 * j]), bf2f(xa[D_ + 32 * j])};
    const float g = bf2f(gw[32 * j + t]); ga = fmaf(v[j].x, g, ga); gb = fmaf(v[j].y, g, gb);
  }
#pragma unroll
  for (int o = 16; o; o >>= 1) { ga += __shfl_xor_sync(~0u, ga, o); gb += __shfl_xor_sync(~0u, gb, o); }
  if (t < 2) g_gate[n + 1024 * t] = __fdividef(1.0f, 1.0f + __expf(-(t ? gb : ga)));
  ev(6);
  bar_sync(13, 256);
  warp_fft1024<false>(v, sm2 + 1024 + w * ROW_BUF, sm2, t, t, [&]() { FENCE_ASYNC_SMEM(); mbar_arrive_warp(release_bar); });
  float ws, wc; sincospif(-(float)n * (1.0f / 1024.0f), &ws, &wc);
  ev(12);
  uint32_t tz = clock_lo();
  float4* z = (float4*)g_z + ((size_t)(t >> 1) * 1024 + cta * 8 + w) * 2 + (t & 1);
#pragma unroll
  for (int j = 0; j < 17; j++) {
    cf q = v[(32 - j) & 31];
    if (j < 16) {
      const cf r = {__shfl_sync(~0u, v[31 - j].x, 32 - t), __shfl_sync(~0u, v[31 - j].y, 32 - t)};
      if (t != 0) q = r;
    }
    const cf a = {v[j].x + q.x, v[j].y - q.y}, b = {v[j].y + q.y, q.x - v[j].x};
    const cf d = cmul({a.x - b.x, a.y - b.y}, wc, ws);
    if (j == POOL_AT) extra();
    if (PACE_Z && j && j < 16) delay_until(tz += PACE_Z);
    if ((j < 16 || t == 0) && ((EXP_ST & 4) || d.x == 123.f)) z[j * 32768] = make_float4(a.x + b.x, a.y + b.y, d.x, d.y);
  }
}
constexpr int CP = X128 == 0 ? 33 : X128 == 2 ? 34 : 36, COL_FS = 32 * 36 + 8, COL_W = (8192 + 16 * COL_FS * 4 + 127) & ~127, COL_SMEM = COL_W + 131072 + 128;

__device__ __forceinline__ void fft_cols(float2* sm2, int cta, const CUtensorMap* twr, const CUtensorMap* twi, const CUtensorMap* tzs) {
  const int grp = __shfl_sync(~0u, (int)(threadIdx.x >> 7), 0), tid = threadIdx.x & 127, tp = tid >> 2, w = __shfl_sync(~0u, tid >> 5, 0);
  float* buf = (float*)(sm2 + 1024) + (grp * 4 + (tid & 3)) * COL_FS;
  const uint32_t wsm = smem_u32(sm2) + COL_W, wbar = wsm + 131072 + (W_FINE ? w * 32 : 0);
  const int res = w * 2 + (tid & 1), el = res + grp * 2 + ((tid >> 1) & 1);
  uint32_t wa = (el >> 3) * 65536 + res * 4096 + (tp & 7) * 16 + (el & 7) * 2;
  auto load_w = [&](int q) {
    const uint32_t bar = wbar + (q & 1) * 8;
    mbar_expect(bar, W_FINE ? 16384 : 65536);
#pragma unroll 1
    for (int i = W_FINE ? 4 * w : 0; i < (W_FINE ? 4 * w + 4 : 16); i++) tma2d(wsm + (q & 1) * 65536 + (i & 1) * 32768 + (i >> 1) * 4096, i & 1 ? twi : twr, (i >> 1) * 512 + q * 8, 0, bar);
  };
  const bool lead = (tid & (W_FINE ? 31 : 127)) == 0, first = grp < 2 && lead;
  if (first) { mbar_init(wbar + grp * 8, 1); sts32(wbar + 16 + grp * 4, grp ? 0 : w); asm volatile("fence.mbarrier_init.release.cluster;" ::: "memory"); }
#pragma unroll 1
  for (int i = threadIdx.x; i < 1024; i += 512) {
    const float2 t = twiddle(z_row(i));
    sm2[tw_at(i)] = t;
    if (cta == 0) g_tw[tw_at(inv_lane(z_row(i)))] = t;
  }
  for (uint32_t n = 0; ld_acquire(g_ctl + C_P1) < 128; ) { watchdog(n, 1u << 22); __nanosleep(200); }
  if (COL_DLY) delay_cycles(COL_DLY);
  if (first) load_w(cta * 16 + grp);
  __syncthreads();
  delay_cycles(1 + grp * DLY_GRP);
  mbar_wait(wbar, 0);
  const int end = cta * 64 + 64 + (cta == 3);
  for (int item = cta * 64 + grp; item < end; item += 4, wa ^= 65536) {
    float2* zp = g_z + (size_t)item * 4096;
    auto next_w = [&]() {
      const int q = (item >> 2) + (W_FINE && grp + w > 3);
      uint32_t n; asm volatile("atom.shared.inc.u32 %0, [%1], 3;" : "=r"(n) : "r"(wbar + 16 + (q & 1) * 4) : "memory");
      if (EXP_W && n == 3 && q < (cta * 16 + 15)) load_w(q + 2);
    };
    cf v[32];
#pragma unroll
    for (int j = 0; j < 32; j++) { const float2 a = ld_once(zp + tid + j * 128); v[j] = {a.x, a.y}; }
#pragma unroll 1
    for (int ph = 0; ; ph++) {
      fft32<false>(v);
      twiddles<false, T128_>(v, (const float4*)sm2 + tp);
      if (Z_ST) asm volatile("cp.async.bulk.wait_group.read 0;" ::: "memory");
      bar_sync(1 + grp, 128);
      if (lead) {
        if (ph) {
          if (!W_AT) next_w();
        } else if (Z_PF && item + 4 < end) asm volatile("cp.async.bulk.prefetch.L2.global [%0], %1;" :: "l"(zp + 4 * 4096 + w * 1024), "n"(W_FINE ? 8192 : 32768) : "memory");
      }
      __syncwarp();
#pragma unroll
      for (int j = 0; j < 32; j++) buf[((j & 3) * 8 + (j >> 2)) * CP + tp] = v[j].x;
      bar_sync(1 + grp, 128);
      if (X128 == 0) {
#pragma unroll
        for (int j = 0; j < 32; j++) v[j].x = buf[tp * CP + (j & 3) * 8 + (j >> 2)];
      } else if (X128 == 2) {
#pragma unroll
        for (int j = 0; j < 16; j++) { const float2 r = *(const float2*)(buf + tp * CP + 2 * j); cf* d = v + (j & 3) * 8 + (j >> 2); d[0].x = r.x; d[4].x = r.y; }
      } else
#pragma unroll
      for (int j = 0; j < 8; j++) {
        const float4 r = *(const float4*)(buf + tp * 36 + 4 * j);
        cf* d = v + (j & 1) * 16 + (j >> 1);
        d[0].x = r.x; d[4].x = r.y; d[8].x = r.z; d[12].x = r.w;
      }
      bar_sync(1 + grp, 128);
#pragma unroll
      for (int j = 0; j < 32; j++) buf[((j & 3) * 8 + (j >> 2)) * CP + tp] = v[j].y;
      bar_sync(1 + grp, 128);
      if (X128 == 0) {
#pragma unroll
        for (int j = 0; j < 32; j++) v[j].y = buf[tp * CP + (j & 3) * 8 + (j >> 2)];
      } else if (X128 == 2) {
#pragma unroll
        for (int j = 0; j < 16; j++) { const float2 r = *(const float2*)(buf + tp * CP + 2 * j); cf* d = v + (j & 3) * 8 + (j >> 2); d[0].y = r.x; d[4].y = r.y; }
      } else
#pragma unroll
      for (int j = 0; j < 8; j++) {
        const float4 r = *(const float4*)(buf + tp * 36 + 4 * j);
        cf* d = v + (j & 1) * 16 + (j >> 1);
        d[0].y = r.x; d[4].y = r.y; d[8].y = r.z; d[12].y = r.w;
      }
      fft32<false>(v);
      if (ph) break;
      const int q = min((item >> 2) + (!W_FINE || grp + w >= 3), 64);
      if (EXP_W) mbar_wait(wbar + (q & 1) * 8, (q >> 1) & 1);
#pragma unroll
      for (int j = 0; j < 32; j++) {
        uint32_t re, im;
        asm volatile("ld.shared.u16 %0, [%1];" : "=r"(re) : "r"(wsm + wa + j * 128) : "memory");
        asm volatile("ld.shared.u16 %0, [%1];" : "=r"(im) : "r"(wsm + wa + 32768 + j * 128) : "memory");
        const cf r = cmul(v[j], __uint_as_float(re << 16), __uint_as_float(im << 16));
        v[j] = {r.y, r.x};
      }
    }
    if (Z_ST) {
      float2* st = sm2 + 1024 + grp * (COL_FS * 2) + w * 512;
      bar_sync(1 + grp, 128);
#pragma unroll
      for (int h = 0; h < 2; h++) {
        if (h && Z_ST == 2) {
#pragma unroll
          for (int j = 16; j < 32; j++) zp[tid + j * 128] = make_float2(v[j].y, v[j].x);
          break;
        }
        if (h) { asm volatile("cp.async.bulk.wait_group.read 0;" ::: "memory"); __syncwarp(); }
#pragma unroll
        for (int j = 0; j < 16; j++) st[j * 32 + (tid & 31)] = make_float2(v[h * 16 + j].y, v[h * 16 + j].x);
        FENCE_ASYNC_SMEM();
        __syncwarp();
        tma2d_st_e(tzs, w * 128, item * 32 + h * 16, smem_u32(st));
        asm volatile("cp.async.bulk.commit_group;" ::: "memory");
      }
    } else {
#pragma unroll
      for (int j = 0; j < 32; j++) zp[tid + j * 128] = make_float2(v[j].y, v[j].x);
    }
    if (W_AT) { if (lead) next_w(); __syncwarp(); }
  }
  if (Z_ST) asm volatile("cp.async.bulk.wait_group 0; fence.proxy.async.global;" ::: "memory");
  const float4 t = ((const float4*)sm2)[threadIdx.x];
  __syncthreads();
  if (TW_L) ((float4*)sm2)[inv_lane(z_row(threadIdx.x))] = t;
  if (threadIdx.x < 32) {
    count_e(g_ctl + C_COLS);
    await_count(g_ctl + C_COLS, 4);
    g_ctl[C_P1] = 0;
  }
  __syncthreads();
  if (!TW_L) {
    ((float4*)sm2)[threadIdx.x] = __ldcg((const float4*)g_tw + threadIdx.x);
    __syncthreads();
  }
}

template<class F> __device__ __forceinline__ void fft_rows_inv(uint32_t zs, float2* buf, const float2* tw, int p, int lane, __nv_bfloat16* out, F read) {
  const int n = z_row(p), t = (lane & 17) | (lane & 6) << 1 | (lane & 8) >> 2, src = inv_lane(-t & 31);
  const uint32_t z = zs + (t >> 1) * 128 + ((((p & 3) * 2 + (t & 1)) ^ (t >> 1 & 7)) << 4);
  FT(0, 0.f);
  float4 e[17];
  uint32_t all = 0;
  e[16] = __ldcg((const float4*)g_z + ((size_t)256 * 1024 + p) * 2);
  const float g0 = __ldcg(g_gate + n), g1 = __ldcg(g_gate + n + 1024);
#pragma unroll
  for (int j = 0; j < 16; j++) { const uint4 u = lds128(z + j * 2048); e[j] = make_float4(__uint_as_float(u.x), __uint_as_float(u.y), __uint_as_float(u.z), __uint_as_float(u.w)); all |= u.x; }
  sched_fence(all);
  read();
  float ws, wc; sincospif((float)n * (1.0f / 1024.0f), &ws, &wc);
  cf v[32], q[17];
#pragma unroll
  for (int j = 0; j < 17; j++) {
    const cf d = cmul({e[j].z, e[j].w}, wc, ws);
    cf a = {e[j].x + d.x, e[j].y + d.y}, b = {e[j].x - d.x, e[j].y - d.y};
    if (j == 16 || (j == 0 && t == 0)) { a.y = 0.f; b.y = 0.f; }
    if (j < 16) v[j] = {a.x - b.y, a.y + b.x};
    q[j] = {a.x + b.y, b.x - a.y};
  }
#pragma unroll
  for (int j = 16; j < 32; j++) {
    v[j] = {__shfl_sync(~0u, q[31 - j].x, src), __shfl_sync(~0u, q[31 - j].y, src)};
    if (t == 0) v[j] = q[32 - j];
  }
  FT(1, v[0].x + v[16].x + v[31].x);
  if (B_ST) { asm volatile("cp.async.bulk.wait_group.read 0;" ::: "memory"); __syncwarp(); }
  warp_fft1024<true>(v, buf, tw, t, lane, []() {});
  FT(3, v[31].y + v[0].x);
  const float sc = 0.5f / (2048.0f * 1024.0f), s0 = (1.f - g0) * sc, s1 = (1.f - g1) * sc;
  uint2* o = (B_ST ? (uint2*)buf : (uint2*)(out + (size_t)n * D_)) + (lane ^ (n & 1) << 3);
#pragma unroll
  for (int j = 0; j < 32; j += 4) {
    o[8 * j] = make_uint2(pack_bf16(v[j].x * s0, v[j + 1].x * s0), pack_bf16(v[j + 2].x * s0, v[j + 3].x * s0));
    o[(B_ST ? 256 : 256 * D_) + 8 * j] = make_uint2(pack_bf16(v[j].y * s1, v[j + 1].y * s1), pack_bf16(v[j + 2].y * s1, v[j + 3].y * s1));
  }
  if (B_ST) {
    FENCE_ASYNC_SMEM();
    __syncwarp();
    asm volatile("{ .reg .pred p; setp.lt.u32 p, %2, 2; @p cp.async.bulk.global.shared::cta.bulk_group [%0], [%1], 2048; cp.async.bulk.commit_group; }"
                 :: "l"(out + (size_t)(n + 1024 * (lane & 1)) * D_), "r"(smem_u32(buf) + (lane & 1) * 2048), "r"(lane) : "memory");
  }
  FT(4, 0.f);
}

constexpr int NP = NP_, NHV = REG_F == 216 ? 5 : 7, NV = 16 - NHV;
constexpr int XEND = NSEG;
constexpr uint32_t SM_WO = 0, SM_V = 65536, SM_LAND = SM_V + 8192, SM_MEM = SM_LAND + 24576, SM_SP = SM_MEM, SM_SPM = SM_MEM + 5120, SM_OM = SM_MEM + 6144,
                   SM_OX = SM_MEM + 8192, SM_RED = SM_OX + 2048, SM_XCH = SM_RED + 1024, SM_SUM = SM_XCH + 4096, SM_VM = SM_SUM + 128, SM_TAB = SM_VM + 2048, SM_TRACE = SM_TAB + 2048,
                   ST_WG = (32 - NP + NV) * 2048,
                   SM_XT = 2 * ST_WG, SM_POOL = SM_XT + 32768, SM_HV = SM_POOL + 2 * NP * 2048,
                   SM_BAR = SM_HV + 2 * NHV * 2048, SM_SEL = SM_BAR + 320, CHAIN_SMEM = SM_SEL + 544 + 1024;
constexpr uint32_t SM_FFT = 49152, SM_GW = SM_XT - 2048;
static_assert(NP % 4 == 0 && NV == 11 && SM_TRACE + 4096 <= SM_XT, "shared memory layout");
static_assert(CHAIN_SMEM <= 232448 && COL_SMEM <= SM_BAR && SM_FFT + (1024 + 8 * ROW_BUF) * 8 <= SM_GW && NP == 12, "shared memory budget");
enum { B_WFULL = 0, B_WREAD = 2, B_WOFULL, B_XFULL, B_XEMPTY, B_E1TRIG, B_E2TRIG, B_PVDONE, B_PUB, B_SC, B_PFULL, B_SPFREE,
       B_LAND, B_LFREE, B_DONE, B_SEL, B_PROBE, B_FREE, B_P1, B_ROWS, B_VFULL, B_VST, B_TW, B_BT, B_WREAD0, B_Z, B_GFULL = B_Z + 4, B_GEMPTY = B_GFULL + 5, B_END = B_GEMPTY + 5 };
static_assert(B_END * 8 <= 320, "barriers");
__host__ __device__ constexpr uint32_t bar_codes(int g) {
  uint32_t r = 0;
  for (int i = 16 * g; i < 16 * g + 16; i++)
    r |= (i == B_LAND ? 3u : i == B_WREAD || i == B_XEMPTY || i == B_E1TRIG || i == B_E2TRIG || i == B_LFREE || i == B_FREE || i == B_VST || i == B_P1 || i == B_ROWS ? 2u :
          i >= B_GEMPTY || i == B_WREAD0 || i == B_PROBE || i == B_DONE || i == B_PVDONE || i == B_PUB || i == B_SC || i == B_SPFREE ? 1u : 0u) << 2 * (i & 15);
  return r;
}
constexpr uint32_t SM_BT = 65536, SM_TW = SM_XT - 8192, COL_Z = 80 * 1024;
static_assert(SM_XT + 3 * 32768 <= SM_BAR && SM_BT + 32768 <= SM_MEM && SM_TRACE <= SM_TW && SM_MEM + 4 * INV_BUF * 8 <= SM_TRACE &&
              8192 + 16 * INV_BUF * 8 <= COL_Z && COL_Z + 131072 <= SM_BAR, "shared memory layout");
__device__ __forceinline__ uint32_t next_stage(uint32_t o) { return o == SM_XT + 65536 ? 0 : o == 32768 ? SM_XT : o + 32768; }

struct ChainCtx { char* mail; uint32_t sb, sel; int r, h, a, b, j, m, w, lane; };
#define BAR(i) (c.sb + SM_BAR + 8 * (i))

__device__ __forceinline__ uint32_t tile_off(int line, int lane) {
  return line * 128 + (((lane & 3) ^ line) << 5) + (lane >> 2) * 4;
}
__device__ __forceinline__ uint32_t read_off(int lane) {
  const int n = lane >> 2, jj = lane & 3, l = 2 * (jj >> 1) + (n & 1);
  return l * 128 + (((n >> 1) ^ l) << 5) + (jj & 1) * 16;
}
__device__ __forceinline__ uint32_t frag_off(int w, int lane) {
  const int mi = lane >> 3, r = lane & 7;
  return ((mi >> 1) * 8 + r) * 128 + (((2 * w + (mi & 1)) ^ r) << 4);
}
__device__ __forceinline__ uint32_t land_off(int w, int lane) { return w * 512 + ((lane ^ (((lane >> 4) | ((w & 1) << 1)) << 1)) << 4); }
__device__ __forceinline__ uint32_t tagged(uint32_t v, uint32_t tag) { return (v | 1u) ^ tag; }
__device__ __forceinline__ void mma_a(float (&d)[4], const uint32_t (&a)[4], uint32_t b0, uint32_t b1) { mma16816(d, a[0], a[1], a[2], a[3], b0, b1); }
__device__ __forceinline__ void mma_q(float (&d)[4], const uint4& a, uint32_t b0, uint32_t b1) { mma16816(d, a.x, a.y, a.z, a.w, b0, b1); }
__device__ __forceinline__ uint4 add4(uint4 a, uint4 b) {
  return make_uint4(add_bf16x2(a.x, b.x), add_bf16x2(a.y, b.y), add_bf16x2(a.z, b.z), add_bf16x2(a.w, b.w));
}
__device__ __forceinline__ void mbar_arrive_both(uint32_t bar, int peer) {
  __syncwarp();
  asm volatile("{ .reg .pred p; .reg .u32 a; mapa.shared::cluster.u32 a, %0, %1; elect.sync _|p, 0xffffffff;\n"
               "@p mbarrier.arrive.shared::cta.b64 _, [%0]; @p mbarrier.arrive.shared::cluster.b64 _, [a]; }" :: "r"(bar), "r"(peer) : "memory");
}

__device__ __forceinline__ void arrive_remote_if(uint32_t a, bool on) {
  asm volatile("{ .reg .pred p; setp.ne.u32 p, %1, 0; @p mbarrier.arrive.shared::cluster.b64 _, [%0]; }" :: "r"(a), "r"((uint32_t)on) : "memory");
}
__device__ __forceinline__ void store_count(void* p, uint4 v, void* cnt) {
  asm volatile("{ .reg .pred p, q; .reg .b128 a, b; .reg .b64 l, h; mov.b64 l, {%1, %2}; mov.b64 h, {%3, %4}; mov.b128 a, {l, h};\n"
               "atom.relaxed.gpu.global.exch.b128 b, [%0], a; mov.b128 {l, h}, b; setp.eq.u64 q, l, 0x7fc17fc17fc17fc1; @q pmevent 1;\n"
               "elect.sync _|p, 0xffffffff; @p red.relaxed.gpu.global.add.u32 [%5], 1; }"
               :: "l"(p), "r"(v.x), "r"(v.y), "r"(v.z), "r"(v.w), "l"(cnt) : "memory");
}

template<int N> __device__ __forceinline__ void pad() {
#pragma unroll
  for (int i = 0; i < N; i++) asm volatile("pmevent 3;");
}
__device__ __forceinline__ int lane_id() {
  int l; asm volatile("{ .reg .u32 t; mov.u32 t, %%laneid; shfl.sync.idx.b32 %0, t, t, 31, 0xffffffff; }" : "=r"(l)); return l;
}
__device__ __forceinline__ uint32_t tid_now() { uint32_t t; asm volatile("mov.u32 %0, %%tid.x;" : "=r"(t)); return t; }
enum { NB_ATT = 1, NB_OM = 2, NB_VM = 3, NB_XCH = 4, NB_MEM = 8, NB_HELP = 12 };
__device__ __forceinline__ uint32_t dep(uint32_t a, uint32_t v, uint32_t z) { uint32_t r; asm("shf.l.wrap.b32 %0, %2, %1, %3;" : "=r"(r) : "r"(a), "r"(v), "r"(z)); return r; }
__device__ __forceinline__ uint32_t vary(uint32_t a, int s, uint32_t z) { return dep(a, 0, z + 32 * s); }
__device__ __forceinline__ char* mk_ptr(uint32_t lo, uint32_t hi) { uint64_t r; asm("mov.b64 %0, {%1, %2};" : "=l"(r) : "r"(lo), "r"(hi)); return (char*)r; }
__device__ __forceinline__ void lds_frag(uint32_t (&r)[4], uint32_t a) {
  asm volatile("ld.shared.v4.u32 {%0,%1,%2,%3}, [%4];" : "=r"(r[0]), "=r"(r[1]), "=r"(r[2]), "=r"(r[3]) : "r"(a) : "memory");
}
__device__ __forceinline__ uint32_t stale2(uint32_t a, uint32_t b, uint32_t t) { uint32_t r; asm("lop3.b32 %0, %1, %2, %3, 0xbd;" : "=r"(r) : "r"(a), "r"(b), "r"(t)); return r; }
__device__ __forceinline__ uint32_t stale1(uint32_t acc, uint32_t a, uint32_t t) { uint32_t r; asm("lop3.b32 %0, %1, %2, %3, 0xf9;" : "=r"(r) : "r"(acc), "r"(a), "r"(t)); return r; }
__device__ __forceinline__ bool all_clear(uint32_t x, uint32_t m) {
  uint32_t r;
  asm volatile("{ .reg .pred p; .reg .u32 t; and.b32 t, %1, %2; setp.eq.u32 p, t, 0; vote.sync.all.pred p, p, 0xffffffff; selp.u32 %0, 1, 0, p; }" : "=r"(r) : "r"(x), "r"(m));
  return r;
}
__device__ __forceinline__ bool arrive_if_all(bool ok, int id, int n) {
  uint32_t r;
  asm volatile("{ .reg .pred p, q; setp.ne.u32 p, %1, 0; vote.sync.all.pred q, p, 0xffffffff; @q bar.arrive %2, %3; selp.u32 %0, 1, 0, q; }"
               : "=r"(r) : "r"((uint32_t)ok), "r"(id), "r"(n) : "memory");
  return r;
}
__device__ __forceinline__ bool arrive_if_clear(uint32_t x, uint32_t m, int id, int n) {
  uint32_t r;
  asm volatile("{ .reg .pred p; .reg .u32 t; and.b32 t, %1, %2; setp.eq.u32 p, t, 0; vote.sync.all.pred p, p, 0xffffffff; @p bar.arrive %3, %4; selp.u32 %0, 1, 0, p; }"
               : "=r"(r) : "r"(x), "r"(m), "r"(id), "r"(n) : "memory");
  return r;
}
__device__ __forceinline__ void touch(const void* p, uint32_t z) {
  asm volatile("{ .reg .pred p; setp.eq.u32 p, %1, 0x7fff0000; @p prefetch.global.L2 [%0]; }" :: "l"(p), "r"(z) : "memory");
}

__device__ __forceinline__ uint64_t desc_x(uint32_t lo, int k) {
  uint64_t d; asm("mov.b64 %0, {%1, %2};" : "=l"(d) : "r"(lo + (k >> 2) * 64 + (k & 3) * 2), "r"(0x40000200)); return d;
}
template<int K0, int K1> __device__ __forceinline__ void issue_qk(float (&xa)[16], const uint32_t (&wt)[16][4], uint32_t lo) {
  WG_FENCE();
#pragma unroll
  for (int k = K0; k < K1; k++) {
    if (k >= EXP_NWG) continue;
    if (k == 0) wgmma_rs_n32<true>(xa, wt[0], desc_x(lo, 0));
    else wgmma_rs_n32<false>(xa, wt[k], desc_x(lo, k));
  }
  WG_COMMIT();
}
__host__ __device__ constexpr int v_order(int i) { return SSPOS == 0 ? i : SSPOS == 2 ? (i + NV) % 16 : NHV == 5 ? (i % 3 == 2 ? NV + i / 3 : i - i / 3) : (i == 15 ? NV - 1 : i % 2 ? NV + i / 2 : i / 2); }
__device__ __forceinline__ void issue_v(float (&xa)[16], const uint32_t (&wv)[16][4], uint32_t lo, uint32_t la) {
  WG_FENCE();
#pragma unroll
  for (int i = 0; i < EXP_NWG; i++) {
    const int k = v_order(i);
    const uint64_t b = desc_x(lo, k);
    if (k < NV) { if (i == 0) wgmma_rs_n32<true>(xa, wv[k], b); else wgmma_rs_n32<false>(xa, wv[k], b); }
    else        { if (i == 0) wgmma_ss_n32_ta<true>(xa, desc128(la + (k - NV) * 128), b); else wgmma_ss_n32_ta<false>(xa, desc128(la + (k - NV) * 128), b); }
  }
  WG_COMMIT();
}
template<bool ISV> __device__ __forceinline__ void park_own(uint32_t (&q)[4], float (&xa)[16], uint32_t dst, int slot, uint32_t z) {
  uint32_t p[8];
#pragma unroll
  for (int i = 0; i < 16; i++) asm volatile("" : "+f"(xa[i]) :: "memory");
#pragma unroll
  for (int i = 0; i < 2; i++) {
    const float* k = xa + 8 * i;
    if (ISV) { p[4 * i] = pack_bf16(k[0], k[1]); p[4 * i + 1] = pack_bf16(k[2], k[3]); p[4 * i + 2] = pack_bf16(k[4], k[5]); p[4 * i + 3] = pack_bf16(k[6], k[7]); }
    else     { p[4 * i] = pack_bf16(k[0], k[2]); p[4 * i + 1] = pack_bf16(k[1], k[3]); p[4 * i + 2] = pack_bf16(k[4], k[6]); p[4 * i + 3] = pack_bf16(k[5], k[7]); }
  }
  sts128(dep(dep(dst, p[4] ^ p[5] ^ p[6], z), p[7], z) + slot * 8192, make_uint4(p[0], p[1], p[2], p[3]));
#pragma unroll
  for (int i = 0; i < 4; i++) q[i] = p[4 + i];
}
__device__ __forceinline__ void park_peer(const uint32_t (&q)[4], uint32_t dst, int slot, const ChainCtx& c) {
  const uint32_t bar = BAR(B_LAND);
  if (EXP_PEER) st_async4(mapa(dst + slot * 8192, c.b ^ 1), q[0], q[1], q[2], q[3], mapa(bar, c.b ^ 1));
  else touch((void*)(uintptr_t)(q[0] ^ q[1] ^ q[2] ^ q[3]), c.sb);
  mbar_arrive_warp(bar);
}
__device__ __forceinline__ uint32_t put_tag(uint32_t v, uint32_t bit, uint32_t t) {
  uint32_t r; asm("lop3.b32 %0, %1, %2, %3, 0x74;" : "=r"(r) : "r"(v), "r"(bit), "r"(t)); return r;
}
__device__ __forceinline__ void mem_proj(const uint32_t (&wa)[16][4], const uint32_t (&wb)[16][4], uint32_t (&wv)[16][4], uint32_t (&af)[16][4],
                                         uint32_t& wo, const char*& pa, uint32_t tab, uint32_t t16, uint32_t pk, const ChainCtx& c, int s) {
  const uint32_t mp = t16 & ~0x600u, id = NB_MEM + (t16 >> 11);
  uint32_t r[8][4];
  float la[4][4] = {}, lg[NLAG][4] = {}, lv[4][4] = {};
  auto lead = [&](int k) { mma_a(la[k & 3], wa[k], r[k >> 1][2 * (k & 1)], r[k >> 1][2 * (k & 1) + 1]); };
  auto lag = [&](int k) { mma_a(lg[k % NLAG], wb[k], r[k >> 1][2 * (k & 1)], r[k >> 1][2 * (k & 1) + 1]); };
  auto sum = [](const float (&d)[4][4], int i) { return (d[0][i] + d[1][i]) + (d[2][i] + d[3][i]); };
  bar_sync(id, 160);
  TR(s, 0);
#pragma unroll
  for (int i = 0; i < 4; i++) ldsm4t(r[i], mp + (c.sb + SM_MEM + i * 512));
  uint4 tq;
  if (!TQ_AT) tq = lds128(tab);
  bar_sync(id + 2, 160);
  uint32_t first = 0;
#pragma unroll
  for (int k = 0; k < 8; k++) { lead(k); if (k == C1_AT - 4) first = dep(mp, __float_as_uint(la[k & 3][0]), c.sb); }
  uint32_t ta, tb;
  if (!TQ_AT) { ta = tq.x | ((pk >> 16) & 511); tb = tq.z ^ ((pk >> 16) & 511); }
  const uint32_t mp1 = C1_AT >= 4 ? (TQ_AT ? first : dep(first, ta ^ tb, c.sb)) : dep(mp, __float_as_uint(la[C1_AT & 3][0]) ^ (TQ_AT ? 0 : ta ^ tb), c.sb);
#pragma unroll
  for (int i = 4; i < 8; i++) ldsm4t(r[i], mp1 + (c.sb + SM_MEM + 2048 + i * 512));
  if (TQ_AT) { tq = lds128(tab); ta = tq.x | ((pk >> 16) & 511); tb = tq.z ^ ((pk >> 16) & 511); }
  char* dst = mk_ptr(ta, tq.y);
  char* dst2 = mk_ptr(tb, tq.w);
  const uint32_t hv = pk & 0xFFFF;
#pragma unroll
  for (int k = NV; k < NV + HV_E; k++) ldsm4t(wv[k], dep(hv, r[HV_R][0], c.sb) + (c.sb + SM_HV + (k - NV) * 2048));
#pragma unroll
  for (int k = 0; k < LAG_0; k++) lag(k);
#pragma unroll
  for (int k = 8; k < 16; k++) lead(k);
  const uint32_t s0 = __float_as_uint(sum(la, 0)), s3 = __float_as_uint(sum(la, 3));
  sts128((HV_E ? dep(t16, wv[NV][0] ^ wv[NV + HV_E / 2][1] ^ wv[NV + HV_E - (HV_E > 0)][2], c.sb) : TQ_AT ? dep(t16, ta ^ tb, c.sb) : t16) + (c.sb + SM_XCH),
         make_uint4(s0, __float_as_uint(sum(la, 1)), __float_as_uint(sum(la, 2)), s3));
  if (XB) bar_sync(NB_XCH, 256); else bar_sync(NB_XCH | ((t16 >> 9) & 3), 64);
#pragma unroll
  for (int k = LAG_0; k < LAG_0 + LAG_G; k++) r[k >> 1][2 * (k & 1)] = dep(r[k >> 1][2 * (k & 1)], LAG_S == 0 ? s3 : __float_as_uint(la[LAG_S - 1][0]), c.sb);
#pragma unroll
  for (int k = LAG_0; k < O_AT; k++) lag(k);
  const uint4 o = lds128((O_AT > LAG_0 ? dep(t16 ^ 2048, __float_as_uint(lg[(O_AT - 1) % NLAG][0]), c.sb) : t16 ^ 2048) + (c.sb + SM_XCH));
#pragma unroll
  for (int k = O_AT > LAG_0 ? O_AT : LAG_0; k < 16; k++) lag(k);
#pragma unroll
  for (int k = 0; k < V_E; k++) mma_a(lv[k & 3], wv[k], r[k >> 1][2 * (k & 1)], r[k >> 1][2 * (k & 1) + 1]);
  float t[4];
#pragma unroll
  for (int i = 0; i < 4; i++) {
    const float oi = __uint_as_float(i == 0 ? o.x : i == 1 ? o.y : i == 2 ? o.z : o.w);
    t[i] = NLAG == 4 ? (LAG_T ? ((lg[0][i] + lg[1][i]) + oi) + (lg[2 % NLAG][i] + lg[3 % NLAG][i]) : (((lg[0][i] + lg[1][i]) + lg[2 % NLAG][i]) + lg[3 % NLAG][i]) + oi) : LAG_T && NLAG == 2 ? (lg[0][i] + lg[1][i]) + oi : NLAG == 3 ? (lg[1][i] + lg[2 % NLAG][i]) + (lg[0][i] + oi) : (lg[0][i] + oi) + lg[1][i];
  }
  const uint32_t y0 = put_tag(pack_bf16(t[0], t[2]), pk >> 31, s >> 1), y1 = put_tag(pack_bf16(t[1], t[3]), pk >> 31, s >> 1);
  st_pub(dst, y0); st_pub(dst2, y1);
  mbar_arrive_warp(BAR(B_E1TRIG));
  TR(s, 1);
  sched_fence(c.sb);
  const uint4 tv = lds128(tab + 16);
#pragma unroll
  for (int k = NV + HV_E; k < 16; k++) ldsm4t(wv[k], (k < NV + HV_E + HV_D ? hv : dep(hv, k == NV + HV_E + HV_D ? wv[k - HV_D][0] ^ tv.x : wv[k - HV_D][0], c.sb)) + (c.sb + SM_HV + (k - NV) * 2048));
  wo = (hv & 2047) | ((t16 & 2048) << 3);
  const uint32_t l8 = (t16 >> 1) & 255;
  char* dv = mk_ptr(tv.x | l8, tv.y);
  pa = mk_ptr(tv.z | l8, tv.w);
#pragma unroll
  for (int f = 0; f < WO_0; f++) ldsm4t(af[f], dep(wo, f < WO_D ? wv[16 - WO_D + f][0] : af[f < WO_D ? 0 : f - WO_D][0], c.sb) + (c.sb + SM_WO + (f & 1) * 32768 + (f >> 1) * 2048));
#pragma unroll
  for (int k = V_E; k < 16; k++) mma_a(lv[k & 3], wv[k], r[k >> 1][2 * (k & 1)], r[k >> 1][2 * (k & 1) + 1]);
  const uint32_t z0 = put_tag(pack_bf16(sum(lv, 0), sum(lv, 1)), (~t16 >> 4) & 1, s >> 1), z1 = pack_bf16(sum(lv, 2), sum(lv, 3));
  st_pub2(dv, z0, z1);
  if (FIN_AT >= 3) mbar_arrive_warp(BAR(B_VST));
  TR(s, 2);
}
__device__ __forceinline__ uint32_t max_bf16x2(uint32_t a, uint32_t b) { uint32_t r; asm("max.bf16x2 %0, %1, %2;" : "=r"(r) : "r"(a), "r"(b)); return r; }
constexpr float SCL = 0.08838834764831845f * 1.4426950408889634f;
__device__ __forceinline__ uint32_t max5(const uint32_t (&sc)[5]) { return max_bf16x2(max_bf16x2(max_bf16x2(max_bf16x2(sc[0], sc[1]), sc[2]), sc[3]), sc[4]); }
__device__ __forceinline__ float row_off(uint32_t m, uint32_t& m1) {
  m1 = __shfl_xor_sync(~0u, m, 1);
  const uint32_t m2 = __shfl_xor_sync(~0u, m, 2), m3 = __shfl_xor_sync(~0u, m, 3);
  const uint32_t mm = max_bf16x2(max_bf16x2(max_bf16x2(m, m1), m2), m3);
  return -SCL * fmaxf(__uint_as_float(mm << 16), __uint_as_float(mm & 0xFFFF0000u));
}
__device__ __forceinline__ void unpack(float (&f)[10], const uint32_t (&sc)[5]) {
#pragma unroll
  for (int i = 0; i < 5; i++) {
    asm volatile("shl.b32 %0, %1, 16;" : "=f"(f[2 * i]) : "r"(sc[i]));
    asm volatile("and.b32 %0, %1, 0xffff0000;" : "=f"(f[2 * i + 1]) : "r"(sc[i]));
  }
}
__device__ __forceinline__ uint32_t exp_pair(const float (&f)[10], int i, float off) {
  return pack_bf16(ex2(fmaf(f[2 * i], SCL, off)), ex2(fmaf(f[2 * i + 1], SCL, off)));
}
template<bool SPLIT> __device__ __forceinline__ void scores_x(float (&a)[2][4], const uint4 (&kf)[4], const uint4& q, uint32_t z) {
#pragma unroll
  for (int t = 0; t < 2; t++) { a[t][0] = a[t][1] = a[t][2] = a[t][3] = 0.f; }
  mma_q(a[0], kf[0], q.x, q.y); mma_q(a[1], kf[2], q.x, q.y);
  if (SPLIT) sched_fence(z);
  mma_q(a[0], kf[1], q.z, q.w); mma_q(a[1], kf[3], q.z, q.w);
}
__device__ __forceinline__ uint32_t scores_m(const uint4& q, const uint4& k) {
  float a[4] = {}, b[4] = {};
  mma_q(a, q, k.x, k.z); mma_q(b, q, k.y, k.w);
  return pack_bf16(a[0] + b[2], a[1] + b[3]);
}
__device__ __forceinline__ void store_scores(const float (&a)[2][4], uint32_t dst) {
  sts64(dst, pack_bf16(a[0][0], a[0][2]), pack_bf16(a[1][0], a[1][2]));
  sts64(dst + 320, pack_bf16(a[0][1], a[0][3]), pack_bf16(a[1][1], a[1][3]));
}
__device__ __forceinline__ uint32_t sum4(uint32_t a, uint32_t b, uint32_t d, uint32_t e) { return add_bf16x2(add_bf16x2(a, b), add_bf16x2(d, e)); }
__device__ __forceinline__ void load_scores(uint32_t (&sc)[5], uint32_t ax, uint32_t am) {
  uint4 p[4];
#pragma unroll
  for (int i = 0; i < 4; i++) p[i] = lds128(ax + i * 1280);
  const uint2 m0 = lds64(am), m1 = lds64(am + 256);
  const uint4 t = add4(add4(add4(p[0], p[1]), p[2]), p[3]);
  sc[1] = t.x; sc[2] = t.y; sc[3] = t.z; sc[4] = t.w;
  sc[0] = sum4(m0.x, m0.y, m1.x, m1.y);
}
constexpr uint32_t ONES = 0x3F803F80u;
__device__ __forceinline__ float pv(float (&o)[2][4], const uint32_t (&p)[5], const uint4 (&vf)[4], const uint4& vm) {
  float a[4] = {}, b[4] = {};
#pragma unroll
  for (int t = 0; t < 2; t++) { o[t][0] = o[t][1] = o[t][2] = o[t][3] = 0.f; }
  mma_q(o[0], vf[0], p[1], p[2]); mma_q(o[1], vf[2], p[1], p[2]);
  mma_q(o[0], vf[1], p[3], p[4]); mma_q(o[1], vf[3], p[3], p[4]);
  mma16816(a, p[1], p[2], p[3], p[4], ONES, ONES);
  mma1688(o[0], vm.x, vm.y, p[0]); mma1688(o[1], vm.z, vm.w, p[0]);
  mma1688(b, p[0], ONES, ONES);
  return (a[0] + a[2]) + b[0];
}
constexpr uint32_t POLL_LIMIT = 1u << 21;
__device__ __forceinline__ uint32_t box(int slot, int cta) { return (slot * 2 + (cta >> 6)) * M_REG + (cta & 63) * 16384; }
__device__ __forceinline__ uint32_t near_page(const ChainCtx& c, int cta, uint32_t off) {
  return off + (((lds32(c.sb + SM_SEL + cta * 4) >> (off >> 21)) ^ __popc(off & 0xB2000)) & 1) * 4096;
}
__device__ __forceinline__ uint32_t e1_box(const ChainCtx& c, int slot, int cta) { return near_page(c, E1OFF ? cta ^ 2 : cta, box(slot, cta) + 8192) ^ (E1OFF ? 0 : 4096); }
__device__ __forceinline__ uint32_t tile_key() {
  uint32_t sm; asm volatile("mov.u32 %0, %%smid;" : "=r"(sm));
  return (sm < 64 ? sm / 2 % 8 : sm < 120 ? 1 + (sm / 2 - 32) % 7 : 0) << 24 | sm << 16;
}
__device__ __forceinline__ uint32_t ox_at(int s, int row, int g, int jj) { return s * 131072 + ((g >> 1) * 32 + row) * 64 + (g & 1) * 32 + 8 * jj; }
__device__ __forceinline__ int tile_of(const ChainCtx& c) { return SIDE ? __shfl_sync(~0u, lds32(c.sb + SM_SEL + 528), 0) : c.r; }

__global__ void __cluster_dims__(2, 1, 1) __launch_bounds__(512, 1)
chain_kernel(const __grid_constant__ CUtensorMap tq, const __grid_constant__ CUtensorMap tk, const __grid_constant__ CUtensorMap tv,
             const __grid_constant__ CUtensorMap tv16, const __grid_constant__ CUtensorMap to, const __grid_constant__ CUtensorMap tx,
             const __grid_constant__ CUtensorMap twr, const __grid_constant__ CUtensorMap twi,
             const __grid_constant__ CUtensorMap ta, const __grid_constant__ CUtensorMap tw,
             const __grid_constant__ CUtensorMap tb, const __grid_constant__ CUtensorMap tout, const __grid_constant__ CUtensorMap tz,
             const __grid_constant__ CUtensorMap tzs, const __grid_constant__ CUtensorMap ta32,
             const __nv_bfloat16* __restrict__ mem0, char* __restrict__ mail, const __nv_bfloat16* __restrict__ x,
             const __nv_bfloat16* __restrict__ gw) {
  extern __shared__ __align__(1024) unsigned char smraw[];
  if (threadIdx.x == 0) TL(0);
  ChainCtx c;
  c.sb = __shfl_sync(~0u, smem_u32(smraw), 0);
  c.mail = mail; c.sel = 0; c.r = blockIdx.x;
  if (ROLE) {
    const uint32_t u = blockIdx.x >> 1, n = u < 36 ? 8 : 7, k = u - (u < 36 ? 4 : 36), q = k * (u < 36 ? 32 : 37) >> 8;
    c.r = __shfl_sync(~0u, 2 * (u - 4 < 60 ? u + k - q * n - (q & 1) * (n - 1) : u) + (blockIdx.x & 1) + (threadIdx.x >> 9), 0);
  }
  c.h = c.r >> 2; c.a = (c.r >> 1) & 1; c.b = c.r & 1; c.j = c.r & 3;
  c.m = __shfl_sync(~0u, (int)(threadIdx.x >> 7), 0); c.w = __shfl_sync(~0u, (int)((threadIdx.x >> 5) & 3), 0);
  char* own = c.mail + (uint32_t)(c.w * M_REG + M_E3 + (c.r >> 5) * 8192 + (c.r & 31) * 128 + (threadIdx.x & 31) * 4);
  uint32_t i0 = 0, i1 = 0;
  if (EARLY) asm volatile("{ .reg .pred p; setp.ne.u32 p, %4, 0; @p atom.relaxed.gpu.global.exch.b32 %0, [%2], %3; @p atom.relaxed.gpu.global.exch.b32 %1, [%2 + 4096], %3; }"
               : "+r"(i0), "+r"(i1) : "l"(own), "r"(SENT), "r"((uint32_t)(c.m == 2 && c.r < 128)) : "memory");
#pragma unroll
  for (int g = 0; g < 3; g++) {
    const int i = c.m * 4 + c.w;
    if (g < 2 || i < B_END - 32)
      asm volatile("{ .reg .pred p; elect.sync _|p, 0xffffffff; @p mbarrier.init.shared::cta.b64 [%0], %1; }"
                   :: "r"(BAR(g * 16 + i)), "r"(0x19080401u >> (bar_codes(g) >> 2 * i & 3) * 8 & 255) : "memory");
  }
  asm volatile("fence.mbarrier_init.release.cluster;" ::: "memory");
  __syncthreads();
  asm volatile("barrier.cluster.arrive.relaxed.aligned;" ::: "memory");

  if (c.r >= 128) {
    fft_cols((float2*)smraw, c.r - 128, &twr, &twi, &tzs);
    if ((threadIdx.x & 127) == 0) TL(7);
    __syncwarp();
  } else if (c.m == 3) {
    asm volatile("setmaxnreg.dec.sync.aligned.u32 %0;" :: "n"(REG_H));
    c.lane = lane_id();
    if (c.sb & 1023) asm volatile("trap;");
    const int col = c.h * 128 + c.a * 64, eq = E3M ? c.w & 1 : c.w >> 1, eh = E3M == 1 ? (c.w >> 1) ^ 1 : E3M ? c.w >> 1 : c.w & 1;
    uint32_t tl = clock_lo();
    TR(-2, 3);
    if (c.w == 0) {
      if (START) delay_until(tl + START);
      if (HOLD == 2) mbar_wait(BAR(B_PROBE), 0);
      if (HOLD == 3) mbar_wait(BAR(B_SEL), 0);
      if (HOLD == 1) mbar_wait(BAR(B_PROBE), 0);
      TR(-2, 4);
      tl = clock_lo();
      mbar_expect_e(BAR(B_PFULL), 2 * NP * 2048);
      mbar_expect_e(BAR(B_WFULL), (48 - NP) * 2048);
      mbar_expect_e(BAR(B_WFULL + 1), (48 - NP) * 2048);
    }
    auto dst_x = [&](int e, int w) {
      const uint32_t g2 = 2 * c.a + (w >> 1), u = w & 1;
      return M_KVQ + c.h * 24576 + (e == 0 ? 8192 + (2 * u + c.b) * 2048 + g2 * 512 : e == 1 ? g2 * 2048 + u * 1024 + c.b * 128 : 16384 + c.b * 4096 + g2 * 512 + u * 256);
    };
    if (c.w == 0) {
      tl += PACE0;
#pragma unroll wunr
      for (int i = 0; i < 24; i++) {
        const int m = i < 4 || i >= 16, k = i < 4 ? i : m ? i - 12 : i - 4;
        const int row = c.b * 512 + m * 256;
        const uint32_t st = c.sb + m * ST_WG, bar = BAR(k < 3 ? B_PFULL : B_WFULL + m);
        if (PACE) delay_until(tl += PACE);
        if (i == 14) { mbar_wait(BAR(B_FREE), 0); if (c.lane == 0) TL2(2); __syncwarp(); }
        if (k < 11) TMA_W(k < 3 ? c.sb + SM_POOL + m * NP * 2048 + k * 8192 : k == 3 ? c.sb + SM_HV + (m * NHV + 1) * 2048 : st + (k - 4) * 8192,
                          k == 3 || k > 8 ? &tv : (k >> 2 & 1) == m ? &tk : &tq, col, row + (k < 8 ? k & 3 : (k - 9) & 3) * 64, bar);
        else {
#pragma unroll 1
          for (int j = 8; j < 12; j++) TMA_W(j < NV ? st + (32 - NP + j) * 2048 : c.sb + SM_HV + m * NHV * 2048, &tv16, col, row + j * 16, bar);
        }
      }
      TR(-2, 7);
    } else if (c.w == 2) {
      const unsigned short* mp = (const unsigned short*)mem0 + (2 * (c.lane & 3)) * D_ + 8 * c.r + (c.lane >> 2);
      uint32_t mv = (uint32_t)mp[0] | (uint32_t)mp[D_] << 16;
      if (mv == SENT) mv = 0x7FFF7FFFu;
      mbar_wait(BAR(B_PROBE), 0);
      char* dst = c.mail + (uint32_t)(M_E3 + (c.r >> 5) * 8192 + (c.r & 31) * 128 + c.lane * 4);
      st_pub(dst, mv); st_pub(dst + 4096, mv);
    } else if (c.w == 3) {
      mbar_wait(BAR(B_FREE), 0);
      mbar_wait(BAR(B_PFULL), 0);
      mbar_expect_e(BAR(B_PFULL), 65536);
      for (int i = 0; i < 2; i++) tma4d_e(c.sb + SM_XT + i * 16384, &tx, c.b * 8, 4 + 2 * (c.b ^ i), BAR(B_PFULL));
    }
    {
      mbar_wait(BAR(B_SEL), 0);
      const int i = tid_now() & 127, sl = i & 3, e = (i >> 2) & 3;
      uint32_t ox = dst_x(e, i >> 5) + sl * M_REG;
      uint32_t oh = e & 1 ? (sl ^ (e & 2)) * M_REG + M_E3 + (c.r >> 5) * 8192 + (c.w & 1) * 4096 + (c.r & 31) * 128
                          : near_page(c, c.r, e ? sl * M_REG + M_E3 + (c.b * 2 + eq) * 8192 : box(~sl & 1, c.r)) + (e ? eh * 2048 : c.w * 1024), of;
      {
        const int e = i & 7, w = (i >> 3) & 3, m = (i >> 5) & 1, sl = i >> 6;
        const int cta = e < 2 ? c.r & ~1 : e == 2 ? c.r | 1 : e == 3 ? c.h * 4 + 2 * m + 1 : c.j * 32 + m * 8 + 2 * w + (e & 2) * 8 + (e & 1);
        const uint32_t off = e < 2 ? c.b * 2048 + m * 1024 + (w >> 1) * 512 + e * 160 : e == 2 ? c.b * 2048 + m * 1024 + w * 256 : e == 3 ? w * 256 : c.h * 128;
        of = (e < 4 ? e1_box(c, sl, cta) : near_page(c, cta, box(sl, cta))) + off;
      }
      char *px = c.mail + ox, *ph = c.mail + oh, *pf = c.mail + of;
      uint32_t at = sl * 128 + (i >> 5) * 32 + e * 8, af = i * 8;
      pin(px); pin(ph); pin(pf); pin(at); pin(af);
      asm volatile("barrier.cluster.wait;" ::: "memory");
      TR(-2, 0);
      mbar_wait(BAR(B_WREAD), 0);
      TR(-2, 1);
      mbar_arrive_both(BAR(B_LFREE), c.b ^ 1);
      sts64(at + (c.sb + SM_TAB + 1536), (uint32_t)(uintptr_t)px, (uint32_t)((uintptr_t)px >> 32));
      sts64(at + (c.sb + SM_TAB + 1024), (uint32_t)(uintptr_t)ph, (uint32_t)((uintptr_t)ph >> 32));
      sts64(af + (c.sb + SM_TAB), (uint32_t)(uintptr_t)pf, (uint32_t)((uintptr_t)pf >> 32));
      TR(-2, 2);
      if (tid_now() == 384) TL2(25);
      __syncwarp();
      bar_sync(14, 160);
    }
    pad<PAD3>();
    for (int s = -1; s < NSEG; s++) {
      if (E30 ? s != 0 : s >= 0) {
        const uint32_t tab = c.sb + SM_TAB + 1024 + (max(s, 0) & 3) * 128 + c.w * 32;
        uint32_t t0;
        if (s > 0) {
          const uint32_t ln = tid_now() & 31;
          const uint4 ta = lds128(tab);
          const char* src = mk_ptr(ta.x | ln * 4, ta.y);
          char* dst = mk_ptr(ta.z | ln * 4, ta.w);
          const uint32_t tg = (s - 1) >> 1, chk = (ln & 3) ? 0u : 1u, red = ln * (RED_L == 3 ? 4 : 8);
          touch(src, dep(c.sb, chk, c.sb)); touch(dst, dep(c.sb, red, c.sb));
          mbar_wait(BAR(B_E2TRIG), (s - 1) & 1);
          TR(s, 0);
          if (ANCH2) delay_fine(lds32(c.sb + SM_SUM + 64) + DLY_E2); else delay_cycles(DLY_E2);
          uint32_t n = 0;
          while (true) {
            uint32_t v[8];
#pragma unroll
            for (int i = 0; i < 8; i++) v[i] = ld_poll1(src + i * 128);
            if (E2_F) sched_fence(c.sb);
            const uint32_t bad = RED_T ? (stale2(v[0], v[1], tg) | stale2(v[2], v[3], tg) | stale2(v[4], v[5], tg)) | stale2(v[6], v[7], tg)
                                       : stale1(stale1(stale2(v[0], v[1], tg), v[2], tg), v[3], tg) | stale1(stale1(stale2(v[4], v[5], tg), v[6], tg), v[7], tg);
            const bool ok = all_clear(bad, chk);
#pragma unroll
            for (int l = 0; l < RED_L; l++)
#pragma unroll
              for (int i = 0; i < (4 >> l); i++) v[i] = add_bf16x2(v[2 * i], v[2 * i + 1]);
            if (RED_L == 3) sts32(red + (c.sb + SM_RED + c.w * 128), v[0]);
            else {
              float lo[8], hi[8];
#pragma unroll
              for (int i = 0; i < (8 >> RED_L); i++) { lo[i] = __uint_as_float(v[i] << 16); hi[i] = __uint_as_float(v[i] & 0xFFFF0000u); }
#pragma unroll
              for (int l = RED_L; l < 3; l++)
#pragma unroll
                for (int i = 0; i < (4 >> l); i++) { lo[i] = lo[2 * i] + lo[2 * i + 1]; hi[i] = hi[2 * i] + hi[2 * i + 1]; }
              sts64(red + (c.sb + SM_RED + c.w * 256), __float_as_uint(lo[0]), __float_as_uint(hi[0]));
            }
            if (ok) break;
            n++; CNT(0);
          }
          bar_sync(NB_HELP, 128);
          const uint32_t rd = red + (c.sb + SM_RED);
          if (!RED_P || c.w < 2) {
            if (RED_L == 3) st_pub_if(dst, sum4(lds32(rd), lds32(rd + 128), lds32(rd + 256), lds32(rd + 384)), c.w < 2);
            else {
              const uint2 p0 = lds64(rd), p1 = lds64(rd + 256), p2 = lds64(rd + 512), p3 = lds64(rd + 768);
              st_pub_if(dst, pack_bf16((__uint_as_float(p0.x) + __uint_as_float(p1.x)) + (__uint_as_float(p2.x) + __uint_as_float(p3.x)),
                                       (__uint_as_float(p0.y) + __uint_as_float(p1.y)) + (__uint_as_float(p2.y) + __uint_as_float(p3.y))), c.w < 2);
            }
          }
          t0 = clock_lo();
          mbar_arrive_warp(BAR(B_PUB));
          TRV(s, 15, n);
          mbar_wait(BAR(B_SPFREE), (s - 1) & 1);
        } else {
          if (tid_now() == 384) TL2(24);
          __syncwarp();
          if (!E30) mbar_wait(BAR(B_PROBE), 1);
          if (!WO_S) mbar_wait(BAR(B_WOFULL), 0);
          if (tid_now() == 384) TL2(19);
          __syncwarp();
          t0 = clock_lo() - DLY_E3;
        }
        TRV(s, 1, t0);
        {
          const uint32_t l16 = (tid_now() & 31) * 16, dst = vary(l16, s, c.sb) + (c.sb + SM_MEM + eh * 4096 + eq * 2048);
          const uint4 tb = lds128(tab + 16);
          st_pub_if(mk_ptr(tb.z | l16 >> 2, tb.w), SENT, c.w >= 2);
          const char* src = mk_ptr(tb.x | l16, tb.y);
          touch(src, dep(c.sb, dst, c.sb));
          delay_fine(t0 + (DLY_E3 + eh * DLY_E3B));
          uint32_t n = 0;
          while (true) {
            uint4 v[4];
#pragma unroll
            for (int i = 0; i < 4; i++) v[i] = ld_poll(src + i * 512);
#pragma unroll
            for (int i = 0; i < 4; i++) sts128(dst + i * 512, v[i]);
            if (arrive_if_all(max(max(v[0].x, v[1].x), max(v[2].x, v[3].x)) != SENT, NB_MEM + eh * 2 + eq, 160)) break;
            n++; CNT(1);
          }
          TR(s, 2); TRV(s, 14, n);
        }

        if (s == 1) CLK(1); if (s == 8) CLK(2); if (s == 56) CLK(3);
        if (c.w == 2 && s == 15) TRSYNC(8);
        if (c.w == 2 && s == 21) TRSYNC(10);
      }
      const int g = s + 1;
      auto load_v = [&]() {
        if (V_TMA && c.w == V_W) {
          mbar_expect_e(BAR(B_VFULL), 8192);
          bulk_load_e(c.sb + SM_V, c.mail + (uint32_t)(M_KVQ + (min(g, XEND - 1) & (NSLOT - 1)) * M_REG + c.h * 24576 + 8192), 8192, BAR(B_VFULL));
        }
      };
      if (XEND < NSEG && g >= XEND && g < NSEG) { mbar_wait(BAR(B_SC), s & 1); load_v(); }
      if (g < XEND) {
        const uint32_t tx_ = c.sb + SM_TAB + 1536 + (g & 3) * 128 + c.w * 32, tag = (g >> 2) & 1;
        if (c.w == 0) mbar_expect_e(BAR(B_LAND), EXP_PEER * 12288);
        auto load_x = [&]() {
          if (c.w == 3 && g + 1 < XEND) {
            mbar_wait(BAR(B_XEMPTY), g & 1);
            mbar_expect_e(BAR(B_XFULL), 16384 * EXP_NXT);
            for (int i = 0; i < EXP_NXT; i++) tma4d_e(c.sb + SM_XT + i * 16384, &tx, c.b * 8, (g + 1) * 4 + 2 * (c.b ^ i), BAR(B_XFULL));
          }
        };
        if (X_AT == 0 && g > 0) load_x();
        TR(s, 6);
        if (E30 && g == 0) mbar_wait(BAR(B_PROBE), 1);
        mbar_wait(BAR(B_LAND), g & 1);
        TR(s, 7);
        if (DLY_F && g > 0) delay_cycles(DLY_F);
        auto total = [&](int w, int lane, uint32_t o0, uint32_t o1) {
          const uint32_t a = c.sb + SM_LAND + land_off(w, lane);
          if (EXP_FL == 1) return make_uint4(a, a, a, a);
          const uint4 t = add4(lds128(a + o0), lds128(a + o1 + 2048));
          const uint32_t a2 = dep(dep(a, t.x ^ t.y ^ t.z, c.sb), t.w, c.sb);
          return add4(t, add4(lds128(a2 + o0 + 4096), lds128(a2 + o1 + 6144)));
        };
        auto get = [&](int e) {
          const int ln = tid_now() & 31;
          return e == 0 ? total(c.w, ln, 16384, 16384)
               : e == 1 ? total((c.w & 2) + ((ln >> 1) & 1), (ln & 1) * 16 + (c.w & 1) * 8 + (ln >> 2), 8192, 0)
                        : total((c.w & 2) + ((ln >> 1) & 1), (ln & 1) * 16 + (ln >> 3) * 4 + (c.w & 1) * 2 + ((ln >> 2) & 1), 0, 8192);
        };
        auto put = [&](int e, uint4 v) {
          const int ln = tid_now() & 31;
          const uint2 d = lds64(tx_ + e * 8);
          if (e < 2) {
            v.x = tagged(v.x, tag);
            st_pub4(mk_ptr(d.x | (e ? (ln & 24) * 32 + (ln & 7) * 16 : ln * 16), d.y), v);
          } else {
            char* dst = mk_ptr(d.x | ((ln & 7) * 16 + (ln >> 3) * 4), d.y);
            const uint32_t bit = ln < 8;
            st_pub(dst, put_tag(v.x, bit, tag)); st_pub(dst + 128, put_tag(v.y, bit, tag));
            st_pub(dst + 2048, put_tag(v.z, bit, tag)); st_pub(dst + 2176, put_tag(v.w, bit, tag));
          }
        };
        auto after_sc = [&]() { if (g > 0) { mbar_wait(BAR(B_SC), s & 1); if (DLY_FK) delay_cycles(DLY_FK); if (X_AT == 1) load_x(); } };
        if (FIN_AT == 5) {
          put(0, get(0));
          if (DLY_F2 && g > 0) delay_cycles(DLY_F2); else sched_fence(c.sb);
          const uint4 k = get(1);
          sched_fence(c.sb);
          const uint4 q = get(2);
          if (g > 0) mbar_wait(BAR(B_VST), s & 1);
          put(1, k); put(2, q);
          TR(s, 5);
          mbar_arrive_both(BAR(B_LFREE), c.b ^ 1);
          after_sc();
          load_v();
          continue;
        }
        if (FIN_AT < 3) {
          if (EXP_FIN & 1) put(0, get(0));
          TR(s, 3);
          if (FIN_AT == 1) after_sc();
          if (V_TMA == 1) load_v();
          if (EXP_FIN & 2) put(1, get(1));
        } else {
          const uint4 v = get(0);
          sched_fence(c.sb);
          const uint4 k = get(1);
          if (g > 0) { mbar_wait(BAR(B_VST), s & 1); if (DLY_FS) delay_cycles(DLY_FS); }
          put(0, v); put(1, k);
        }
        TR(s, 4);
        if (FIN_AT == 4) {
          const uint4 q = get(2);
          after_sc();
          load_v();
          put(2, q);
        } else {
          if (FIN_AT >= 2) after_sc();
          if (V_TMA == 2) load_v();
          if (EXP_FIN & 4) put(2, get(2));
        }
        mbar_arrive_both(BAR(B_LFREE), c.b ^ 1);
        if (V_TMA == 3) load_v();
        TR(s, 5);
        if (!FIN_AT && X_AT && g > 0) { mbar_wait(BAR(B_SC), s & 1); if (DLY_FK) delay_cycles(DLY_FK); load_x(); }
      }
    }
    const int tile = tile_of(c), s0 = (tile >> 3) * 4, n0 = (tile & 7) * 128;
    if (c.w == 1) {
      mbar_wait(BAR(B_PVDONE), 0);
      count_e(g_ctl + (EARLY2 ? C_LAST : C_EARLY));
      st_pub(c.mail + (uint32_t)((tid_now() & 6) * (M_REG / 2) + M_SEL + (tid_now() & 1) * 4096 + c.r * 4), 0);
      await_count(g_ctl + C_COLS, 4);
      mbar_expect_e(BAR(B_TW), 8192);
      bulk_load_e(c.sb + SM_TW, g_tw, 8192, BAR(B_TW));
    } else if (c.w == 2) {
      const uint32_t ln = tid_now() & 31, rel = mapa(BAR(B_GEMPTY) + (ln >> 2) * 8, ln & 1);
      mbar_wait(BAR(B_VST), 1); mbar_wait(BAR(PRE_AT), 1);
      arrive_remote_if(rel, ln < 12);
      mbar_wait(BAR(B_E2TRIG), 1);
      if (GATE) mbar_wait(BAR(B_DONE), 0);
      arrive_remote_if(rel, ln >= 12 && ln < 20);
    } else {
      auto ahead = [&](int k) {
        if (c.w) { if (PF_A && (k & 3) == (tile >> 1 & 3)) prefetch3d_e(&ta, k * 32, s0 + 2 * c.b); }
        else if (PF_B && (k & 7) == (tile >> 4)) prefetch2d_e<(ONCE & 512) != 0>(&tw, n0 + (tile & 8) * 8, k * 64);
      };
#pragma unroll 1
      for (int k = 0; k < PF_D; k++) ahead(k);
      if (c.w == 3) await_count(g_ctl + C_EARLY, 128);
      const int skew = tile < 120 ? 0 : SKEW;
      uint32_t o = SM_XT, st = 0, ph = 0;
#pragma unroll 1
      for (int kb = 0; kb < 64 + skew; kb++, o = next_stage(o)) {
        const bool solo = kb < skew || kb >= 64;
        const uint32_t bar = BAR(B_GFULL + st), k = kb & 63;
        if (c.w && kb == skew) {
          if (tile >= 120) await_count(g_ctl + C_LAST, EARLY2 ? 640 : 512);
          if (tid_now() == 480) TL(10);
          __syncwarp();
        }
        mbar_wait(BAR(B_GEMPTY + st), ph);
        if (c.w) {
          const int r = solo ? (kb >> 5) + c.b : c.b * 2;
          tma3d_mc_e(c.sb + o + r * 4096, solo ? &ta32 : &ta, k * 32, s0 + r, bar);
        } else {
          mbar_expect_e(bar, solo ? 24576 : 32768);
          tma2d_o<(ONCE & 2) != 0>(c.sb + o + 16384, &tw, n0, k * 64, bar);
          tma2d_o<(ONCE & 2) != 0>(c.sb + o + 24576, &tw, n0 + 64, k * 64, bar);
        }
        if (kb + PF_D < 64) ahead(kb + PF_D);
        if (++st == 5) { st = 0; ph ^= 1; }
      }
    }
    return;
  } else if (c.m == 2) {
    asm volatile("setmaxnreg.dec.sync.aligned.u32 %0;" :: "n"(512 - 2 * REG_F - REG_H));
    c.lane = lane_id();
    {
      uint32_t tl = clock_lo() + (PACE0 + WO_AT * PACE);
      TR(-2, 0);
      sched_fence(i0 ^ i1);
      TR(-2, 7);
      int far1 = 0;
#pragma unroll 1
      for (int rep = EARLY; rep <= NPROBE; rep++) {
        const int lag = race_init(own + (rep & 1) * 4096, own + (~rep & 1) * 4096, SENT);
        if (rep) far1 += ((rep ^ c.r >> 5) & 1 ? 1 : -1) * min(lag, 200);
      }
      sts32(c.sb + SM_SEL + 512 + c.w * 4, (8 + far1 / (16 * NPROBE)) << 4 * c.w);
      TR(-2, 1);
      if (tid_now() == 256) TL2(14);
      __syncwarp();
      mbar_arrive_warp(BAR(B_PROBE));
      if (c.w == 0) {
        mbar_wait(BAR(B_PROBE), 0);
        const uint4 bits = lds128(c.sb + SM_SEL + 512);
        const uint32_t res = bits.x | bits.y | bits.z | bits.w;
        st_pub_if(c.mail + (uint32_t)((c.lane & 6) * (M_REG / 2) + M_SEL + (c.lane & 1) * 4096 + c.r * 4), res | tile_key(), c.lane < 8);
        const int q = (res >> 4 * ((c.lane + c.r) & 3) & 15) - 8, best = __reduce_max_sync(~0u, abs(q) * 64 + (c.lane & 3) * 16 + ((c.lane + c.r) & 3) * 2 + (q <= 0));
        const char* src = c.mail + (uint32_t)((best & 6) * (M_REG / 2) + M_SEL + (best & 1) * 4096 + c.lane * 16);
        if (SEL_AT) delay_until(tl - (PACE0 + WO_AT * PACE - SEL_AT));
        uint4 v; uint32_t n = 0;
        TR(-2, 4);
        while (true) {
          delay_cycles(DLY_SEL);
          TR(-2, 6);
          v = ld_poll(src);
          if (__all_sync(~0u, v.x && v.y && v.z && v.w)) break;
          watchdog(n, POLL_LIMIT);
        }
        TR(-2, 5);
        int ta = 0, tb = 0, pa = 0, pb = 0;
        uint32_t flip = 0;
#pragma unroll 1
        for (int i = 0; i < 4; i++) {
          const int a = (v.x >> 4 * i & 15) + (v.y >> 4 * i & 15) - 16, b = (v.z >> 4 * i & 15) + (v.w >> 4 * i & 15) - 16;
          const bool f = __reduce_add_sync(~0u, a * ta + b * tb) < 0;
          ta += f ? -a : a; tb += f ? -b : b; flip |= (uint32_t)f << i;
        }
#pragma unroll 1
        for (uint32_t g = 0; g < 8; g++) {
          const bool a = (v.x >> 16) - g * 256 < 120, b = (v.z >> 16) - g * 256 < 120;
          const int n = __reduce_add_sync(~0u, (a ? ta : 0) + (b ? tb : 0)) > 0 ? PRIOR : -PRIOR;
          if (a) pa = n;
          if (b) pb = n;
        }
        const uint32_t ka = AWARE && ta + pa > 0 ? ~flip : flip, kb = AWARE && tb + pb > 0 ? ~flip : flip;
        sts128(c.sb + SM_SEL + c.lane * 16, make_uint4(ka, ka, kb, kb));
        mbar_arrive_warp(BAR(B_SEL));
        const uint32_t key = __shfl_sync(~0u, c.a ? v.z : v.x, c.h);
        const int u = __popc(__ballot_sync(~0u, v.x < key)) + __popc(__ballot_sync(~0u, v.z < key));
        sts32(c.sb + SM_SEL + 528, (u & 32) * 2 + (u & 7) * 8 + (u >> 2 & 6) + c.b);
        TR(-2, 2);
        if (c.lane == 0) TL2(13);
        __syncwarp();
        bar_sync(14, 160);
        if (ZDLY) delay_cycles(ZDLY);
#pragma unroll 4
        for (int k = c.lane >> 3; k < (ZINIT ? 128 : 0); k += 4) {
          const int e = k & 7;
          const uint2 d = lds64(c.sb + SM_TAB + (e == 3 ? k - 1 : k) * 8);
          st_pub4(mk_ptr((d.x & ~127u) + (e < 2 ? (k & 8) * 32 : e == 3 ? 128 : 0) + (c.lane & 7) * 16, d.y), make_uint4(0, 0, 0, 0));
        }
        __syncwarp();
        if (c.lane < 4) asm volatile("mbarrier.arrive.shared::cta.b64 _, [%0];" :: "r"(BAR(B_PROBE)) : "memory");
        __syncwarp();
        TR(-2, 8);
      }
      if (c.w == 2) {
        mbar_wait(BAR(B_P1), 0);
        if (P1_AT) { mbar_wait(BAR(B_WFULL), 0); mbar_wait(BAR(B_WFULL + 1), 0); }
        st_pub_if(g_ctl + C_COLS + (c.r & 15) * 32 + c.lane, 0, c.r < (C_END - C_COLS) / 32);
        count_e(g_ctl + C_P1);
        TR(-2, 3);
      }
      if (c.w == 1) for (int i = 0; i < WO_N; i++) { delay_until(tl += WO_P * PACE); prefetch2d_e(&to, c.j * 256 + (i ^ WO_X) * 64, c.h * 128); }
      if (c.w == 3) {
        mbar_wait(BAR(B_WREAD0), 0);
        for (int i = 0; i < 2; i++) tma4d_e(c.sb + SM_WO + i * 16384, &tx, c.b * 8, 2 * (c.b ^ i), BAR(B_PFULL));
        mbar_expect_e(BAR(B_WOFULL), 65536);
#pragma unroll 1
        for (int i = 3; i >= 0; i--) {
          if (i & 1) mbar_wait(BAR(i < 2 ? B_XEMPTY : B_WREAD), 0);
          TMA_O(c.sb + SM_WO + i * 16384, &to, c.j * 256 + i * 64, c.h * 128, BAR(B_WOFULL));
        }
      }
    }
    asm volatile("barrier.cluster.wait;" ::: "memory");
    const int g = c.w, src0 = c.h * 4 + (g >> 1) * 2;
    mbar_wait(BAR(B_SEL), 0);
    c.sel = __shfl_sync(~0u, (e1_box(c, 0, src0 + (c.lane >> 5)) & 4096) | (e1_box(c, 1, src0) & 4096) * 2, 0);
    mbar_wait(BAR(B_WREAD), 0);
    uint32_t l16 = c.sb + g * 512 + c.lane * 16;
    auto lane = [&](uint32_t v) { l16 = dep(l16, v, c.sb); return (int)((l16 & 511) >> 4); };
    pad<PAD2>();
    for (int s = 0; s < NSEG; s++) {
      l16 = vary(l16, s, c.sb);
      int ln = (l16 & 511) >> 4;
      uint4 kf[4], qx;
      {
        const int gs = min(s, XEND - 1);
        const char* pk = c.mail + (uint32_t)(M_KVQ + (gs & (NSLOT - 1)) * M_REG + c.h * 24576 + g * 2048 + ln * 16);
        const char* pq = pk + (16384 + c.j * 2048 - g * 1536);
        const uint32_t tg = (gs / NSLOT) & 1;
        touch(pk, c.sb); touch(pq, c.sb);
        TR(s, 0);
        mbar_wait(BAR(B_VFULL), s & 1);
        TR(s, 1);
        if (s > 0) mbar_wait(BAR(B_PUB), (s - 1) & 1);
        for (uint32_t n = 0; ; ) {
          uint4 k[4];
#pragma unroll
          for (int t = 0; t < 4; t++) k[t] = ld_poll(pk + t * 512);
          qx = ld_poll(pq);
#pragma unroll
          for (int t = 0; t < 2; t++) {
            auto cp = [&](uint32_t v) { return dep(v, 0, c.sb); };
            kf[t] = make_uint4(cp(k[2 * t].x), cp(k[2 * t].y), cp(k[2 * t + 1].x), cp(k[2 * t + 1].y));
            kf[2 + t] = make_uint4(cp(k[2 * t].z), cp(k[2 * t].w), cp(k[2 * t + 1].z), cp(k[2 * t + 1].w));
          }
          if (all_clear(stale1(stale2(k[0].x, k[1].x, tg) | stale2(k[2].x, k[3].x, tg), qx.x, tg), EXP_CHK)) break;
          watchdog(n, POLL_LIMIT); CNT(4);
        }
        TR(s, 2);
      }
      if (X_AT >= 2 && g == 0 && s + 2 < XEND) {
        mbar_wait(BAR(B_XEMPTY), ~s & 1);
        mbar_expect_e(BAR(B_XFULL), 16384 * EXP_NXT);
        for (int i = 0; i < EXP_NXT; i++) tma4d_e(c.sb + SM_XT + i * 16384, &tx, c.b * 8, (s + 2) * 4 + 2 * (c.b ^ i), BAR(B_XFULL));
      }
      ln = lane(kf[0].y);
      const char* pa = c.mail + (uint32_t)(box(s & 1, src0) + 8192 + (c.sel >> (s & 1) & 4096) + (g & 1) * 512 + (EXP_LIN ? ln * 16 : read_off(ln)));
      const uint32_t spw = c.sb + SM_SP + g * 1280 + (ln & 3) * 64 + ((((ln >> 3) ^ ln) & 2) << 4) + (ln & 4) * 4 + (ln & 8),
                     spr = c.sb + SM_SP + (ln & 4) * 80 + (ln >> 3) * 64 + (((ln & 3) ^ ((ln >> 3) & 2)) << 4), l8 = ln * 8;
      const uint32_t tg = s >> 1;
      float sx[2][4];
      uint32_t sm;
      uint4 km;
      touch(pa, c.sb);
      mbar_wait(BAR(B_E1TRIG), s & 1);
      const uint32_t t0 = clock_lo();
      TRV(s, 3, t0);
      scores_x<false>(sx, kf, qx, 0);
      store_scores(sx, spw + 640);
      if (DLY_E1) delay_fine(t0 + DLY_E1);
      uint32_t nr = 0;
      while (true) {
        const uint4 q0 = ld_poll(pa), q1 = ld_poll(pa + 2048), k0 = ld_poll(pa + 1024), k1 = ld_poll(pa + 3072);
        uint4 qm = add4(q0, q1);
        const uint32_t bq = stale2(q0.x, q1.x, tg);
        qm.x = dep(qm.x, bq, c.sb);
        scores_x<SC_F>(sx, kf, qm, c.sb);
        const uint32_t bk = stale2(k0.x, k1.x, tg);
        km = add4(k0, k1);
        km.x = dep(km.x, bk, c.sb);
        const bool ok = all_clear(bq | bk, 1);
        sm = scores_m(qm, km);
        store_scores(sx, spw);
        if (ok) break;
        nr++; CNT(2);
      }
      sts32(l8 + (c.sb + SM_SPM + (g >> 1) * 256 + (g & 1) * 4), sm);
      bar_sync(NB_ATT, 128);
      TR(s, 5); TRV(s, 13, nr);
      float o[2][4];
      uint32_t sp[5];
      uint4 vf[4];
      load_scores(sp, spr, l8 + (c.sb + SM_SPM));
      const uint32_t m5 = max5(sp);
      uint32_t m1;
      float off = row_off(m5, m1), f[10];
      l16 = dep(l16, VF_AT ? m1 : m5, c.sb);
#pragma unroll
      for (int t = 0; t < 4; t++) vf[(t >> 1) + 2 * (t & 1)] = lds128(l16 + SM_V + ((t >> 1) + 2 * (t & 1)) * 2048);
      qx.x = dep(qx.x, sp[0], c.sb);
      sts32(l8 + (c.sb + SM_SPM + 512 + (g >> 1) * 256 + (g & 1) * 4), scores_m(qx, km));
      mbar_arrive_warp(BAR(B_SC));
      unpack(f, sp);
      if (UP_F) sched_fence(c.sb);
      uint4 vm;
      if (VM_AT < 2) {
        bar_sync(NB_VM, 384);
        sp[1] = exp_pair(f, 1, off);
        const uint32_t av = dep(l8, VM_AT ? sp[1] : __float_as_uint(off), c.sb) + (c.sb + g * 512 + SM_VM);
        const uint2 vm0 = lds64(av), vm1 = lds64(av + 256);
        vm = make_uint4(vm0.x, vm0.y, vm1.x, vm1.y);
#pragma unroll
        for (int i = 2; i < 6; i++) sp[i % 5] = exp_pair(f, i % 5, off);
      } else {
#pragma unroll
        for (int i = 1; i < 6; i++) sp[i % 5] = exp_pair(f, i % 5, off);
        bar_sync(VM_AT == 2 ? dep(dep(0, sp[1] ^ sp[2], c.sb) + NB_VM, sp[0], c.sb) : dep(dep(0, sp[0] ^ sp[1] ^ sp[2], c.sb) + NB_VM, sp[3], c.sb), 384);
        const uint32_t av = l8 + (c.sb + g * 512 + SM_VM);
        const uint2 vm0 = lds64(av), vm1 = lds64(av + 256);
        vm = make_uint4(vm0.x, vm0.y, vm1.x, vm1.y);
      }
      float sum;
      auto rows_m = [&]() {
        const uint32_t tv = min(s, XEND - 1) / NSLOT;
        sum = pv(o, sp, vf, vm);
        stsm4<false>(l16 + SM_OM, pack_bf16(o[0][0], o[0][1]), pack_bf16(o[0][2], o[0][3]), pack_bf16(o[1][0], o[1][1]), pack_bf16(o[1][2], o[1][3]));
        sts32(c.sb + SM_SUM + ((l16 >> 4) & 28), __float_as_uint(sum));
        return arrive_if_clear(stale2(vf[0].x, vf[1].x, tv) | stale2(vf[2].x, vf[3].x, tv), EXP_CHK, NB_OM, 384);
      };
      if (!rows_m()) {
        const char* pv_ = c.mail + (uint32_t)(M_KVQ + (min(s, XEND - 1) & (NSLOT - 1)) * M_REG + c.h * 24576 + 8192 + (l16 - c.sb));
        uint32_t n = 0;
        do {
#pragma unroll
          for (int t = 0; t < 4; t++) vf[t] = ld_poll(pv_ + t * 2048);
          watchdog(n, POLL_LIMIT); CNT(5);
        } while (!rows_m());
      }
      const uint32_t tom = clock_lo();
      TRV(s, 8, tom);
      sched_fence(c.sb);
      ln = lane(tom);
      const int n = ln >> 2, jj = ln & 3, tq_ = 8 * c.j + (n & 4) + 2 * (n & 1) + ((n >> 1) & 1), lim = 16 * (tq_ - 2 * jj + 1);
      if (DLY_X) delay_until(tom + DLY_X);
      load_scores(sp, spr + 640, c.sb + SM_SPM + 512 + ln * 8);
#pragma unroll
      for (int w = 0; w < 4; w++) {
        uint32_t m; asm("shl.b32 %0, 0xffffffff, %1;" : "=r"(m) : "r"(max(lim - 128 * w, 0)));
        sp[1 + w] = (sp[1 + w] & ~m) | (0xD029D029u & m);
      }
      mbar_arrive_warp(dep(dep(0, sp[0], c.sb), sp[1], c.sb) + BAR(B_SPFREE));
      off = row_off(max5(sp), m1);
      unpack(f, sp);
#pragma unroll
      for (int i = 1; i < 6; i++) sp[i % 5] = exp_pair(f, i % 5, off);
      sum = pv(o, sp, vf, vm);
      TR(s, 7);
      sum = rcp(sum);
      const float i0 = __shfl_sync(~0u, sum, 8 * jj), i1 = __shfl_sync(~0u, sum, 8 * jj + 4);
      const uint32_t oxs = c.sb + SM_OX + g * 512;
      stsm4<true>(oxs + (ln & 7) * 64 + (((ln >> 3) ^ ((ln >> 1) & 3)) << 4),
                  pack_bf16(o[0][0] * i0, o[0][1] * i1), pack_bf16(o[0][2] * i0, o[0][3] * i1), pack_bf16(o[1][0] * i0, o[1][1] * i1), pack_bf16(o[1][2] * i0, o[1][3] * i1));
      __syncwarp();
      *(uint4*)(g_ox + ox_at(s, tq_, c.h * 4 + g, jj)) = lds128(oxs + n * 64 + ((jj ^ (n >> 1)) << 4));
      mbar_arrive_warp(BAR(B_PVDONE));
      TR(s, 9);
    }
    if (LASTM) {
      const int ln = tid_now() & 31, n = ln >> 2, jj = ln & 3, tq_ = 8 * c.j + (n & 4) + 2 * (n & 1) + ((n >> 1) & 1);
      store_count(g_ox + ox_at(NSEG - 1, tq_, c.h * 4 + g, jj), lds128(c.sb + SM_OX + g * 512 + n * 64 + ((jj ^ (n >> 1)) << 4)), (char*)(g_ctl + C_LAST) + (LASTM == 2 ? c.r * 4 + g : 0));
    } else count_e(g_ctl + C_LAST);
    mbar_arrive_warp(BAR(B_DONE));
    if (tid_now() == 256) TL(8);
    __syncwarp();
    mbar_wait(BAR(B_E2TRIG), 1); mbar_wait(BAR(B_DONE), 0); mbar_wait(BAR(B_TW), 0);
    asm volatile("setmaxnreg.inc.sync.aligned.u32 128;");
  } else {
    {
      const int w = c.m * 4 + c.w;
      mbar_expect_e(BAR(B_ROWS), 4096 + 256);
      for (int i = 0; i < 2; i++) bulk_load_e(c.sb + SM_FFT + (1024 + w * ROW_BUF) * 8 + i * 2048, x + (size_t)(z_row(c.r * 8 + w) + i * 1024) * D_, 2048, BAR(B_ROWS));
      bulk_load_e(c.sb + SM_GW + w * 256, gw + w * 128, 256, BAR(B_ROWS));
    }
    asm volatile("setmaxnreg.inc.sync.aligned.u32 %0;" :: "n"(REG_F));
    c.lane = lane_id();
    uint32_t wa[16][4], wb[16][4], wv[16][4];
    TR(-2, 4);
    fft_rows_fwd((float2*)(smraw + SM_FFT), (const __nv_bfloat16*)(smraw + SM_GW), c.r, threadIdx.x, BAR(B_ROWS), BAR(B_FREE), [&](int e) { TR(-2, e); }, [&]() {
      mbar_spin(BAR(B_PFULL), 0);
#pragma unroll
      for (int k = 0; k < NP; k++) ldsm4t(wa[k], c.sb + SM_POOL + c.m * NP * 2048 + frag_off(c.w, c.lane) + k * 2048);
      bar_sync(NB_XCH, 256);
#pragma unroll
      for (int k = 0; k < NP; k++) sts128(c.sb + SM_POOL + c.m * 2048 + c.w * 512 + c.lane * 16 + k * 4096, make_uint4(wa[k][0], wa[k][1], wa[k][2], wa[k][3]));
    });
    mbar_arrive_warp(BAR(B_P1));
    TR(-2, 0);
    if (tid_now() == 0) TL2(1);
    __syncwarp();
    mbar_spin(BAR(B_WFULL + c.m), 0);
    TR(-2, 1);
    if ((tid_now() & 127) == 0) TL2(16);
    __syncwarp();
    {
      const uint32_t st = c.sb + c.m * ST_WG + frag_off(c.w, c.lane);
#pragma unroll
      for (int k = 0; k < 16; k++) ldsm4t(wb[k], st + k * 2048);
#pragma unroll
      for (int k = NP; k < 16; k++) ldsm4t(wa[k], st + (16 + k - NP) * 2048);
#pragma unroll
      for (int k = 0; k < NV; k++) ldsm4t(wv[k], st + (32 - NP + k) * 2048);
      mbar_arrive_warp(BAR(B_WREAD));
      if (c.m == 0) mbar_arrive_warp(BAR(B_WREAD0));
#pragma unroll
      for (int k = 0; k < (LP_IN == 2 ? 0 : NP); k++) lds_frag(wa[k], c.sb + SM_POOL + c.m * 2048 + c.w * 512 + c.lane * 16 + k * 4096);
      TR(-2, 2);
    }
    TR(-2, 3);
    if (tid_now() == 0) TL2(12);
    __syncwarp();
    asm volatile("barrier.cluster.wait;" ::: "memory");
    uint32_t t16 = c.m * 2048 + c.w * 512 + c.lane * 16;
    uint32_t pk = (c.m * NHV * 2048 + frag_off(c.w, c.lane)) | (tile_off(2 * (c.w & 1), c.lane) << 16) | ((c.lane & 12) ? 0u : 0x80000000u);
    const uint32_t dx1 = desc_lo(c.sb + SM_XT + c.m * 4096), dh = desc_lo(c.sb + SM_HV + c.m * NHV * 2048);
    mbar_spin(BAR(B_PFULL), 1);
    pad<PAD0>();
    for (int s = -2; ; s++) {
      t16 = vary(t16, s, c.sb); pk = vary(pk, s, c.sb);
      const uint32_t dx = dx1 - (s == -2 ? (SM_XT - SM_WO) / 16 : 0);
      auto ldp = [&](int k0, int k1, int d, int back = 0) {
#pragma unroll
        for (int k = k0; k < k1; k++) lds_frag(wa[k], (k < k0 + d - back ? t16 : dep(t16, wa[k < d ? 0 : k - d][0], c.sb)) + (c.sb + SM_POOL + k * 4096));
      };
      if (s >= 0) {
        uint32_t af[16][4], bf[4][4], wo;
        const uint32_t tab = ((t16 >> 3) & 0x1C0) + (c.sb + SM_TAB + (s & 1) * 512);
        const char* pa;
        mem_proj(wa, wb, wv, af, wo, pa, tab, t16, pk, c, s);
        const uint32_t t0 = clock_lo();
        t16 = dep(t16, t0, c.sb);
        auto ldwo = [&](int f) { ldsm4t(af[f], (f < WO_D ? wo : dep(wo, af[f < WO_D ? 0 : f - WO_D][0], c.sb)) + (c.sb + SM_WO + (f & 1) * 32768 + (f >> 1) * 2048)); };
        {
          const uint32_t tg = s >> 1, vm = t16 >> 1, chk = (~t16 >> 4) & 1;
          if (WO_S && s == 0) {
            mbar_spin(BAR(B_WOFULL), 0);
#pragma unroll
            for (int f = 0; f < WO_0; f++) ldwo(f);
          }
#pragma unroll
          for (int f = WO_0; f < WO_1; f++) ldwo(f);
          if (DLY_V) delay_fine(t0 + DLY_V); else sched_fence(c.sb);
          uint2 v0 = ld_poll2(pa), v1 = ld_poll2(pa + 1024), v2 = ld_poll2(pa + 2048), v3 = ld_poll2(pa + 3072);
          TR(s, 3);
#pragma unroll
          for (int f = WO_1; f < 16 - WO_L; f++) ldwo(f);
          TR(s, 4);
          uint32_t n = 0;
          while (true) {
            sts64(vm + (c.sb + SM_VM), sum4(v0.x, v1.x, v2.x, v3.x), sum4(v0.y, v1.y, v2.y, v3.y));
            if (arrive_if_clear(stale1(stale1(stale2(v0.x, v1.x, tg), v2.x, tg), v3.x, tg), chk, NB_VM, 384)) break;
            v0 = ld_poll2(pa); v1 = ld_poll2(pa + 1024); v2 = ld_poll2(pa + 2048); v3 = ld_poll2(pa + 3072);
            n++; CNT(3);
          }
          TR(s, 12); TRV(s, 15, n);
        }
        const uint32_t ob = dep(dep(t16 & 511, af[14 - WO_L][0], c.sb), af[15 - WO_L][0], c.sb);
        uint32_t l4 = ob >> 2;
        const uint32_t bit = (t16 & 48) ? 0u : 1u;
        if (LF_AT) mbar_spin2_if(BAR(B_XFULL), BAR(B_LFREE), s & 1, s + 2 < XEND); else mbar_spin_if(BAR(B_XFULL), s & 1, s + 2 < XEND);
        bar_sync(NB_OM, 384);
        TR(s, 5);
#pragma unroll
        for (int i = 0; i < 4; i++) ldsm4t(bf[i], ob + (c.sb + SM_OM + i * 512));
        uint2 sum = lds64(((t16 >> 1) & 24) + (c.sb + SM_SUM));
        if (OM_F) sched_fence(c.sb);
        float d[WO_C][4] = {};
        uint4 d0, d1;
#pragma unroll
        for (int f = 0; f < 16; f++) {
          mma_a(d[f % WO_C], af[f], bf[f >> 2][f & 2], bf[f >> 2][(f & 2) + 1]);
          if (f >= WO_C && f < WO_C + WO_L) {
            const int l = 16 - WO_L + f - WO_C;
            ldsm4t(af[l], (WO_LD ? dep(wo, __float_as_uint(d[(f + 1) % WO_C][0]), c.sb) : wo) + (c.sb + SM_WO + (l & 1) * 32768 + (l >> 1) * 2048));
          }
          if (f == WO_T) {
            const uint32_t tb2 = dep((t16 >> 3) & 0x1C0, __float_as_uint(d[f % WO_C][0]), c.sb) + (c.sb + SM_TAB + (s & 1) * 512);
            d0 = lds128(tb2 + 32); d1 = lds128(tb2 + 48);
          }
          if (f >= PL_WA && f < PL_WA + PL_W) lds_frag(wa[f - PL_WA], (PL_WD ? dep(t16, __float_as_uint(d[(f + PL_WD) % WO_C][0]), c.sb) : t16) + (c.sb + SM_POOL + (f - PL_WA) * 4096));
          if (PL_W && PL_WF == 1 && f == PL_WA + PL_W - 1) sched_fence(c.sb);
          if (f == 4) { sum.x = dep(sum.x, __float_as_uint(d[0][0]), c.sb); sum.y = dep(sum.y, __float_as_uint(d[0][0]), c.sb); }
        }
        if (PL_W && !PL_WF) {
          uint32_t all = 0;
#pragma unroll
          for (int k = 0; k < PL_W; k++) all ^= wa[k][0];
          l4 = dep(l4, all, c.sb);
        }
        char* dst[4] = {mk_ptr(d0.x | l4, d0.y), mk_ptr(d0.z | l4, d0.w), mk_ptr(d1.x | l4, d1.y), mk_ptr(d1.z | l4, d1.w)};
        const float i0 = rcp(__uint_as_float(sum.x)), i1 = rcp(__uint_as_float(sum.y));
#pragma unroll
        for (int i = 0; i < 4; i++) {
          const int t = i >> 1, e = 2 * (i & 1);
          const float y0 = WO_C == 2 ? d[t][e] : d[t][e] + d[(t + 2) % WO_C][e], y1 = WO_C == 2 ? d[t][e + 1] : d[t][e + 1] + d[(t + 2) % WO_C][e + 1];
          st_pub(dst[i], put_tag(pack_bf16(y0 * i0, y1 * i1), bit, s >> 1));
        }
        if (ANCH2) sts32(c.sb + SM_SUM + 64, clock_lo());
        mbar_arrive_warp(BAR(B_E2TRIG));
        TR(s, 6);
        sched_fence(c.sb);
        if (W_E2 == 2) mbar_spin(BAR(B_E2TRIG), s & 1);
      }
      if (__builtin_expect(s + 2 < XEND, 1)) {
        const uint32_t tg0 = DLY_P ? clock_lo() + DLY_P : 0;
        if (LP_IN) ldp(PL_W, PL_0, PL_D);
        float xa[16];
        uint32_t q[4];
        if (W_E2 == 1 && s >= 0) mbar_spin(BAR(B_E2TRIG), s & 1);
        TR(s, 7);
        constexpr int S1 = ORDER ? 0 : 2, S2 = ORDER == 0 ? 0 : ORDER == 1 ? 2 : 1, S3 = ORDER == 2 ? 2 : 1;
        if (ORDER) issue_qk<0, 16>(xa, wb, vary(dx, s, c.sb)); else issue_v(xa, wv, vary(dx, s, c.sb), vary(dh, s, c.sb));
        if (DLY_P) delay_until(tg0); else if (IS_F) sched_fence(c.sb);
        ldp(PL_0, PL_1, PL_D1);
        const uint32_t land = (t16 ^ ((t16 >> 3) & 0x60)) + vary(c.sb + SM_LAND + c.b * 4096, s, c.sb);
        TR(s, 14);
        if (LF_AT == 1) mbar_spin_if(BAR(B_LFREE), s & 1, s < 0); else if (!LF_AT) mbar_spin(BAR(B_LFREE), s & 1);
        TR(s, 15);
        WG_WAIT(0);
        TR(s, 8);
        park_own<S1 == 2>(q, xa, land, S1, c.sb);
        if (W_PUB == 4 && s >= 0) mbar_spin(BAR(B_PUB), s & 1);
        if (ORDER == 1) issue_v(xa, wv, vary(dx, s, c.sb + 32), vary(dh, s, c.sb)); else issue_qk<0, 16>(xa, ORDER ? wa : wb, vary(dx, s, c.sb + 32));
        if (IS_F) sched_fence(c.sb);
        ldp(PL_1, PL_2, PL_D1);
        if (W_PUB == 1) mbar_spin_if(BAR(B_PUB), s & 1, s >= 0);
        uint32_t tp = clock_lo(), q1[4] = {q[0], q[1], q[2], q[3]};
        if (PL_2B) ldp(PL_2, NP - PL_L, PL_D1);
        if (W_PUB != 3) park_peer(q, land, S1, c);
        if (!PL_2B) ldp(PL_2, NP - PL_L, PL_D1);
        TR(s, 13);
        WG_WAIT(0);
        TR(s, 9);
        park_own<S2 == 2>(q, xa, land, S2, c.sb);
        if (ORDER == 2) issue_v(xa, wv, vary(dx, s, c.sb + 64), vary(dh, s, c.sb));
        else {
          issue_qk<0, PL_L ? NP - PL_L : 16>(xa, wa, vary(dx, s, c.sb + 64));
          ldp(NP - PL_L, NP, PL_E);
          if (PL_L) issue_qk<NP - PL_L, 16>(xa, wa, vary(dx, s, c.sb + 64));
        }
        if ((W_PUB == 2 || W_PUB == 3) && s >= 0) { mbar_spin(BAR(B_PUB), s & 1); tp = clock_lo(); }
        if (W_PUB == 3) park_peer(q1, land, S1, c);
        if (DLY_S && s >= 0) delay_until(tp + DLY_S);
        park_peer(q, land, S2, c);
        WG_WAIT(0);
        TR(s, 10);
        mbar_arrive_warp(BAR(B_XEMPTY));
        park_own<S3 == 2>(q, xa, land, S3, c.sb);
        park_peer(q, land, S3, c);
        TR(s, 11);
      } else {
        if (s == NSEG - 1) break;
        if (EARLY2 && (XEND == NSEG || s == NSEG - 2) && c.m * 4 + c.w == 0) count_e(g_ctl + C_EARLY);
        ldp(PL_W, NP, 2);
      }
    }
    asm volatile("setmaxnreg.dec.sync.aligned.u32 %0;" :: "n"(BPRE == 2 ? 176 : 128));
    const int tid = tid_now(), lane = tid & 31, tile = tile_of(c), m0 = (tile >> 3) * 128, n0 = (tile & 7) * 128;
    float acc[64];
#pragma unroll
    for (int i = 0; i < 64; i++) acc[i] = 0.f;
    const uint32_t rel = mapa(BAR(B_GEMPTY), lane & 1), la = desc_lo(c.sb + c.m * 8192), lb = ((c.sb + 16384) & 0x3FFFF) >> 4 | (8192 >> 4) << 16;
    bool relon = false;
    const int skew = tile < 120 ? 0 : SKEW, kend = 64 + skew - c.m * skew, hold = c.m * (65 - LEAD) - 1;
    const float g0 = __ldcg(g_gate + m0 + (tid >> 5) * 16 + (lane >> 2)), g1 = __ldcg(g_gate + m0 + (tid >> 5) * 16 + (lane >> 2) + 8);
    uint32_t o = SM_XT, st = 0, ph = 0, prev = 0;
    if (tid == 0) TL(9);
    __syncwarp();
    GT(0);
#pragma unroll 1
    for (int kb = -c.m * skew; kb < max(kend - 4, 64); kb++, o = next_stage(o)) {
      if (LEAD && kb == hold) bar_sync(15, 256);
      mbar_lim(BAR(B_GFULL + st), ph);
      if ((uint32_t)kb < 64) {
        WG_FENCE();
#pragma unroll
        for (int k = 0; k < 4; k++) wgmma_ss_n128_tb(acc, desc128(la + (o >> 4) + k * 2), desc128(lb + (o >> 4) + k * 128));
        WG_COMMIT();
        WG_WAIT(1);
      } else WG_WAIT(0);
      arrive_remote_if(rel + 8 * prev, relon && kb < kend - 4);
      relon = (tid & 127) < 2;
      prev = st;
      if (++st == 5) { st = 0; ph ^= 1; }
    }
    if (LEAD && c.m == 0) asm volatile("bar.arrive 15, 256;" ::: "memory");
    const uint32_t row = (tid >> 5) * 2048 + (lane & 15) * 128 + (((lane >> 4) ^ (lane & 7)) << 4);
    if (!BPRE) WG_WAIT(0);
    mbar_lim(BAR(B_BT), 0);
    uint32_t b[2][4][4];
    const uint32_t rb = (tid >> 5) * 2048 + (lane >> 2) * 128 + (((lane & 7) ^ (lane >> 2)) << 4);
#pragma unroll
    for (int i = 0; i < 8; i++) lds_frag(b[i & 1][i >> 1], (rb ^ (i & 2) * 32) + (c.sb + SM_BT + (i >> 2) * 16384 + (i & 1) * 1024));
    float bl[2][4][4], bh[2][4][4];
    if (BPRE == 2) {
#pragma unroll
      for (int i = 0; i < 32; i++) {
        asm volatile("shl.b32 %0, %1, 16;" : "=f"(bl[i >> 4][i >> 2 & 3][i & 3]) : "r"(b[i >> 4][i >> 2 & 3][i & 3]));
        asm volatile("and.b32 %0, %1, 0xffff0000;" : "=f"(bh[i >> 4][i >> 2 & 3][i & 3]) : "r"(b[i >> 4][i >> 2 & 3][i & 3]));
      }
    }
    if (BPRE) { sched_fence(c.sb); WG_WAIT(0); sched_fence(c.sb); }
#pragma unroll
    for (int i = 0; i < 64; i++) asm volatile("" : "+f"(acc[i]) :: "memory");
    GT(17);
    if (tid == 0) TL(4);
    __syncwarp();
#pragma unroll
    for (int hf = 0; hf < 2; hf++) {
#pragma unroll
      for (int t = 0; t < 4; t++) {
        uint32_t y[4];
#pragma unroll
        for (int i = 0; i < 4; i++) {
          const float* a = acc + 32 * hf + 8 * t + 2 * i, g = i & 1 ? g1 : g0;
          const uint32_t* q = b[i & 1][2 * (t & 1) + (i >> 1)] + hf;
          const float* f = (t & 2 ? bh : bl)[i & 1][2 * (t & 1) + (i >> 1)] + hf;
          if (BPRE == 2) y[i] = pack_bf16(fmaf(g, a[0], f[0]), fmaf(g, a[1], f[2])); else
          y[i] = pack_bf16(fmaf(g, a[0], __uint_as_float(t & 2 ? q[0] & 0xFFFF0000u : q[0] << 16)), fmaf(g, a[1], __uint_as_float(t & 2 ? q[2] & 0xFFFF0000u : q[2] << 16)));
        }
        stsm4<false>((row ^ t * 32) + (c.sb + SM_BT + hf * 16384), y[0], y[1], y[2], y[3]);
      }
      if (EP_F && !hf) { sched_fence(c.sb); for (int i = 32; i < 64; i++) asm volatile("" : "+f"(acc[i]) :: "memory"); }
      FENCE_ASYNC_SMEM();
      __syncwarp();
      tma2d_out_e(&tout, n0 + hf * 64, m0 + (c.m * 4 + c.w) * 16, c.sb + SM_BT + hf * 16384 + (c.m * 4 + c.w) * 2048);
    }
    asm volatile("cp.async.bulk.commit_group; cp.async.bulk.wait_group" WAITRD " 0;" ::: "memory");
    GT(18);
    if ((tid & 127) == 0) TL(11);
    return;
  }
  constexpr int NH = NQ < 106 ? 4 * (106 - NQ) : 0;
  const bool col = c.r >= 128;
  const int tile = col ? 0 : tile_of(c);
  const int q0 = col ? 256 - NQ + (c.r - 128) + c.m * 4 : tile < 120 ? tile : 256, u = (tile >> 1 & 32) | (tile >> 3 & 7) | (tile & 6) << 2, e = QSH == 2 ? 2 * (u - (u > 39) - (u > 47) - (NQ < 110 && u > 55)) + c.b : tile,
            dq = col ? 16 : QSH ? 120 + (e < NH ? e >> 1 : (e + NH) >> 2) - tile : 120, qe = col ? 256 : 256 - NQ,
            qw = col || !QSH || (e < NH ? c.w >> 1 == c.b : c.w == ((e + NH) & 3)) ? qe : 120;
  const uint32_t zs = c.sb + (col ? COL_Z + c.m * 32768 : SM_BT), zb = BAR(B_Z + c.m);
  auto load_z = [&](int q) { if (c.w == 0 && q < qe) { mbar_expect_e(zb, 32768); tma2d_o<(ONCE & 4) != 0>(zs, &tz, q * 64, 0, zb); } };
  asm volatile("fence.proxy.async.global;" ::: "memory");
  load_z(q0);
  uint32_t ph = 0;
#pragma unroll 1
  for (int q = q0; q < qe; q += dq, ph ^= 1) {
    mbar_lim(zb, ph);
    const int p = q * 4 + c.w;
    if (EXP_INV && q < qw) fft_rows_inv(zs, (float2*)(smraw + (col ? 8192 + c.m * INV_BUF * 32 : SM_MEM)) + c.w * INV_BUF, (const float2*)(smraw + (col ? 0 : SM_TW)), p, tid_now() & 31, g_b,
                              [&]() { bar_sync(5 + c.m, 128); load_z(q + dq); });
    else { bar_sync(5 + c.m, 128); load_z(q + dq); }
  }
  if (B_ST) asm volatile("cp.async.bulk.wait_group 0; fence.proxy.async.global;" ::: "memory");
  asm volatile("fence.acq_rel.gpu;" ::: "memory");
  __syncwarp();
  { const int q = q0 + (tid_now() & 31) * dq; if (q < qw) asm volatile("red.relaxed.gpu.global.add.u32 [%0], 1;" :: "l"(g_ctl + C_ROWS + (q >> 5) * 32) : "memory"); }
  if (tid_now() == 256) { if (col) TL(27); else TL(3); }
  __syncwarp();
  if (!col && c.w == 0) {
    await_count<AW_NS>(g_ctl + C_ROWS + ((tile >> 3) & 7) * 32, 128);
    mbar_expect_e(BAR(B_BT), 32768);
    for (int i = 0; i < 2; i++) tma2d_o<(ONCE & 8) != 0>(c.sb + SM_BT + i * 16384, &tb, (tile & 7) * 128 + i * 64, (tile >> 3) * 128, BAR(B_BT));
    if (tid_now() == 256) TL(5);
  }
}

typedef CUresult (*EncodeFn)(CUtensorMap*, CUtensorMapDataType, cuuint32_t, void*, const cuuint64_t*, const cuuint64_t*,
                             const cuuint32_t*, const cuuint32_t*, CUtensorMapInterleave, CUtensorMapSwizzle,
                             CUtensorMapL2promotion, CUtensorMapFloatOOBfill);

void make_map(EncodeFn enc, CUtensorMap* tm, const void* p, int rank, const cuuint64_t* dims, const cuuint64_t* strides, const cuuint32_t* box, bool swz = true) {
  const cuuint32_t es[4] = {1, 1, 1, 1};
  enc(tm, CU_TENSOR_MAP_DATA_TYPE_BFLOAT16, rank, (void*)p, dims, strides, box, es, CU_TENSOR_MAP_INTERLEAVE_NONE,
      swz ? CU_TENSOR_MAP_SWIZZLE_128B : CU_TENSOR_MAP_SWIZZLE_NONE, swz ? CU_TENSOR_MAP_L2_PROMOTION_L2_128B : W_PROMO, CU_TENSOR_MAP_FLOAT_OOB_FILL_NONE);
}
void make_map2(EncodeFn enc, CUtensorMap* tm, const void* p, uint64_t cols, uint64_t rows, uint32_t boxrows) {
  const cuuint64_t dims[2] = {cols, rows}, strides[1] = {cols * 2};
  const cuuint32_t box[2] = {64, boxrows};
  make_map(enc, tm, p, 2, dims, strides, box);
}

}

extern "C" void kernel_launch(void* const* d_in, const int* in_sizes, int n_in, void* d_out, int out_size) {
  (void)in_sizes; (void)n_in; (void)out_size;
  const __nv_bfloat16* x = (const __nv_bfloat16*)d_in[0];
  const __nv_bfloat16* mem0 = (const __nv_bfloat16*)d_in[1];
  const __nv_bfloat16* gw = (const __nv_bfloat16*)d_in[10];

  EncodeFn enc = nullptr;
  cudaDriverEntryPointQueryResult qr;
  cudaGetDriverEntryPoint("cuTensorMapEncodeTiled", (void**)&enc, cudaEnableDefault, &qr);
  void *p_ox, *p_b, *p_z, *p_mail;
  cudaGetSymbolAddress(&p_ox, g_ox); cudaGetSymbolAddress(&p_b, g_b); cudaGetSymbolAddress(&p_z, g_z); cudaGetSymbolAddress(&p_mail, g_mail);
  CUtensorMap tq, tk, tv, tv16, to, tx, twr, twi, ta, tw, tb, tout, tz, tzs, ta32;
  make_map2(enc, &tq, d_in[2], 4096, 1024, 64);
  make_map2(enc, &tk, d_in[3], 4096, 1024, 64);
  make_map2(enc, &tv, d_in[4], 4096, 1024, 64);
  make_map2(enc, &tv16, d_in[4], 4096, 1024, 16);
  make_map2(enc, &to, d_in[5], 1024, 4096, 128);
  make_map2(enc, &tw, d_in[5], 1024, 4096, 64);
  {
    const cuuint64_t dims[3] = {64, 2048, 64}, strides[2] = {128, 262144};
    const cuuint32_t box[3] = {64, 32, 2}, box1[3] = {64, 32, 1};
    make_map(enc, &ta, p_ox, 3, dims, strides, box);
    make_map(enc, &ta32, p_ox, 3, dims, strides, box1);
  }
  make_map2(enc, &tb, p_b, 1024, 2048, 128);
  make_map2(enc, &tout, d_out, 1024, 2048, 16);
  make_map2(enc, &tz, p_z, 16384, 257, 256);
  {
    const cuuint64_t dims[4] = {64, 8, 16, 256}, strides[3] = {2048, 128, 16384};
    const cuuint32_t box[4] = {64, 8, 8, 2};
    make_map(enc, &tx, x, 4, dims, strides, box);
  }
  {
    const cuuint64_t dims[2] = {512, 257 * 32}, strides[1] = {1024};
    const cuuint32_t box[2] = {128, 16};
    make_map(enc, &tzs, p_z, 2, dims, strides, box, false);
  }
  {
    const cuuint64_t dims[2] = {8 * 513, 256}, strides[1] = {8 * 513 * 2};
    const cuuint32_t box[2] = {8, 256};
    make_map(enc, &twr, d_in[8], 2, dims, strides, box, false);
    make_map(enc, &twi, d_in[9], 2, dims, strides, box, false);
  }
  cudaFuncSetAttribute(chain_kernel, cudaFuncAttributeMaxDynamicSharedMemorySize, CHAIN_SMEM);

  cudaStream_t st = cudaStreamPerThread;
  char* mail = (char*)(((uintptr_t)p_mail + M_REG - 1) & ~(uintptr_t)(M_REG - 1));
  chain_kernel<<<132, 512, CHAIN_SMEM, st>>>(tq, tk, tv, tv16, to, tx, twr, twi, ta, tw, tb, tout, tz, tzs, ta32, mem0, mail, x, gw);
}
```

```cpp
#include <cuda_runtime.h>
#include <cuda_bf16.h>
#include <cuda.h>
#include <stdint.h>

#define DLY_E1 190
#define DLY_V 300
#define DLY_E2 280
#define DLY_E3 480
#define DLY_X 0
#define DLY_S 0
#define DLY_F 230
#define VM_AT 3
#define OM_F 1
#define C1_AT 5
#define NLAG 2
#define WO_D 2
#define WO_0 3
#define WO_1 10
#define PL_0 10
#define PL_1 10
#define PL_D 2
#define PL_L 0
#define HV_D 4
#define DLY_FK 40
#define REG_F 216
#define REG_H 24
#define SC_F 1
#define E2_F 0
#define X_AT 2
#define PL_2 10
#define PL_E 2
#define ORDER 1
#define SSPOS 1
#define W_PUB 1
#define FIN_AT 5
#define AWARE 1
#define NPROBE 2
#define NP_ 12
#define DLY_GRP 1000
#define EXP_CHK 1
#define EXP_NXT 2
#define EXP_PEER 1
#define EXP_FIN 7
#define EXP_NWG 16
#define ANCH2 1
#define IS_F 1
#define PL_D1 2
#define W_E2 0
#define V_TMA 2
#define V_W 2
#define RED_L 3
#define RED_T 1
#define RED_P 1
#define DLY_E3B 40
#define HV_E 2
#define HV_R 4
#define HOLD 0
#define PACE 500
#define PACE0 0
#define EXP_ST 7
#define WO_AT 38
#define WO_P 2
#define DLY_SEL 300
#define P1_AT 1
#define TMA_W tma2d_once
#define TMA_O tma2d_once
#define PACE_Z 580
#define EXP_INV 1
#define VF_AT 1
#define UP_F 0
#define WO_L (12 - NP_)
#define WO_C 4
#define WO_T 0
#define WO_LD 0
#define EXP_LIN 0
#define PL_W 4
#define PL_WA 10
#define PL_WD 0
#define PL_WF 2
#define EXP_FL 0
#define DLY_FS 0
#define DLY_F2 40
#define PF_D 4
#define PF_A 1
#define PF_B 0
#define SIDE 1
#define ROLE 1
#define E1OFF 1
#define EPI 0
#define WAITRD ".read"
#define START 1000
#define WUNR 1
#define WO_N 0
#define PL_2B 1
#define DLY_P 0
#define LP_IN 1
#define LF_AT 1
#define FINE 0
#define E30 1
#define WO_S 1
#define POOL_AT 12
#define COL_DLY 0
#define PAD0 2
#define PAD2 4
#define PAD3 4
#define WO_X 0
#define PRIOR 12
#define EARLY 1
#define SEL_AT 3000
#define FUNR 0
#define ZINIT 1
#define ZDLY 0
#define NQ 100
#define GATE 0
#define LASTM 1
#define X_ONCE 1
#define ONCE 31
#define Z_PF 0
#define EXP_W 1
#define W_PROMO CU_TENSOR_MAP_L2_PROMOTION_L2_128B
#define Z_ST 1
#define W_FINE 0
#define X128 2
#define T128_ 1
#define W_AT 0
#define SKEW 7
#define AW_NS 0
#define QSH 2
#define EARLY2 1
#define LEAD 3
#define BPRE 2
#define EP_F 1
#define TQ_AT 0
#define LAG_0 8
#define LAG_G 0
#define LAG_S 0
#define O_AT 0
#define XB 1
#define V_E 1
#define LAG_T 0
#define E3M 0
#define B_ST 1
#define TW_L 1
#define K_TMA 100
#define KL_AT 0
#define DLY_K 350
#define PRE_AT B_SC

namespace {
constexpr int wunr = WUNR;

constexpr int S_ = 2048, D_ = 1024, NSEG = 64;
constexpr uint32_t SENT = 0xFFFFFFFFu;
constexpr int NSLOT = 4;

constexpr uint32_t M_REG = 1 << 21, M_E3 = 64 * 16384, M_KVQ = M_E3 + 4 * 8192, M_SEL = M_KVQ + 32 * 24576;
__device__ __align__(1024) unsigned char g_mail[5 * M_REG];
constexpr int C_P1 = 0, C_COLS = C_P1 + 32, C_EARLY = C_COLS + 32, C_LAST = C_EARLY + 32, C_ROWS = C_LAST + 128, C_END = C_ROWS + 8 * 32;
__device__ __align__(1024) uint32_t g_ctl[C_END];
#define CLK(i)
#define TL(i)
#define TL2(i)
#define FT(i, v)
#define GT(i)
#define CNT(i)
__device__ __align__(1024) __nv_bfloat16 g_ox[S_ * 4096];
__device__ __align__(1024) float2 g_z[257 * 4096];
__device__ __align__(1024) __nv_bfloat16 g_b[S_ * D_];
__device__ float g_gate[S_];
__device__ __align__(1024) float2 g_tw[1024];

#define TRV(s, ev, val)
#define TR(s, ev)
#define TRSYNC(ev)
__device__ __forceinline__ uint32_t smem_u32(const void* p) { return (uint32_t)__cvta_generic_to_shared(p); }
__device__ __forceinline__ void watchdog(uint32_t& n, uint32_t limit) {
  asm volatile("{ .reg .pred p; add.u32 %0, %0, 1; setp.gt.u32 p, %0, %1; @p trap; }" : "+r"(n) : "r"(limit));
}
__device__ __forceinline__ void mbar_init(uint32_t bar, uint32_t cnt) {
  asm volatile("mbarrier.init.shared::cta.b64 [%0], %1;" :: "r"(bar), "r"(cnt) : "memory");
}
__device__ __forceinline__ void mbar_arrive_warp(uint32_t bar) {
  __syncwarp();
  asm volatile("{ .reg .pred p; elect.sync _|p, 0xffffffff; @p mbarrier.arrive.shared::cta.b64 _, [%0]; }" :: "r"(bar) : "memory");
}
__device__ __forceinline__ uint32_t clock_lo() {
  uint32_t r; asm volatile("{ .reg .u64 c; .reg .u32 h; mov.u64 c, %%clock64; mov.b64 {%0, h}, c; }" : "=r"(r) :: "memory"); return r;
}
__device__ __forceinline__ void delay_until(uint32_t t) {
  asm volatile("{ .reg .pred p; .reg .u64 c; .reg .u32 l, h;\n"
               "DLY: mov.u64 c, %%clock64; mov.b64 {l, h}, c; sub.s32 l, l, %0; setp.lt.s32 p, l, 0; @p bra.uni DLY; }" :: "r"(t) : "memory");
}
__device__ __forceinline__ void delay_fine(uint32_t t) {
  delay_until(t);
}
__device__ __forceinline__ void delay_cycles(uint32_t n) { delay_until(clock_lo() + n); }
__device__ __forceinline__ void sched_fence(uint32_t z) {
  asm volatile("{ .reg .pred p; setp.eq.u32 p, %0, 0x7fff0000; @p pmevent 1; }" :: "r"(z) : "memory");
}
__device__ __forceinline__ void pdl_wait() { asm volatile("griddepcontrol.wait;" ::: "memory"); }
__device__ __forceinline__ void pdl_launch() { asm volatile("griddepcontrol.launch_dependents;" ::: "memory"); }
__device__ __forceinline__ float ex2(float x) { float r; asm("ex2.approx.ftz.f32 %0, %1;" : "=f"(r) : "f"(x)); return r; }
__device__ __forceinline__ float rcp(float x) { float r; asm("rcp.approx.ftz.f32 %0, %1;" : "=f"(r) : "f"(x)); return r; }
__device__ __forceinline__ void mbar_expect(uint32_t bar, uint32_t bytes) {
  asm volatile("mbarrier.arrive.expect_tx.shared::cta.b64 _, [%0], %1;" :: "r"(bar), "r"(bytes) : "memory");
}
__device__ __forceinline__ bool mbar_try(uint32_t bar, uint32_t ph) {
  uint32_t ok;
  asm volatile("{ .reg .pred p; mbarrier.try_wait.parity.shared::cta.b64 p, [%1], %2; selp.u32 %0, 1, 0, p; }"
               : "=r"(ok) : "r"(bar), "r"(ph) : "memory");
  return ok;
}
__device__ __forceinline__ void mbar_wait(uint32_t bar, uint32_t ph) {
  uint32_t n = 0;
  while (!mbar_try(bar, ph)) { watchdog(n, (1u << 20)); }
}
__device__ __forceinline__ void mbar_spin(uint32_t bar, uint32_t ph) { while (!mbar_try(bar, ph)) {} }
__device__ __forceinline__ void mbar_spin_if(uint32_t bar, uint32_t ph, bool on) {
  asm volatile("{ .reg .pred p, q; setp.ne.u32 p, %2, 0;\n"
               "SPN: setp.eq.u32 q, 0, 0; @p mbarrier.try_wait.parity.shared::cta.b64 q, [%0], %1; @!q bra.uni SPN; }" :: "r"(bar), "r"(ph), "r"((uint32_t)on) : "memory");
}
__device__ __forceinline__ void mbar_spin2_if(uint32_t bar, uint32_t bar2, uint32_t ph, bool on) {
  asm volatile("{ .reg .pred p, q, r; setp.ne.u32 p, %3, 0;\n"
               "SPN: setp.eq.u32 q, 0, 0; setp.eq.u32 r, 0, 0; @p mbarrier.try_wait.parity.shared::cta.b64 q, [%0], %2;\n"
               "@p mbarrier.try_wait.parity.shared::cta.b64 r, [%1], %2; and.pred q, q, r; @!q bra.uni SPN; }" :: "r"(bar), "r"(bar2), "r"(ph), "r"((uint32_t)on) : "memory");
}
__device__ __forceinline__ void mbar_spin_cluster(uint32_t bar, uint32_t ph) {
  uint32_t ok;
  do {
    asm volatile("{ .reg .pred p; mbarrier.try_wait.parity.acquire.cluster.shared::cta.b64 p, [%1], %2; selp.u32 %0, 1, 0, p; }"
                 : "=r"(ok) : "r"(bar), "r"(ph) : "memory");
  } while (!ok);
}
#define ONCE_H "mov.b64 h, 0x12F0000000000000; "
__device__ __forceinline__ void tma2d(uint32_t dst, const CUtensorMap* tm, int c0, int c1, uint32_t bar) {
  if (ONCE & 32) asm volatile("{ .reg .b64 h; " ONCE_H "cp.async.bulk.tensor.2d.shared::cluster.global.mbarrier::complete_tx::bytes.L2::cache_hint [%0], [%1, {%3, %4}], [%2], h; }"
               :: "r"(dst), "l"(tm), "r"(bar), "r"(c0), "r"(c1) : "memory");
  else asm volatile("cp.async.bulk.tensor.2d.shared::cluster.global.mbarrier::complete_tx::bytes [%0], [%1, {%3, %4}], [%2];"
               :: "r"(dst), "l"(tm), "r"(bar), "r"(c0), "r"(c1) : "memory");
}
__device__ __forceinline__ void mbar_expect_e(uint32_t bar, uint32_t bytes) {
  asm volatile("{ .reg .pred p; elect.sync _|p, 0xffffffff; @p mbarrier.arrive.expect_tx.shared::cta.b64 _, [%0], %1; }" :: "r"(bar), "r"(bytes) : "memory");
}
__device__ __forceinline__ void tma2d_e(uint32_t dst, const CUtensorMap* tm, int c0, int c1, uint32_t bar) {
  asm volatile("{ .reg .pred p; elect.sync _|p, 0xffffffff;\n"
               "@p cp.async.bulk.tensor.2d.shared::cluster.global.mbarrier::complete_tx::bytes [%0], [%1, {%3, %4}], [%2]; }"
               :: "r"(dst), "l"(tm), "r"(bar), "r"(c0), "r"(c1) : "memory");
}
__device__ __forceinline__ void tma2d_st_e(const CUtensorMap* tm, int c0, int c1, uint32_t src) {
  asm volatile("{ .reg .pred p; elect.sync _|p, 0xffffffff;\n"
               "@p cp.async.bulk.tensor.2d.global.shared::cta.bulk_group [%0, {%2, %3}], [%1]; }" :: "l"(tm), "r"(src), "r"(c0), "r"(c1) : "memory");
}
__device__ __forceinline__ void tma2d_out_e(const CUtensorMap* tm, int c0, int c1, uint32_t src) {
  if (EPI) asm volatile("{ .reg .pred p; elect.sync _|p, 0xffffffff;\n"
               "@p cp.reduce.async.bulk.tensor.2d.global.shared::cta.add.bulk_group [%0, {%2, %3}], [%1]; }" :: "l"(tm), "r"(src), "r"(c0), "r"(c1) : "memory");
  else if (ONCE & 16) asm volatile("{ .reg .pred p; .reg .b64 h; " ONCE_H "elect.sync _|p, 0xffffffff;\n"
               "@p cp.async.bulk.tensor.2d.global.shared::cta.bulk_group.L2::cache_hint [%0, {%2, %3}], [%1], h; }" :: "l"(tm), "r"(src), "r"(c0), "r"(c1) : "memory");
  else asm volatile("{ .reg .pred p; elect.sync _|p, 0xffffffff;\n"
               "@p cp.async.bulk.tensor.2d.global.shared::cta.bulk_group [%0, {%2, %3}], [%1]; }" :: "l"(tm), "r"(src), "r"(c0), "r"(c1) : "memory");
}
__device__ __forceinline__ void tma2d_once(uint32_t dst, const CUtensorMap* tm, int c0, int c1, uint32_t bar) {
  asm volatile("{ .reg .pred p; .reg .b64 h; " ONCE_H "elect.sync _|p, 0xffffffff;\n"
               "@p cp.async.bulk.tensor.2d.shared::cluster.global.mbarrier::complete_tx::bytes.L2::cache_hint [%0], [%1, {%3, %4}], [%2], h; }"
               :: "r"(dst), "l"(tm), "r"(bar), "r"(c0), "r"(c1) : "memory");
}
__device__ __forceinline__ void bulk_once(uint32_t dst, const void* src, uint32_t bytes, uint32_t bar) {
  asm volatile("{ .reg .pred p; .reg .b64 h; " ONCE_H "elect.sync _|p, 0xffffffff;\n"
               "@p cp.async.bulk.shared::cluster.global.mbarrier::complete_tx::bytes.L2::cache_hint [%0], [%1], %2, [%3], h; }"
               :: "r"(dst), "l"(src), "r"(bytes), "r"(bar) : "memory");
}
__device__ __forceinline__ void tma4d_e(uint32_t dst, const CUtensorMap* tm, int c2, int c3, uint32_t bar) {
  asm volatile("{ .reg .pred p; .reg .b64 h; " ONCE_H "elect.sync _|p, 0xffffffff;\n"
               "@p cp.async.bulk.tensor.4d.shared::cluster.global.mbarrier::complete_tx::bytes.L2::cache_hint [%0], [%1, {0, 0, %3, %4}], [%2], h; }"
               :: "r"(dst), "l"(tm), "r"(bar), "r"(c2), "r"(c3) : "memory");
}
__device__ __forceinline__ void bulk_load_e(uint32_t dst, const void* src, uint32_t bytes, uint32_t bar) {
  asm volatile("{ .reg .pred p; elect.sync _|p, 0xffffffff;\n"
               "@p cp.async.bulk.shared::cluster.global.mbarrier::complete_tx::bytes [%0], [%1], %2, [%3]; }"
               :: "r"(dst), "l"(src), "r"(bytes), "r"(bar) : "memory");
}
template<bool O> __device__ __forceinline__ void tma2d_o(uint32_t dst, const CUtensorMap* tm, int c0, int c1, uint32_t bar) {
  if (O) tma2d_once(dst, tm, c0, c1, bar); else tma2d_e(dst, tm, c0, c1, bar);
}
__device__ __forceinline__ float2 ld_once(const float2* p) {
  float2 v;
  if (ONCE & 64) asm volatile("{ .reg .b64 h; " ONCE_H "ld.global.cg.L2::cache_hint.v2.f32 {%0, %1}, [%2], h; }" : "=f"(v.x), "=f"(v.y) : "l"(p));
  else v = __ldcg(p);
  return v;
}
template<bool O = false> __device__ __forceinline__ void prefetch2d_e(const CUtensorMap* tm, int c0, int c1) {
  if (O) asm volatile("{ .reg .pred p; .reg .b64 h; " ONCE_H "elect.sync _|p, 0xffffffff;\n"
               "@p cp.async.bulk.prefetch.tensor.2d.L2.global.L2::cache_hint [%0, {%1, %2}], h; }" :: "l"(tm), "r"(c0), "r"(c1) : "memory");
  else asm volatile("{ .reg .pred p; elect.sync _|p, 0xffffffff;\n"
               "@p cp.async.bulk.prefetch.tensor.2d.L2.global [%0, {%1, %2}]; }" :: "l"(tm), "r"(c0), "r"(c1) : "memory");
}
__device__ __forceinline__ void st_pub4(void* p, uint4 v) {
  asm volatile("st.relaxed.gpu.global.v4.u32 [%0], {%1,%2,%3,%4};" :: "l"(p), "r"(v.x), "r"(v.y), "r"(v.z), "r"(v.w) : "memory");
}
__device__ __forceinline__ void st_pub_if(void* p, uint32_t v, bool on) {
  asm volatile("{ .reg .pred p; setp.ne.u32 p, %2, 0; @p st.relaxed.gpu.global.u32 [%0], %1; }" :: "l"(p), "r"(v), "r"((uint32_t)on) : "memory");
}
__device__ __forceinline__ uint32_t mapa(uint32_t a, uint32_t r) {
  uint32_t d; asm volatile("mapa.shared::cluster.u32 %0, %1, %2;" : "=r"(d) : "r"(a), "r"(r)); return d;
}
__device__ __forceinline__ void st_async4(uint32_t a, uint32_t x, uint32_t y, uint32_t z, uint32_t w, uint32_t bar) {
  asm volatile("st.async.shared::cluster.mbarrier::complete_tx::bytes.v4.u32 [%0], {%1,%2,%3,%4}, [%5];"
               :: "r"(a), "r"(x), "r"(y), "r"(z), "r"(w), "r"(bar) : "memory");
}
__device__ __forceinline__ uint4 ld_poll(const void* p) {
  uint4 v;
  asm volatile("ld.volatile.global.v4.u32 {%0,%1,%2,%3}, [%4];" : "=r"(v.x), "=r"(v.y), "=r"(v.z), "=r"(v.w) : "l"(p) : "memory");
  return v;
}
__device__ __forceinline__ uint2 ld_poll2(const void* p) {
  uint2 v; asm volatile("ld.volatile.global.v2.u32 {%0,%1}, [%2];" : "=r"(v.x), "=r"(v.y) : "l"(p) : "memory"); return v;
}
__device__ __forceinline__ void st_pub2(void* p, uint32_t a, uint32_t b) {
  asm volatile("st.relaxed.gpu.global.v2.u32 [%0], {%1,%2};" :: "l"(p), "r"(a), "r"(b) : "memory");
}
__device__ __forceinline__ uint32_t ld_poll1(const void* p) {
  uint32_t v; asm volatile("ld.volatile.global.u32 %0, [%1];" : "=r"(v) : "l"(p) : "memory"); return v;
}
__device__ __forceinline__ uint32_t ld_acquire(const uint32_t* p) {
  uint32_t v; asm volatile("ld.acquire.gpu.global.u32 %0, [%1];" : "=r"(v) : "l"(p) : "memory"); return v;
}
__device__ __forceinline__ void st_pub(void* p, uint32_t v) {
  asm volatile("st.relaxed.gpu.global.u32 [%0], %1;" :: "l"(p), "r"(v) : "memory");
}
__device__ __forceinline__ uint32_t lds32(uint32_t a) {
  uint32_t v; asm volatile("ld.shared.u32 %0, [%1];" : "=r"(v) : "r"(a) : "memory"); return v;
}
__device__ __forceinline__ int race_init(void* p0, void* p1, uint32_t val) {
  int t;
  asm volatile("{ .reg .pred r; .reg .u32 a, b, u, v;\n"
               "atom.relaxed.gpu.global.exch.b32 u, [%1], %3; atom.relaxed.gpu.global.exch.b32 v, [%2], %3;\n"
               "setp.eq.u32 r, u, 0x12345; @r pmevent 1; mov.u32 a, %%clock;\n"
               "setp.eq.u32 r, v, 0x12345; @r pmevent 1; mov.u32 b, %%clock; sub.u32 %0, b, a; }" : "=r"(t) : "l"(p0), "l"(p1), "r"(val) : "memory");
  return t;
}
__device__ __forceinline__ void race_init2(void* p0, void* p1, uint32_t val) {
  asm volatile("{ .reg .pred r; .reg .u32 a, b, u, v;\n"
               "atom.relaxed.gpu.global.exch.b32 u, [%0], %2; atom.relaxed.gpu.global.exch.b32 v, [%1], %2;\n"
               "atom.relaxed.gpu.global.exch.b32 a, [%0 + 4096], %2; atom.relaxed.gpu.global.exch.b32 b, [%1 + 4096], %2;\n"
               "lop3.b32 u, u, v, a, 0x96; setp.eq.u32 r, u, 0x12345; setp.eq.and.u32 r, b, u, r; @r pmevent 1; }" :: "l"(p0), "l"(p1), "r"(val) : "memory");
}
__device__ __forceinline__ uint4 lds128(uint32_t a) {
  uint4 v; asm volatile("ld.shared.v4.u32 {%0,%1,%2,%3}, [%4];" : "=r"(v.x), "=r"(v.y), "=r"(v.z), "=r"(v.w) : "r"(a) : "memory"); return v;
}
__device__ __forceinline__ uint2 lds64(uint32_t a) {
  uint2 v; asm volatile("ld.shared.v2.u32 {%0,%1}, [%2];" : "=r"(v.x), "=r"(v.y) : "r"(a) : "memory"); return v;
}
__device__ __forceinline__ void sts128(uint32_t a, uint4 v) {
  asm volatile("st.shared.v4.u32 [%0], {%1,%2,%3,%4};" :: "r"(a), "r"(v.x), "r"(v.y), "r"(v.z), "r"(v.w) : "memory");
}
__device__ __forceinline__ void sts64(uint32_t a, uint32_t x, uint32_t y) { asm volatile("st.shared.v2.u32 [%0], {%1,%2};" :: "r"(a), "r"(x), "r"(y) : "memory"); }
__device__ __forceinline__ void sts32(uint32_t a, uint32_t x) { asm volatile("st.shared.u32 [%0], %1;" :: "r"(a), "r"(x) : "memory"); }
__device__ __forceinline__ void ldsm4t(uint32_t (&r)[4], uint32_t a) {
  asm volatile("ldmatrix.sync.aligned.m8n8.x4.trans.shared.b16 {%0,%1,%2,%3}, [%4];"
               : "=r"(r[0]), "=r"(r[1]), "=r"(r[2]), "=r"(r[3]) : "r"(a) : "memory");
}
__device__ __forceinline__ void ldsm4(uint32_t (&r)[4], uint32_t a) {
  asm volatile("ldmatrix.sync.aligned.m8n8.x4.shared.b16 {%0,%1,%2,%3}, [%4];"
               : "=r"(r[0]), "=r"(r[1]), "=r"(r[2]), "=r"(r[3]) : "r"(a) : "memory");
}
template<bool TRANS> __device__ __forceinline__ void stsm4(uint32_t a, uint32_t r0, uint32_t r1, uint32_t r2, uint32_t r3) {
  if (TRANS) asm volatile("stmatrix.sync.aligned.m8n8.x4.trans.shared.b16 [%0], {%1,%2,%3,%4};" :: "r"(a), "r"(r0), "r"(r1), "r"(r2), "r"(r3) : "memory");
  else       asm volatile("stmatrix.sync.aligned.m8n8.x4.shared.b16 [%0], {%1,%2,%3,%4};" :: "r"(a), "r"(r0), "r"(r1), "r"(r2), "r"(r3) : "memory");
}
__device__ __forceinline__ void mma16816(float (&d)[4], uint32_t a0, uint32_t a1, uint32_t a2, uint32_t a3, uint32_t b0, uint32_t b1) {
  asm volatile("mma.sync.aligned.m16n8k16.row.col.f32.bf16.bf16.f32 {%0,%1,%2,%3}, {%4,%5,%6,%7}, {%8,%9}, {%0,%1,%2,%3};"
               : "+f"(d[0]), "+f"(d[1]), "+f"(d[2]), "+f"(d[3]) : "r"(a0), "r"(a1), "r"(a2), "r"(a3), "r"(b0), "r"(b1));
}
__device__ __forceinline__ void mma1688(float (&d)[4], uint32_t a0, uint32_t a1, uint32_t b0) {
  asm volatile("mma.sync.aligned.m16n8k8.row.col.f32.bf16.bf16.f32 {%0,%1,%2,%3}, {%4,%5}, {%6}, {%0,%1,%2,%3};"
               : "+f"(d[0]), "+f"(d[1]), "+f"(d[2]), "+f"(d[3]) : "r"(a0), "r"(a1), "r"(b0));
}
__device__ __forceinline__ uint32_t pack_bf16(float lo, float hi) {
  uint32_t r; asm("cvt.rn.bf16x2.f32 %0, %1, %2;" : "=r"(r) : "f"(hi), "f"(lo)); return r;
}
__device__ __forceinline__ uint32_t add_bf16x2(uint32_t a, uint32_t b) {
  uint32_t r; asm("add.rn.bf16x2 %0, %1, %2;" : "=r"(r) : "r"(a), "r"(b)); return r;
}
__device__ __forceinline__ uint32_t umax4(uint4 v) { return max(max(v.x, v.y), max(v.z, v.w)); }
__device__ __forceinline__ uint32_t opaque(uint32_t x) { uint32_t r; asm volatile("mov.u32 %0, %1;" : "=r"(r) : "r"(x)); return r; }
template<class T> __device__ __forceinline__ void pin(T*& p) { asm volatile("" : "+l"(p)); }
__device__ __forceinline__ void pin(uint32_t& v) { asm volatile("" : "+r"(v)); }
__device__ __forceinline__ uint32_t desc_lo(uint32_t addr) { return ((addr & 0x3FFFF) >> 4) | 0x10000; }
__device__ __forceinline__ uint64_t desc128(uint32_t lo) {
  uint64_t d; asm("mov.b64 %0, {%1, %2};" : "=l"(d) : "r"(lo), "r"(0x40000040)); return d;
}
#define WG_FENCE()  asm volatile("wgmma.fence.sync.aligned;" ::: "memory")
#define WG_COMMIT() asm volatile("wgmma.commit_group.sync.aligned;" ::: "memory")
#define WG_WAIT(n)  asm volatile("wgmma.wait_group.sync.aligned " #n ";" ::: "memory")
#define FENCE_ASYNC_SMEM() asm volatile("fence.proxy.async.shared::cta;" ::: "memory")
__device__ __forceinline__ void bar_sync(int id, int n) { asm volatile("bar.sync %0, %1;" :: "r"(id), "r"(n) : "memory"); }

#define D16(c) c(d[0]), c(d[1]), c(d[2]), c(d[3]), c(d[4]), c(d[5]), c(d[6]), c(d[7]), \
               c(d[8]), c(d[9]), c(d[10]), c(d[11]), c(d[12]), c(d[13]), c(d[14]), c(d[15])
template<bool FIRST> __device__ __forceinline__ void wgmma_rs_n32(float (&d)[16], const uint32_t (&a)[4], uint64_t b) {
  if (FIRST)
    asm volatile("wgmma.mma_async.sync.aligned.m64n32k16.f32.bf16.bf16 {%0,%1,%2,%3,%4,%5,%6,%7,%8,%9,%10,%11,%12,%13,%14,%15}, {%16,%17,%18,%19}, %20, 0, 1, 1, 0;"
      : D16("=f") : "r"(a[0]), "r"(a[1]), "r"(a[2]), "r"(a[3]), "l"(b));
  else
    asm volatile("wgmma.mma_async.sync.aligned.m64n32k16.f32.bf16.bf16 {%0,%1,%2,%3,%4,%5,%6,%7,%8,%9,%10,%11,%12,%13,%14,%15}, {%16,%17,%18,%19}, %20, 1, 1, 1, 0;"
      : D16("+f") : "r"(a[0]), "r"(a[1]), "r"(a[2]), "r"(a[3]), "l"(b));
}
template<bool FIRST> __device__ __forceinline__ void wgmma_ss_n32_ta(float (&d)[16], uint64_t a, uint64_t b) {
  if (FIRST)
    asm volatile("wgmma.mma_async.sync.aligned.m64n32k16.f32.bf16.bf16 {%0,%1,%2,%3,%4,%5,%6,%7,%8,%9,%10,%11,%12,%13,%14,%15}, %16, %17, 0, 1, 1, 1, 0;"
      : D16("=f") : "l"(a), "l"(b));
  else
    asm volatile("wgmma.mma_async.sync.aligned.m64n32k16.f32.bf16.bf16 {%0,%1,%2,%3,%4,%5,%6,%7,%8,%9,%10,%11,%12,%13,%14,%15}, %16, %17, 1, 1, 1, 1, 0;"
      : D16("+f") : "l"(a), "l"(b));
}
__device__ __forceinline__ void wgmma_ss_n128_tb(float (&d)[64], uint64_t a, uint64_t b) {
  asm volatile("wgmma.mma_async.sync.aligned.m64n128k16.f32.bf16.bf16 "
    "{%0,%1,%2,%3,%4,%5,%6,%7,%8,%9,%10,%11,%12,%13,%14,%15,%16,%17,%18,%19,%20,%21,%22,%23,%24,%25,%26,%27,%28,%29,%30,%31,"
    "%32,%33,%34,%35,%36,%37,%38,%39,%40,%41,%42,%43,%44,%45,%46,%47,%48,%49,%50,%51,%52,%53,%54,%55,%56,%57,%58,%59,%60,%61,%62,%63}, "
    "%64, %65, 1, 1, 1, 0, 1;"
    : "+f"(d[0]), "+f"(d[1]), "+f"(d[2]), "+f"(d[3]), "+f"(d[4]), "+f"(d[5]), "+f"(d[6]), "+f"(d[7]),
      "+f"(d[8]), "+f"(d[9]), "+f"(d[10]), "+f"(d[11]), "+f"(d[12]), "+f"(d[13]), "+f"(d[14]), "+f"(d[15]),
      "+f"(d[16]), "+f"(d[17]), "+f"(d[18]), "+f"(d[19]), "+f"(d[20]), "+f"(d[21]), "+f"(d[22]), "+f"(d[23]),
      "+f"(d[24]), "+f"(d[25]), "+f"(d[26]), "+f"(d[27]), "+f"(d[28]), "+f"(d[29]), "+f"(d[30]), "+f"(d[31]),
      "+f"(d[32]), "+f"(d[33]), "+f"(d[34]), "+f"(d[35]), "+f"(d[36]), "+f"(d[37]), "+f"(d[38]), "+f"(d[39]),
      "+f"(d[40]), "+f"(d[41]), "+f"(d[42]), "+f"(d[43]), "+f"(d[44]), "+f"(d[45]), "+f"(d[46]), "+f"(d[47]),
      "+f"(d[48]), "+f"(d[49]), "+f"(d[50]), "+f"(d[51]), "+f"(d[52]), "+f"(d[53]), "+f"(d[54]), "+f"(d[55]),
      "+f"(d[56]), "+f"(d[57]), "+f"(d[58]), "+f"(d[59]), "+f"(d[60]), "+f"(d[61]), "+f"(d[62]), "+f"(d[63])
    : "l"(a), "l"(b));
}

__device__ __forceinline__ void tma3d_mc_e(uint32_t dst, const CUtensorMap* tm, int c1, int c2, uint32_t bar) {
  asm volatile("{ .reg .pred p; .reg .b64 h; " ONCE_H "elect.sync _|p, 0xffffffff;\n"
               "@p cp.async.bulk.tensor.3d.shared::cluster.global.mbarrier::complete_tx::bytes.multicast::cluster.L2::cache_hint [%0], [%1, {0, %3, %4}], [%2], %5, h; }"
               :: "r"(dst), "l"(tm), "r"(bar), "r"(c1), "r"(c2), "h"((uint16_t)3) : "memory");
}
__device__ __forceinline__ void prefetch3d_e(const CUtensorMap* tm, int c1, int c2) {
  asm volatile("{ .reg .pred p; elect.sync _|p, 0xffffffff;\n"
               "@p cp.async.bulk.prefetch.tensor.3d.L2.global [%0, {0, %1, %2}]; }" :: "l"(tm), "r"(c1), "r"(c2) : "memory");
}

__device__ __forceinline__ void count_e(uint32_t* p) {
  asm volatile("fence.acq_rel.gpu;" ::: "memory");
  __syncwarp();
  asm volatile("{ .reg .pred p; elect.sync _|p, 0xffffffff; @p red.relaxed.gpu.global.add.u32 [%0], 1; }" :: "l"(p) : "memory");
}
template<int NS = 0> __device__ __forceinline__ void await_count(const uint32_t* p, uint32_t n) {
  for (uint32_t i = 0; ld_acquire(p) < n && i < (1u << 22); i++) { if (NS) __nanosleep(NS); }
  asm volatile("fence.proxy.async.global;" ::: "memory");
}
__device__ __forceinline__ void await_flags(const uint32_t* p) {
  for (uint32_t i = 0; i < (1u << 22); i++) {
    uint4 v;
    asm volatile("ld.acquire.gpu.global.v4.u32 {%0,%1,%2,%3}, [%4];" : "=r"(v.x), "=r"(v.y), "=r"(v.z), "=r"(v.w) : "l"(p) : "memory");
    if (__all_sync(~0u, (v.x & v.y & v.z & v.w) == 0x01010101u)) break;
  }
  asm volatile("fence.proxy.async.global;" ::: "memory");
}
__device__ __forceinline__ void mbar_lim(uint32_t bar, uint32_t ph) { for (uint32_t i = 0; !mbar_try(bar, ph) && i < (1u << 20); i++) {} }

struct cf { float x, y; };
__host__ __device__ constexpr float cos64(int k) {
  return k == 0 ? 1.0f : k == 1 ? 0.99518472667219689f : k == 2 ? 0.98078528040323045f : k == 3 ? 0.95694033573220887f :
         k == 4 ? 0.92387953251128676f : k == 5 ? 0.88192126434835503f : k == 6 ? 0.83146961230254524f : k == 7 ? 0.77301045336273696f :
         k == 8 ? 0.70710678118654752f : k == 9 ? 0.63439328416364550f : k == 10 ? 0.55557023301960222f : k == 11 ? 0.47139673682599765f :
         k == 12 ? 0.38268343236508977f : k == 13 ? 0.29028467725446236f : k == 14 ? 0.19509032201612827f : k == 15 ? 0.09801714032956060f : 0.0f;
}
__host__ __device__ constexpr float c64(int k) { return k <= 16 ? cos64(k) : -cos64(32 - k); }
__host__ __device__ constexpr float s64(int k) { return k <= 16 ? cos64(16 - k) : cos64(k - 16); }

template<int N, int ST, bool INV> struct Fft {
  template<int K> static __device__ __forceinline__ void bf(const cf* e, const cf* o, cf* out) {
    if constexpr (K < N / 2) {
      constexpr int idx = K * (64 / N);
      const cf a = e[K], b = o[K];
      if constexpr (idx == 0) {
        out[K] = {a.x + b.x, a.y + b.y}; out[K + N / 2] = {a.x - b.x, a.y - b.y};
      } else if constexpr (idx == 16) {
        if constexpr (INV) { out[K] = {a.x - b.y, a.y + b.x}; out[K + N / 2] = {a.x + b.y, a.y - b.x}; }
        else               { out[K] = {a.x + b.y, a.y - b.x}; out[K + N / 2] = {a.x - b.y, a.y + b.x}; }
      } else {
        constexpr float c = c64(idx), s = INV ? s64(idx) : -s64(idx);
        cf p; p.x = fmaf(-s, b.y, fmaf(c, b.x, a.x)); p.y = fmaf(s, b.x, fmaf(c, b.y, a.y));
        out[K] = p; out[K + N / 2] = {fmaf(2.0f, a.x, -p.x), fmaf(2.0f, a.y, -p.y)};
      }
      bf<K + 1>(e, o, out);
    }
  }
  static __device__ __forceinline__ void run(const cf* in, cf* out) {
    cf e[N / 2], o[N / 2];
    Fft<N / 2, 2 * ST, INV>::run(in, e);
    Fft<N / 2, 2 * ST, INV>::run(in + ST, o);
    bf<0>(e, o, out);
  }
};
template<int ST, bool INV> struct Fft<1, ST, INV> {
  static __device__ __forceinline__ void run(const cf* in, cf* out) { out[0] = in[0]; }
};
template<bool INV> __device__ __forceinline__ void fft32(cf (&v)[32]) {
  cf o[32]; Fft<32, 1, INV>::run(v, o);
#pragma unroll
  for (int i = 0; i < 32; i++) v[i] = o[i];
}
__device__ __forceinline__ cf cmul(cf a, float c, float s) { return {fmaf(-a.y, s, a.x * c), fmaf(a.x, s, a.y * c)}; }
__device__ __forceinline__ float bf2f(__nv_bfloat16 v) { return __bfloat162float(v); }

__device__ __forceinline__ int tw_at(int i) { return (i & ~63) | (i & 31) << 1 | (i >> 5 & 1); }
template<bool INV, bool T128 = true> __device__ __forceinline__ void twiddles(cf (&v)[32], const float4* __restrict__ tw) {
#pragma unroll
  for (int j = 0; j < 32; j += 2) {
    float4 w;
    if (T128) w = tw[j * 16];
    else { const uint2 a = lds64(smem_u32(tw + j * 16)), b = lds64(smem_u32(tw + j * 16) + 8); w = make_float4(__uint_as_float(a.x), __uint_as_float(a.y), __uint_as_float(b.x), __uint_as_float(b.y)); }
    if (j) v[j] = cmul(v[j], w.x, INV ? -w.y : w.y);
    v[j + 1] = cmul(v[j + 1], w.z, INV ? -w.w : w.w);
  }
}
template<bool INV, class F> __device__ __forceinline__ void warp_fft1024(cf (&v)[32], float2* __restrict__ buf, const float2* __restrict__ tw, int t, int u, F mid) {
#pragma unroll 1
  for (uint32_t h = 0; h < 2; h++) {
    fft32<INV>(v);
    if (FUNR ? h : opaque(h)) continue;
    twiddles<INV>(v, (const float4*)tw + u);
    if (INV) {
      float* f = (float*)buf;
#pragma unroll
      for (int j = 0; j < 32; j++) f[j * 36 + t] = v[j].x;
      __syncwarp();
#pragma unroll
      for (int j = 0; j < 32; j += 4) { const float4 r = *(const float4*)(f + u * 36 + j); v[j].x = r.x; v[j + 1].x = r.y; v[j + 2].x = r.z; v[j + 3].x = r.w; }
      __syncwarp();
#pragma unroll
      for (int j = 0; j < 32; j++) f[j * 36 + t] = v[j].y;
      __syncwarp();
#pragma unroll
      for (int j = 0; j < 32; j += 4) { const float4 r = *(const float4*)(f + u * 36 + j); v[j].y = r.x; v[j + 1].y = r.y; v[j + 2].y = r.z; v[j + 3].y = r.w; }
    } else {
#pragma unroll
      for (int j = 0; j < 32; j++) buf[j * 33 + t] = make_float2(v[j].x, v[j].y);
      __syncwarp();
#pragma unroll
      for (int j = 0; j < 32; j++) { const float2 r = buf[u * 33 + j]; v[j] = {r.x, r.y}; }
    }
    __syncwarp();
    mid();
  }
}
constexpr int ROW_BUF = 32 * 33, INV_BUF = 32 * 18;

__device__ __forceinline__ int z_row(int p) { return (p & ~31) | (p & 7) << 2 | (p & 31) >> 3; }
__device__ __forceinline__ int inv_lane(int t) { return (t & ~14) | (t & 12) >> 1 | (t & 2) << 2; }
__device__ __forceinline__ float2 twiddle(int i) { float s, c; sincospif(-(float)((i >> 5) * (i & 31)) * (1.0f / 512.0f), &s, &c); return make_float2(c, s); }
template<class F, class G> __device__ __forceinline__ void fft_rows_fwd(float2* sm2, const __nv_bfloat16* gw, int cta, int tid, uint32_t full_bar, uint32_t release_bar, F ev, G extra) {
  const int t = tid & 31, w = tid >> 5, n = z_row(cta * 8 + w);
#pragma unroll 1
  for (int i = tid; i < 1024; i += 256) sm2[tw_at(i)] = twiddle(i);
  ev(5);
  mbar_spin(full_bar, 0);
  if (tid == 0) TL2(6);
  __syncwarp();
  const __nv_bfloat16* xa = (const __nv_bfloat16*)(sm2 + 1024 + w * ROW_BUF) + t;
  cf v[32];
  float ga = 0.f, gb = 0.f;
#pragma unroll
  for (int j = 0; j < 32; j++) {
    v[j] = {bf2f(xa[32 * j]), bf2f(xa[D_ + 32 * j])};
    const float g = bf2f(gw[32 * j + t]); ga = fmaf(v[j].x, g, ga); gb = fmaf(v[j].y, g, gb);
  }
#pragma unroll
  for (int o = 16; o; o >>= 1) { ga += __shfl_xor_sync(~0u, ga, o); gb += __shfl_xor_sync(~0u, gb, o); }
  if (t < 2) g_gate[n + 1024 * t] = __fdividef(1.0f, 1.0f + __expf(-(t ? gb : ga)));
  ev(6);
  bar_sync(13, 256);
  warp_fft1024<false>(v, sm2 + 1024 + w * ROW_BUF, sm2, t, t, [&]() { FENCE_ASYNC_SMEM(); mbar_arrive_warp(release_bar); });
  float ws, wc; sincospif(-(float)n * (1.0f / 1024.0f), &ws, &wc);
  ev(12);
  uint32_t tz = clock_lo();
  float4* z = (float4*)g_z + ((size_t)(t >> 1) * 1024 + cta * 8 + w) * 2 + (t & 1);
#pragma unroll
  for (int j = 0; j < 17; j++) {
    cf q = v[(32 - j) & 31];
    if (j < 16) {
      const cf r = {__shfl_sync(~0u, v[31 - j].x, 32 - t), __shfl_sync(~0u, v[31 - j].y, 32 - t)};
      if (t != 0) q = r;
    }
    const cf a = {v[j].x + q.x, v[j].y - q.y}, b = {v[j].y + q.y, q.x - v[j].x};
    const cf d = cmul({a.x - b.x, a.y - b.y}, wc, ws);
    if (j == POOL_AT) extra();
    if (PACE_Z && j && j < 16) delay_until(tz += PACE_Z);
    if ((j < 16 || t == 0) && ((EXP_ST & 4) || d.x == 123.f)) z[j * 32768] = make_float4(a.x + b.x, a.y + b.y, d.x, d.y);
  }
}
constexpr int CP = X128 == 0 ? 33 : X128 == 2 ? 34 : 36, COL_FS = 32 * 36 + 8, COL_W = (8192 + 16 * COL_FS * 4 + 127) & ~127, COL_SMEM = COL_W + 131072 + 128;

__device__ __forceinline__ void fft_cols(float2* sm2, int cta, const CUtensorMap* twr, const CUtensorMap* twi, const CUtensorMap* tzs) {
  const int grp = __shfl_sync(~0u, (int)(threadIdx.x >> 7), 0), tid = threadIdx.x & 127, tp = tid >> 2, w = __shfl_sync(~0u, tid >> 5, 0);
  float* buf = (float*)(sm2 + 1024) + (grp * 4 + (tid & 3)) * COL_FS;
  const uint32_t wsm = smem_u32(sm2) + COL_W, wbar = wsm + 131072 + (W_FINE ? w * 32 : 0);
  const int res = w * 2 + (tid & 1), el = res + grp * 2 + ((tid >> 1) & 1);
  uint32_t wa = (el >> 3) * 65536 + res * 4096 + (tp & 7) * 16 + (el & 7) * 2;
  auto load_w = [&](int q) {
    const uint32_t bar = wbar + (q & 1) * 8;
    mbar_expect(bar, W_FINE ? 16384 : 65536);
#pragma unroll 1
    for (int i = W_FINE ? 4 * w : 0; i < (W_FINE ? 4 * w + 4 : 16); i++) tma2d(wsm + (q & 1) * 65536 + (i & 1) * 32768 + (i >> 1) * 4096, i & 1 ? twi : twr, (i >> 1) * 512 + q * 8, 0, bar);
  };
  const bool lead = (tid & (W_FINE ? 31 : 127)) == 0, first = grp < 2 && lead;
  if (first) { mbar_init(wbar + grp * 8, 1); sts32(wbar + 16 + grp * 4, grp ? 0 : w); asm volatile("fence.mbarrier_init.release.cluster;" ::: "memory"); }
#pragma unroll 1
  for (int i = threadIdx.x; i < 1024; i += 512) {
    const float2 t = twiddle(z_row(i));
    sm2[tw_at(i)] = t;
    if (cta == 0) g_tw[tw_at(inv_lane(z_row(i)))] = t;
  }
  for (uint32_t n = 0; ld_acquire(g_ctl + C_P1) < 128; ) { watchdog(n, 1u << 22); __nanosleep(200); }
  if (COL_DLY) delay_cycles(COL_DLY);
  if (first) load_w(cta * 16 + grp);
  __syncthreads();
  delay_cycles(1 + grp * DLY_GRP);
  mbar_wait(wbar, 0);
  const int end = cta * 64 + 64 + (cta == 3);
  for (int item = cta * 64 + grp; item < end; item += 4, wa ^= 65536) {
    float2* zp = g_z + (size_t)item * 4096;
    auto next_w = [&]() {
      const int q = (item >> 2) + (W_FINE && grp + w > 3);
      uint32_t n; asm volatile("atom.shared.inc.u32 %0, [%1], 3;" : "=r"(n) : "r"(wbar + 16 + (q & 1) * 4) : "memory");
      if (EXP_W && n == 3 && q < (cta * 16 + 15)) load_w(q + 2);
    };
    cf v[32];
#pragma unroll
    for (int j = 0; j < 32; j++) { const float2 a = ld_once(zp + tid + j * 128); v[j] = {a.x, a.y}; }
#pragma unroll 1
    for (int ph = 0; ; ph++) {
      fft32<false>(v);
      twiddles<false, T128_>(v, (const float4*)sm2 + tp);
      if (Z_ST) asm volatile("cp.async.bulk.wait_group.read 0;" ::: "memory");
      bar_sync(1 + grp, 128);
      if (lead) {
        if (ph) {
          if (!W_AT) next_w();
        } else if (Z_PF && item + 4 < end) asm volatile("cp.async.bulk.prefetch.L2.global [%0], %1;" :: "l"(zp + 4 * 4096 + w * 1024), "n"(W_FINE ? 8192 : 32768) : "memory");
      }
      __syncwarp();
#pragma unroll
      for (int j = 0; j < 32; j++) buf[((j & 3) * 8 + (j >> 2)) * CP + tp] = v[j].x;
      bar_sync(1 + grp, 128);
      if (X128 == 0) {
#pragma unroll
        for (int j = 0; j < 32; j++) v[j].x = buf[tp * CP + (j & 3) * 8 + (j >> 2)];
      } else if (X128 == 2) {
#pragma unroll
        for (int j = 0; j < 16; j++) { const float2 r = *(const float2*)(buf + tp * CP + 2 * j); cf* d = v + (j & 3) * 8 + (j >> 2); d[0].x = r.x; d[4].x = r.y; }
      } else
#pragma unroll
      for (int j = 0; j < 8; j++) {
        const float4 r = *(const float4*)(buf + tp * 36 + 4 * j);
        cf* d = v + (j & 1) * 16 + (j >> 1);
        d[0].x = r.x; d[4].x = r.y; d[8].x = r.z; d[12].x = r.w;
      }
      bar_sync(1 + grp, 128);
#pragma unroll
      for (int j = 0; j < 32; j++) buf[((j & 3) * 8 + (j >> 2)) * CP + tp] = v[j].y;
      bar_sync(1 + grp, 128);
      if (X128 == 0) {
#pragma unroll
        for (int j = 0; j < 32; j++) v[j].y = buf[tp * CP + (j & 3) * 8 + (j >> 2)];
      } else if (X128 == 2) {
#pragma unroll
        for (int j = 0; j < 16; j++) { const float2 r = *(const float2*)(buf + tp * CP + 2 * j); cf* d = v + (j & 3) * 8 + (j >> 2); d[0].y = r.x; d[4].y = r.y; }
      } else
#pragma unroll
      for (int j = 0; j < 8; j++) {
        const float4 r = *(const float4*)(buf + tp * 36 + 4 * j);
        cf* d = v + (j & 1) * 16 + (j >> 1);
        d[0].y = r.x; d[4].y = r.y; d[8].y = r.z; d[12].y = r.w;
      }
      fft32<false>(v);
      if (ph) break;
      const int q = min((item >> 2) + (!W_FINE || grp + w >= 3), 64);
      if (EXP_W) mbar_wait(wbar + (q & 1) * 8, (q >> 1) & 1);
#pragma unroll
      for (int j = 0; j < 32; j++) {
        uint32_t re, im;
        asm volatile("ld.shared.u16 %0, [%1];" : "=r"(re) : "r"(wsm + wa + j * 128) : "memory");
        asm volatile("ld.shared.u16 %0, [%1];" : "=r"(im) : "r"(wsm + wa + 32768 + j * 128) : "memory");
        const cf r = cmul(v[j], __uint_as_float(re << 16), __uint_as_float(im << 16));
        v[j] = {r.y, r.x};
      }
    }
    if (Z_ST) {
      float2* st = sm2 + 1024 + grp * (COL_FS * 2) + w * 512;
      bar_sync(1 + grp, 128);
#pragma unroll
      for (int h = 0; h < 2; h++) {
        if (h && Z_ST == 2) {
#pragma unroll
          for (int j = 16; j < 32; j++) zp[tid + j * 128] = make_float2(v[j].y, v[j].x);
          break;
        }
        if (h) { asm volatile("cp.async.bulk.wait_group.read 0;" ::: "memory"); __syncwarp(); }
#pragma unroll
        for (int j = 0; j < 16; j++) st[j * 32 + (tid & 31)] = make_float2(v[h * 16 + j].y, v[h * 16 + j].x);
        FENCE_ASYNC_SMEM();
        __syncwarp();
        tma2d_st_e(tzs, w * 128, item * 32 + h * 16, smem_u32(st));
        asm volatile("cp.async.bulk.commit_group;" ::: "memory");
      }
    } else {
#pragma unroll
      for (int j = 0; j < 32; j++) zp[tid + j * 128] = make_float2(v[j].y, v[j].x);
    }
    if (W_AT) { if (lead) next_w(); __syncwarp(); }
  }
  if (Z_ST) asm volatile("cp.async.bulk.wait_group 0; fence.proxy.async.global;" ::: "memory");
  const float4 t = ((const float4*)sm2)[threadIdx.x];
  __syncthreads();
  if (TW_L) ((float4*)sm2)[inv_lane(z_row(threadIdx.x))] = t;
  if (threadIdx.x < 32) {
    count_e(g_ctl + C_COLS);
    await_count(g_ctl + C_COLS, 4);
    g_ctl[C_P1] = 0;
  }
  __syncthreads();
  if (!TW_L) {
    ((float4*)sm2)[threadIdx.x] = __ldcg((const float4*)g_tw + threadIdx.x);
    __syncthreads();
  }
}

template<class F> __device__ __forceinline__ void fft_rows_inv(uint32_t zs, float2* buf, const float2* tw, int p, int lane, __nv_bfloat16* out, F read) {
  const int n = z_row(p), t = (lane & 17) | (lane & 6) << 1 | (lane & 8) >> 2, src = inv_lane(-t & 31);
  const uint32_t z = zs + (t >> 1) * 128 + ((((p & 3) * 2 + (t & 1)) ^ (t >> 1 & 7)) << 4);
  FT(0, 0.f);
  float4 e[17];
  uint32_t all = 0;
  e[16] = __ldcg((const float4*)g_z + ((size_t)256 * 1024 + p) * 2);
  const float g0 = __ldcg(g_gate + n), g1 = __ldcg(g_gate + n + 1024);
#pragma unroll
  for (int j = 0; j < 16; j++) { const uint4 u = lds128(z + j * 2048); e[j] = make_float4(__uint_as_float(u.x), __uint_as_float(u.y), __uint_as_float(u.z), __uint_as_float(u.w)); all |= u.x; }
  sched_fence(all);
  read();
  float ws, wc; sincospif((float)n * (1.0f / 1024.0f), &ws, &wc);
  cf v[32], q[17];
#pragma unroll
  for (int j = 0; j < 17; j++) {
    const cf d = cmul({e[j].z, e[j].w}, wc, ws);
    cf a = {e[j].x + d.x, e[j].y + d.y}, b = {e[j].x - d.x, e[j].y - d.y};
    if (j == 16 || (j == 0 && t == 0)) { a.y = 0.f; b.y = 0.f; }
    if (j < 16) v[j] = {a.x - b.y, a.y + b.x};
    q[j] = {a.x + b.y, b.x - a.y};
  }
#pragma unroll
  for (int j = 16; j < 32; j++) {
    v[j] = {__shfl_sync(~0u, q[31 - j].x, src), __shfl_sync(~0u, q[31 - j].y, src)};
    if (t == 0) v[j] = q[32 - j];
  }
  FT(1, v[0].x + v[16].x + v[31].x);
  if (B_ST) { asm volatile("cp.async.bulk.wait_group.read 0;" ::: "memory"); __syncwarp(); }
  warp_fft1024<true>(v, buf, tw, t, lane, []() {});
  FT(3, v[31].y + v[0].x);
  const float sc = 0.5f / (2048.0f * 1024.0f), s0 = (1.f - g0) * sc, s1 = (1.f - g1) * sc;
  uint2* o = (B_ST ? (uint2*)buf : (uint2*)(out + (size_t)n * D_)) + (lane ^ (n & 1) << 3);
#pragma unroll
  for (int j = 0; j < 32; j += 4) {
    o[8 * j] = make_uint2(pack_bf16(v[j].x * s0, v[j + 1].x * s0), pack_bf16(v[j + 2].x * s0, v[j + 3].x * s0));
    o[(B_ST ? 256 : 256 * D_) + 8 * j] = make_uint2(pack_bf16(v[j].y * s1, v[j + 1].y * s1), pack_bf16(v[j + 2].y * s1, v[j + 3].y * s1));
  }
  if (B_ST) {
    FENCE_ASYNC_SMEM();
    __syncwarp();
    asm volatile("{ .reg .pred p; setp.lt.u32 p, %2, 2; @p cp.async.bulk.global.shared::cta.bulk_group [%0], [%1], 2048; cp.async.bulk.commit_group; }"
                 :: "l"(out + (size_t)(n + 1024 * (lane & 1)) * D_), "r"(smem_u32(buf) + (lane & 1) * 2048), "r"(lane) : "memory");
  }
  FT(4, 0.f);
}

constexpr int NP = NP_, NHV = REG_F == 216 ? 5 : 7, NV = 16 - NHV;
constexpr int XEND = NSEG;
constexpr uint32_t SM_WO = 0, SM_V = 65536, SM_LAND = SM_V + 8192, SM_MEM = SM_LAND + 24576, SM_SP = SM_MEM, SM_SPM = SM_MEM + 5120, SM_OM = SM_MEM + 6144,
                   SM_OX = SM_MEM + 8192, SM_RED = SM_OX + 2048, SM_XCH = SM_RED + 1024, SM_SUM = SM_XCH + 4096, SM_VM = SM_SUM + 128, SM_TAB = SM_VM + 2048, SM_TRACE = SM_TAB + 2048, SM_K = SM_TRACE,
                   ST_WG = (32 - NP + NV) * 2048,
                   SM_XT = 2 * ST_WG, SM_POOL = SM_XT + 32768, SM_HV = SM_POOL + 2 * NP * 2048,
                   SM_BAR = SM_HV + 2 * NHV * 2048, SM_SEL = SM_BAR + 320, CHAIN_SMEM = SM_SEL + 544 + 1024;
constexpr uint32_t SM_FFT = 49152, SM_GW = SM_XT - 2048;
static_assert(NP % 4 == 0 && NV == 11 && SM_TRACE + 8192 <= SM_XT, "shared memory layout");
static_assert(CHAIN_SMEM <= 232448 && COL_SMEM <= SM_BAR && SM_FFT + (1024 + 8 * ROW_BUF) * 8 <= SM_GW && NP == 12, "shared memory budget");
enum { B_WFULL = 0, B_WREAD = 2, B_WOFULL, B_XFULL, B_XEMPTY, B_E1TRIG, B_E2TRIG, B_PVDONE, B_PUB, B_SC, B_PFULL, B_SPFREE,
       B_LAND, B_LFREE, B_DONE, B_SEL, B_PROBE, B_FREE, B_P1, B_ROWS, B_VFULL, B_VST, B_TW, B_BT, B_WREAD0, B_Z, B_GFULL = B_Z + 4, B_GEMPTY = B_GFULL + 5, B_END = B_GEMPTY + 5 };
static_assert(B_END * 8 <= 320, "barriers");
__host__ __device__ constexpr uint32_t bar_codes(int g) {
  uint32_t r = 0;
  for (int i = 16 * g; i < 16 * g + 16; i++)
    r |= (i == B_LAND ? 3u : i == B_WREAD || i == B_XEMPTY || i == B_E1TRIG || i == B_E2TRIG || i == B_LFREE || i == B_FREE || i == B_VST || i == B_P1 || i == B_ROWS ? 2u :
          i >= B_GEMPTY || i == B_WREAD0 || i == B_PROBE || i == B_DONE || i == B_PVDONE || i == B_PUB || i == B_SC || i == B_SPFREE ? 1u : 0u) << 2 * (i & 15);
  return r;
}
constexpr uint32_t SM_BT = 65536, SM_TW = SM_XT - 8192, COL_Z = 80 * 1024;
static_assert(SM_XT + 3 * 32768 <= SM_BAR && SM_BT + 32768 <= SM_MEM && SM_TRACE <= SM_TW && SM_MEM + 4 * INV_BUF * 8 <= SM_TRACE &&
              8192 + 16 * INV_BUF * 8 <= COL_Z && COL_Z + 131072 <= SM_BAR, "shared memory layout");
__device__ __forceinline__ uint32_t next_stage(uint32_t o) { return o == SM_XT + 65536 ? 0 : o == 32768 ? SM_XT : o + 32768; }

struct ChainCtx { char* mail; uint32_t sb, sel; int r, h, a, b, j, m, w, lane; };
#define BAR(i) (c.sb + SM_BAR + 8 * (i))

__device__ __forceinline__ uint32_t tile_off(int line, int lane) {
  return line * 128 + (((lane & 3) ^ line) << 5) + (lane >> 2) * 4;
}
__device__ __forceinline__ uint32_t read_off(int lane) {
  const int n = lane >> 2, jj = lane & 3, l = 2 * (jj >> 1) + (n & 1);
  return l * 128 + (((n >> 1) ^ l) << 5) + (jj & 1) * 16;
}
__device__ __forceinline__ uint32_t frag_off(int w, int lane) {
  const int mi = lane >> 3, r = lane & 7;
  return ((mi >> 1) * 8 + r) * 128 + (((2 * w + (mi & 1)) ^ r) << 4);
}
__device__ __forceinline__ uint32_t land_off(int w, int lane) { return w * 512 + ((lane ^ (((lane >> 4) | ((w & 1) << 1)) << 1)) << 4); }
__device__ __forceinline__ uint32_t tagged(uint32_t v, uint32_t tag) { return (v | 1u) ^ tag; }
__device__ __forceinline__ void mma_a(float (&d)[4], const uint32_t (&a)[4], uint32_t b0, uint32_t b1) { mma16816(d, a[0], a[1], a[2], a[3], b0, b1); }
__device__ __forceinline__ void mma_q(float (&d)[4], const uint4& a, uint32_t b0, uint32_t b1) { mma16816(d, a.x, a.y, a.z, a.w, b0, b1); }
__device__ __forceinline__ uint4 add4(uint4 a, uint4 b) {
  return make_uint4(add_bf16x2(a.x, b.x), add_bf16x2(a.y, b.y), add_bf16x2(a.z, b.z), add_bf16x2(a.w, b.w));
}
__device__ __forceinline__ void mbar_arrive_both(uint32_t bar, int peer) {
  __syncwarp();
  asm volatile("{ .reg .pred p; .reg .u32 a; mapa.shared::cluster.u32 a, %0, %1; elect.sync _|p, 0xffffffff;\n"
               "@p mbarrier.arrive.shared::cta.b64 _, [%0]; @p mbarrier.arrive.shared::cluster.b64 _, [a]; }" :: "r"(bar), "r"(peer) : "memory");
}

__device__ __forceinline__ void arrive_remote_if(uint32_t a, bool on) {
  asm volatile("{ .reg .pred p; setp.ne.u32 p, %1, 0; @p mbarrier.arrive.shared::cluster.b64 _, [%0]; }" :: "r"(a), "r"((uint32_t)on) : "memory");
}
__device__ __forceinline__ void store_count(void* p, uint4 v, void* cnt) {
  asm volatile("{ .reg .pred p, q; .reg .b128 a, b; .reg .b64 l, h; mov.b64 l, {%1, %2}; mov.b64 h, {%3, %4}; mov.b128 a, {l, h};\n"
               "atom.relaxed.gpu.global.exch.b128 b, [%0], a; mov.b128 {l, h}, b; setp.eq.u64 q, l, 0x7fc17fc17fc17fc1; @q pmevent 1;\n"
               "elect.sync _|p, 0xffffffff; @p red.relaxed.gpu.global.add.u32 [%5], 1; }"
               :: "l"(p), "r"(v.x), "r"(v.y), "r"(v.z), "r"(v.w), "l"(cnt) : "memory");
}

template<int N> __device__ __forceinline__ void pad() {
#pragma unroll
  for (int i = 0; i < N; i++) asm volatile("pmevent 3;");
}
__device__ __forceinline__ int lane_id() {
  int l; asm volatile("{ .reg .u32 t; mov.u32 t, %%laneid; shfl.sync.idx.b32 %0, t, t, 31, 0xffffffff; }" : "=r"(l)); return l;
}
__device__ __forceinline__ uint32_t tid_now() { uint32_t t; asm volatile("mov.u32 %0, %%tid.x;" : "=r"(t)); return t; }
enum { NB_ATT = 1, NB_OM = 2, NB_VM = 3, NB_XCH = 4, NB_MEM = 8, NB_HELP = 12 };
__device__ __forceinline__ uint32_t dep(uint32_t a, uint32_t v, uint32_t z) { uint32_t r; asm("shf.l.wrap.b32 %0, %2, %1, %3;" : "=r"(r) : "r"(a), "r"(v), "r"(z)); return r; }
__device__ __forceinline__ uint32_t vary(uint32_t a, int s, uint32_t z) { return dep(a, 0, z + 32 * s); }
__device__ __forceinline__ char* mk_ptr(uint32_t lo, uint32_t hi) { uint64_t r; asm("mov.b64 %0, {%1, %2};" : "=l"(r) : "r"(lo), "r"(hi)); return (char*)r; }
__device__ __forceinline__ void lds_frag(uint32_t (&r)[4], uint32_t a) {
  asm volatile("ld.shared.v4.u32 {%0,%1,%2,%3}, [%4];" : "=r"(r[0]), "=r"(r[1]), "=r"(r[2]), "=r"(r[3]) : "r"(a) : "memory");
}
__device__ __forceinline__ uint32_t stale2(uint32_t a, uint32_t b, uint32_t t) { uint32_t r; asm("lop3.b32 %0, %1, %2, %3, 0xbd;" : "=r"(r) : "r"(a), "r"(b), "r"(t)); return r; }
__device__ __forceinline__ uint32_t stale1(uint32_t acc, uint32_t a, uint32_t t) { uint32_t r; asm("lop3.b32 %0, %1, %2, %3, 0xf9;" : "=r"(r) : "r"(acc), "r"(a), "r"(t)); return r; }
__device__ __forceinline__ bool all_clear(uint32_t x, uint32_t m) {
  uint32_t r;
  asm volatile("{ .reg .pred p; .reg .u32 t; and.b32 t, %1, %2; setp.eq.u32 p, t, 0; vote.sync.all.pred p, p, 0xffffffff; selp.u32 %0, 1, 0, p; }" : "=r"(r) : "r"(x), "r"(m));
  return r;
}
__device__ __forceinline__ bool arrive_if_all(bool ok, int id, int n) {
  uint32_t r;
  asm volatile("{ .reg .pred p, q; setp.ne.u32 p, %1, 0; vote.sync.all.pred q, p, 0xffffffff; @q bar.arrive %2, %3; selp.u32 %0, 1, 0, q; }"
               : "=r"(r) : "r"((uint32_t)ok), "r"(id), "r"(n) : "memory");
  return r;
}
__device__ __forceinline__ bool arrive_if_clear(uint32_t x, uint32_t m, int id, int n) {
  uint32_t r;
  asm volatile("{ .reg .pred p; .reg .u32 t; and.b32 t, %1, %2; setp.eq.u32 p, t, 0; vote.sync.all.pred p, p, 0xffffffff; @p bar.arrive %3, %4; selp.u32 %0, 1, 0, p; }"
               : "=r"(r) : "r"(x), "r"(m), "r"(id), "r"(n) : "memory");
  return r;
}
__device__ __forceinline__ void touch(const void* p, uint32_t z) {
  asm volatile("{ .reg .pred p; setp.eq.u32 p, %1, 0x7fff0000; @p prefetch.global.L2 [%0]; }" :: "l"(p), "r"(z) : "memory");
}

__device__ __forceinline__ uint64_t desc_x(uint32_t lo, int k) {
  uint64_t d; asm("mov.b64 %0, {%1, %2};" : "=l"(d) : "r"(lo + (k >> 2) * 64 + (k & 3) * 2), "r"(0x40000200)); return d;
}
template<int K0, int K1> __device__ __forceinline__ void issue_qk(float (&xa)[16], const uint32_t (&wt)[16][4], uint32_t lo) {
  WG_FENCE();
#pragma unroll
  for (int k = K0; k < K1; k++) {
    if (k >= EXP_NWG) continue;
    if (k == 0) wgmma_rs_n32<true>(xa, wt[0], desc_x(lo, 0));
    else wgmma_rs_n32<false>(xa, wt[k], desc_x(lo, k));
  }
  WG_COMMIT();
}
__host__ __device__ constexpr int v_order(int i) { return SSPOS == 0 ? i : SSPOS == 2 ? (i + NV) % 16 : NHV == 5 ? (i % 3 == 2 ? NV + i / 3 : i - i / 3) : (i == 15 ? NV - 1 : i % 2 ? NV + i / 2 : i / 2); }
__device__ __forceinline__ void issue_v(float (&xa)[16], const uint32_t (&wv)[16][4], uint32_t lo, uint32_t la) {
  WG_FENCE();
#pragma unroll
  for (int i = 0; i < EXP_NWG; i++) {
    const int k = v_order(i);
    const uint64_t b = desc_x(lo, k);
    if (k < NV) { if (i == 0) wgmma_rs_n32<true>(xa, wv[k], b); else wgmma_rs_n32<false>(xa, wv[k], b); }
    else        { if (i == 0) wgmma_ss_n32_ta<true>(xa, desc128(la + (k - NV) * 128), b); else wgmma_ss_n32_ta<false>(xa, desc128(la + (k - NV) * 128), b); }
  }
  WG_COMMIT();
}
template<bool ISV> __device__ __forceinline__ void park_own(uint32_t (&q)[4], float (&xa)[16], uint32_t dst, int slot, uint32_t z) {
  uint32_t p[8];
#pragma unroll
  for (int i = 0; i < 16; i++) asm volatile("" : "+f"(xa[i]) :: "memory");
#pragma unroll
  for (int i = 0; i < 2; i++) {
    const float* k = xa + 8 * i;
    if (ISV) { p[4 * i] = pack_bf16(k[0], k[1]); p[4 * i + 1] = pack_bf16(k[2], k[3]); p[4 * i + 2] = pack_bf16(k[4], k[5]); p[4 * i + 3] = pack_bf16(k[6], k[7]); }
    else     { p[4 * i] = pack_bf16(k[0], k[2]); p[4 * i + 1] = pack_bf16(k[1], k[3]); p[4 * i + 2] = pack_bf16(k[4], k[6]); p[4 * i + 3] = pack_bf16(k[5], k[7]); }
  }
  sts128(dep(dep(dst, p[4] ^ p[5] ^ p[6], z), p[7], z) + slot * 8192, make_uint4(p[0], p[1], p[2], p[3]));
#pragma unroll
  for (int i = 0; i < 4; i++) q[i] = p[4 + i];
}
__device__ __forceinline__ void park_peer(const uint32_t (&q)[4], uint32_t dst, int slot, const ChainCtx& c) {
  const uint32_t bar = BAR(B_LAND);
  if (EXP_PEER) st_async4(mapa(dst + slot * 8192, c.b ^ 1), q[0], q[1], q[2], q[3], mapa(bar, c.b ^ 1));
  else touch((void*)(uintptr_t)(q[0] ^ q[1] ^ q[2] ^ q[3]), c.sb);
  mbar_arrive_warp(bar);
}
__device__ __forceinline__ uint32_t put_tag(uint32_t v, uint32_t bit, uint32_t t) {
  uint32_t r; asm("lop3.b32 %0, %1, %2, %3, 0x74;" : "=r"(r) : "r"(v), "r"(bit), "r"(t)); return r;
}
__device__ __forceinline__ void mem_proj(const uint32_t (&wa)[16][4], const uint32_t (&wb)[16][4], uint32_t (&wv)[16][4], uint32_t (&af)[16][4],
                                         uint32_t& wo, const char*& pa, uint32_t tab, uint32_t t16, uint32_t pk, const ChainCtx& c, int s) {
  const uint32_t mp = t16 & ~0x600u, id = NB_MEM + (t16 >> 11);
  uint32_t r[8][4];
  float la[4][4] = {}, lg[NLAG][4] = {}, lv[4][4] = {};
  auto lead = [&](int k) { mma_a(la[k & 3], wa[k], r[k >> 1][2 * (k & 1)], r[k >> 1][2 * (k & 1) + 1]); };
  auto lag = [&](int k) { mma_a(lg[k % NLAG], wb[k], r[k >> 1][2 * (k & 1)], r[k >> 1][2 * (k & 1) + 1]); };
  auto sum = [](const float (&d)[4][4], int i) { return (d[0][i] + d[1][i]) + (d[2][i] + d[3][i]); };
  bar_sync(id, 160);
  TR(s, 0);
#pragma unroll
  for (int i = 0; i < 4; i++) ldsm4t(r[i], mp + (c.sb + SM_MEM + i * 512));
  uint4 tq;
  if (!TQ_AT) tq = lds128(tab);
  bar_sync(id + 2, 160);
  uint32_t first = 0;
#pragma unroll
  for (int k = 0; k < 8; k++) { lead(k); if (k == C1_AT - 4) first = dep(mp, __float_as_uint(la[k & 3][0]), c.sb); }
  uint32_t ta, tb;
  if (!TQ_AT) { ta = tq.x | ((pk >> 16) & 511); tb = tq.z ^ ((pk >> 16) & 511); }
  const uint32_t mp1 = C1_AT >= 4 ? (TQ_AT ? first : dep(first, ta ^ tb, c.sb)) : dep(mp, __float_as_uint(la[C1_AT & 3][0]) ^ (TQ_AT ? 0 : ta ^ tb), c.sb);
#pragma unroll
  for (int i = 4; i < 8; i++) ldsm4t(r[i], mp1 + (c.sb + SM_MEM + 2048 + i * 512));
  if (TQ_AT) { tq = lds128(tab); ta = tq.x | ((pk >> 16) & 511); tb = tq.z ^ ((pk >> 16) & 511); }
  char* dst = mk_ptr(ta, tq.y);
  char* dst2 = mk_ptr(tb, tq.w);
  const uint32_t hv = pk & 0xFFFF;
#pragma unroll
  for (int k = NV; k < NV + HV_E; k++) ldsm4t(wv[k], dep(hv, r[HV_R][0], c.sb) + (c.sb + SM_HV + (k - NV) * 2048));
#pragma unroll
  for (int k = 0; k < LAG_0; k++) lag(k);
#pragma unroll
  for (int k = 8; k < 16; k++) lead(k);
  const uint32_t s0 = __float_as_uint(sum(la, 0)), s3 = __float_as_uint(sum(la, 3));
  sts128((HV_E ? dep(t16, wv[NV][0] ^ wv[NV + HV_E / 2][1] ^ wv[NV + HV_E - (HV_E > 0)][2], c.sb) : TQ_AT ? dep(t16, ta ^ tb, c.sb) : t16) + (c.sb + SM_XCH),
         make_uint4(s0, __float_as_uint(sum(la, 1)), __float_as_uint(sum(la, 2)), s3));
  if (XB) bar_sync(NB_XCH, 256); else bar_sync(NB_XCH | ((t16 >> 9) & 3), 64);
#pragma unroll
  for (int k = LAG_0; k < LAG_0 + LAG_G; k++) r[k >> 1][2 * (k & 1)] = dep(r[k >> 1][2 * (k & 1)], LAG_S == 0 ? s3 : __float_as_uint(la[LAG_S - 1][0]), c.sb);
#pragma unroll
  for (int k = LAG_0; k < O_AT; k++) lag(k);
  const uint4 o = lds128((O_AT > LAG_0 ? dep(t16 ^ 2048, __float_as_uint(lg[(O_AT - 1) % NLAG][0]), c.sb) : t16 ^ 2048) + (c.sb + SM_XCH));
#pragma unroll
  for (int k = O_AT > LAG_0 ? O_AT : LAG_0; k < 16; k++) lag(k);
#pragma unroll
  for (int k = 0; k < V_E; k++) mma_a(lv[k & 3], wv[k], r[k >> 1][2 * (k & 1)], r[k >> 1][2 * (k & 1) + 1]);
  float t[4];
#pragma unroll
  for (int i = 0; i < 4; i++) {
    const float oi = __uint_as_float(i == 0 ? o.x : i == 1 ? o.y : i == 2 ? o.z : o.w);
    t[i] = NLAG == 4 ? (LAG_T ? ((lg[0][i] + lg[1][i]) + oi) + (lg[2 % NLAG][i] + lg[3 % NLAG][i]) : (((lg[0][i] + lg[1][i]) + lg[2 % NLAG][i]) + lg[3 % NLAG][i]) + oi) : LAG_T && NLAG == 2 ? (lg[0][i] + lg[1][i]) + oi : NLAG == 3 ? (lg[1][i] + lg[2 % NLAG][i]) + (lg[0][i] + oi) : (lg[0][i] + oi) + lg[1][i];
  }
  const uint32_t y0 = put_tag(pack_bf16(t[0], t[2]), pk >> 31, s >> 1), y1 = put_tag(pack_bf16(t[1], t[3]), pk >> 31, s >> 1);
  st_pub(dst, y0); st_pub(dst2, y1);
  mbar_arrive_warp(BAR(B_E1TRIG));
  TR(s, 1);
  sched_fence(c.sb);
  const uint4 tv = lds128(tab + 16);
#pragma unroll
  for (int k = NV + HV_E; k < 16; k++) ldsm4t(wv[k], (k < NV + HV_E + HV_D ? hv : dep(hv, k == NV + HV_E + HV_D ? wv[k - HV_D][0] ^ tv.x : wv[k - HV_D][0], c.sb)) + (c.sb + SM_HV + (k - NV) * 2048));
  wo = (hv & 2047) | ((t16 & 2048) << 3);
  const uint32_t l8 = (t16 >> 1) & 255;
  char* dv = mk_ptr(tv.x | l8, tv.y);
  pa = mk_ptr(tv.z | l8, tv.w);
#pragma unroll
  for (int f = 0; f < WO_0; f++) ldsm4t(af[f], dep(wo, f < WO_D ? wv[16 - WO_D + f][0] : af[f < WO_D ? 0 : f - WO_D][0], c.sb) + (c.sb + SM_WO + (f & 1) * 32768 + (f >> 1) * 2048));
#pragma unroll
  for (int k = V_E; k < 16; k++) mma_a(lv[k & 3], wv[k], r[k >> 1][2 * (k & 1)], r[k >> 1][2 * (k & 1) + 1]);
  const uint32_t z0 = put_tag(pack_bf16(sum(lv, 0), sum(lv, 1)), (~t16 >> 4) & 1, s >> 1), z1 = pack_bf16(sum(lv, 2), sum(lv, 3));
  st_pub2(dv, z0, z1);
  if (FIN_AT >= 3) mbar_arrive_warp(BAR(B_VST));
  TR(s, 2);
}
__device__ __forceinline__ uint32_t max_bf16x2(uint32_t a, uint32_t b) { uint32_t r; asm("max.bf16x2 %0, %1, %2;" : "=r"(r) : "r"(a), "r"(b)); return r; }
constexpr float SCL = 0.08838834764831845f * 1.4426950408889634f;
__device__ __forceinline__ uint32_t max5(const uint32_t (&sc)[5]) { return max_bf16x2(max_bf16x2(max_bf16x2(max_bf16x2(sc[0], sc[1]), sc[2]), sc[3]), sc[4]); }
__device__ __forceinline__ float row_off(uint32_t m, uint32_t& m1) {
  m1 = __shfl_xor_sync(~0u, m, 1);
  const uint32_t m2 = __shfl_xor_sync(~0u, m, 2), m3 = __shfl_xor_sync(~0u, m, 3);
  const uint32_t mm = max_bf16x2(max_bf16x2(max_bf16x2(m, m1), m2), m3);
  return -SCL * fmaxf(__uint_as_float(mm << 16), __uint_as_float(mm & 0xFFFF0000u));
}
__device__ __forceinline__ void unpack(float (&f)[10], const uint32_t (&sc)[5]) {
#pragma unroll
  for (int i = 0; i < 5; i++) {
    asm volatile("shl.b32 %0, %1, 16;" : "=f"(f[2 * i]) : "r"(sc[i]));
    asm volatile("and.b32 %0, %1, 0xffff0000;" : "=f"(f[2 * i + 1]) : "r"(sc[i]));
  }
}
__device__ __forceinline__ uint32_t exp_pair(const float (&f)[10], int i, float off) {
  return pack_bf16(ex2(fmaf(f[2 * i], SCL, off)), ex2(fmaf(f[2 * i + 1], SCL, off)));
}
template<bool SPLIT> __device__ __forceinline__ void scores_x(float (&a)[2][4], const uint4 (&kf)[4], const uint4& q, uint32_t z) {
#pragma unroll
  for (int t = 0; t < 2; t++) { a[t][0] = a[t][1] = a[t][2] = a[t][3] = 0.f; }
  mma_q(a[0], kf[0], q.x, q.y); mma_q(a[1], kf[2], q.x, q.y);
  if (SPLIT) sched_fence(z);
  mma_q(a[0], kf[1], q.z, q.w); mma_q(a[1], kf[3], q.z, q.w);
}
__device__ __forceinline__ uint32_t scores_m(const uint4& q, const uint4& k) {
  float a[4] = {}, b[4] = {};
  mma_q(a, q, k.x, k.z); mma_q(b, q, k.y, k.w);
  return pack_bf16(a[0] + b[2], a[1] + b[3]);
}
__device__ __forceinline__ void store_scores(const float (&a)[2][4], uint32_t dst) {
  sts64(dst, pack_bf16(a[0][0], a[0][2]), pack_bf16(a[1][0], a[1][2]));
  sts64(dst + 320, pack_bf16(a[0][1], a[0][3]), pack_bf16(a[1][1], a[1][3]));
}
__device__ __forceinline__ uint32_t sum4(uint32_t a, uint32_t b, uint32_t d, uint32_t e) { return add_bf16x2(add_bf16x2(a, b), add_bf16x2(d, e)); }
__device__ __forceinline__ void load_scores(uint32_t (&sc)[5], uint32_t ax, uint32_t am) {
  uint4 p[4];
#pragma unroll
  for (int i = 0; i < 4; i++) p[i] = lds128(ax + i * 1280);
  const uint2 m0 = lds64(am), m1 = lds64(am + 256);
  const uint4 t = add4(add4(add4(p[0], p[1]), p[2]), p[3]);
  sc[1] = t.x; sc[2] = t.y; sc[3] = t.z; sc[4] = t.w;
  sc[0] = sum4(m0.x, m0.y, m1.x, m1.y);
}
constexpr uint32_t ONES = 0x3F803F80u;
__device__ __forceinline__ float pv(float (&o)[2][4], const uint32_t (&p)[5], const uint4 (&vf)[4], const uint4& vm) {
  float a[4] = {}, b[4] = {};
#pragma unroll
  for (int t = 0; t < 2; t++) { o[t][0] = o[t][1] = o[t][2] = o[t][3] = 0.f; }
  mma_q(o[0], vf[0], p[1], p[2]); mma_q(o[1], vf[2], p[1], p[2]);
  mma_q(o[0], vf[1], p[3], p[4]); mma_q(o[1], vf[3], p[3], p[4]);
  mma16816(a, p[1], p[2], p[3], p[4], ONES, ONES);
  mma1688(o[0], vm.x, vm.y, p[0]); mma1688(o[1], vm.z, vm.w, p[0]);
  mma1688(b, p[0], ONES, ONES);
  return (a[0] + a[2]) + b[0];
}
constexpr uint32_t POLL_LIMIT = 1u << 21;
__device__ __forceinline__ uint32_t box(int slot, int cta) { return (slot * 2 + (cta >> 6)) * M_REG + (cta & 63) * 16384; }
__device__ __forceinline__ uint32_t near_page(const ChainCtx& c, int cta, uint32_t off) {
  return off + (((lds32(c.sb + SM_SEL + cta * 4) >> (off >> 21)) ^ __popc(off & 0xB2000)) & 1) * 4096;
}
__device__ __forceinline__ uint32_t e1_box(const ChainCtx& c, int slot, int cta) { return near_page(c, E1OFF ? cta ^ 2 : cta, box(slot, cta) + 8192) ^ (E1OFF ? 0 : 4096); }
__device__ __forceinline__ uint32_t tile_key() {
  uint32_t sm; asm volatile("mov.u32 %0, %%smid;" : "=r"(sm));
  return (sm < 64 ? sm / 2 % 8 : sm < 120 ? 1 + (sm / 2 - 32) % 7 : 0) << 24 | sm << 16;
}
__device__ __forceinline__ uint32_t ox_at(int s, int row, int g, int jj) { return s * 131072 + ((g >> 1) * 32 + row) * 64 + (g & 1) * 32 + 8 * jj; }
__device__ __forceinline__ int tile_of(const ChainCtx& c) { return SIDE ? __shfl_sync(~0u, lds32(c.sb + SM_SEL + 528), 0) : c.r; }

__global__ void __cluster_dims__(2, 1, 1) __launch_bounds__(512, 1)
chain_kernel(const __grid_constant__ CUtensorMap tq, const __grid_constant__ CUtensorMap tk, const __grid_constant__ CUtensorMap tv,
             const __grid_constant__ CUtensorMap tv16, const __grid_constant__ CUtensorMap to, const __grid_constant__ CUtensorMap tx,
             const __grid_constant__ CUtensorMap twr, const __grid_constant__ CUtensorMap twi,
             const __grid_constant__ CUtensorMap ta, const __grid_constant__ CUtensorMap tw,
             const __grid_constant__ CUtensorMap tb, const __grid_constant__ CUtensorMap tout, const __grid_constant__ CUtensorMap tz,
             const __grid_constant__ CUtensorMap tzs, const __grid_constant__ CUtensorMap ta32,
             const __nv_bfloat16* __restrict__ mem0, char* __restrict__ mail, const __nv_bfloat16* __restrict__ x,
             const __nv_bfloat16* __restrict__ gw) {
  extern __shared__ __align__(1024) unsigned char smraw[];
  if (threadIdx.x == 0) TL(0);
  ChainCtx c;
  c.sb = __shfl_sync(~0u, smem_u32(smraw), 0);
  c.mail = mail; c.sel = 0; c.r = blockIdx.x;
  if (ROLE) {
    const uint32_t u = blockIdx.x >> 1, n = u < 36 ? 8 : 7, k = u - (u < 36 ? 4 : 36), q = k * (u < 36 ? 32 : 37) >> 8;
    c.r = __shfl_sync(~0u, 2 * (u - 4 < 60 ? u + k - q * n - (q & 1) * (n - 1) : u) + (blockIdx.x & 1) + (threadIdx.x >> 9), 0);
  }
  c.h = c.r >> 2; c.a = (c.r >> 1) & 1; c.b = c.r & 1; c.j = c.r & 3;
  c.m = __shfl_sync(~0u, (int)(threadIdx.x >> 7), 0); c.w = __shfl_sync(~0u, (int)((threadIdx.x >> 5) & 3), 0);
  char* own = c.mail + (uint32_t)(c.w * M_REG + M_E3 + (c.r >> 5) * 8192 + (c.r & 31) * 128 + (threadIdx.x & 31) * 4);
  uint32_t i0 = 0, i1 = 0;
  if (EARLY) asm volatile("{ .reg .pred p; setp.ne.u32 p, %4, 0; @p atom.relaxed.gpu.global.exch.b32 %0, [%2], %3; @p atom.relaxed.gpu.global.exch.b32 %1, [%2 + 4096], %3; }"
               : "+r"(i0), "+r"(i1) : "l"(own), "r"(SENT), "r"((uint32_t)(c.m == 2 && c.r < 128)) : "memory");
#pragma unroll
  for (int g = 0; g < 3; g++) {
    const int i = c.m * 4 + c.w;
    if (g < 2 || i < B_END - 32)
      asm volatile("{ .reg .pred p; elect.sync _|p, 0xffffffff; @p mbarrier.init.shared::cta.b64 [%0], %1; }"
                   :: "r"(BAR(g * 16 + i)), "r"(0x19080401u >> (bar_codes(g) >> 2 * i & 3) * 8 & 255) : "memory");
  }
  asm volatile("fence.mbarrier_init.release.cluster;" ::: "memory");
  __syncthreads();
  asm volatile("barrier.cluster.arrive.relaxed.aligned;" ::: "memory");

  if (c.r >= 128) {
    fft_cols((float2*)smraw, c.r - 128, &twr, &twi, &tzs);
    if ((threadIdx.x & 127) == 0) TL(7);
    __syncwarp();
  } else if (c.m == 3) {
    asm volatile("setmaxnreg.dec.sync.aligned.u32 %0;" :: "n"(REG_H));
    c.lane = lane_id();
    if (c.sb & 1023) asm volatile("trap;");
    const int col = c.h * 128 + c.a * 64, eq = E3M ? c.w & 1 : c.w >> 1, eh = E3M == 1 ? (c.w >> 1) ^ 1 : E3M ? c.w >> 1 : c.w & 1;
    uint32_t tl = clock_lo();
    TR(-2, 3);
    if (c.w == 0) {
      if (START) delay_until(tl + START);
      if (HOLD == 2) mbar_wait(BAR(B_PROBE), 0);
      if (HOLD == 3) mbar_wait(BAR(B_SEL), 0);
      if (HOLD == 1) mbar_wait(BAR(B_PROBE), 0);
      TR(-2, 4);
      tl = clock_lo();
      mbar_expect_e(BAR(B_PFULL), 2 * NP * 2048);
      mbar_expect_e(BAR(B_WFULL), (48 - NP) * 2048);
      mbar_expect_e(BAR(B_WFULL + 1), (48 - NP) * 2048);
    }
    auto dst_x = [&](int e, int w) {
      const uint32_t g2 = 2 * c.a + (w >> 1), u = w & 1;
      return M_KVQ + c.h * 24576 + (e == 0 ? 8192 + (2 * u + c.b) * 2048 + g2 * 512 : e == 1 ? g2 * 2048 + u * 1024 + c.b * 128 : 16384 + c.b * 4096 + g2 * 512 + u * 256);
    };
    if (c.w == 0) {
      tl += PACE0;
#pragma unroll wunr
      for (int i = 0; i < 24; i++) {
        const int m = i < 4 || i >= 16, k = i < 4 ? i : m ? i - 12 : i - 4;
        const int row = c.b * 512 + m * 256;
        const uint32_t st = c.sb + m * ST_WG, bar = BAR(k < 3 ? B_PFULL : B_WFULL + m);
        if (PACE) delay_until(tl += PACE);
        if (i == 14) { mbar_wait(BAR(B_FREE), 0); if (c.lane == 0) TL2(2); __syncwarp(); }
        if (k < 11) TMA_W(k < 3 ? c.sb + SM_POOL + m * NP * 2048 + k * 8192 : k == 3 ? c.sb + SM_HV + (m * NHV + 1) * 2048 : st + (k - 4) * 8192,
                          k == 3 || k > 8 ? &tv : (k >> 2 & 1) == m ? &tk : &tq, col, row + (k < 8 ? k & 3 : (k - 9) & 3) * 64, bar);
        else {
#pragma unroll 1
          for (int j = 8; j < 12; j++) TMA_W(j < NV ? st + (32 - NP + j) * 2048 : c.sb + SM_HV + m * NHV * 2048, &tv16, col, row + j * 16, bar);
        }
      }
      TR(-2, 7);
    } else if (c.w == 2) {
      const unsigned short* mp = (const unsigned short*)mem0 + (2 * (c.lane & 3)) * D_ + 8 * c.r + (c.lane >> 2);
      uint32_t mv = (uint32_t)mp[0] | (uint32_t)mp[D_] << 16;
      if (mv == SENT) mv = 0x7FFF7FFFu;
      mbar_wait(BAR(B_PROBE), 0);
      char* dst = c.mail + (uint32_t)(M_E3 + (c.r >> 5) * 8192 + (c.r & 31) * 128 + c.lane * 4);
      st_pub(dst, mv); st_pub(dst + 4096, mv);
    } else if (c.w == 3) {
      mbar_wait(BAR(B_FREE), 0);
      mbar_wait(BAR(B_PFULL), 0);
      mbar_expect_e(BAR(B_PFULL), 65536);
      for (int i = 0; i < 2; i++) tma4d_e(c.sb + SM_XT + i * 16384, &tx, c.b * 8, 4 + 2 * (c.b ^ i), BAR(B_PFULL));
    }
    {
      mbar_wait(BAR(B_SEL), 0);
      const int i = tid_now() & 127, sl = i & 3, e = (i >> 2) & 3;
      uint32_t ox = dst_x(e, i >> 5) + sl * M_REG;
      uint32_t oh = e & 1 ? (sl ^ (e & 2)) * M_REG + M_E3 + (c.r >> 5) * 8192 + (c.w & 1) * 4096 + (c.r & 31) * 128
                          : near_page(c, c.r, e ? sl * M_REG + M_E3 + (c.b * 2 + eq) * 8192 : box(~sl & 1, c.r)) + (e ? eh * 2048 : c.w * 1024), of;
      {
        const int e = i & 7, w = (i >> 3) & 3, m = (i >> 5) & 1, sl = i >> 6;
        const int cta = e < 2 ? c.r & ~1 : e == 2 ? c.r | 1 : e == 3 ? c.h * 4 + 2 * m + 1 : c.j * 32 + m * 8 + 2 * w + (e & 2) * 8 + (e & 1);
        const uint32_t off = e < 2 ? c.b * 2048 + m * 1024 + (w >> 1) * 512 + e * 160 : e == 2 ? c.b * 2048 + m * 1024 + w * 256 : e == 3 ? w * 256 : c.h * 128;
        of = (e < 4 ? e1_box(c, sl, cta) : near_page(c, cta, box(sl, cta))) + off;
      }
      char *px = c.mail + ox, *ph = c.mail + oh, *pf = c.mail + of;
      uint32_t at = sl * 128 + (i >> 5) * 32 + e * 8, af = i * 8;
      pin(px); pin(ph); pin(pf); pin(at); pin(af);
      asm volatile("barrier.cluster.wait;" ::: "memory");
      TR(-2, 0);
      mbar_wait(BAR(B_WREAD), 0);
      TR(-2, 1);
      mbar_arrive_both(BAR(B_LFREE), c.b ^ 1);
      sts64(at + (c.sb + SM_TAB + 1536), (uint32_t)(uintptr_t)px, (uint32_t)((uintptr_t)px >> 32));
      sts64(at + (c.sb + SM_TAB + 1024), (uint32_t)(uintptr_t)ph, (uint32_t)((uintptr_t)ph >> 32));
      sts64(af + (c.sb + SM_TAB), (uint32_t)(uintptr_t)pf, (uint32_t)((uintptr_t)pf >> 32));
      TR(-2, 2);
      if (tid_now() == 384) TL2(25);
      __syncwarp();
      bar_sync(14, 160);
    }
    pad<PAD3>();
    for (int s = -1; s < NSEG; s++) {
      if (E30 ? s != 0 : s >= 0) {
        const uint32_t tab = c.sb + SM_TAB + 1024 + (max(s, 0) & 3) * 128 + c.w * 32;
        uint32_t t0;
        if (s > 0) {
          const uint32_t ln = tid_now() & 31;
          const uint4 ta = lds128(tab);
          const char* src = mk_ptr(ta.x | ln * 4, ta.y);
          char* dst = mk_ptr(ta.z | ln * 4, ta.w);
          const uint32_t tg = (s - 1) >> 1, chk = (ln & 3) ? 0u : 1u, red = ln * (RED_L == 3 ? 4 : 8);
          touch(src, dep(c.sb, chk, c.sb)); touch(dst, dep(c.sb, red, c.sb));
          mbar_wait(BAR(B_E2TRIG), (s - 1) & 1);
          TR(s, 0);
          if (ANCH2) delay_fine(lds32(c.sb + SM_SUM + 64) + DLY_E2); else delay_cycles(DLY_E2);
          uint32_t n = 0;
          while (true) {
            uint32_t v[8];
#pragma unroll
            for (int i = 0; i < 8; i++) v[i] = ld_poll1(src + i * 128);
            if (E2_F) sched_fence(c.sb);
            const uint32_t bad = RED_T ? (stale2(v[0], v[1], tg) | stale2(v[2], v[3], tg) | stale2(v[4], v[5], tg)) | stale2(v[6], v[7], tg)
                                       : stale1(stale1(stale2(v[0], v[1], tg), v[2], tg), v[3], tg) | stale1(stale1(stale2(v[4], v[5], tg), v[6], tg), v[7], tg);
            const bool ok = all_clear(bad, chk);
#pragma unroll
            for (int l = 0; l < RED_L; l++)
#pragma unroll
              for (int i = 0; i < (4 >> l); i++) v[i] = add_bf16x2(v[2 * i], v[2 * i + 1]);
            if (RED_L == 3) sts32(red + (c.sb + SM_RED + c.w * 128), v[0]);
            else {
              float lo[8], hi[8];
#pragma unroll
              for (int i = 0; i < (8 >> RED_L); i++) { lo[i] = __uint_as_float(v[i] << 16); hi[i] = __uint_as_float(v[i] & 0xFFFF0000u); }
#pragma unroll
              for (int l = RED_L; l < 3; l++)
#pragma unroll
                for (int i = 0; i < (4 >> l); i++) { lo[i] = lo[2 * i] + lo[2 * i + 1]; hi[i] = hi[2 * i] + hi[2 * i + 1]; }
              sts64(red + (c.sb + SM_RED + c.w * 256), __float_as_uint(lo[0]), __float_as_uint(hi[0]));
            }
            if (ok) break;
            n++; CNT(0);
          }
          bar_sync(NB_HELP, 128);
          const uint32_t rd = red + (c.sb + SM_RED);
          if (!RED_P || c.w < 2) {
            if (RED_L == 3) st_pub_if(dst, sum4(lds32(rd), lds32(rd + 128), lds32(rd + 256), lds32(rd + 384)), c.w < 2);
            else {
              const uint2 p0 = lds64(rd), p1 = lds64(rd + 256), p2 = lds64(rd + 512), p3 = lds64(rd + 768);
              st_pub_if(dst, pack_bf16((__uint_as_float(p0.x) + __uint_as_float(p1.x)) + (__uint_as_float(p2.x) + __uint_as_float(p3.x)),
                                       (__uint_as_float(p0.y) + __uint_as_float(p1.y)) + (__uint_as_float(p2.y) + __uint_as_float(p3.y))), c.w < 2);
            }
          }
          t0 = clock_lo();
          mbar_arrive_warp(BAR(B_PUB));
          TRV(s, 15, n);
          mbar_wait(BAR(B_SPFREE), (s - 1) & 1);
        } else {
          if (tid_now() == 384) TL2(24);
          __syncwarp();
          if (!E30) mbar_wait(BAR(B_PROBE), 1);
          if (!WO_S) mbar_wait(BAR(B_WOFULL), 0);
          if (tid_now() == 384) TL2(19);
          __syncwarp();
          t0 = clock_lo() - DLY_E3;
        }
        TRV(s, 1, t0);
        {
          const uint32_t l16 = (tid_now() & 31) * 16, dst = vary(l16, s, c.sb) + (c.sb + SM_MEM + eh * 4096 + eq * 2048);
          const uint4 tb = lds128(tab + 16);
          st_pub_if(mk_ptr(tb.z | l16 >> 2, tb.w), SENT, c.w >= 2);
          const char* src = mk_ptr(tb.x | l16, tb.y);
          touch(src, dep(c.sb, dst, c.sb));
          delay_fine(t0 + (DLY_E3 + eh * DLY_E3B));
          uint32_t n = 0;
          while (true) {
            uint4 v[4];
#pragma unroll
            for (int i = 0; i < 4; i++) v[i] = ld_poll(src + i * 512);
#pragma unroll
            for (int i = 0; i < 4; i++) sts128(dst + i * 512, v[i]);
            if (arrive_if_all(max(max(v[0].x, v[1].x), max(v[2].x, v[3].x)) != SENT, NB_MEM + eh * 2 + eq, 160)) break;
            n++; CNT(1);
          }
          TR(s, 2); TRV(s, 14, n);
        }

        if (s == 1) CLK(1); if (s == 8) CLK(2); if (s == 56) CLK(3);
        if (c.w == 2 && s == 15) TRSYNC(8);
        if (c.w == 2 && s == 21) TRSYNC(10);
      }
      const int g = s + 1;
      auto load_v = [&]() {
        if (V_TMA && c.w == V_W) {
          mbar_expect_e(BAR(B_VFULL), K_TMA ? 16384 : 8192);
          const char* src = c.mail + (uint32_t)(M_KVQ + (min(g, XEND - 1) & (NSLOT - 1)) * M_REG + c.h * 24576);
          bulk_load_e(c.sb + SM_V, src + 8192, 8192, BAR(B_VFULL));
          if (K_TMA > 1) delay_cycles(K_TMA);
          if (K_TMA) bulk_load_e(c.sb + SM_K, src, 8192, BAR(B_VFULL));
        }
      };
      if (XEND < NSEG && g >= XEND && g < NSEG) { mbar_wait(BAR(B_SC), s & 1); load_v(); }
      if (g < XEND) {
        const uint32_t tx_ = c.sb + SM_TAB + 1536 + (g & 3) * 128 + c.w * 32, tag = (g >> 2) & 1;
        if (c.w == 0) mbar_expect_e(BAR(B_LAND), EXP_PEER * 12288);
        auto load_x = [&]() {
          if (c.w == 3 && g + 1 < XEND) {
            mbar_wait(BAR(B_XEMPTY), g & 1);
            mbar_expect_e(BAR(B_XFULL), 16384 * EXP_NXT);
            for (int i = 0; i < EXP_NXT; i++) tma4d_e(c.sb + SM_XT + i * 16384, &tx, c.b * 8, (g + 1) * 4 + 2 * (c.b ^ i), BAR(B_XFULL));
          }
        };
        if (X_AT == 0 && g > 0) load_x();
        TR(s, 6);
        if (E30 && g == 0) mbar_wait(BAR(B_PROBE), 1);
        mbar_wait(BAR(B_LAND), g & 1);
        TR(s, 7);
        if (DLY_F && g > 0) delay_cycles(DLY_F);
        auto total = [&](int w, int lane, uint32_t o0, uint32_t o1) {
          const uint32_t a = c.sb + SM_LAND + land_off(w, lane);
          if (EXP_FL == 1) return make_uint4(a, a, a, a);
          const uint4 t = add4(lds128(a + o0), lds128(a + o1 + 2048));
          const uint32_t a2 = dep(dep(a, t.x ^ t.y ^ t.z, c.sb), t.w, c.sb);
          return add4(t, add4(lds128(a2 + o0 + 4096), lds128(a2 + o1 + 6144)));
        };
        auto get = [&](int e) {
          const int ln = tid_now() & 31;
          return e == 0 ? total(c.w, ln, 16384, 16384)
               : e == 1 ? total((c.w & 2) + ((ln >> 1) & 1), (ln & 1) * 16 + (c.w & 1) * 8 + (ln >> 2), 8192, 0)
                        : total((c.w & 2) + ((ln >> 1) & 1), (ln & 1) * 16 + (ln >> 3) * 4 + (c.w & 1) * 2 + ((ln >> 2) & 1), 0, 8192);
        };
        auto put = [&](int e, uint4 v) {
          const int ln = tid_now() & 31;
          const uint2 d = lds64(tx_ + e * 8);
          if (e < 2) {
            v.x = tagged(v.x, tag);
            st_pub4(mk_ptr(d.x | (e ? (ln & 24) * 32 + (ln & 7) * 16 : ln * 16), d.y), v);
          } else {
            char* dst = mk_ptr(d.x | ((ln & 7) * 16 + (ln >> 3) * 4), d.y);
            const uint32_t bit = ln < 8;
            st_pub(dst, put_tag(v.x, bit, tag)); st_pub(dst + 128, put_tag(v.y, bit, tag));
            st_pub(dst + 2048, put_tag(v.z, bit, tag)); st_pub(dst + 2176, put_tag(v.w, bit, tag));
          }
        };
        auto after_sc = [&]() { if (g > 0) { mbar_wait(BAR(B_SC), s & 1); if (DLY_FK) delay_cycles(DLY_FK); if (X_AT == 1) load_x(); } };
        if (FIN_AT == 5) {
          put(0, get(0));
          if (DLY_F2 && g > 0) delay_cycles(DLY_F2); else sched_fence(c.sb);
          const uint4 k = get(1);
          sched_fence(c.sb);
          const uint4 q = get(2);
          if (g > 0) mbar_wait(BAR(B_VST), s & 1);
          put(1, k); put(2, q);
          TR(s, 5);
          mbar_arrive_both(BAR(B_LFREE), c.b ^ 1);
          after_sc();
          load_v();
          continue;
        }
        if (FIN_AT < 3) {
          if (EXP_FIN & 1) put(0, get(0));
          TR(s, 3);
          if (FIN_AT == 1) after_sc();
          if (V_TMA == 1) load_v();
          if (EXP_FIN & 2) put(1, get(1));
        } else {
          const uint4 v = get(0);
          sched_fence(c.sb);
          const uint4 k = get(1);
          if (g > 0) { mbar_wait(BAR(B_VST), s & 1); if (DLY_FS) delay_cycles(DLY_FS); }
          put(0, v); put(1, k);
        }
        TR(s, 4);
        if (FIN_AT == 4) {
          const uint4 q = get(2);
          after_sc();
          load_v();
          put(2, q);
        } else {
          if (FIN_AT >= 2) after_sc();
          if (V_TMA == 2) load_v();
          if (EXP_FIN & 4) put(2, get(2));
        }
        mbar_arrive_both(BAR(B_LFREE), c.b ^ 1);
        if (V_TMA == 3) load_v();
        TR(s, 5);
        if (!FIN_AT && X_AT && g > 0) { mbar_wait(BAR(B_SC), s & 1); if (DLY_FK) delay_cycles(DLY_FK); load_x(); }
      }
    }
    const int tile = tile_of(c), s0 = (tile >> 3) * 4, n0 = (tile & 7) * 128;
    if (c.w == 1) {
      mbar_wait(BAR(B_PVDONE), 0);
      count_e(g_ctl + (EARLY2 ? C_LAST : C_EARLY));
      st_pub(c.mail + (uint32_t)((tid_now() & 6) * (M_REG / 2) + M_SEL + (tid_now() & 1) * 4096 + c.r * 4), 0);
      await_count(g_ctl + C_COLS, 4);
      if (K_TMA) mbar_wait(BAR(B_SC), 1);
      mbar_expect_e(BAR(B_TW), 8192);
      bulk_load_e(c.sb + SM_TW, g_tw, 8192, BAR(B_TW));
    } else if (c.w == 2) {
      const uint32_t ln = tid_now() & 31, rel = mapa(BAR(B_GEMPTY) + (ln >> 2) * 8, ln & 1);
      mbar_wait(BAR(B_VST), 1); mbar_wait(BAR(PRE_AT), 1);
      arrive_remote_if(rel, ln < 12);
      mbar_wait(BAR(B_E2TRIG), 1);
      if (GATE) mbar_wait(BAR(B_DONE), 0);
      arrive_remote_if(rel, ln >= 12 && ln < 20);
    } else {
      auto ahead = [&](int k) {
        if (c.w) { if (PF_A && (k & 3) == (tile >> 1 & 3)) prefetch3d_e(&ta, k * 32, s0 + 2 * c.b); }
        else if (PF_B && (k & 7) == (tile >> 4)) prefetch2d_e<(ONCE & 512) != 0>(&tw, n0 + (tile & 8) * 8, k * 64);
      };
#pragma unroll 1
      for (int k = 0; k < PF_D; k++) ahead(k);
      if (c.w == 3) await_count(g_ctl + C_EARLY, 128);
      const int skew = tile < 120 ? 0 : SKEW;
      uint32_t o = SM_XT, st = 0, ph = 0;
#pragma unroll 1
      for (int kb = 0; kb < 64 + skew; kb++, o = next_stage(o)) {
        const bool solo = kb < skew || kb >= 64;
        const uint32_t bar = BAR(B_GFULL + st), k = kb & 63;
        if (c.w && kb == skew) {
          if (tile >= 120) await_count(g_ctl + C_LAST, EARLY2 ? 640 : 512);
          if (tid_now() == 480) TL(10);
          __syncwarp();
        }
        mbar_wait(BAR(B_GEMPTY + st), ph);
        if (c.w) {
          const int r = solo ? (kb >> 5) + c.b : c.b * 2;
          tma3d_mc_e(c.sb + o + r * 4096, solo ? &ta32 : &ta, k * 32, s0 + r, bar);
        } else {
          mbar_expect_e(bar, solo ? 24576 : 32768);
          tma2d_o<(ONCE & 2) != 0>(c.sb + o + 16384, &tw, n0, k * 64, bar);
          tma2d_o<(ONCE & 2) != 0>(c.sb + o + 24576, &tw, n0 + 64, k * 64, bar);
        }
        if (kb + PF_D < 64) ahead(kb + PF_D);
        if (++st == 5) { st = 0; ph ^= 1; }
      }
    }
    return;
  } else if (c.m == 2) {
    asm volatile("setmaxnreg.dec.sync.aligned.u32 %0;" :: "n"(512 - 2 * REG_F - REG_H));
    c.lane = lane_id();
    {
      uint32_t tl = clock_lo() + (PACE0 + WO_AT * PACE);
      TR(-2, 0);
      sched_fence(i0 ^ i1);
      TR(-2, 7);
      int far1 = 0;
#pragma unroll 1
      for (int rep = EARLY; rep <= NPROBE; rep++) {
        const int lag = race_init(own + (rep & 1) * 4096, own + (~rep & 1) * 4096, SENT);
        if (rep) far1 += ((rep ^ c.r >> 5) & 1 ? 1 : -1) * min(lag, 200);
      }
      sts32(c.sb + SM_SEL + 512 + c.w * 4, (8 + far1 / (16 * NPROBE)) << 4 * c.w);
      TR(-2, 1);
      if (tid_now() == 256) TL2(14);
      __syncwarp();
      mbar_arrive_warp(BAR(B_PROBE));
      if (c.w == 0) {
        mbar_wait(BAR(B_PROBE), 0);
        const uint4 bits = lds128(c.sb + SM_SEL + 512);
        const uint32_t res = bits.x | bits.y | bits.z | bits.w;
        st_pub_if(c.mail + (uint32_t)((c.lane & 6) * (M_REG / 2) + M_SEL + (c.lane & 1) * 4096 + c.r * 4), res | tile_key(), c.lane < 8);
        const int q = (res >> 4 * ((c.lane + c.r) & 3) & 15) - 8, best = __reduce_max_sync(~0u, abs(q) * 64 + (c.lane & 3) * 16 + ((c.lane + c.r) & 3) * 2 + (q <= 0));
        const char* src = c.mail + (uint32_t)((best & 6) * (M_REG / 2) + M_SEL + (best & 1) * 4096 + c.lane * 16);
        if (SEL_AT) delay_until(tl - (PACE0 + WO_AT * PACE - SEL_AT));
        uint4 v; uint32_t n = 0;
        TR(-2, 4);
        while (true) {
          delay_cycles(DLY_SEL);
          TR(-2, 6);
          v = ld_poll(src);
          if (__all_sync(~0u, v.x && v.y && v.z && v.w)) break;
          watchdog(n, POLL_LIMIT);
        }
        TR(-2, 5);
        int ta = 0, tb = 0, pa = 0, pb = 0;
        uint32_t flip = 0;
#pragma unroll 1
        for (int i = 0; i < 4; i++) {
          const int a = (v.x >> 4 * i & 15) + (v.y >> 4 * i & 15) - 16, b = (v.z >> 4 * i & 15) + (v.w >> 4 * i & 15) - 16;
          const bool f = __reduce_add_sync(~0u, a * ta + b * tb) < 0;
          ta += f ? -a : a; tb += f ? -b : b; flip |= (uint32_t)f << i;
        }
#pragma unroll 1
        for (uint32_t g = 0; g < 8; g++) {
          const bool a = (v.x >> 16) - g * 256 < 120, b = (v.z >> 16) - g * 256 < 120;
          const int n = __reduce_add_sync(~0u, (a ? ta : 0) + (b ? tb : 0)) > 0 ? PRIOR : -PRIOR;
          if (a) pa = n;
          if (b) pb = n;
        }
        const uint32_t ka = AWARE && ta + pa > 0 ? ~flip : flip, kb = AWARE && tb + pb > 0 ? ~flip : flip;
        sts128(c.sb + SM_SEL + c.lane * 16, make_uint4(ka, ka, kb, kb));
        mbar_arrive_warp(BAR(B_SEL));
        const uint32_t key = __shfl_sync(~0u, c.a ? v.z : v.x, c.h);
        const int u = __popc(__ballot_sync(~0u, v.x < key)) + __popc(__ballot_sync(~0u, v.z < key));
        sts32(c.sb + SM_SEL + 528, (u & 32) * 2 + (u & 7) * 8 + (u >> 2 & 6) + c.b);
        TR(-2, 2);
        if (c.lane == 0) TL2(13);
        __syncwarp();
        bar_sync(14, 160);
        if (ZDLY) delay_cycles(ZDLY);
#pragma unroll 4
        for (int k = c.lane >> 3; k < (ZINIT ? 128 : 0); k += 4) {
          const int e = k & 7;
          const uint2 d = lds64(c.sb + SM_TAB + (e == 3 ? k - 1 : k) * 8);
          st_pub4(mk_ptr((d.x & ~127u) + (e < 2 ? (k & 8) * 32 : e == 3 ? 128 : 0) + (c.lane & 7) * 16, d.y), make_uint4(0, 0, 0, 0));
        }
        __syncwarp();
        if (c.lane < 4) asm volatile("mbarrier.arrive.shared::cta.b64 _, [%0];" :: "r"(BAR(B_PROBE)) : "memory");
        __syncwarp();
        TR(-2, 8);
      }
      if (c.w == 2) {
        mbar_wait(BAR(B_P1), 0);
        if (P1_AT) { mbar_wait(BAR(B_WFULL), 0); mbar_wait(BAR(B_WFULL + 1), 0); }
        st_pub_if(g_ctl + C_COLS + (c.r & 15) * 32 + c.lane, 0, c.r < (C_END - C_COLS) / 32);
        count_e(g_ctl + C_P1);
        TR(-2, 3);
      }
      if (c.w == 1) for (int i = 0; i < WO_N; i++) { delay_until(tl += WO_P * PACE); prefetch2d_e(&to, c.j * 256 + (i ^ WO_X) * 64, c.h * 128); }
      if (c.w == 3) {
        mbar_wait(BAR(B_WREAD0), 0);
        for (int i = 0; i < 2; i++) tma4d_e(c.sb + SM_WO + i * 16384, &tx, c.b * 8, 2 * (c.b ^ i), BAR(B_PFULL));
        mbar_expect_e(BAR(B_WOFULL), 65536);
#pragma unroll 1
        for (int i = 3; i >= 0; i--) {
          if (i & 1) mbar_wait(BAR(i < 2 ? B_XEMPTY : B_WREAD), 0);
          TMA_O(c.sb + SM_WO + i * 16384, &to, c.j * 256 + i * 64, c.h * 128, BAR(B_WOFULL));
        }
      }
    }
    asm volatile("barrier.cluster.wait;" ::: "memory");
    const int g = c.w, src0 = c.h * 4 + (g >> 1) * 2;
    mbar_wait(BAR(B_SEL), 0);
    c.sel = __shfl_sync(~0u, (e1_box(c, 0, src0 + (c.lane >> 5)) & 4096) | (e1_box(c, 1, src0) & 4096) * 2, 0);
    mbar_wait(BAR(B_WREAD), 0);
    uint32_t l16 = c.sb + g * 512 + c.lane * 16;
    auto lane = [&](uint32_t v) { l16 = dep(l16, v, c.sb); return (int)((l16 & 511) >> 4); };
    pad<PAD2>();
    for (int s = 0; s < NSEG; s++) {
      l16 = vary(l16, s, c.sb);
      int ln = (l16 & 511) >> 4;
      uint4 kf[4], qx;
      auto load_x = [&]() {
        if (X_AT >= 2 && g == 0 && s + 2 < XEND) {
          if (KL_AT != 2) mbar_wait(BAR(B_XEMPTY), ~s & 1);
          mbar_expect_e(BAR(B_XFULL), 16384 * EXP_NXT);
          for (int i = 0; i < EXP_NXT; i++) tma4d_e(c.sb + SM_XT + i * 16384, &tx, c.b * 8, (s + 2) * 4 + 2 * (c.b ^ i), BAR(B_XFULL));
        }
      };
      {
        const int gs = min(s, XEND - 1);
        const char* pk = c.mail + (uint32_t)(M_KVQ + (gs & (NSLOT - 1)) * M_REG + c.h * 24576 + g * 2048 + ln * 16);
        const char* pq = pk + (16384 + c.j * 2048 - g * 1536);
        const uint32_t tg = (gs / NSLOT) & 1;
        touch(pk, c.sb); touch(pq, c.sb);
        TR(s, 0);
        mbar_wait(BAR(B_VFULL), s & 1);
        TR(s, 1);
        uint4 k[4];
        auto load_k = [&]() {
          if (DLY_K) delay_cycles(DLY_K);
#pragma unroll
          for (int t = 0; t < 4; t++) k[t] = lds128(l16 + (g * 1536 + SM_K + t * 512));
        };
        if (K_TMA && KL_AT == 1) load_k();
        if (s > 0) mbar_wait(BAR(B_PUB), (s - 1) & 1);
        if (K_TMA) {
          qx = ld_poll(pq);
          if (KL_AT == 2) { mbar_spin_if(BAR(B_XEMPTY), ~s & 1, s + 1 < XEND); load_x(); }
          if (KL_AT != 1) load_k();
        }
        for (uint32_t n = 0; ; ) {
          if (!K_TMA) {
#pragma unroll
            for (int t = 0; t < 4; t++) k[t] = ld_poll(pk + t * 512);
            qx = ld_poll(pq);
          }
#pragma unroll
          for (int t = 0; t < 2; t++) {
            auto cp = [&](uint32_t v) { return dep(v, 0, c.sb); };
            kf[t] = make_uint4(cp(k[2 * t].x), cp(k[2 * t].y), cp(k[2 * t + 1].x), cp(k[2 * t + 1].y));
            kf[2 + t] = make_uint4(cp(k[2 * t].z), cp(k[2 * t].w), cp(k[2 * t + 1].z), cp(k[2 * t + 1].w));
          }
          if (all_clear(stale1(stale2(k[0].x, k[1].x, tg) | stale2(k[2].x, k[3].x, tg), qx.x, tg), EXP_CHK)) break;
          watchdog(n, POLL_LIMIT); CNT(4);
          if (K_TMA) {
#pragma unroll
            for (int t = 0; t < 4; t++) k[t] = ld_poll(pk + t * 512);
            qx = ld_poll(pq);
          }
        }
        TR(s, 2);
      }
      if (KL_AT != 2) load_x();
      ln = lane(kf[0].y);
      const char* pa = c.mail + (uint32_t)(box(s & 1, src0) + 8192 + (c.sel >> (s & 1) & 4096) + (g & 1) * 512 + (EXP_LIN ? ln * 16 : read_off(ln)));
      const uint32_t spw = c.sb + SM_SP + g * 1280 + (ln & 3) * 64 + ((((ln >> 3) ^ ln) & 2) << 4) + (ln & 4) * 4 + (ln & 8),
                     spr = c.sb + SM_SP + (ln & 4) * 80 + (ln >> 3) * 64 + (((ln & 3) ^ ((ln >> 3) & 2)) << 4), l8 = ln * 8;
      const uint32_t tg = s >> 1;
      float sx[2][4];
      uint32_t sm;
      uint4 km;
      touch(pa, c.sb);
      mbar_wait(BAR(B_E1TRIG), s & 1);
      const uint32_t t0 = clock_lo();
      TRV(s, 3, t0);
      scores_x<false>(sx, kf, qx, 0);
      store_scores(sx, spw + 640);
      if (DLY_E1) delay_fine(t0 + DLY_E1);
      uint32_t nr = 0;
      while (true) {
        const uint4 q0 = ld_poll(pa), q1 = ld_poll(pa + 2048), k0 = ld_poll(pa + 1024), k1 = ld_poll(pa + 3072);
        uint4 qm = add4(q0, q1);
        const uint32_t bq = stale2(q0.x, q1.x, tg);
        qm.x = dep(qm.x, bq, c.sb);
        scores_x<SC_F>(sx, kf, qm, c.sb);
        const uint32_t bk = stale2(k0.x, k1.x, tg);
        km = add4(k0, k1);
        km.x = dep(km.x, bk, c.sb);
        const bool ok = all_clear(bq | bk, 1);
        sm = scores_m(qm, km);
        store_scores(sx, spw);
        if (ok) break;
        nr++; CNT(2);
      }
      sts32(l8 + (c.sb + SM_SPM + (g >> 1) * 256 + (g & 1) * 4), sm);
      bar_sync(NB_ATT, 128);
      TR(s, 5); TRV(s, 13, nr);
      float o[2][4];
      uint32_t sp[5];
      uint4 vf[4];
      load_scores(sp, spr, l8 + (c.sb + SM_SPM));
      const uint32_t m5 = max5(sp);
      uint32_t m1;
      float off = row_off(m5, m1), f[10];
      l16 = dep(l16, VF_AT ? m1 : m5, c.sb);
#pragma unroll
      for (int t = 0; t < 4; t++) vf[(t >> 1) + 2 * (t & 1)] = lds128(l16 + SM_V + ((t >> 1) + 2 * (t & 1)) * 2048);
      qx.x = dep(qx.x, sp[0], c.sb);
      sts32(l8 + (c.sb + SM_SPM + 512 + (g >> 1) * 256 + (g & 1) * 4), scores_m(qx, km));
      mbar_arrive_warp(BAR(B_SC));
      unpack(f, sp);
      if (UP_F) sched_fence(c.sb);
      uint4 vm;
      if (VM_AT < 2) {
        bar_sync(NB_VM, 384);
        sp[1] = exp_pair(f, 1, off);
        const uint32_t av = dep(l8, VM_AT ? sp[1] : __float_as_uint(off), c.sb) + (c.sb + g * 512 + SM_VM);
        const uint2 vm0 = lds64(av), vm1 = lds64(av + 256);
        vm = make_uint4(vm0.x, vm0.y, vm1.x, vm1.y);
#pragma unroll
        for (int i = 2; i < 6; i++) sp[i % 5] = exp_pair(f, i % 5, off);
      } else {
#pragma unroll
        for (int i = 1; i < 6; i++) sp[i % 5] = exp_pair(f, i % 5, off);
        bar_sync(VM_AT == 2 ? dep(dep(0, sp[1] ^ sp[2], c.sb) + NB_VM, sp[0], c.sb) : dep(dep(0, sp[0] ^ sp[1] ^ sp[2], c.sb) + NB_VM, sp[3], c.sb), 384);
        const uint32_t av = l8 + (c.sb + g * 512 + SM_VM);
        const uint2 vm0 = lds64(av), vm1 = lds64(av + 256);
        vm = make_uint4(vm0.x, vm0.y, vm1.x, vm1.y);
      }
      float sum;
      auto rows_m = [&]() {
        const uint32_t tv = min(s, XEND - 1) / NSLOT;
        sum = pv(o, sp, vf, vm);
        stsm4<false>(l16 + SM_OM, pack_bf16(o[0][0], o[0][1]), pack_bf16(o[0][2], o[0][3]), pack_bf16(o[1][0], o[1][1]), pack_bf16(o[1][2], o[1][3]));
        sts32(c.sb + SM_SUM + ((l16 >> 4) & 28), __float_as_uint(sum));
        return arrive_if_clear(stale2(vf[0].x, vf[1].x, tv) | stale2(vf[2].x, vf[3].x, tv), EXP_CHK, NB_OM, 384);
      };
      if (!rows_m()) {
        const char* pv_ = c.mail + (uint32_t)(M_KVQ + (min(s, XEND - 1) & (NSLOT - 1)) * M_REG + c.h * 24576 + 8192 + (l16 - c.sb));
        uint32_t n = 0;
        do {
#pragma unroll
          for (int t = 0; t < 4; t++) vf[t] = ld_poll(pv_ + t * 2048);
          watchdog(n, POLL_LIMIT); CNT(5);
        } while (!rows_m());
      }
      const uint32_t tom = clock_lo();
      TRV(s, 8, tom);
      sched_fence(c.sb);
      ln = lane(tom);
      const int n = ln >> 2, jj = ln & 3, tq_ = 8 * c.j + (n & 4) + 2 * (n & 1) + ((n >> 1) & 1), lim = 16 * (tq_ - 2 * jj + 1);
      if (DLY_X) delay_until(tom + DLY_X);
      load_scores(sp, spr + 640, c.sb + SM_SPM + 512 + ln * 8);
#pragma unroll
      for (int w = 0; w < 4; w++) {
        uint32_t m; asm("shl.b32 %0, 0xffffffff, %1;" : "=r"(m) : "r"(max(lim - 128 * w, 0)));
        sp[1 + w] = (sp[1 + w] & ~m) | (0xD029D029u & m);
      }
      mbar_arrive_warp(dep(dep(0, sp[0], c.sb), sp[1], c.sb) + BAR(B_SPFREE));
      off = row_off(max5(sp), m1);
      unpack(f, sp);
#pragma unroll
      for (int i = 1; i < 6; i++) sp[i % 5] = exp_pair(f, i % 5, off);
      sum = pv(o, sp, vf, vm);
      TR(s, 7);
      sum = rcp(sum);
      const float i0 = __shfl_sync(~0u, sum, 8 * jj), i1 = __shfl_sync(~0u, sum, 8 * jj + 4);
      const uint32_t oxs = c.sb + SM_OX + g * 512;
      stsm4<true>(oxs + (ln & 7) * 64 + (((ln >> 3) ^ ((ln >> 1) & 3)) << 4),
                  pack_bf16(o[0][0] * i0, o[0][1] * i1), pack_bf16(o[0][2] * i0, o[0][3] * i1), pack_bf16(o[1][0] * i0, o[1][1] * i1), pack_bf16(o[1][2] * i0, o[1][3] * i1));
      __syncwarp();
      *(uint4*)(g_ox + ox_at(s, tq_, c.h * 4 + g, jj)) = lds128(oxs + n * 64 + ((jj ^ (n >> 1)) << 4));
      mbar_arrive_warp(BAR(B_PVDONE));
      TR(s, 9);
    }
    if (LASTM) {
      const int ln = tid_now() & 31, n = ln >> 2, jj = ln & 3, tq_ = 8 * c.j + (n & 4) + 2 * (n & 1) + ((n >> 1) & 1);
      store_count(g_ox + ox_at(NSEG - 1, tq_, c.h * 4 + g, jj), lds128(c.sb + SM_OX + g * 512 + n * 64 + ((jj ^ (n >> 1)) << 4)), (char*)(g_ctl + C_LAST) + (LASTM == 2 ? c.r * 4 + g : 0));
    } else count_e(g_ctl + C_LAST);
    mbar_arrive_warp(BAR(B_DONE));
    if (tid_now() == 256) TL(8);
    __syncwarp();
    mbar_wait(BAR(B_E2TRIG), 1); mbar_wait(BAR(B_DONE), 0); mbar_wait(BAR(B_TW), 0);
    asm volatile("setmaxnreg.inc.sync.aligned.u32 128;");
  } else {
    {
      const int w = c.m * 4 + c.w;
      mbar_expect_e(BAR(B_ROWS), 4096 + 256);
      for (int i = 0; i < 2; i++) bulk_load_e(c.sb + SM_FFT + (1024 + w * ROW_BUF) * 8 + i * 2048, x + (size_t)(z_row(c.r * 8 + w) + i * 1024) * D_, 2048, BAR(B_ROWS));
      bulk_load_e(c.sb + SM_GW + w * 256, gw + w * 128, 256, BAR(B_ROWS));
    }
    asm volatile("setmaxnreg.inc.sync.aligned.u32 %0;" :: "n"(REG_F));
    c.lane = lane_id();
    uint32_t wa[16][4], wb[16][4], wv[16][4];
    TR(-2, 4);
    fft_rows_fwd((float2*)(smraw + SM_FFT), (const __nv_bfloat16*)(smraw + SM_GW), c.r, threadIdx.x, BAR(B_ROWS), BAR(B_FREE), [&](int e) { TR(-2, e); }, [&]() {
      mbar_spin(BAR(B_PFULL), 0);
#pragma unroll
      for (int k = 0; k < NP; k++) ldsm4t(wa[k], c.sb + SM_POOL + c.m * NP * 2048 + frag_off(c.w, c.lane) + k * 2048);
      bar_sync(NB_XCH, 256);
#pragma unroll
      for (int k = 0; k < NP; k++) sts128(c.sb + SM_POOL + c.m * 2048 + c.w * 512 + c.lane * 16 + k * 4096, make_uint4(wa[k][0], wa[k][1], wa[k][2], wa[k][3]));
    });
    mbar_arrive_warp(BAR(B_P1));
    TR(-2, 0);
    if (tid_now() == 0) TL2(1);
    __syncwarp();
    mbar_spin(BAR(B_WFULL + c.m), 0);
    TR(-2, 1);
    if ((tid_now() & 127) == 0) TL2(16);
    __syncwarp();
    {
      const uint32_t st = c.sb + c.m * ST_WG + frag_off(c.w, c.lane);
#pragma unroll
      for (int k = 0; k < 16; k++) ldsm4t(wb[k], st + k * 2048);
#pragma unroll
      for (int k = NP; k < 16; k++) ldsm4t(wa[k], st + (16 + k - NP) * 2048);
#pragma unroll
      for (int k = 0; k < NV; k++) ldsm4t(wv[k], st + (32 - NP + k) * 2048);
      mbar_arrive_warp(BAR(B_WREAD));
      if (c.m == 0) mbar_arrive_warp(BAR(B_WREAD0));
#pragma unroll
      for (int k = 0; k < (LP_IN == 2 ? 0 : NP); k++) lds_frag(wa[k], c.sb + SM_POOL + c.m * 2048 + c.w * 512 + c.lane * 16 + k * 4096);
      TR(-2, 2);
    }
    TR(-2, 3);
    if (tid_now() == 0) TL2(12);
    __syncwarp();
    asm volatile("barrier.cluster.wait;" ::: "memory");
    uint32_t t16 = c.m * 2048 + c.w * 512 + c.lane * 16;
    uint32_t pk = (c.m * NHV * 2048 + frag_off(c.w, c.lane)) | (tile_off(2 * (c.w & 1), c.lane) << 16) | ((c.lane & 12) ? 0u : 0x80000000u);
    const uint32_t dx1 = desc_lo(c.sb + SM_XT + c.m * 4096), dh = desc_lo(c.sb + SM_HV + c.m * NHV * 2048);
    mbar_spin(BAR(B_PFULL), 1);
    pad<PAD0>();
    for (int s = -2; ; s++) {
      t16 = vary(t16, s, c.sb); pk = vary(pk, s, c.sb);
      const uint32_t dx = dx1 - (s == -2 ? (SM_XT - SM_WO) / 16 : 0);
      auto ldp = [&](int k0, int k1, int d, int back = 0) {
#pragma unroll
        for (int k = k0; k < k1; k++) lds_frag(wa[k], (k < k0 + d - back ? t16 : dep(t16, wa[k < d ? 0 : k - d][0], c.sb)) + (c.sb + SM_POOL + k * 4096));
      };
      if (s >= 0) {
        uint32_t af[16][4], bf[4][4], wo;
        const uint32_t tab = ((t16 >> 3) & 0x1C0) + (c.sb + SM_TAB + (s & 1) * 512);
        const char* pa;
        mem_proj(wa, wb, wv, af, wo, pa, tab, t16, pk, c, s);
        const uint32_t t0 = clock_lo();
        t16 = dep(t16, t0, c.sb);
        auto ldwo = [&](int f) { ldsm4t(af[f], (f < WO_D ? wo : dep(wo, af[f < WO_D ? 0 : f - WO_D][0], c.sb)) + (c.sb + SM_WO + (f & 1) * 32768 + (f >> 1) * 2048)); };
        {
          const uint32_t tg = s >> 1, vm = t16 >> 1, chk = (~t16 >> 4) & 1;
          if (WO_S && s == 0) {
            mbar_spin(BAR(B_WOFULL), 0);
#pragma unroll
            for (int f = 0; f < WO_0; f++) ldwo(f);
          }
#pragma unroll
          for (int f = WO_0; f < WO_1; f++) ldwo(f);
          if (DLY_V) delay_fine(t0 + DLY_V); else sched_fence(c.sb);
          uint2 v0 = ld_poll2(pa), v1 = ld_poll2(pa + 1024), v2 = ld_poll2(pa + 2048), v3 = ld_poll2(pa + 3072);
          TR(s, 3);
#pragma unroll
          for (int f = WO_1; f < 16 - WO_L; f++) ldwo(f);
          TR(s, 4);
          uint32_t n = 0;
          while (true) {
            sts64(vm + (c.sb + SM_VM), sum4(v0.x, v1.x, v2.x, v3.x), sum4(v0.y, v1.y, v2.y, v3.y));
            if (arrive_if_clear(stale1(stale1(stale2(v0.x, v1.x, tg), v2.x, tg), v3.x, tg), chk, NB_VM, 384)) break;
            v0 = ld_poll2(pa); v1 = ld_poll2(pa + 1024); v2 = ld_poll2(pa + 2048); v3 = ld_poll2(pa + 3072);
            n++; CNT(3);
          }
          TR(s, 12); TRV(s, 15, n);
        }
        const uint32_t ob = dep(dep(t16 & 511, af[14 - WO_L][0], c.sb), af[15 - WO_L][0], c.sb);
        uint32_t l4 = ob >> 2;
        const uint32_t bit = (t16 & 48) ? 0u : 1u;
        if (LF_AT) mbar_spin2_if(BAR(B_XFULL), BAR(B_LFREE), s & 1, s + 2 < XEND); else mbar_spin_if(BAR(B_XFULL), s & 1, s + 2 < XEND);
        bar_sync(NB_OM, 384);
        TR(s, 5);
#pragma unroll
        for (int i = 0; i < 4; i++) ldsm4t(bf[i], ob + (c.sb + SM_OM + i * 512));
        uint2 sum = lds64(((t16 >> 1) & 24) + (c.sb + SM_SUM));
        if (OM_F) sched_fence(c.sb);
        float d[WO_C][4] = {};
        uint4 d0, d1;
#pragma unroll
        for (int f = 0; f < 16; f++) {
          mma_a(d[f % WO_C], af[f], bf[f >> 2][f & 2], bf[f >> 2][(f & 2) + 1]);
          if (f >= WO_C && f < WO_C + WO_L) {
            const int l = 16 - WO_L + f - WO_C;
            ldsm4t(af[l], (WO_LD ? dep(wo, __float_as_uint(d[(f + 1) % WO_C][0]), c.sb) : wo) + (c.sb + SM_WO + (l & 1) * 32768 + (l >> 1) * 2048));
          }
          if (f == WO_T) {
            const uint32_t tb2 = dep((t16 >> 3) & 0x1C0, __float_as_uint(d[f % WO_C][0]), c.sb) + (c.sb + SM_TAB + (s & 1) * 512);
            d0 = lds128(tb2 + 32); d1 = lds128(tb2 + 48);
          }
          if (f >= PL_WA && f < PL_WA + PL_W) lds_frag(wa[f - PL_WA], (PL_WD ? dep(t16, __float_as_uint(d[(f + PL_WD) % WO_C][0]), c.sb) : t16) + (c.sb + SM_POOL + (f - PL_WA) * 4096));
          if (PL_W && PL_WF == 1 && f == PL_WA + PL_W - 1) sched_fence(c.sb);
          if (f == 4) { sum.x = dep(sum.x, __float_as_uint(d[0][0]), c.sb); sum.y = dep(sum.y, __float_as_uint(d[0][0]), c.sb); }
        }
        if (PL_W && !PL_WF) {
          uint32_t all = 0;
#pragma unroll
          for (int k = 0; k < PL_W; k++) all ^= wa[k][0];
          l4 = dep(l4, all, c.sb);
        }
        char* dst[4] = {mk_ptr(d0.x | l4, d0.y), mk_ptr(d0.z | l4, d0.w), mk_ptr(d1.x | l4, d1.y), mk_ptr(d1.z | l4, d1.w)};
        const float i0 = rcp(__uint_as_float(sum.x)), i1 = rcp(__uint_as_float(sum.y));
#pragma unroll
        for (int i = 0; i < 4; i++) {
          const int t = i >> 1, e = 2 * (i & 1);
          const float y0 = WO_C == 2 ? d[t][e] : d[t][e] + d[(t + 2) % WO_C][e], y1 = WO_C == 2 ? d[t][e + 1] : d[t][e + 1] + d[(t + 2) % WO_C][e + 1];
          st_pub(dst[i], put_tag(pack_bf16(y0 * i0, y1 * i1), bit, s >> 1));
        }
        if (ANCH2) sts32(c.sb + SM_SUM + 64, clock_lo());
        mbar_arrive_warp(BAR(B_E2TRIG));
        TR(s, 6);
        sched_fence(c.sb);
        if (W_E2 == 2) mbar_spin(BAR(B_E2TRIG), s & 1);
      }
      if (__builtin_expect(s + 2 < XEND, 1)) {
        const uint32_t tg0 = DLY_P ? clock_lo() + DLY_P : 0;
        if (LP_IN) ldp(PL_W, PL_0, PL_D);
        float xa[16];
        uint32_t q[4];
        if (W_E2 == 1 && s >= 0) mbar_spin(BAR(B_E2TRIG), s & 1);
        TR(s, 7);
        constexpr int S1 = ORDER ? 0 : 2, S2 = ORDER == 0 ? 0 : ORDER == 1 ? 2 : 1, S3 = ORDER == 2 ? 2 : 1;
        if (ORDER) issue_qk<0, 16>(xa, wb, vary(dx, s, c.sb)); else issue_v(xa, wv, vary(dx, s, c.sb), vary(dh, s, c.sb));
        if (DLY_P) delay_until(tg0); else if (IS_F) sched_fence(c.sb);
        ldp(PL_0, PL_1, PL_D1);
        const uint32_t land = (t16 ^ ((t16 >> 3) & 0x60)) + vary(c.sb + SM_LAND + c.b * 4096, s, c.sb);
        TR(s, 14);
        if (LF_AT == 1) mbar_spin_if(BAR(B_LFREE), s & 1, s < 0); else if (!LF_AT) mbar_spin(BAR(B_LFREE), s & 1);
        TR(s, 15);
        WG_WAIT(0);
        TR(s, 8);
        park_own<S1 == 2>(q, xa, land, S1, c.sb);
        if (W_PUB == 4 && s >= 0) mbar_spin(BAR(B_PUB), s & 1);
        if (ORDER == 1) issue_v(xa, wv, vary(dx, s, c.sb + 32), vary(dh, s, c.sb)); else issue_qk<0, 16>(xa, ORDER ? wa : wb, vary(dx, s, c.sb + 32));
        if (IS_F) sched_fence(c.sb);
        ldp(PL_1, PL_2, PL_D1);
        if (W_PUB == 1) mbar_spin_if(BAR(B_PUB), s & 1, s >= 0);
        uint32_t tp = clock_lo(), q1[4] = {q[0], q[1], q[2], q[3]};
        if (PL_2B) ldp(PL_2, NP - PL_L, PL_D1);
        if (W_PUB != 3) park_peer(q, land, S1, c);
        if (!PL_2B) ldp(PL_2, NP - PL_L, PL_D1);
        TR(s, 13);
        WG_WAIT(0);
        TR(s, 9);
        park_own<S2 == 2>(q, xa, land, S2, c.sb);
        if (ORDER == 2) issue_v(xa, wv, vary(dx, s, c.sb + 64), vary(dh, s, c.sb));
        else {
          issue_qk<0, PL_L ? NP - PL_L : 16>(xa, wa, vary(dx, s, c.sb + 64));
          ldp(NP - PL_L, NP, PL_E);
          if (PL_L) issue_qk<NP - PL_L, 16>(xa, wa, vary(dx, s, c.sb + 64));
        }
        if ((W_PUB == 2 || W_PUB == 3) && s >= 0) { mbar_spin(BAR(B_PUB), s & 1); tp = clock_lo(); }
        if (W_PUB == 3) park_peer(q1, land, S1, c);
        if (DLY_S && s >= 0) delay_until(tp + DLY_S);
        park_peer(q, land, S2, c);
        WG_WAIT(0);
        TR(s, 10);
        mbar_arrive_warp(BAR(B_XEMPTY));
        park_own<S3 == 2>(q, xa, land, S3, c.sb);
        park_peer(q, land, S3, c);
        TR(s, 11);
      } else {
        if (s == NSEG - 1) break;
        if (EARLY2 && (XEND == NSEG || s == NSEG - 2) && c.m * 4 + c.w == 0) count_e(g_ctl + C_EARLY);
        ldp(PL_W, NP, 2);
      }
    }
    asm volatile("setmaxnreg.dec.sync.aligned.u32 %0;" :: "n"(BPRE == 2 ? 176 : 128));
    const int tid = tid_now(), lane = tid & 31, tile = tile_of(c), m0 = (tile >> 3) * 128, n0 = (tile & 7) * 128;
    float acc[64];
#pragma unroll
    for (int i = 0; i < 64; i++) acc[i] = 0.f;
    const uint32_t rel = mapa(BAR(B_GEMPTY), lane & 1), la = desc_lo(c.sb + c.m * 8192), lb = ((c.sb + 16384) & 0x3FFFF) >> 4 | (8192 >> 4) << 16;
    bool relon = false;
    const int skew = tile < 120 ? 0 : SKEW, kend = 64 + skew - c.m * skew, hold = c.m * (65 - LEAD) - 1;
    const float g0 = __ldcg(g_gate + m0 + (tid >> 5) * 16 + (lane >> 2)), g1 = __ldcg(g_gate + m0 + (tid >> 5) * 16 + (lane >> 2) + 8);
    uint32_t o = SM_XT, st = 0, ph = 0, prev = 0;
    if (tid == 0) TL(9);
    __syncwarp();
    GT(0);
#pragma unroll 1
    for (int kb = -c.m * skew; kb < max(kend - 4, 64); kb++, o = next_stage(o)) {
      if (LEAD && kb == hold) bar_sync(15, 256);
      mbar_lim(BAR(B_GFULL + st), ph);
      if ((uint32_t)kb < 64) {
        WG_FENCE();
#pragma unroll
        for (int k = 0; k < 4; k++) wgmma_ss_n128_tb(acc, desc128(la + (o >> 4) + k * 2), desc128(lb + (o >> 4) + k * 128));
        WG_COMMIT();
        WG_WAIT(1);
      } else WG_WAIT(0);
      arrive_remote_if(rel + 8 * prev, relon && kb < kend - 4);
      relon = (tid & 127) < 2;
      prev = st;
      if (++st == 5) { st = 0; ph ^= 1; }
    }
    if (LEAD && c.m == 0) asm volatile("bar.arrive 15, 256;" ::: "memory");
    const uint32_t row = (tid >> 5) * 2048 + (lane & 15) * 128 + (((lane >> 4) ^ (lane & 7)) << 4);
    if (!BPRE) WG_WAIT(0);
    mbar_lim(BAR(B_BT), 0);
    uint32_t b[2][4][4];
    const uint32_t rb = (tid >> 5) * 2048 + (lane >> 2) * 128 + (((lane & 7) ^ (lane >> 2)) << 4);
#pragma unroll
    for (int i = 0; i < 8; i++) lds_frag(b[i & 1][i >> 1], (rb ^ (i & 2) * 32) + (c.sb + SM_BT + (i >> 2) * 16384 + (i & 1) * 1024));
    float bl[2][4][4], bh[2][4][4];
    if (BPRE == 2) {
#pragma unroll
      for (int i = 0; i < 32; i++) {
        asm volatile("shl.b32 %0, %1, 16;" : "=f"(bl[i >> 4][i >> 2 & 3][i & 3]) : "r"(b[i >> 4][i >> 2 & 3][i & 3]));
        asm volatile("and.b32 %0, %1, 0xffff0000;" : "=f"(bh[i >> 4][i >> 2 & 3][i & 3]) : "r"(b[i >> 4][i >> 2 & 3][i & 3]));
      }
    }
    if (BPRE) { sched_fence(c.sb); WG_WAIT(0); sched_fence(c.sb); }
#pragma unroll
    for (int i = 0; i < 64; i++) asm volatile("" : "+f"(acc[i]) :: "memory");
    GT(17);
    if (tid == 0) TL(4);
    __syncwarp();
#pragma unroll
    for (int hf = 0; hf < 2; hf++) {
#pragma unroll
      for (int t = 0; t < 4; t++) {
        uint32_t y[4];
#pragma unroll
        for (int i = 0; i < 4; i++) {
          const float* a = acc + 32 * hf + 8 * t + 2 * i, g = i & 1 ? g1 : g0;
          const uint32_t* q = b[i & 1][2 * (t & 1) + (i >> 1)] + hf;
          const float* f = (t & 2 ? bh : bl)[i & 1][2 * (t & 1) + (i >> 1)] + hf;
          if (BPRE == 2) y[i] = pack_bf16(fmaf(g, a[0], f[0]), fmaf(g, a[1], f[2])); else
          y[i] = pack_bf16(fmaf(g, a[0], __uint_as_float(t & 2 ? q[0] & 0xFFFF0000u : q[0] << 16)), fmaf(g, a[1], __uint_as_float(t & 2 ? q[2] & 0xFFFF0000u : q[2] << 16)));
        }
        stsm4<false>((row ^ t * 32) + (c.sb + SM_BT + hf * 16384), y[0], y[1], y[2], y[3]);
      }
      if (EP_F && !hf) { sched_fence(c.sb); for (int i = 32; i < 64; i++) asm volatile("" : "+f"(acc[i]) :: "memory"); }
      FENCE_ASYNC_SMEM();
      __syncwarp();
      tma2d_out_e(&tout, n0 + hf * 64, m0 + (c.m * 4 + c.w) * 16, c.sb + SM_BT + hf * 16384 + (c.m * 4 + c.w) * 2048);
    }
    asm volatile("cp.async.bulk.commit_group; cp.async.bulk.wait_group" WAITRD " 0;" ::: "memory");
    GT(18);
    if ((tid & 127) == 0) TL(11);
    return;
  }
  constexpr int NH = NQ < 106 ? 4 * (106 - NQ) : 0;
  const bool col = c.r >= 128;
  const int tile = col ? 0 : tile_of(c);
  const int q0 = col ? 256 - NQ + (c.r - 128) + c.m * 4 : tile < 120 ? tile : 256, u = (tile >> 1 & 32) | (tile >> 3 & 7) | (tile & 6) << 2, e = QSH == 2 ? 2 * (u - (u > 39) - (u > 47) - (NQ < 110 && u > 55)) + c.b : tile,
            dq = col ? 16 : QSH ? 120 + (e < NH ? e >> 1 : (e + NH) >> 2) - tile : 120, qe = col ? 256 : 256 - NQ,
            qw = col || !QSH || (e < NH ? c.w >> 1 == c.b : c.w == ((e + NH) & 3)) ? qe : 120;
  const uint32_t zs = c.sb + (col ? COL_Z + c.m * 32768 : SM_BT), zb = BAR(B_Z + c.m);
  auto load_z = [&](int q) { if (c.w == 0 && q < qe) { mbar_expect_e(zb, 32768); tma2d_o<(ONCE & 4) != 0>(zs, &tz, q * 64, 0, zb); } };
  asm volatile("fence.proxy.async.global;" ::: "memory");
  load_z(q0);
  uint32_t ph = 0;
#pragma unroll 1
  for (int q = q0; q < qe; q += dq, ph ^= 1) {
    mbar_lim(zb, ph);
    const int p = q * 4 + c.w;
    if (EXP_INV && q < qw) fft_rows_inv(zs, (float2*)(smraw + (col ? 8192 + c.m * INV_BUF * 32 : SM_MEM)) + c.w * INV_BUF, (const float2*)(smraw + (col ? 0 : SM_TW)), p, tid_now() & 31, g_b,
                              [&]() { bar_sync(5 + c.m, 128); load_z(q + dq); });
    else { bar_sync(5 + c.m, 128); load_z(q + dq); }
  }
  if (B_ST) asm volatile("cp.async.bulk.wait_group 0; fence.proxy.async.global;" ::: "memory");
  asm volatile("fence.acq_rel.gpu;" ::: "memory");
  __syncwarp();
  { const int q = q0 + (tid_now() & 31) * dq; if (q < qw) asm volatile("red.relaxed.gpu.global.add.u32 [%0], 1;" :: "l"(g_ctl + C_ROWS + (q >> 5) * 32) : "memory"); }
  if (tid_now() == 256) { if (col) TL(27); else TL(3); }
  __syncwarp();
  if (!col && c.w == 0) {
    await_count<AW_NS>(g_ctl + C_ROWS + ((tile >> 3) & 7) * 32, 128);
    mbar_expect_e(BAR(B_BT), 32768);
    for (int i = 0; i < 2; i++) tma2d_o<(ONCE & 8) != 0>(c.sb + SM_BT + i * 16384, &tb, (tile & 7) * 128 + i * 64, (tile >> 3) * 128, BAR(B_BT));
    if (tid_now() == 256) TL(5);
  }
}

typedef CUresult (*EncodeFn)(CUtensorMap*, CUtensorMapDataType, cuuint32_t, void*, const cuuint64_t*, const cuuint64_t*,
                             const cuuint32_t*, const cuuint32_t*, CUtensorMapInterleave, CUtensorMapSwizzle,
                             CUtensorMapL2promotion, CUtensorMapFloatOOBfill);

void make_map(EncodeFn enc, CUtensorMap* tm, const void* p, int rank, const cuuint64_t* dims, const cuuint64_t* strides, const cuuint32_t* box, bool swz = true) {
  const cuuint32_t es[4] = {1, 1, 1, 1};
  enc(tm, CU_TENSOR_MAP_DATA_TYPE_BFLOAT16, rank, (void*)p, dims, strides, box, es, CU_TENSOR_MAP_INTERLEAVE_NONE,
      swz ? CU_TENSOR_MAP_SWIZZLE_128B : CU_TENSOR_MAP_SWIZZLE_NONE, swz ? CU_TENSOR_MAP_L2_PROMOTION_L2_128B : W_PROMO, CU_TENSOR_MAP_FLOAT_OOB_FILL_NONE);
}
void make_map2(EncodeFn enc, CUtensorMap* tm, const void* p, uint64_t cols, uint64_t rows, uint32_t boxrows) {
  const cuuint64_t dims[2] = {cols, rows}, strides[1] = {cols * 2};
  const cuuint32_t box[2] = {64, boxrows};
  make_map(enc, tm, p, 2, dims, strides, box);
}

}

extern "C" void kernel_launch(void* const* d_in, const int* in_sizes, int n_in, void* d_out, int out_size) {
  (void)in_sizes; (void)n_in; (void)out_size;
  const __nv_bfloat16* x = (const __nv_bfloat16*)d_in[0];
  const __nv_bfloat16* mem0 = (const __nv_bfloat16*)d_in[1];
  const __nv_bfloat16* gw = (const __nv_bfloat16*)d_in[10];

  EncodeFn enc = nullptr;
  cudaDriverEntryPointQueryResult qr;
  cudaGetDriverEntryPoint("cuTensorMapEncodeTiled", (void**)&enc, cudaEnableDefault, &qr);
  void *p_ox, *p_b, *p_z, *p_mail;
  cudaGetSymbolAddress(&p_ox, g_ox); cudaGetSymbolAddress(&p_b, g_b); cudaGetSymbolAddress(&p_z, g_z); cudaGetSymbolAddress(&p_mail, g_mail);
  CUtensorMap tq, tk, tv, tv16, to, tx, twr, twi, ta, tw, tb, tout, tz, tzs, ta32;
  make_map2(enc, &tq, d_in[2], 4096, 1024, 64);
  make_map2(enc, &tk, d_in[3], 4096, 1024, 64);
  make_map2(enc, &tv, d_in[4], 4096, 1024, 64);
  make_map2(enc, &tv16, d_in[4], 4096, 1024, 16);
  make_map2(enc, &to, d_in[5], 1024, 4096, 128);
  make_map2(enc, &tw, d_in[5], 1024, 4096, 64);
  {
    const cuuint64_t dims[3] = {64, 2048, 64}, strides[2] = {128, 262144};
    const cuuint32_t box[3] = {64, 32, 2}, box1[3] = {64, 32, 1};
    make_map(enc, &ta, p_ox, 3, dims, strides, box);
    make_map(enc, &ta32, p_ox, 3, dims, strides, box1);
  }
  make_map2(enc, &tb, p_b, 1024, 2048, 128);
  make_map2(enc, &tout, d_out, 1024, 2048, 16);
  make_map2(enc, &tz, p_z, 16384, 257, 256);
  {
    const cuuint64_t dims[4] = {64, 8, 16, 256}, strides[3] = {2048, 128, 16384};
    const cuuint32_t box[4] = {64, 8, 8, 2};
    make_map(enc, &tx, x, 4, dims, strides, box);
  }
  {
    const cuuint64_t dims[2] = {512, 257 * 32}, strides[1] = {1024};
    const cuuint32_t box[2] = {128, 16};
    make_map(enc, &tzs, p_z, 2, dims, strides, box, false);
  }
  {
    const cuuint64_t dims[2] = {8 * 513, 256}, strides[1] = {8 * 513 * 2};
    const cuuint32_t box[2] = {8, 256};
    make_map(enc, &twr, d_in[8], 2, dims, strides, box, false);
    make_map(enc, &twi, d_in[9], 2, dims, strides, box, false);
  }
  cudaFuncSetAttribute(chain_kernel, cudaFuncAttributeMaxDynamicSharedMemorySize, CHAIN_SMEM);

  cudaStream_t st = cudaStreamPerThread;
  char* mail = (char*)(((uintptr_t)p_mail + M_REG - 1) & ~(uintptr_t)(M_REG - 1));
  chain_kernel<<<132, 512, CHAIN_SMEM, st>>>(tq, tk, tv, tv16, to, tx, twr, twi, ta, tw, tb, tout, tz, tzs, ta32, mem0, mail, x, gw);
}
```

```cpp
#include <cuda_runtime.h>
#include <cuda_bf16.h>
#include <cuda.h>
#include <stdint.h>

#define DLY_E1 220
#define DLY_V 330
#define DLY_E2 300
#define DLY_E3 440
#define DLY_X 0
#define DLY_S 200
#define DLY_F 150
#define VM_AT 3
#define OM_F 1
#define C1_AT 5
#define NLAG 2
#define WO_D 2
#define WO_0 3
#define WO_1 11
#define PL_0 10
#define PL_1 11
#define PL_D 2
#define PL_L 0
#define HV_D 4
#define DLY_FK 0
#define REG_F 216
#define REG_H 24
#define SC_F 1
#define E2_F 0
#define X_AT 2
#define PL_2 11
#define PL_E 2
#define ORDER 1
#define SSPOS 1
#define W_PUB 1
#define FIN_AT 5
#define AWARE 1
#define NPROBE 2
#define NP_ 12
#define DLY_GRP 1000
#define EXP_CHK 1
#define EXP_NXT 2
#define EXP_PEER 1
#define EXP_FIN 7
#define EXP_NWG 16
#define ANCH2 1
#define IS_F 1
#define PL_D1 1
#define W_E2 0
#define V_TMA 2
#define V_W 2
#define RED_L 3
#define RED_T 0
#define RED_P 1
#define DLY_E3B 60
#define HV_E 2
#define HV_R 5
#define HOLD 0
#define PACE 500
#define PACE0 0
#define EXP_ST 7
#define WO_AT 38
#define WO_P 2
#define DLY_SEL 300
#define P1_AT 1
#define TMA_W tma2d_once
#define TMA_O tma2d_once
#define PACE_Z 580
#define EXP_INV 1
#define VF_AT 1
#define UP_F 0
#define WO_L (12 - NP_)
#define WO_C 4
#define WO_T 2
#define WO_LD 0
#define EXP_LIN 0
#define PL_W 5
#define PL_WA 10
#define PL_WD 0
#define PL_WF 2
#define EXP_FL 0
#define DLY_FS 0
#define DLY_F2 40
#define PF_D 4
#define PF_A 1
#define PF_B 0
#define SIDE 1
#define ROLE 1
#define E1OFF 1
#define EPI 0
#define WAITRD ".read"
#define START 1000
#define WUNR 1
#define WO_N 0
#define PL_2B 1
#define DLY_P 0
#define LP_IN 1
#define LF_AT 1
#define FINE 0
#define E30 1
#define WO_S 1
#define POOL_AT 12
#define COL_DLY 0
#define PAD0 2
#define PAD2 2
#define PAD3 4
#define WO_X 0
#define PRIOR 12
#define EARLY 1
#define SEL_AT 3000
#define FUNR 0
#define ZINIT 1
#define ZDLY 0
#define NQ 92
#define GATE 0
#define LASTM 1
#define X_ONCE 1
#define ONCE 31
#define Z_PF 0
#define EXP_W 1
#define W_PROMO CU_TENSOR_MAP_L2_PROMOTION_L2_128B
#define Z_ST 1
#define W_FINE 0
#define X128 2
#define T128_ 1
#define W_AT 0
#define SKEW 7
#define AW_NS 0
#define QSH 2
#define EARLY2 1
#define LEAD 3
#define BPRE 2
#define EP_F 1
#define TQ_AT 0
#define LAG_0 4
#define LAG_G 0
#define LAG_S 0
#define O_AT 0
#define XB 1
#define V_E 1
#define LAG_T 0
#define E3M 0
#define B_ST 1
#define TW_L 1
#define K_TMA 1
#define KL_AT 0
#define DLY_K 350
#define Q_TMA 0
#define Q_AT 1
#define IDLE 1
#define PL_AN 4
#define PL_A (PL_0 - PL_AN < PL_W ? PL_W : PL_0 - PL_AN)
#define ASY 0
#define ASY_AT 2
#define DLY_XL 0
#define SXP 1
#define DLY_SA 0
#define DLY_SB 0
#define XL_AT 2
#define DLY_Y 0
#define PRE_AT B_SC

namespace {
constexpr int wunr = WUNR;

constexpr int S_ = 2048, D_ = 1024, NSEG = 64;
constexpr uint32_t SENT = 0xFFFFFFFFu;
constexpr int NSLOT = 4;

constexpr uint32_t M_REG = 1 << 21, M_E3 = 64 * 16384, M_KVQ = M_E3 + 4 * 8192, M_SEL = M_KVQ + 32 * 24576;
__device__ __align__(1024) unsigned char g_mail[5 * M_REG];
constexpr int C_P1 = 0, C_COLS = C_P1 + 32, C_EARLY = C_COLS + 32, C_LAST = C_EARLY + 32, C_ROWS = C_LAST + 128, C_END = C_ROWS + 8 * 32;
__device__ __align__(1024) uint32_t g_ctl[C_END];
#define CLK(i)
#define TL(i)
#define TL2(i)
#define FT(i, v)
#define GT(i)
#define CNT(i)
__device__ __align__(1024) __nv_bfloat16 g_ox[S_ * 4096];
__device__ __align__(1024) float2 g_z[257 * 4096];
__device__ __align__(1024) __nv_bfloat16 g_b[S_ * D_];
__device__ float g_gate[S_];
__device__ __align__(1024) float2 g_tw[1024];

#define TRV(s, ev, val)
#define TR(s, ev)
#define TRSYNC(ev)
__device__ __forceinline__ uint32_t smem_u32(const void* p) { return (uint32_t)__cvta_generic_to_shared(p); }
__device__ __forceinline__ void watchdog(uint32_t& n, uint32_t limit) {
  asm volatile("{ .reg .pred p; add.u32 %0, %0, 1; setp.gt.u32 p, %0, %1; @p trap; }" : "+r"(n) : "r"(limit));
}
__device__ __forceinline__ void mbar_init(uint32_t bar, uint32_t cnt) {
  asm volatile("mbarrier.init.shared::cta.b64 [%0], %1;" :: "r"(bar), "r"(cnt) : "memory");
}
__device__ __forceinline__ void mbar_arrive_warp(uint32_t bar) {
  __syncwarp();
  asm volatile("{ .reg .pred p; elect.sync _|p, 0xffffffff; @p mbarrier.arrive.shared::cta.b64 _, [%0]; }" :: "r"(bar) : "memory");
}
__device__ __forceinline__ uint32_t clock_lo() {
  uint32_t r; asm volatile("{ .reg .u64 c; .reg .u32 h; mov.u64 c, %%clock64; mov.b64 {%0, h}, c; }" : "=r"(r) :: "memory"); return r;
}
__device__ __forceinline__ void delay_until(uint32_t t) {
  asm volatile("{ .reg .pred p; .reg .u64 c; .reg .u32 l, h;\n"
               "DLY: mov.u64 c, %%clock64; mov.b64 {l, h}, c; sub.s32 l, l, %0; setp.lt.s32 p, l, 0; @p bra.uni DLY; }" :: "r"(t) : "memory");
}
__device__ __forceinline__ void delay_fine(uint32_t t) {
  delay_until(t);
}
__device__ __forceinline__ void delay_cycles(uint32_t n) { delay_until(clock_lo() + n); }
__device__ __forceinline__ void sched_fence(uint32_t z) {
  asm volatile("{ .reg .pred p; setp.eq.u32 p, %0, 0x7fff0000; @p pmevent 1; }" :: "r"(z) : "memory");
}
__device__ __forceinline__ void pdl_wait() { asm volatile("griddepcontrol.wait;" ::: "memory"); }
__device__ __forceinline__ void pdl_launch() { asm volatile("griddepcontrol.launch_dependents;" ::: "memory"); }
__device__ __forceinline__ float ex2(float x) { float r; asm("ex2.approx.ftz.f32 %0, %1;" : "=f"(r) : "f"(x)); return r; }
__device__ __forceinline__ float rcp(float x) { float r; asm("rcp.approx.ftz.f32 %0, %1;" : "=f"(r) : "f"(x)); return r; }
__device__ __forceinline__ void mbar_expect(uint32_t bar, uint32_t bytes) {
  asm volatile("mbarrier.arrive.expect_tx.shared::cta.b64 _, [%0], %1;" :: "r"(bar), "r"(bytes) : "memory");
}
__device__ __forceinline__ bool mbar_try(uint32_t bar, uint32_t ph) {
  uint32_t ok;
  asm volatile("{ .reg .pred p; mbarrier.try_wait.parity.shared::cta.b64 p, [%1], %2; selp.u32 %0, 1, 0, p; }"
               : "=r"(ok) : "r"(bar), "r"(ph) : "memory");
  return ok;
}
__device__ __forceinline__ void mbar_wait(uint32_t bar, uint32_t ph) {
  uint32_t n = 0;
  while (!mbar_try(bar, ph)) { watchdog(n, (1u << 20)); }
}
__device__ __forceinline__ void mbar_spin(uint32_t bar, uint32_t ph) { while (!mbar_try(bar, ph)) {} }
__device__ __forceinline__ void mbar_idle(uint32_t bar, uint32_t ph) {
  if (!IDLE) { mbar_wait(bar, ph); return; }
  asm volatile("{ .reg .pred q; SPN: mbarrier.try_wait.parity.shared::cta.b64 q, [%0], %1; @!q bra.uni SPN; }" :: "r"(bar), "r"(ph) : "memory");
}
__device__ __forceinline__ void mbar_spin_if(uint32_t bar, uint32_t ph, bool on) {
  asm volatile("{ .reg .pred p, q; setp.ne.u32 p, %2, 0;\n"
               "SPN: setp.eq.u32 q, 0, 0; @p mbarrier.try_wait.parity.shared::cta.b64 q, [%0], %1; @!q bra.uni SPN; }" :: "r"(bar), "r"(ph), "r"((uint32_t)on) : "memory");
}
__device__ __forceinline__ void mbar_spin2_if(uint32_t bar, uint32_t bar2, uint32_t ph, bool on) {
  asm volatile("{ .reg .pred p, q, r; setp.ne.u32 p, %3, 0;\n"
               "SPN: setp.eq.u32 q, 0, 0; setp.eq.u32 r, 0, 0; @p mbarrier.try_wait.parity.shared::cta.b64 q, [%0], %2;\n"
               "@p mbarrier.try_wait.parity.shared::cta.b64 r, [%1], %2; and.pred q, q, r; @!q bra.uni SPN; }" :: "r"(bar), "r"(bar2), "r"(ph), "r"((uint32_t)on) : "memory");
}
__device__ __forceinline__ void mbar_spin_cluster(uint32_t bar, uint32_t ph) {
  uint32_t ok;
  do {
    asm volatile("{ .reg .pred p; mbarrier.try_wait.parity.acquire.cluster.shared::cta.b64 p, [%1], %2; selp.u32 %0, 1, 0, p; }"
                 : "=r"(ok) : "r"(bar), "r"(ph) : "memory");
  } while (!ok);
}
#define ONCE_H "mov.b64 h, 0x12F0000000000000; "
__device__ __forceinline__ void tma2d(uint32_t dst, const CUtensorMap* tm, int c0, int c1, uint32_t bar) {
  if (ONCE & 32) asm volatile("{ .reg .b64 h; " ONCE_H "cp.async.bulk.tensor.2d.shared::cluster.global.mbarrier::complete_tx::bytes.L2::cache_hint [%0], [%1, {%3, %4}], [%2], h; }"
               :: "r"(dst), "l"(tm), "r"(bar), "r"(c0), "r"(c1) : "memory");
  else asm volatile("cp.async.bulk.tensor.2d.shared::cluster.global.mbarrier::complete_tx::bytes [%0], [%1, {%3, %4}], [%2];"
               :: "r"(dst), "l"(tm), "r"(bar), "r"(c0), "r"(c1) : "memory");
}
__device__ __forceinline__ void mbar_expect_e(uint32_t bar, uint32_t bytes) {
  asm volatile("{ .reg .pred p; elect.sync _|p, 0xffffffff; @p mbarrier.arrive.expect_tx.shared::cta.b64 _, [%0], %1; }" :: "r"(bar), "r"(bytes) : "memory");
}
__device__ __forceinline__ void tma2d_e(uint32_t dst, const CUtensorMap* tm, int c0, int c1, uint32_t bar) {
  asm volatile("{ .reg .pred p; elect.sync _|p, 0xffffffff;\n"
               "@p cp.async.bulk.tensor.2d.shared::cluster.global.mbarrier::complete_tx::bytes [%0], [%1, {%3, %4}], [%2]; }"
               :: "r"(dst), "l"(tm), "r"(bar), "r"(c0), "r"(c1) : "memory");
}
__device__ __forceinline__ void tma2d_st_e(const CUtensorMap* tm, int c0, int c1, uint32_t src) {
  asm volatile("{ .reg .pred p; elect.sync _|p, 0xffffffff;\n"
               "@p cp.async.bulk.tensor.2d.global.shared::cta.bulk_group [%0, {%2, %3}], [%1]; }" :: "l"(tm), "r"(src), "r"(c0), "r"(c1) : "memory");
}
__device__ __forceinline__ void tma2d_out_e(const CUtensorMap* tm, int c0, int c1, uint32_t src) {
  if (EPI) asm volatile("{ .reg .pred p; elect.sync _|p, 0xffffffff;\n"
               "@p cp.reduce.async.bulk.tensor.2d.global.shared::cta.add.bulk_group [%0, {%2, %3}], [%1]; }" :: "l"(tm), "r"(src), "r"(c0), "r"(c1) : "memory");
  else if (ONCE & 16) asm volatile("{ .reg .pred p; .reg .b64 h; " ONCE_H "elect.sync _|p, 0xffffffff;\n"
               "@p cp.async.bulk.tensor.2d.global.shared::cta.bulk_group.L2::cache_hint [%0, {%2, %3}], [%1], h; }" :: "l"(tm), "r"(src), "r"(c0), "r"(c1) : "memory");
  else asm volatile("{ .reg .pred p; elect.sync _|p, 0xffffffff;\n"
               "@p cp.async.bulk.tensor.2d.global.shared::cta.bulk_group [%0, {%2, %3}], [%1]; }" :: "l"(tm), "r"(src), "r"(c0), "r"(c1) : "memory");
}
__device__ __forceinline__ void tma2d_once(uint32_t dst, const CUtensorMap* tm, int c0, int c1, uint32_t bar) {
  asm volatile("{ .reg .pred p; .reg .b64 h; " ONCE_H "elect.sync _|p, 0xffffffff;\n"
               "@p cp.async.bulk.tensor.2d.shared::cluster.global.mbarrier::complete_tx::bytes.L2::cache_hint [%0], [%1, {%3, %4}], [%2], h; }"
               :: "r"(dst), "l"(tm), "r"(bar), "r"(c0), "r"(c1) : "memory");
}
__device__ __forceinline__ void bulk_once(uint32_t dst, const void* src, uint32_t bytes, uint32_t bar) {
  asm volatile("{ .reg .pred p; .reg .b64 h; " ONCE_H "elect.sync _|p, 0xffffffff;\n"
               "@p cp.async.bulk.shared::cluster.global.mbarrier::complete_tx::bytes.L2::cache_hint [%0], [%1], %2, [%3], h; }"
               :: "r"(dst), "l"(src), "r"(bytes), "r"(bar) : "memory");
}
__device__ __forceinline__ void tma4d_e(uint32_t dst, const CUtensorMap* tm, int c2, int c3, uint32_t bar) {
  asm volatile("{ .reg .pred p; .reg .b64 h; " ONCE_H "elect.sync _|p, 0xffffffff;\n"
               "@p cp.async.bulk.tensor.4d.shared::cluster.global.mbarrier::complete_tx::bytes.L2::cache_hint [%0], [%1, {0, 0, %3, %4}], [%2], h; }"
               :: "r"(dst), "l"(tm), "r"(bar), "r"(c2), "r"(c3) : "memory");
}
__device__ __forceinline__ void bulk_load_e(uint32_t dst, const void* src, uint32_t bytes, uint32_t bar) {
  asm volatile("{ .reg .pred p; elect.sync _|p, 0xffffffff;\n"
               "@p cp.async.bulk.shared::cluster.global.mbarrier::complete_tx::bytes [%0], [%1], %2, [%3]; }"
               :: "r"(dst), "l"(src), "r"(bytes), "r"(bar) : "memory");
}
template<bool O> __device__ __forceinline__ void tma2d_o(uint32_t dst, const CUtensorMap* tm, int c0, int c1, uint32_t bar) {
  if (O) tma2d_once(dst, tm, c0, c1, bar); else tma2d_e(dst, tm, c0, c1, bar);
}
__device__ __forceinline__ float2 ld_once(const float2* p) {
  float2 v;
  if (ONCE & 64) asm volatile("{ .reg .b64 h; " ONCE_H "ld.global.cg.L2::cache_hint.v2.f32 {%0, %1}, [%2], h; }" : "=f"(v.x), "=f"(v.y) : "l"(p));
  else v = __ldcg(p);
  return v;
}
template<bool O = false> __device__ __forceinline__ void prefetch2d_e(const CUtensorMap* tm, int c0, int c1) {
  if (O) asm volatile("{ .reg .pred p; .reg .b64 h; " ONCE_H "elect.sync _|p, 0xffffffff;\n"
               "@p cp.async.bulk.prefetch.tensor.2d.L2.global.L2::cache_hint [%0, {%1, %2}], h; }" :: "l"(tm), "r"(c0), "r"(c1) : "memory");
  else asm volatile("{ .reg .pred p; elect.sync _|p, 0xffffffff;\n"
               "@p cp.async.bulk.prefetch.tensor.2d.L2.global [%0, {%1, %2}]; }" :: "l"(tm), "r"(c0), "r"(c1) : "memory");
}
__device__ __forceinline__ void st_pub4(void* p, uint4 v) {
  asm volatile("st.relaxed.gpu.global.v4.u32 [%0], {%1,%2,%3,%4};" :: "l"(p), "r"(v.x), "r"(v.y), "r"(v.z), "r"(v.w) : "memory");
}
__device__ __forceinline__ void st_pub_if(void* p, uint32_t v, bool on) {
  asm volatile("{ .reg .pred p; setp.ne.u32 p, %2, 0; @p st.relaxed.gpu.global.u32 [%0], %1; }" :: "l"(p), "r"(v), "r"((uint32_t)on) : "memory");
}
__device__ __forceinline__ uint32_t mapa(uint32_t a, uint32_t r) {
  uint32_t d; asm volatile("mapa.shared::cluster.u32 %0, %1, %2;" : "=r"(d) : "r"(a), "r"(r)); return d;
}
__device__ __forceinline__ void st_async4(uint32_t a, uint32_t x, uint32_t y, uint32_t z, uint32_t w, uint32_t bar) {
  asm volatile("st.async.shared::cluster.mbarrier::complete_tx::bytes.v4.u32 [%0], {%1,%2,%3,%4}, [%5];"
               :: "r"(a), "r"(x), "r"(y), "r"(z), "r"(w), "r"(bar) : "memory");
}
__device__ __forceinline__ uint4 ld_poll(const void* p) {
  uint4 v;
  asm volatile("ld.volatile.global.v4.u32 {%0,%1,%2,%3}, [%4];" : "=r"(v.x), "=r"(v.y), "=r"(v.z), "=r"(v.w) : "l"(p) : "memory");
  return v;
}
__device__ __forceinline__ uint2 ld_poll2(const void* p) {
  uint2 v; asm volatile("ld.volatile.global.v2.u32 {%0,%1}, [%2];" : "=r"(v.x), "=r"(v.y) : "l"(p) : "memory"); return v;
}
__device__ __forceinline__ void st_pub2(void* p, uint32_t a, uint32_t b) {
  asm volatile("st.relaxed.gpu.global.v2.u32 [%0], {%1,%2};" :: "l"(p), "r"(a), "r"(b) : "memory");
}
__device__ __forceinline__ uint32_t ld_poll1(const void* p) {
  uint32_t v; asm volatile("ld.volatile.global.u32 %0, [%1];" : "=r"(v) : "l"(p) : "memory"); return v;
}
__device__ __forceinline__ uint32_t ld_acquire(const uint32_t* p) {
  uint32_t v; asm volatile("ld.acquire.gpu.global.u32 %0, [%1];" : "=r"(v) : "l"(p) : "memory"); return v;
}
__device__ __forceinline__ void st_pub(void* p, uint32_t v) {
  asm volatile("st.relaxed.gpu.global.u32 [%0], %1;" :: "l"(p), "r"(v) : "memory");
}
__device__ __forceinline__ uint32_t lds32(uint32_t a) {
  uint32_t v; asm volatile("ld.shared.u32 %0, [%1];" : "=r"(v) : "r"(a) : "memory"); return v;
}
__device__ __forceinline__ int race_init(void* p0, void* p1, uint32_t val) {
  int t;
  asm volatile("{ .reg .pred r; .reg .u32 a, b, u, v;\n"
               "atom.relaxed.gpu.global.exch.b32 u, [%1], %3; atom.relaxed.gpu.global.exch.b32 v, [%2], %3;\n"
               "setp.eq.u32 r, u, 0x12345; @r pmevent 1; mov.u32 a, %%clock;\n"
               "setp.eq.u32 r, v, 0x12345; @r pmevent 1; mov.u32 b, %%clock; sub.u32 %0, b, a; }" : "=r"(t) : "l"(p0), "l"(p1), "r"(val) : "memory");
  return t;
}
__device__ __forceinline__ void race_init2(void* p0, void* p1, uint32_t val) {
  asm volatile("{ .reg .pred r; .reg .u32 a, b, u, v;\n"
               "atom.relaxed.gpu.global.exch.b32 u, [%0], %2; atom.relaxed.gpu.global.exch.b32 v, [%1], %2;\n"
               "atom.relaxed.gpu.global.exch.b32 a, [%0 + 4096], %2; atom.relaxed.gpu.global.exch.b32 b, [%1 + 4096], %2;\n"
               "lop3.b32 u, u, v, a, 0x96; setp.eq.u32 r, u, 0x12345; setp.eq.and.u32 r, b, u, r; @r pmevent 1; }" :: "l"(p0), "l"(p1), "r"(val) : "memory");
}
__device__ __forceinline__ uint4 lds128(uint32_t a) {
  uint4 v; asm volatile("ld.shared.v4.u32 {%0,%1,%2,%3}, [%4];" : "=r"(v.x), "=r"(v.y), "=r"(v.z), "=r"(v.w) : "r"(a) : "memory"); return v;
}
__device__ __forceinline__ uint2 lds64(uint32_t a) {
  uint2 v; asm volatile("ld.shared.v2.u32 {%0,%1}, [%2];" : "=r"(v.x), "=r"(v.y) : "r"(a) : "memory"); return v;
}
__device__ __forceinline__ void sts128(uint32_t a, uint4 v) {
  asm volatile("st.shared.v4.u32 [%0], {%1,%2,%3,%4};" :: "r"(a), "r"(v.x), "r"(v.y), "r"(v.z), "r"(v.w) : "memory");
}
__device__ __forceinline__ void sts64(uint32_t a, uint32_t x, uint32_t y) { asm volatile("st.shared.v2.u32 [%0], {%1,%2};" :: "r"(a), "r"(x), "r"(y) : "memory"); }
__device__ __forceinline__ void sts32(uint32_t a, uint32_t x) { asm volatile("st.shared.u32 [%0], %1;" :: "r"(a), "r"(x) : "memory"); }
__device__ __forceinline__ void ldsm4t(uint32_t (&r)[4], uint32_t a) {
  asm volatile("ldmatrix.sync.aligned.m8n8.x4.trans.shared.b16 {%0,%1,%2,%3}, [%4];"
               : "=r"(r[0]), "=r"(r[1]), "=r"(r[2]), "=r"(r[3]) : "r"(a) : "memory");
}
__device__ __forceinline__ void ldsm4(uint32_t (&r)[4], uint32_t a) {
  asm volatile("ldmatrix.sync.aligned.m8n8.x4.shared.b16 {%0,%1,%2,%3}, [%4];"
               : "=r"(r[0]), "=r"(r[1]), "=r"(r[2]), "=r"(r[3]) : "r"(a) : "memory");
}
template<bool TRANS> __device__ __forceinline__ void stsm4(uint32_t a, uint32_t r0, uint32_t r1, uint32_t r2, uint32_t r3) {
  if (TRANS) asm volatile("stmatrix.sync.aligned.m8n8.x4.trans.shared.b16 [%0], {%1,%2,%3,%4};" :: "r"(a), "r"(r0), "r"(r1), "r"(r2), "r"(r3) : "memory");
  else       asm volatile("stmatrix.sync.aligned.m8n8.x4.shared.b16 [%0], {%1,%2,%3,%4};" :: "r"(a), "r"(r0), "r"(r1), "r"(r2), "r"(r3) : "memory");
}
__device__ __forceinline__ void mma16816(float (&d)[4], uint32_t a0, uint32_t a1, uint32_t a2, uint32_t a3, uint32_t b0, uint32_t b1) {
  asm volatile("mma.sync.aligned.m16n8k16.row.col.f32.bf16.bf16.f32 {%0,%1,%2,%3}, {%4,%5,%6,%7}, {%8,%9}, {%0,%1,%2,%3};"
               : "+f"(d[0]), "+f"(d[1]), "+f"(d[2]), "+f"(d[3]) : "r"(a0), "r"(a1), "r"(a2), "r"(a3), "r"(b0), "r"(b1));
}
__device__ __forceinline__ void mma1688(float (&d)[4], uint32_t a0, uint32_t a1, uint32_t b0) {
  asm volatile("mma.sync.aligned.m16n8k8.row.col.f32.bf16.bf16.f32 {%0,%1,%2,%3}, {%4,%5}, {%6}, {%0,%1,%2,%3};"
               : "+f"(d[0]), "+f"(d[1]), "+f"(d[2]), "+f"(d[3]) : "r"(a0), "r"(a1), "r"(b0));
}
__device__ __forceinline__ uint32_t pack_bf16(float lo, float hi) {
  uint32_t r; asm("cvt.rn.bf16x2.f32 %0, %1, %2;" : "=r"(r) : "f"(hi), "f"(lo)); return r;
}
__device__ __forceinline__ uint32_t add_bf16x2(uint32_t a, uint32_t b) {
  uint32_t r; asm("add.rn.bf16x2 %0, %1, %2;" : "=r"(r) : "r"(a), "r"(b)); return r;
}
__device__ __forceinline__ uint32_t umax4(uint4 v) { return max(max(v.x, v.y), max(v.z, v.w)); }
__device__ __forceinline__ uint32_t opaque(uint32_t x) { uint32_t r; asm volatile("mov.u32 %0, %1;" : "=r"(r) : "r"(x)); return r; }
template<class T> __device__ __forceinline__ void pin(T*& p) { asm volatile("" : "+l"(p)); }
__device__ __forceinline__ void pin(uint32_t& v) { asm volatile("" : "+r"(v)); }
__device__ __forceinline__ uint32_t desc_lo(uint32_t addr) { return ((addr & 0x3FFFF) >> 4) | 0x10000; }
__device__ __forceinline__ uint64_t desc128(uint32_t lo) {
  uint64_t d; asm("mov.b64 %0, {%1, %2};" : "=l"(d) : "r"(lo), "r"(0x40000040)); return d;
}
#define WG_FENCE()  asm volatile("wgmma.fence.sync.aligned;" ::: "memory")
#define WG_COMMIT() asm volatile("wgmma.commit_group.sync.aligned;" ::: "memory")
#define WG_WAIT(n)  asm volatile("wgmma.wait_group.sync.aligned " #n ";" ::: "memory")
#define FENCE_ASYNC_SMEM() asm volatile("fence.proxy.async.shared::cta;" ::: "memory")
__device__ __forceinline__ void bar_sync(int id, int n) { asm volatile("bar.sync %0, %1;" :: "r"(id), "r"(n) : "memory"); }

#define D16(c) c(d[0]), c(d[1]), c(d[2]), c(d[3]), c(d[4]), c(d[5]), c(d[6]), c(d[7]), \
               c(d[8]), c(d[9]), c(d[10]), c(d[11]), c(d[12]), c(d[13]), c(d[14]), c(d[15])
template<bool FIRST> __device__ __forceinline__ void wgmma_rs_n32(float (&d)[16], const uint32_t (&a)[4], uint64_t b) {
  if (FIRST)
    asm volatile("wgmma.mma_async.sync.aligned.m64n32k16.f32.bf16.bf16 {%0,%1,%2,%3,%4,%5,%6,%7,%8,%9,%10,%11,%12,%13,%14,%15}, {%16,%17,%18,%19}, %20, 0, 1, 1, 0;"
      : D16("=f") : "r"(a[0]), "r"(a[1]), "r"(a[2]), "r"(a[3]), "l"(b));
  else
    asm volatile("wgmma.mma_async.sync.aligned.m64n32k16.f32.bf16.bf16 {%0,%1,%2,%3,%4,%5,%6,%7,%8,%9,%10,%11,%12,%13,%14,%15}, {%16,%17,%18,%19}, %20, 1, 1, 1, 0;"
      : D16("+f") : "r"(a[0]), "r"(a[1]), "r"(a[2]), "r"(a[3]), "l"(b));
}
template<bool FIRST> __device__ __forceinline__ void wgmma_ss_n32_ta(float (&d)[16], uint64_t a, uint64_t b) {
  if (FIRST)
    asm volatile("wgmma.mma_async.sync.aligned.m64n32k16.f32.bf16.bf16 {%0,%1,%2,%3,%4,%5,%6,%7,%8,%9,%10,%11,%12,%13,%14,%15}, %16, %17, 0, 1, 1, 1, 0;"
      : D16("=f") : "l"(a), "l"(b));
  else
    asm volatile("wgmma.mma_async.sync.aligned.m64n32k16.f32.bf16.bf16 {%0,%1,%2,%3,%4,%5,%6,%7,%8,%9,%10,%11,%12,%13,%14,%15}, %16, %17, 1, 1, 1, 1, 0;"
      : D16("+f") : "l"(a), "l"(b));
}
__device__ __forceinline__ void wgmma_ss_n128_tb(float (&d)[64], uint64_t a, uint64_t b) {
  asm volatile("wgmma.mma_async.sync.aligned.m64n128k16.f32.bf16.bf16 "
    "{%0,%1,%2,%3,%4,%5,%6,%7,%8,%9,%10,%11,%12,%13,%14,%15,%16,%17,%18,%19,%20,%21,%22,%23,%24,%25,%26,%27,%28,%29,%30,%31,"
    "%32,%33,%34,%35,%36,%37,%38,%39,%40,%41,%42,%43,%44,%45,%46,%47,%48,%49,%50,%51,%52,%53,%54,%55,%56,%57,%58,%59,%60,%61,%62,%63}, "
    "%64, %65, 1, 1, 1, 0, 1;"
    : "+f"(d[0]), "+f"(d[1]), "+f"(d[2]), "+f"(d[3]), "+f"(d[4]), "+f"(d[5]), "+f"(d[6]), "+f"(d[7]),
      "+f"(d[8]), "+f"(d[9]), "+f"(d[10]), "+f"(d[11]), "+f"(d[12]), "+f"(d[13]), "+f"(d[14]), "+f"(d[15]),
      "+f"(d[16]), "+f"(d[17]), "+f"(d[18]), "+f"(d[19]), "+f"(d[20]), "+f"(d[21]), "+f"(d[22]), "+f"(d[23]),
      "+f"(d[24]), "+f"(d[25]), "+f"(d[26]), "+f"(d[27]), "+f"(d[28]), "+f"(d[29]), "+f"(d[30]), "+f"(d[31]),
      "+f"(d[32]), "+f"(d[33]), "+f"(d[34]), "+f"(d[35]), "+f"(d[36]), "+f"(d[37]), "+f"(d[38]), "+f"(d[39]),
      "+f"(d[40]), "+f"(d[41]), "+f"(d[42]), "+f"(d[43]), "+f"(d[44]), "+f"(d[45]), "+f"(d[46]), "+f"(d[47]),
      "+f"(d[48]), "+f"(d[49]), "+f"(d[50]), "+f"(d[51]), "+f"(d[52]), "+f"(d[53]), "+f"(d[54]), "+f"(d[55]),
      "+f"(d[56]), "+f"(d[57]), "+f"(d[58]), "+f"(d[59]), "+f"(d[60]), "+f"(d[61]), "+f"(d[62]), "+f"(d[63])
    : "l"(a), "l"(b));
}

__device__ __forceinline__ void tma3d_mc_e(uint32_t dst, const CUtensorMap* tm, int c1, int c2, uint32_t bar) {
  asm volatile("{ .reg .pred p; .reg .b64 h; " ONCE_H "elect.sync _|p, 0xffffffff;\n"
               "@p cp.async.bulk.tensor.3d.shared::cluster.global.mbarrier::complete_tx::bytes.multicast::cluster.L2::cache_hint [%0], [%1, {0, %3, %4}], [%2], %5, h; }"
               :: "r"(dst), "l"(tm), "r"(bar), "r"(c1), "r"(c2), "h"((uint16_t)3) : "memory");
}
__device__ __forceinline__ void prefetch3d_e(const CUtensorMap* tm, int c1, int c2) {
  asm volatile("{ .reg .pred p; elect.sync _|p, 0xffffffff;\n"
               "@p cp.async.bulk.prefetch.tensor.3d.L2.global [%0, {0, %1, %2}]; }" :: "l"(tm), "r"(c1), "r"(c2) : "memory");
}

__device__ __forceinline__ void count_e(uint32_t* p) {
  asm volatile("fence.acq_rel.gpu;" ::: "memory");
  __syncwarp();
  asm volatile("{ .reg .pred p; elect.sync _|p, 0xffffffff; @p red.relaxed.gpu.global.add.u32 [%0], 1; }" :: "l"(p) : "memory");
}
template<int NS = 0> __device__ __forceinline__ void await_count(const uint32_t* p, uint32_t n) {
  for (uint32_t i = 0; ld_acquire(p) < n && i < (1u << 22); i++) { if (NS) __nanosleep(NS); }
  asm volatile("fence.proxy.async.global;" ::: "memory");
}
__device__ __forceinline__ void await_flags(const uint32_t* p) {
  for (uint32_t i = 0; i < (1u << 22); i++) {
    uint4 v;
    asm volatile("ld.acquire.gpu.global.v4.u32 {%0,%1,%2,%3}, [%4];" : "=r"(v.x), "=r"(v.y), "=r"(v.z), "=r"(v.w) : "l"(p) : "memory");
    if (__all_sync(~0u, (v.x & v.y & v.z & v.w) == 0x01010101u)) break;
  }
  asm volatile("fence.proxy.async.global;" ::: "memory");
}
__device__ __forceinline__ void mbar_lim(uint32_t bar, uint32_t ph) { for (uint32_t i = 0; !mbar_try(bar, ph) && i < (1u << 20); i++) {} }

struct cf { float x, y; };
__host__ __device__ constexpr float cos64(int k) {
  return k == 0 ? 1.0f : k == 1 ? 0.99518472667219689f : k == 2 ? 0.98078528040323045f : k == 3 ? 0.95694033573220887f :
         k == 4 ? 0.92387953251128676f : k == 5 ? 0.88192126434835503f : k == 6 ? 0.83146961230254524f : k == 7 ? 0.77301045336273696f :
         k == 8 ? 0.70710678118654752f : k == 9 ? 0.63439328416364550f : k == 10 ? 0.55557023301960222f : k == 11 ? 0.47139673682599765f :
         k == 12 ? 0.38268343236508977f : k == 13 ? 0.29028467725446236f : k == 14 ? 0.19509032201612827f : k == 15 ? 0.09801714032956060f : 0.0f;
}
__host__ __device__ constexpr float c64(int k) { return k <= 16 ? cos64(k) : -cos64(32 - k); }
__host__ __device__ constexpr float s64(int k) { return k <= 16 ? cos64(16 - k) : cos64(k - 16); }

template<int N, int ST, bool INV> struct Fft {
  template<int K> static __device__ __forceinline__ void bf(const cf* e, const cf* o, cf* out) {
    if constexpr (K < N / 2) {
      constexpr int idx = K * (64 / N);
      const cf a = e[K], b = o[K];
      if constexpr (idx == 0) {
        out[K] = {a.x + b.x, a.y + b.y}; out[K + N / 2] = {a.x - b.x, a.y - b.y};
      } else if constexpr (idx == 16) {
        if constexpr (INV) { out[K] = {a.x - b.y, a.y + b.x}; out[K + N / 2] = {a.x + b.y, a.y - b.x}; }
        else               { out[K] = {a.x + b.y, a.y - b.x}; out[K + N / 2] = {a.x - b.y, a.y + b.x}; }
      } else {
        constexpr float c = c64(idx), s = INV ? s64(idx) : -s64(idx);
        cf p; p.x = fmaf(-s, b.y, fmaf(c, b.x, a.x)); p.y = fmaf(s, b.x, fmaf(c, b.y, a.y));
        out[K] = p; out[K + N / 2] = {fmaf(2.0f, a.x, -p.x), fmaf(2.0f, a.y, -p.y)};
      }
      bf<K + 1>(e, o, out);
    }
  }
  static __device__ __forceinline__ void run(const cf* in, cf* out) {
    cf e[N / 2], o[N / 2];
    Fft<N / 2, 2 * ST, INV>::run(in, e);
    Fft<N / 2, 2 * ST, INV>::run(in + ST, o);
    bf<0>(e, o, out);
  }
};
template<int ST, bool INV> struct Fft<1, ST, INV> {
  static __device__ __forceinline__ void run(const cf* in, cf* out) { out[0] = in[0]; }
};
template<bool INV> __device__ __forceinline__ void fft32(cf (&v)[32]) {
  cf o[32]; Fft<32, 1, INV>::run(v, o);
#pragma unroll
  for (int i = 0; i < 32; i++) v[i] = o[i];
}
__device__ __forceinline__ cf cmul(cf a, float c, float s) { return {fmaf(-a.y, s, a.x * c), fmaf(a.x, s, a.y * c)}; }
__device__ __forceinline__ float bf2f(__nv_bfloat16 v) { return __bfloat162float(v); }

__device__ __forceinline__ int tw_at(int i) { return (i & ~63) | (i & 31) << 1 | (i >> 5 & 1); }
template<bool INV, bool T128 = true> __device__ __forceinline__ void twiddles(cf (&v)[32], const float4* __restrict__ tw) {
#pragma unroll
  for (int j = 0; j < 32; j += 2) {
    float4 w;
    if (T128) w = tw[j * 16];
    else { const uint2 a = lds64(smem_u32(tw + j * 16)), b = lds64(smem_u32(tw + j * 16) + 8); w = make_float4(__uint_as_float(a.x), __uint_as_float(a.y), __uint_as_float(b.x), __uint_as_float(b.y)); }
    if (j) v[j] = cmul(v[j], w.x, INV ? -w.y : w.y);
    v[j + 1] = cmul(v[j + 1], w.z, INV ? -w.w : w.w);
  }
}
template<bool INV, class F> __device__ __forceinline__ void warp_fft1024(cf (&v)[32], float2* __restrict__ buf, const float2* __restrict__ tw, int t, int u, F mid) {
#pragma unroll 1
  for (uint32_t h = 0; h < 2; h++) {
    fft32<INV>(v);
    if (FUNR ? h : opaque(h)) continue;
    twiddles<INV>(v, (const float4*)tw + u);
    if (INV) {
      float* f = (float*)buf;
#pragma unroll
      for (int j = 0; j < 32; j++) f[j * 36 + t] = v[j].x;
      __syncwarp();
#pragma unroll
      for (int j = 0; j < 32; j += 4) { const float4 r = *(const float4*)(f + u * 36 + j); v[j].x = r.x; v[j + 1].x = r.y; v[j + 2].x = r.z; v[j + 3].x = r.w; }
      __syncwarp();
#pragma unroll
      for (int j = 0; j < 32; j++) f[j * 36 + t] = v[j].y;
      __syncwarp();
#pragma unroll
      for (int j = 0; j < 32; j += 4) { const float4 r = *(const float4*)(f + u * 36 + j); v[j].y = r.x; v[j + 1].y = r.y; v[j + 2].y = r.z; v[j + 3].y = r.w; }
    } else {
#pragma unroll
      for (int j = 0; j < 32; j++) buf[j * 33 + t] = make_float2(v[j].x, v[j].y);
      __syncwarp();
#pragma unroll
      for (int j = 0; j < 32; j++) { const float2 r = buf[u * 33 + j]; v[j] = {r.x, r.y}; }
    }
    __syncwarp();
    mid();
  }
}
constexpr int ROW_BUF = 32 * 33, INV_BUF = 32 * 18;

__device__ __forceinline__ int z_row(int p) { return (p & ~31) | (p & 7) << 2 | (p & 31) >> 3; }
__device__ __forceinline__ int inv_lane(int t) { return (t & ~14) | (t & 12) >> 1 | (t & 2) << 2; }
__device__ __forceinline__ float2 twiddle(int i) { float s, c; sincospif(-(float)((i >> 5) * (i & 31)) * (1.0f / 512.0f), &s, &c); return make_float2(c, s); }
template<class F, class G> __device__ __forceinline__ void fft_rows_fwd(float2* sm2, const __nv_bfloat16* gw, int cta, int tid, uint32_t full_bar, uint32_t release_bar, F ev, G extra) {
  const int t = tid & 31, w = tid >> 5, n = z_row(cta * 8 + w);
#pragma unroll 1
  for (int i = tid; i < 1024; i += 256) sm2[tw_at(i)] = twiddle(i);
  ev(5);
  mbar_spin(full_bar, 0);
  if (tid == 0) TL2(6);
  __syncwarp();
  const __nv_bfloat16* xa = (const __nv_bfloat16*)(sm2 + 1024 + w * ROW_BUF) + t;
  cf v[32];
  float ga = 0.f, gb = 0.f;
#pragma unroll
  for (int j = 0; j < 32; j++) {
    v[j] = {bf2f(xa[32 * j]), bf2f(xa[D_ + 32 * j])};
    const float g = bf2f(gw[32 * j + t]); ga = fmaf(v[j].x, g, ga); gb = fmaf(v[j].y, g, gb);
  }
#pragma unroll
  for (int o = 16; o; o >>= 1) { ga += __shfl_xor_sync(~0u, ga, o); gb += __shfl_xor_sync(~0u, gb, o); }
  if (t < 2) g_gate[n + 1024 * t] = __fdividef(1.0f, 1.0f + __expf(-(t ? gb : ga)));
  ev(6);
  bar_sync(13, 256);
  warp_fft1024<false>(v, sm2 + 1024 + w * ROW_BUF, sm2, t, t, [&]() { FENCE_ASYNC_SMEM(); mbar_arrive_warp(release_bar); });
  float ws, wc; sincospif(-(float)n * (1.0f / 1024.0f), &ws, &wc);
  ev(12);
  uint32_t tz = clock_lo();
  float4* z = (float4*)g_z + ((size_t)(t >> 1) * 1024 + cta * 8 + w) * 2 + (t & 1);
#pragma unroll
  for (int j = 0; j < 17; j++) {
    cf q = v[(32 - j) & 31];
    if (j < 16) {
      const cf r = {__shfl_sync(~0u, v[31 - j].x, 32 - t), __shfl_sync(~0u, v[31 - j].y, 32 - t)};
      if (t != 0) q = r;
    }
    const cf a = {v[j].x + q.x, v[j].y - q.y}, b = {v[j].y + q.y, q.x - v[j].x};
    const cf d = cmul({a.x - b.x, a.y - b.y}, wc, ws);
    if (j == POOL_AT) extra();
    if (PACE_Z && j && j < 16) delay_until(tz += PACE_Z);
    if ((j < 16 || t == 0) && ((EXP_ST & 4) || d.x == 123.f)) z[j * 32768] = make_float4(a.x + b.x, a.y + b.y, d.x, d.y);
  }
}
constexpr int CP = X128 == 0 ? 33 : X128 == 2 ? 34 : 36, COL_FS = 32 * 36 + 8, COL_W = (8192 + 16 * COL_FS * 4 + 127) & ~127, COL_SMEM = COL_W + 131072 + 128;

__device__ __forceinline__ void fft_cols(float2* sm2, int cta, const CUtensorMap* twr, const CUtensorMap* twi, const CUtensorMap* tzs) {
  const int grp = __shfl_sync(~0u, (int)(threadIdx.x >> 7), 0), tid = threadIdx.x & 127, tp = tid >> 2, w = __shfl_sync(~0u, tid >> 5, 0);
  float* buf = (float*)(sm2 + 1024) + (grp * 4 + (tid & 3)) * COL_FS;
  const uint32_t wsm = smem_u32(sm2) + COL_W, wbar = wsm + 131072 + (W_FINE ? w * 32 : 0);
  const int res = w * 2 + (tid & 1), el = res + grp * 2 + ((tid >> 1) & 1);
  uint32_t wa = (el >> 3) * 65536 + res * 4096 + (tp & 7) * 16 + (el & 7) * 2;
  auto load_w = [&](int q) {
    const uint32_t bar = wbar + (q & 1) * 8;
    mbar_expect(bar, W_FINE ? 16384 : 65536);
#pragma unroll 1
    for (int i = W_FINE ? 4 * w : 0; i < (W_FINE ? 4 * w + 4 : 16); i++) tma2d(wsm + (q & 1) * 65536 + (i & 1) * 32768 + (i >> 1) * 4096, i & 1 ? twi : twr, (i >> 1) * 512 + q * 8, 0, bar);
  };
  const bool lead = (tid & (W_FINE ? 31 : 127)) == 0, first = grp < 2 && lead;
  if (first) { mbar_init(wbar + grp * 8, 1); sts32(wbar + 16 + grp * 4, grp ? 0 : w); asm volatile("fence.mbarrier_init.release.cluster;" ::: "memory"); }
#pragma unroll 1
  for (int i = threadIdx.x; i < 1024; i += 512) {
    const float2 t = twiddle(z_row(i));
    sm2[tw_at(i)] = t;
    if (cta == 0) g_tw[tw_at(inv_lane(z_row(i)))] = t;
  }
  for (uint32_t n = 0; ld_acquire(g_ctl + C_P1) < 128; ) { watchdog(n, 1u << 22); __nanosleep(200); }
  if (COL_DLY) delay_cycles(COL_DLY);
  if (first) load_w(cta * 16 + grp);
  __syncthreads();
  delay_cycles(1 + grp * DLY_GRP);
  mbar_wait(wbar, 0);
  const int end = cta * 64 + 64 + (cta == 3);
  for (int item = cta * 64 + grp; item < end; item += 4, wa ^= 65536) {
    float2* zp = g_z + (size_t)item * 4096;
    auto next_w = [&]() {
      const int q = (item >> 2) + (W_FINE && grp + w > 3);
      uint32_t n; asm volatile("atom.shared.inc.u32 %0, [%1], 3;" : "=r"(n) : "r"(wbar + 16 + (q & 1) * 4) : "memory");
      if (EXP_W && n == 3 && q < (cta * 16 + 15)) load_w(q + 2);
    };
    cf v[32];
#pragma unroll
    for (int j = 0; j < 32; j++) { const float2 a = ld_once(zp + tid + j * 128); v[j] = {a.x, a.y}; }
#pragma unroll 1
    for (int ph = 0; ; ph++) {
      fft32<false>(v);
      twiddles<false, T128_>(v, (const float4*)sm2 + tp);
      if (Z_ST) asm volatile("cp.async.bulk.wait_group.read 0;" ::: "memory");
      bar_sync(1 + grp, 128);
      if (lead) {
        if (ph) {
          if (!W_AT) next_w();
        } else if (Z_PF && item + 4 < end) asm volatile("cp.async.bulk.prefetch.L2.global [%0], %1;" :: "l"(zp + 4 * 4096 + w * 1024), "n"(W_FINE ? 8192 : 32768) : "memory");
      }
      __syncwarp();
#pragma unroll
      for (int j = 0; j < 32; j++) buf[((j & 3) * 8 + (j >> 2)) * CP + tp] = v[j].x;
      bar_sync(1 + grp, 128);
      if (X128 == 0) {
#pragma unroll
        for (int j = 0; j < 32; j++) v[j].x = buf[tp * CP + (j & 3) * 8 + (j >> 2)];
      } else if (X128 == 2) {
#pragma unroll
        for (int j = 0; j < 16; j++) { const float2 r = *(const float2*)(buf + tp * CP + 2 * j); cf* d = v + (j & 3) * 8 + (j >> 2); d[0].x = r.x; d[4].x = r.y; }
      } else
#pragma unroll
      for (int j = 0; j < 8; j++) {
        const float4 r = *(const float4*)(buf + tp * 36 + 4 * j);
        cf* d = v + (j & 1) * 16 + (j >> 1);
        d[0].x = r.x; d[4].x = r.y; d[8].x = r.z; d[12].x = r.w;
      }
      bar_sync(1 + grp, 128);
#pragma unroll
      for (int j = 0; j < 32; j++) buf[((j & 3) * 8 + (j >> 2)) * CP + tp] = v[j].y;
      bar_sync(1 + grp, 128);
      if (X128 == 0) {
#pragma unroll
        for (int j = 0; j < 32; j++) v[j].y = buf[tp * CP + (j & 3) * 8 + (j >> 2)];
      } else if (X128 == 2) {
#pragma unroll
        for (int j = 0; j < 16; j++) { const float2 r = *(const float2*)(buf + tp * CP + 2 * j); cf* d = v + (j & 3) * 8 + (j >> 2); d[0].y = r.x; d[4].y = r.y; }
      } else
#pragma unroll
      for (int j = 0; j < 8; j++) {
        const float4 r = *(const float4*)(buf + tp * 36 + 4 * j);
        cf* d = v + (j & 1) * 16 + (j >> 1);
        d[0].y = r.x; d[4].y = r.y; d[8].y = r.z; d[12].y = r.w;
      }
      fft32<false>(v);
      if (ph) break;
      const int q = min((item >> 2) + (!W_FINE || grp + w >= 3), 64);
      if (EXP_W) mbar_wait(wbar + (q & 1) * 8, (q >> 1) & 1);
#pragma unroll
      for (int j = 0; j < 32; j++) {
        uint32_t re, im;
        asm volatile("ld.shared.u16 %0, [%1];" : "=r"(re) : "r"(wsm + wa + j * 128) : "memory");
        asm volatile("ld.shared.u16 %0, [%1];" : "=r"(im) : "r"(wsm + wa + 32768 + j * 128) : "memory");
        const cf r = cmul(v[j], __uint_as_float(re << 16), __uint_as_float(im << 16));
        v[j] = {r.y, r.x};
      }
    }
    if (Z_ST) {
      float2* st = sm2 + 1024 + grp * (COL_FS * 2) + w * 512;
      bar_sync(1 + grp, 128);
#pragma unroll
      for (int h = 0; h < 2; h++) {
        if (h && Z_ST == 2) {
#pragma unroll
          for (int j = 16; j < 32; j++) zp[tid + j * 128] = make_float2(v[j].y, v[j].x);
          break;
        }
        if (h) { asm volatile("cp.async.bulk.wait_group.read 0;" ::: "memory"); __syncwarp(); }
#pragma unroll
        for (int j = 0; j < 16; j++) st[j * 32 + (tid & 31)] = make_float2(v[h * 16 + j].y, v[h * 16 + j].x);
        FENCE_ASYNC_SMEM();
        __syncwarp();
        tma2d_st_e(tzs, w * 128, item * 32 + h * 16, smem_u32(st));
        asm volatile("cp.async.bulk.commit_group;" ::: "memory");
      }
    } else {
#pragma unroll
      for (int j = 0; j < 32; j++) zp[tid + j * 128] = make_float2(v[j].y, v[j].x);
    }
    if (W_AT) { if (lead) next_w(); __syncwarp(); }
  }
  if (Z_ST) asm volatile("cp.async.bulk.wait_group 0; fence.proxy.async.global;" ::: "memory");
  const float4 t = ((const float4*)sm2)[threadIdx.x];
  __syncthreads();
  if (TW_L) ((float4*)sm2)[inv_lane(z_row(threadIdx.x))] = t;
  if (threadIdx.x < 32) {
    count_e(g_ctl + C_COLS);
    await_count(g_ctl + C_COLS, 4);
    g_ctl[C_P1] = 0;
  }
  __syncthreads();
  if (!TW_L) {
    ((float4*)sm2)[threadIdx.x] = __ldcg((const float4*)g_tw + threadIdx.x);
    __syncthreads();
  }
}

template<class F> __device__ __forceinline__ void fft_rows_inv(uint32_t zs, float2* buf, const float2* tw, int p, int lane, __nv_bfloat16* out, F read) {
  const int n = z_row(p), t = (lane & 17) | (lane & 6) << 1 | (lane & 8) >> 2, src = inv_lane(-t & 31);
  const uint32_t z = zs + (t >> 1) * 128 + ((((p & 3) * 2 + (t & 1)) ^ (t >> 1 & 7)) << 4);
  FT(0, 0.f);
  float4 e[17];
  uint32_t all = 0;
  e[16] = __ldcg((const float4*)g_z + ((size_t)256 * 1024 + p) * 2);
  const float g0 = __ldcg(g_gate + n), g1 = __ldcg(g_gate + n + 1024);
#pragma unroll
  for (int j = 0; j < 16; j++) { const uint4 u = lds128(z + j * 2048); e[j] = make_float4(__uint_as_float(u.x), __uint_as_float(u.y), __uint_as_float(u.z), __uint_as_float(u.w)); all |= u.x; }
  sched_fence(all);
  read();
  float ws, wc; sincospif((float)n * (1.0f / 1024.0f), &ws, &wc);
  cf v[32], q[17];
#pragma unroll
  for (int j = 0; j < 17; j++) {
    const cf d = cmul({e[j].z, e[j].w}, wc, ws);
    cf a = {e[j].x + d.x, e[j].y + d.y}, b = {e[j].x - d.x, e[j].y - d.y};
    if (j == 16 || (j == 0 && t == 0)) { a.y = 0.f; b.y = 0.f; }
    if (j < 16) v[j] = {a.x - b.y, a.y + b.x};
    q[j] = {a.x + b.y, b.x - a.y};
  }
#pragma unroll
  for (int j = 16; j < 32; j++) {
    v[j] = {__shfl_sync(~0u, q[31 - j].x, src), __shfl_sync(~0u, q[31 - j].y, src)};
    if (t == 0) v[j] = q[32 - j];
  }
  FT(1, v[0].x + v[16].x + v[31].x);
  if (B_ST) { asm volatile("cp.async.bulk.wait_group.read 0;" ::: "memory"); __syncwarp(); }
  warp_fft1024<true>(v, buf, tw, t, lane, []() {});
  FT(3, v[31].y + v[0].x);
  const float sc = 0.5f / (2048.0f * 1024.0f), s0 = (1.f - g0) * sc, s1 = (1.f - g1) * sc;
  uint2* o = (B_ST ? (uint2*)buf : (uint2*)(out + (size_t)n * D_)) + (lane ^ (n & 1) << 3);
#pragma unroll
  for (int j = 0; j < 32; j += 4) {
    o[8 * j] = make_uint2(pack_bf16(v[j].x * s0, v[j + 1].x * s0), pack_bf16(v[j + 2].x * s0, v[j + 3].x * s0));
    o[(B_ST ? 256 : 256 * D_) + 8 * j] = make_uint2(pack_bf16(v[j].y * s1, v[j + 1].y * s1), pack_bf16(v[j + 2].y * s1, v[j + 3].y * s1));
  }
  if (B_ST) {
    FENCE_ASYNC_SMEM();
    __syncwarp();
    asm volatile("{ .reg .pred p; setp.lt.u32 p, %2, 2; @p cp.async.bulk.global.shared::cta.bulk_group [%0], [%1], 2048; cp.async.bulk.commit_group; }"
                 :: "l"(out + (size_t)(n + 1024 * (lane & 1)) * D_), "r"(smem_u32(buf) + (lane & 1) * 2048), "r"(lane) : "memory");
  }
  FT(4, 0.f);
}

constexpr int NP = NP_, NHV = REG_F == 216 ? 5 : 7, NV = 16 - NHV;
constexpr int XEND = NSEG;
constexpr uint32_t SM_WO = 0, SM_V = 65536, SM_LAND = SM_V + 8192, SM_MEM = SM_LAND + 24576, SM_SP = SM_MEM, SM_SPM = SM_MEM + 5120, SM_OM = SM_MEM + 6144,
                   SM_OX = SM_MEM + 8192, SM_RED = SM_OX + 2048, SM_XCH = SM_RED + 1024, SM_SUM = SM_XCH + 4096, SM_VM = SM_SUM + 128, SM_TAB = SM_VM + 2048, SM_TRACE = SM_TAB + 2048, SM_K = SM_TRACE,
                   ST_WG = (32 - NP + NV) * 2048,
                   SM_XT = 2 * ST_WG, SM_POOL = SM_XT + 32768, SM_HV = SM_POOL + 2 * NP * 2048,
                   SM_BAR = SM_HV + 2 * NHV * 2048, SM_SEL = SM_BAR + 320, SM_Q = SM_SEL + 576, CHAIN_SMEM = SM_Q + (Q_TMA ? 2048 : 1024);
constexpr uint32_t SM_FFT = 49152, SM_GW = SM_XT - 2048;
static_assert(NP % 4 == 0 && NV == 11 && SM_TRACE + 8192 <= SM_XT, "shared memory layout");
static_assert(CHAIN_SMEM <= 232448 && COL_SMEM <= SM_BAR && SM_FFT + (1024 + 8 * ROW_BUF) * 8 <= SM_GW && NP == 12, "shared memory budget");
enum { B_WFULL = 0, B_WREAD = 2, B_WOFULL, B_XFULL, B_XEMPTY, B_E1TRIG, B_E2TRIG, B_PVDONE, B_PUB, B_SC, B_PFULL, B_SPFREE,
       B_LAND, B_LFREE, B_DONE, B_SEL, B_PROBE, B_FREE, B_P1, B_ROWS, B_VFULL, B_VST, B_TW, B_BT, B_WREAD0, B_Z, B_GFULL = B_Z + 4, B_GEMPTY = B_GFULL + 5, B_END = B_GEMPTY + 5 };
static_assert(B_END * 8 <= 320, "barriers");
__host__ __device__ constexpr uint32_t bar_codes(int g) {
  uint32_t r = 0;
  for (int i = 16 * g; i < 16 * g + 16; i++)
    r |= (i == B_LAND ? 3u : i == B_WREAD || i == B_XEMPTY || i == B_E1TRIG || i == B_E2TRIG || i == B_LFREE || i == B_FREE || i == B_VST || i == B_P1 || i == B_ROWS ? 2u :
          i >= B_GEMPTY || i == B_WREAD0 || i == B_PROBE || i == B_DONE || i == B_PVDONE || i == B_PUB || i == B_SC || i == B_SPFREE ? 1u : 0u) << 2 * (i & 15);
  return r;
}
constexpr uint32_t SM_BT = 65536, SM_TW = SM_XT - 8192, COL_Z = 80 * 1024;
static_assert(SM_XT + 3 * 32768 <= SM_BAR && SM_BT + 32768 <= SM_MEM && SM_TRACE <= SM_TW && SM_MEM + 4 * INV_BUF * 8 <= SM_TRACE &&
              8192 + 16 * INV_BUF * 8 <= COL_Z && COL_Z + 131072 <= SM_BAR, "shared memory layout");
__device__ __forceinline__ uint32_t next_stage(uint32_t o) { return o == SM_XT + 65536 ? 0 : o == 32768 ? SM_XT : o + 32768; }

struct ChainCtx { char* mail; uint32_t sb, sel; int r, h, a, b, j, m, w, lane; };
#define BAR(i) (c.sb + SM_BAR + 8 * (i))

__device__ __forceinline__ uint32_t tile_off(int line, int lane) {
  return line * 128 + (((lane & 3) ^ line) << 5) + (lane >> 2) * 4;
}
__device__ __forceinline__ uint32_t read_off(int lane) {
  const int n = lane >> 2, jj = lane & 3, l = 2 * (jj >> 1) + (n & 1);
  return l * 128 + (((n >> 1) ^ l) << 5) + (jj & 1) * 16;
}
__device__ __forceinline__ uint32_t frag_off(int w, int lane) {
  const int mi = lane >> 3, r = lane & 7;
  return ((mi >> 1) * 8 + r) * 128 + (((2 * w + (mi & 1)) ^ r) << 4);
}
__device__ __forceinline__ uint32_t land_off(int w, int lane) { return w * 512 + ((lane ^ (((lane >> 4) | ((w & 1) << 1)) << 1)) << 4); }
__device__ __forceinline__ uint32_t tagged(uint32_t v, uint32_t tag) { return (v | 1u) ^ tag; }
__device__ __forceinline__ void mma_a(float (&d)[4], const uint32_t (&a)[4], uint32_t b0, uint32_t b1) { mma16816(d, a[0], a[1], a[2], a[3], b0, b1); }
__device__ __forceinline__ void mma_q(float (&d)[4], const uint4& a, uint32_t b0, uint32_t b1) { mma16816(d, a.x, a.y, a.z, a.w, b0, b1); }
__device__ __forceinline__ uint4 add4(uint4 a, uint4 b) {
  return make_uint4(add_bf16x2(a.x, b.x), add_bf16x2(a.y, b.y), add_bf16x2(a.z, b.z), add_bf16x2(a.w, b.w));
}
__device__ __forceinline__ void mbar_arrive_both(uint32_t bar, int peer) {
  __syncwarp();
  asm volatile("{ .reg .pred p; .reg .u32 a; mapa.shared::cluster.u32 a, %0, %1; elect.sync _|p, 0xffffffff;\n"
               "@p mbarrier.arrive.shared::cta.b64 _, [%0]; @p mbarrier.arrive.shared::cluster.b64 _, [a]; }" :: "r"(bar), "r"(peer) : "memory");
}

__device__ __forceinline__ void arrive_remote_if(uint32_t a, bool on) {
  asm volatile("{ .reg .pred p; setp.ne.u32 p, %1, 0; @p mbarrier.arrive.shared::cluster.b64 _, [%0]; }" :: "r"(a), "r"((uint32_t)on) : "memory");
}
__device__ __forceinline__ void store_count(void* p, uint4 v, void* cnt) {
  asm volatile("{ .reg .pred p, q; .reg .b128 a, b; .reg .b64 l, h; mov.b64 l, {%1, %2}; mov.b64 h, {%3, %4}; mov.b128 a, {l, h};\n"
               "atom.relaxed.gpu.global.exch.b128 b, [%0], a; mov.b128 {l, h}, b; setp.eq.u64 q, l, 0x7fc17fc17fc17fc1; @q pmevent 1;\n"
               "elect.sync _|p, 0xffffffff; @p red.relaxed.gpu.global.add.u32 [%5], 1; }"
               :: "l"(p), "r"(v.x), "r"(v.y), "r"(v.z), "r"(v.w), "l"(cnt) : "memory");
}

template<int N> __device__ __forceinline__ void pad() {
#pragma unroll
  for (int i = 0; i < N; i++) asm volatile("pmevent 3;");
}
__device__ __forceinline__ int lane_id() {
  int l; asm volatile("{ .reg .u32 t; mov.u32 t, %%laneid; shfl.sync.idx.b32 %0, t, t, 31, 0xffffffff; }" : "=r"(l)); return l;
}
__device__ __forceinline__ uint32_t tid_now() { uint32_t t; asm volatile("mov.u32 %0, %%tid.x;" : "=r"(t)); return t; }
enum { NB_ATT = 1, NB_OM = 2, NB_VM = 3, NB_XCH = 4, NB_MEM = 8, NB_HELP = 12 };
__device__ __forceinline__ uint32_t dep(uint32_t a, uint32_t v, uint32_t z) { uint32_t r; asm("shf.l.wrap.b32 %0, %2, %1, %3;" : "=r"(r) : "r"(a), "r"(v), "r"(z)); return r; }
__device__ __forceinline__ uint32_t vary(uint32_t a, int s, uint32_t z) { return dep(a, 0, z + 32 * s); }
__device__ __forceinline__ char* mk_ptr(uint32_t lo, uint32_t hi) { uint64_t r; asm("mov.b64 %0, {%1, %2};" : "=l"(r) : "r"(lo), "r"(hi)); return (char*)r; }
__device__ __forceinline__ void lds_frag(uint32_t (&r)[4], uint32_t a) {
  asm volatile("ld.shared.v4.u32 {%0,%1,%2,%3}, [%4];" : "=r"(r[0]), "=r"(r[1]), "=r"(r[2]), "=r"(r[3]) : "r"(a) : "memory");
}
__device__ __forceinline__ uint32_t stale2(uint32_t a, uint32_t b, uint32_t t) { uint32_t r; asm("lop3.b32 %0, %1, %2, %3, 0xbd;" : "=r"(r) : "r"(a), "r"(b), "r"(t)); return r; }
__device__ __forceinline__ uint32_t stale1(uint32_t acc, uint32_t a, uint32_t t) { uint32_t r; asm("lop3.b32 %0, %1, %2, %3, 0xf9;" : "=r"(r) : "r"(acc), "r"(a), "r"(t)); return r; }
__device__ __forceinline__ bool all_clear(uint32_t x, uint32_t m) {
  uint32_t r;
  asm volatile("{ .reg .pred p; .reg .u32 t; and.b32 t, %1, %2; setp.eq.u32 p, t, 0; vote.sync.all.pred p, p, 0xffffffff; selp.u32 %0, 1, 0, p; }" : "=r"(r) : "r"(x), "r"(m));
  return r;
}
__device__ __forceinline__ bool arrive_if_all(bool ok, int id, int n) {
  uint32_t r;
  asm volatile("{ .reg .pred p, q; setp.ne.u32 p, %1, 0; vote.sync.all.pred q, p, 0xffffffff; @q bar.arrive %2, %3; selp.u32 %0, 1, 0, q; }"
               : "=r"(r) : "r"((uint32_t)ok), "r"(id), "r"(n) : "memory");
  return r;
}
__device__ __forceinline__ bool arrive_if_clear(uint32_t x, uint32_t m, int id, int n) {
  uint32_t r;
  asm volatile("{ .reg .pred p; .reg .u32 t; and.b32 t, %1, %2; setp.eq.u32 p, t, 0; vote.sync.all.pred p, p, 0xffffffff; @p bar.arrive %3, %4; selp.u32 %0, 1, 0, p; }"
               : "=r"(r) : "r"(x), "r"(m), "r"(id), "r"(n) : "memory");
  return r;
}
__device__ __forceinline__ void touch(const void* p, uint32_t z) {
  asm volatile("{ .reg .pred p; setp.eq.u32 p, %1, 0x7fff0000; @p prefetch.global.L2 [%0]; }" :: "l"(p), "r"(z) : "memory");
}

__device__ __forceinline__ uint64_t desc_x(uint32_t lo, int k) {
  uint64_t d; asm("mov.b64 %0, {%1, %2};" : "=l"(d) : "r"(lo + (k >> 2) * 64 + (k & 3) * 2), "r"(0x40000200)); return d;
}
template<int K0, int K1> __device__ __forceinline__ void issue_qk(float (&xa)[16], const uint32_t (&wt)[16][4], uint32_t lo) {
  WG_FENCE();
#pragma unroll
  for (int k = K0; k < K1; k++) {
    if (k >= EXP_NWG) continue;
    if (k == 0) wgmma_rs_n32<true>(xa, wt[0], desc_x(lo, 0));
    else wgmma_rs_n32<false>(xa, wt[k], desc_x(lo, k));
  }
  WG_COMMIT();
}
__host__ __device__ constexpr int v_order(int i) { return SSPOS == 0 ? i : SSPOS == 2 ? (i + NV) % 16 : NHV == 5 ? (i % 3 == 2 ? NV + i / 3 : i - i / 3) : (i == 15 ? NV - 1 : i % 2 ? NV + i / 2 : i / 2); }
__device__ __forceinline__ void issue_v(float (&xa)[16], const uint32_t (&wv)[16][4], uint32_t lo, uint32_t la) {
  WG_FENCE();
#pragma unroll
  for (int i = 0; i < EXP_NWG; i++) {
    const int k = v_order(i);
    const uint64_t b = desc_x(lo, k);
    if (k < NV) { if (i == 0) wgmma_rs_n32<true>(xa, wv[k], b); else wgmma_rs_n32<false>(xa, wv[k], b); }
    else        { if (i == 0) wgmma_ss_n32_ta<true>(xa, desc128(la + (k - NV) * 128), b); else wgmma_ss_n32_ta<false>(xa, desc128(la + (k - NV) * 128), b); }
  }
  WG_COMMIT();
}
template<bool ISV> __device__ __forceinline__ void park_own(uint32_t (&q)[4], float (&xa)[16], uint32_t dst, int slot, uint32_t z) {
  uint32_t p[8];
#pragma unroll
  for (int i = 0; i < 16; i++) asm volatile("" : "+f"(xa[i]) :: "memory");
#pragma unroll
  for (int i = 0; i < 2; i++) {
    const float* k = xa + 8 * i;
    if (ISV) { p[4 * i] = pack_bf16(k[0], k[1]); p[4 * i + 1] = pack_bf16(k[2], k[3]); p[4 * i + 2] = pack_bf16(k[4], k[5]); p[4 * i + 3] = pack_bf16(k[6], k[7]); }
    else     { p[4 * i] = pack_bf16(k[0], k[2]); p[4 * i + 1] = pack_bf16(k[1], k[3]); p[4 * i + 2] = pack_bf16(k[4], k[6]); p[4 * i + 3] = pack_bf16(k[5], k[7]); }
  }
  sts128(dep(dep(dst, p[4] ^ p[5] ^ p[6], z), p[7], z) + slot * 8192, make_uint4(p[0], p[1], p[2], p[3]));
#pragma unroll
  for (int i = 0; i < 4; i++) q[i] = p[4 + i];
}
__device__ __forceinline__ void park_peer(const uint32_t (&q)[4], uint32_t dst, int slot, const ChainCtx& c) {
  const uint32_t bar = BAR(B_LAND);
  if (EXP_PEER) st_async4(mapa(dst + slot * 8192, c.b ^ 1), q[0], q[1], q[2], q[3], mapa(bar, c.b ^ 1));
  else touch((void*)(uintptr_t)(q[0] ^ q[1] ^ q[2] ^ q[3]), c.sb);
  mbar_arrive_warp(bar);
}
__device__ __forceinline__ uint32_t put_tag(uint32_t v, uint32_t bit, uint32_t t) {
  uint32_t r; asm("lop3.b32 %0, %1, %2, %3, 0x74;" : "=r"(r) : "r"(v), "r"(bit), "r"(t)); return r;
}
__device__ __forceinline__ void mem_proj(const uint32_t (&wa)[16][4], const uint32_t (&wb)[16][4], uint32_t (&wv)[16][4], uint32_t (&af)[16][4],
                                         uint32_t& wo, const char*& pa, uint32_t tab, uint32_t t16, uint32_t pk, const ChainCtx& c, int s) {
  const uint32_t mp = t16 & ~0x600u, id = NB_MEM + (t16 >> 11);
  uint32_t r[8][4];
  float la[4][4] = {}, lg[NLAG][4] = {}, lv[4][4] = {};
  auto lead = [&](int k) { mma_a(la[k & 3], wa[k], r[k >> 1][2 * (k & 1)], r[k >> 1][2 * (k & 1) + 1]); };
  auto lag = [&](int k) { mma_a(lg[k % NLAG], wb[k], r[k >> 1][2 * (k & 1)], r[k >> 1][2 * (k & 1) + 1]); };
  auto sum = [](const float (&d)[4][4], int i) { return (d[0][i] + d[1][i]) + (d[2][i] + d[3][i]); };
  bar_sync(id, 160);
  TR(s, 0);
#pragma unroll
  for (int i = 0; i < 4; i++) ldsm4t(r[i], mp + (c.sb + SM_MEM + i * 512));
  uint4 tq;
  if (!TQ_AT) tq = lds128(tab);
  bar_sync(id + 2, 160);
  uint32_t first = 0;
#pragma unroll
  for (int k = 0; k < 8; k++) { lead(k); if (k == C1_AT - 4) first = dep(mp, __float_as_uint(la[k & 3][0]), c.sb); }
  uint32_t ta, tb;
  if (!TQ_AT) { ta = tq.x | ((pk >> 16) & 511); tb = tq.z ^ ((pk >> 16) & 511); }
  const uint32_t mp1 = C1_AT >= 4 ? (TQ_AT ? first : dep(first, ta ^ tb, c.sb)) : dep(mp, __float_as_uint(la[C1_AT & 3][0]) ^ (TQ_AT ? 0 : ta ^ tb), c.sb);
#pragma unroll
  for (int i = 4; i < 8; i++) ldsm4t(r[i], mp1 + (c.sb + SM_MEM + 2048 + i * 512));
  if (TQ_AT) { tq = lds128(tab); ta = tq.x | ((pk >> 16) & 511); tb = tq.z ^ ((pk >> 16) & 511); }
  char* dst = mk_ptr(ta, tq.y);
  char* dst2 = mk_ptr(tb, tq.w);
  const uint32_t hv = pk & 0xFFFF;
#pragma unroll
  for (int k = NV; k < NV + HV_E; k++) ldsm4t(wv[k], dep(hv, r[HV_R][0], c.sb) + (c.sb + SM_HV + (k - NV) * 2048));
#pragma unroll
  for (int k = 0; k < LAG_0; k++) lag(k);
#pragma unroll
  for (int k = 8; k < 16; k++) lead(k);
  const uint32_t s0 = __float_as_uint(sum(la, 0)), s3 = __float_as_uint(sum(la, 3));
  sts128((HV_E ? dep(t16, wv[NV][0] ^ wv[NV + HV_E / 2][1] ^ wv[NV + HV_E - (HV_E > 0)][2], c.sb) : TQ_AT ? dep(t16, ta ^ tb, c.sb) : t16) + (c.sb + SM_XCH),
         make_uint4(s0, __float_as_uint(sum(la, 1)), __float_as_uint(sum(la, 2)), s3));
  if (XB) bar_sync(NB_XCH, 256); else bar_sync(NB_XCH | ((t16 >> 9) & 3), 64);
#pragma unroll
  for (int k = LAG_0; k < LAG_0 + LAG_G; k++) r[k >> 1][2 * (k & 1)] = dep(r[k >> 1][2 * (k & 1)], LAG_S == 0 ? s3 : __float_as_uint(la[LAG_S - 1][0]), c.sb);
#pragma unroll
  for (int k = LAG_0; k < O_AT; k++) lag(k);
  const uint4 o = lds128((O_AT > LAG_0 ? dep(t16 ^ 2048, __float_as_uint(lg[(O_AT - 1) % NLAG][0]), c.sb) : t16 ^ 2048) + (c.sb + SM_XCH));
#pragma unroll
  for (int k = O_AT > LAG_0 ? O_AT : LAG_0; k < 16; k++) lag(k);
#pragma unroll
  for (int k = 0; k < V_E; k++) mma_a(lv[k & 3], wv[k], r[k >> 1][2 * (k & 1)], r[k >> 1][2 * (k & 1) + 1]);
  float t[4];
#pragma unroll
  for (int i = 0; i < 4; i++) {
    const float oi = __uint_as_float(i == 0 ? o.x : i == 1 ? o.y : i == 2 ? o.z : o.w);
    t[i] = NLAG == 4 ? (LAG_T ? ((lg[0][i] + lg[1][i]) + oi) + (lg[2 % NLAG][i] + lg[3 % NLAG][i]) : (((lg[0][i] + lg[1][i]) + lg[2 % NLAG][i]) + lg[3 % NLAG][i]) + oi) : LAG_T && NLAG == 2 ? (lg[0][i] + lg[1][i]) + oi : NLAG == 3 ? (lg[1][i] + lg[2 % NLAG][i]) + (lg[0][i] + oi) : (lg[0][i] + oi) + lg[1][i];
  }
  const uint32_t y0 = put_tag(pack_bf16(t[0], t[2]), pk >> 31, s >> 1), y1 = put_tag(pack_bf16(t[1], t[3]), pk >> 31, s >> 1);
  st_pub(dst, y0); st_pub(dst2, y1);
  mbar_arrive_warp(BAR(B_E1TRIG));
  TR(s, 1);
  sched_fence(c.sb);
  const uint4 tv = lds128(tab + 16);
#pragma unroll
  for (int k = NV + HV_E; k < 16; k++) ldsm4t(wv[k], (k < NV + HV_E + HV_D ? hv : dep(hv, k == NV + HV_E + HV_D ? wv[k - HV_D][0] ^ tv.x : wv[k - HV_D][0], c.sb)) + (c.sb + SM_HV + (k - NV) * 2048));
  wo = (hv & 2047) | ((t16 & 2048) << 3);
  const uint32_t l8 = (t16 >> 1) & 255;
  char* dv = mk_ptr(tv.x | l8, tv.y);
  pa = mk_ptr(tv.z | l8, tv.w);
#pragma unroll
  for (int f = 0; f < WO_0; f++) ldsm4t(af[f], dep(wo, f < WO_D ? wv[16 - WO_D + f][0] : af[f < WO_D ? 0 : f - WO_D][0], c.sb) + (c.sb + SM_WO + (f & 1) * 32768 + (f >> 1) * 2048));
#pragma unroll
  for (int k = V_E; k < 16; k++) mma_a(lv[k & 3], wv[k], r[k >> 1][2 * (k & 1)], r[k >> 1][2 * (k & 1) + 1]);
  const uint32_t z0 = put_tag(pack_bf16(sum(lv, 0), sum(lv, 1)), (~t16 >> 4) & 1, s >> 1), z1 = pack_bf16(sum(lv, 2), sum(lv, 3));
  st_pub2(dv, z0, z1);
  if (FIN_AT >= 3) mbar_arrive_warp(BAR(B_VST));
  TR(s, 2);
}
__device__ __forceinline__ uint32_t max_bf16x2(uint32_t a, uint32_t b) { uint32_t r; asm("max.bf16x2 %0, %1, %2;" : "=r"(r) : "r"(a), "r"(b)); return r; }
constexpr float SCL = 0.08838834764831845f * 1.4426950408889634f;
__device__ __forceinline__ uint32_t max5(const uint32_t (&sc)[5]) { return max_bf16x2(max_bf16x2(max_bf16x2(max_bf16x2(sc[0], sc[1]), sc[2]), sc[3]), sc[4]); }
__device__ __forceinline__ float row_off(uint32_t m, uint32_t& m1) {
  m1 = __shfl_xor_sync(~0u, m, 1);
  const uint32_t m2 = __shfl_xor_sync(~0u, m, 2), m3 = __shfl_xor_sync(~0u, m, 3);
  const uint32_t mm = max_bf16x2(max_bf16x2(max_bf16x2(m, m1), m2), m3);
  return -SCL * fmaxf(__uint_as_float(mm << 16), __uint_as_float(mm & 0xFFFF0000u));
}
__device__ __forceinline__ void unpack(float (&f)[10], const uint32_t (&sc)[5]) {
#pragma unroll
  for (int i = 0; i < 5; i++) {
    asm volatile("shl.b32 %0, %1, 16;" : "=f"(f[2 * i]) : "r"(sc[i]));
    asm volatile("and.b32 %0, %1, 0xffff0000;" : "=f"(f[2 * i + 1]) : "r"(sc[i]));
  }
}
__device__ __forceinline__ uint32_t exp_pair(const float (&f)[10], int i, float off) {
  return pack_bf16(ex2(fmaf(f[2 * i], SCL, off)), ex2(fmaf(f[2 * i + 1], SCL, off)));
}
template<bool SPLIT> __device__ __forceinline__ void scores_x(float (&a)[2][4], const uint4 (&kf)[4], const uint4& q, uint32_t z) {
#pragma unroll
  for (int t = 0; t < 2; t++) { a[t][0] = a[t][1] = a[t][2] = a[t][3] = 0.f; }
  mma_q(a[0], kf[0], q.x, q.y); mma_q(a[1], kf[2], q.x, q.y);
  if (SPLIT) sched_fence(z);
  mma_q(a[0], kf[1], q.z, q.w); mma_q(a[1], kf[3], q.z, q.w);
}
__device__ __forceinline__ uint32_t scores_m(const uint4& q, const uint4& k) {
  float a[4] = {}, b[4] = {};
  mma_q(a, q, k.x, k.z); mma_q(b, q, k.y, k.w);
  return pack_bf16(a[0] + b[2], a[1] + b[3]);
}
__device__ __forceinline__ void store_scores(const float (&a)[2][4], uint32_t dst) {
  sts64(dst, pack_bf16(a[0][0], a[0][2]), pack_bf16(a[1][0], a[1][2]));
  sts64(dst + 320, pack_bf16(a[0][1], a[0][3]), pack_bf16(a[1][1], a[1][3]));
}
__device__ __forceinline__ uint32_t sum4(uint32_t a, uint32_t b, uint32_t d, uint32_t e) { return add_bf16x2(add_bf16x2(a, b), add_bf16x2(d, e)); }
__device__ __forceinline__ void load_scores(uint32_t (&sc)[5], uint32_t ax, uint32_t am) {
  uint4 p[4];
#pragma unroll
  for (int i = 0; i < 4; i++) p[i] = lds128(ax + i * 1280);
  const uint2 m0 = lds64(am), m1 = lds64(am + 256);
  const uint4 t = add4(add4(add4(p[0], p[1]), p[2]), p[3]);
  sc[1] = t.x; sc[2] = t.y; sc[3] = t.z; sc[4] = t.w;
  sc[0] = sum4(m0.x, m0.y, m1.x, m1.y);
}
constexpr uint32_t ONES = 0x3F803F80u;
__device__ __forceinline__ float pv(float (&o)[2][4], const uint32_t (&p)[5], const uint4 (&vf)[4], const uint4& vm) {
  float a[4] = {}, b[4] = {};
#pragma unroll
  for (int t = 0; t < 2; t++) { o[t][0] = o[t][1] = o[t][2] = o[t][3] = 0.f; }
  mma_q(o[0], vf[0], p[1], p[2]); mma_q(o[1], vf[2], p[1], p[2]);
  mma_q(o[0], vf[1], p[3], p[4]); mma_q(o[1], vf[3], p[3], p[4]);
  mma16816(a, p[1], p[2], p[3], p[4], ONES, ONES);
  mma1688(o[0], vm.x, vm.y, p[0]); mma1688(o[1], vm.z, vm.w, p[0]);
  mma1688(b, p[0], ONES, ONES);
  return (a[0] + a[2]) + b[0];
}
constexpr uint32_t POLL_LIMIT = 1u << 21;
__device__ __forceinline__ uint32_t box(int slot, int cta) { return (slot * 2 + (cta >> 6)) * M_REG + (cta & 63) * 16384; }
__device__ __forceinline__ uint32_t near_page(const ChainCtx& c, int cta, uint32_t off) {
  return off + (((lds32(c.sb + SM_SEL + cta * 4) >> (off >> 21)) ^ __popc(off & 0xB2000)) & 1) * 4096;
}
__device__ __forceinline__ uint32_t e1_box(const ChainCtx& c, int slot, int cta) { return near_page(c, E1OFF ? cta ^ 2 : cta, box(slot, cta) + 8192) ^ (E1OFF ? 0 : 4096); }
__device__ __forceinline__ uint32_t tile_key() {
  uint32_t sm; asm volatile("mov.u32 %0, %%smid;" : "=r"(sm));
  return (sm < 64 ? sm / 2 % 8 : sm < 120 ? 1 + (sm / 2 - 32) % 7 : 0) << 24 | sm << 16;
}
__device__ __forceinline__ uint32_t ox_at(int s, int row, int g, int jj) { return s * 131072 + ((g >> 1) * 32 + row) * 64 + (g & 1) * 32 + 8 * jj; }
__device__ __forceinline__ int tile_of(const ChainCtx& c) { return SIDE ? __shfl_sync(~0u, lds32(c.sb + SM_SEL + 528), 0) : c.r; }

__global__ void __cluster_dims__(2, 1, 1) __launch_bounds__(512, 1)
chain_kernel(const __grid_constant__ CUtensorMap tq, const __grid_constant__ CUtensorMap tk, const __grid_constant__ CUtensorMap tv,
             const __grid_constant__ CUtensorMap tv16, const __grid_constant__ CUtensorMap to, const __grid_constant__ CUtensorMap tx,
             const __grid_constant__ CUtensorMap twr, const __grid_constant__ CUtensorMap twi,
             const __grid_constant__ CUtensorMap ta, const __grid_constant__ CUtensorMap tw,
             const __grid_constant__ CUtensorMap tb, const __grid_constant__ CUtensorMap tout, const __grid_constant__ CUtensorMap tz,
             const __grid_constant__ CUtensorMap tzs, const __grid_constant__ CUtensorMap ta32,
             const __nv_bfloat16* __restrict__ mem0, char* __restrict__ mail, const __nv_bfloat16* __restrict__ x,
             const __nv_bfloat16* __restrict__ gw) {
  extern __shared__ __align__(1024) unsigned char smraw[];
  if (threadIdx.x == 0) TL(0);
  ChainCtx c;
  c.sb = __shfl_sync(~0u, smem_u32(smraw), 0);
  c.mail = mail; c.sel = 0; c.r = blockIdx.x;
  if (ROLE) {
    const uint32_t u = blockIdx.x >> 1, n = u < 36 ? 8 : 7, k = u - (u < 36 ? 4 : 36), q = k * (u < 36 ? 32 : 37) >> 8;
    c.r = __shfl_sync(~0u, 2 * (u - 4 < 60 ? u + k - q * n - (q & 1) * (n - 1) : u) + (blockIdx.x & 1) + (threadIdx.x >> 9), 0);
  }
  c.h = c.r >> 2; c.a = (c.r >> 1) & 1; c.b = c.r & 1; c.j = c.r & 3;
  c.m = __shfl_sync(~0u, (int)(threadIdx.x >> 7), 0); c.w = __shfl_sync(~0u, (int)((threadIdx.x >> 5) & 3), 0);
  char* own = c.mail + (uint32_t)(c.w * M_REG + M_E3 + (c.r >> 5) * 8192 + (c.r & 31) * 128 + (threadIdx.x & 31) * 4);
  uint32_t i0 = 0, i1 = 0;
  if (EARLY) asm volatile("{ .reg .pred p; setp.ne.u32 p, %4, 0; @p atom.relaxed.gpu.global.exch.b32 %0, [%2], %3; @p atom.relaxed.gpu.global.exch.b32 %1, [%2 + 4096], %3; }"
               : "+r"(i0), "+r"(i1) : "l"(own), "r"(SENT), "r"((uint32_t)(c.m == 2 && c.r < 128)) : "memory");
#pragma unroll
  for (int g = 0; g < 3; g++) {
    const int i = c.m * 4 + c.w;
    if (g < 2 || i < B_END - 32)
      asm volatile("{ .reg .pred p; elect.sync _|p, 0xffffffff; @p mbarrier.init.shared::cta.b64 [%0], %1; }"
                   :: "r"(BAR(g * 16 + i)), "r"(0x19080401u >> (bar_codes(g) >> 2 * i & 3) * 8 & 255) : "memory");
  }
  asm volatile("fence.mbarrier_init.release.cluster;" ::: "memory");
  __syncthreads();
  asm volatile("barrier.cluster.arrive.relaxed.aligned;" ::: "memory");

  if (c.r >= 128) {
    fft_cols((float2*)smraw, c.r - 128, &twr, &twi, &tzs);
    if ((threadIdx.x & 127) == 0) TL(7);
    __syncwarp();
  } else if (c.m == 3) {
    asm volatile("setmaxnreg.dec.sync.aligned.u32 %0;" :: "n"(REG_H));
    c.lane = lane_id();
    if (c.sb & 1023) asm volatile("trap;");
    const int col = c.h * 128 + c.a * 64, eq = E3M ? c.w & 1 : c.w >> 1, eh = E3M == 1 ? (c.w >> 1) ^ 1 : E3M ? c.w >> 1 : c.w & 1;
    uint32_t tl = clock_lo();
    TR(-2, 3);
    if (c.w == 0) {
      if (START) delay_until(tl + START);
      if (HOLD == 2) mbar_wait(BAR(B_PROBE), 0);
      if (HOLD == 3) mbar_wait(BAR(B_SEL), 0);
      if (HOLD == 1) mbar_wait(BAR(B_PROBE), 0);
      TR(-2, 4);
      tl = clock_lo();
      mbar_expect_e(BAR(B_PFULL), 2 * NP * 2048);
      mbar_expect_e(BAR(B_WFULL), (48 - NP) * 2048);
      mbar_expect_e(BAR(B_WFULL + 1), (48 - NP) * 2048);
    }
    auto dst_x = [&](int e, int w) {
      const uint32_t g2 = 2 * c.a + (w >> 1), u = w & 1;
      return M_KVQ + c.h * 24576 + (e == 0 ? 8192 + (2 * u + c.b) * 2048 + g2 * 512 : e == 1 ? g2 * 2048 + u * 1024 + c.b * 128 : 16384 + c.b * 4096 + g2 * 512 + u * 256);
    };
    if (c.w == 0) {
      tl += PACE0;
#pragma unroll wunr
      for (int i = 0; i < 24; i++) {
        const int m = i < 4 || i >= 16, k = i < 4 ? i : m ? i - 12 : i - 4;
        const int row = c.b * 512 + m * 256;
        const uint32_t st = c.sb + m * ST_WG, bar = BAR(k < 3 ? B_PFULL : B_WFULL + m);
        if (PACE) delay_until(tl += PACE);
        if (i == 14) { mbar_idle(BAR(B_FREE), 0); if (c.lane == 0) TL2(2); __syncwarp(); }
        if (k < 11) TMA_W(k < 3 ? c.sb + SM_POOL + m * NP * 2048 + k * 8192 : k == 3 ? c.sb + SM_HV + (m * NHV + 1) * 2048 : st + (k - 4) * 8192,
                          k == 3 || k > 8 ? &tv : (k >> 2 & 1) == m ? &tk : &tq, col, row + (k < 8 ? k & 3 : (k - 9) & 3) * 64, bar);
        else {
#pragma unroll 1
          for (int j = 8; j < 12; j++) TMA_W(j < NV ? st + (32 - NP + j) * 2048 : c.sb + SM_HV + m * NHV * 2048, &tv16, col, row + j * 16, bar);
        }
      }
      TR(-2, 7);
    } else if (c.w == 2) {
      const unsigned short* mp = (const unsigned short*)mem0 + (2 * (c.lane & 3)) * D_ + 8 * c.r + (c.lane >> 2);
      uint32_t mv = (uint32_t)mp[0] | (uint32_t)mp[D_] << 16;
      if (mv == SENT) mv = 0x7FFF7FFFu;
      mbar_idle(BAR(B_PROBE), 0);
      char* dst = c.mail + (uint32_t)(M_E3 + (c.r >> 5) * 8192 + (c.r & 31) * 128 + c.lane * 4);
      st_pub(dst, mv); st_pub(dst + 4096, mv);
    } else if (c.w == 3) {
      mbar_idle(BAR(B_FREE), 0);
      mbar_idle(BAR(B_PFULL), 0);
      mbar_expect_e(BAR(B_PFULL), 65536);
      for (int i = 0; i < 2; i++) tma4d_e(c.sb + SM_XT + i * 16384, &tx, c.b * 8, 4 + 2 * (c.b ^ i), BAR(B_PFULL));
    }
    {
      mbar_idle(BAR(B_SEL), 0);
      const int i = tid_now() & 127, sl = i & 3, e = (i >> 2) & 3;
      uint32_t ox = dst_x(e, i >> 5) + sl * M_REG;
      uint32_t oh = e & 1 ? (sl ^ (e & 2)) * M_REG + M_E3 + (c.r >> 5) * 8192 + (c.w & 1) * 4096 + (c.r & 31) * 128
                          : near_page(c, c.r, e ? sl * M_REG + M_E3 + (c.b * 2 + eq) * 8192 : box(~sl & 1, c.r)) + (e ? eh * 2048 : c.w * 1024), of;
      {
        const int e = i & 7, w = (i >> 3) & 3, m = (i >> 5) & 1, sl = i >> 6;
        const int cta = e < 2 ? c.r & ~1 : e == 2 ? c.r | 1 : e == 3 ? c.h * 4 + 2 * m + 1 : c.j * 32 + m * 8 + 2 * w + (e & 2) * 8 + (e & 1);
        const uint32_t off = e < 2 ? c.b * 2048 + m * 1024 + (w >> 1) * 512 + e * 160 : e == 2 ? c.b * 2048 + m * 1024 + w * 256 : e == 3 ? w * 256 : c.h * 128;
        of = (e < 4 ? e1_box(c, sl, cta) : near_page(c, cta, box(sl, cta))) + off;
      }
      char *px = c.mail + ox, *ph = c.mail + oh, *pf = c.mail + of;
      uint32_t at = sl * 128 + (i >> 5) * 32 + e * 8, af = i * 8;
      pin(px); pin(ph); pin(pf); pin(at); pin(af);
      asm volatile("barrier.cluster.wait;" ::: "memory");
      TR(-2, 0);
      mbar_idle(BAR(B_WREAD), 0);
      TR(-2, 1);
      mbar_arrive_both(BAR(B_LFREE), c.b ^ 1);
      sts64(at + (c.sb + SM_TAB + 1536), (uint32_t)(uintptr_t)px, (uint32_t)((uintptr_t)px >> 32));
      sts64(at + (c.sb + SM_TAB + 1024), (uint32_t)(uintptr_t)ph, (uint32_t)((uintptr_t)ph >> 32));
      sts64(af + (c.sb + SM_TAB), (uint32_t)(uintptr_t)pf, (uint32_t)((uintptr_t)pf >> 32));
      TR(-2, 2);
      if (tid_now() == 384) TL2(25);
      __syncwarp();
      bar_sync(14, 160);
    }
    pad<PAD3>();
    for (int s = -1; s < NSEG; s++) {
      if (E30 ? s != 0 : s >= 0) {
        const uint32_t tab = c.sb + SM_TAB + 1024 + (max(s, 0) & 3) * 128 + c.w * 32;
        uint32_t t0;
        if (s > 0) {
          const uint32_t ln = tid_now() & 31;
          const uint4 ta = lds128(tab);
          const char* src = mk_ptr(ta.x | ln * 4, ta.y);
          char* dst = mk_ptr(ta.z | ln * 4, ta.w);
          const uint32_t tg = (s - 1) >> 1, chk = (ln & 3) ? 0u : 1u, red = ln * (RED_L == 3 ? 4 : 8);
          touch(src, dep(c.sb, chk, c.sb)); touch(dst, dep(c.sb, red, c.sb));
          mbar_wait(BAR(B_E2TRIG), (s - 1) & 1);
          TR(s, 0);
          if (ANCH2) delay_fine(lds32(c.sb + SM_SUM + 64) + DLY_E2); else delay_cycles(DLY_E2);
          uint32_t n = 0;
          while (true) {
            uint32_t v[8];
#pragma unroll
            for (int i = 0; i < 8; i++) v[i] = ld_poll1(src + i * 128);
            if (E2_F) sched_fence(c.sb);
            const uint32_t bad = RED_T ? (stale2(v[0], v[1], tg) | stale2(v[2], v[3], tg) | stale2(v[4], v[5], tg)) | stale2(v[6], v[7], tg)
                                       : stale1(stale1(stale2(v[0], v[1], tg), v[2], tg), v[3], tg) | stale1(stale1(stale2(v[4], v[5], tg), v[6], tg), v[7], tg);
            const bool ok = all_clear(bad, chk);
#pragma unroll
            for (int l = 0; l < RED_L; l++)
#pragma unroll
              for (int i = 0; i < (4 >> l); i++) v[i] = add_bf16x2(v[2 * i], v[2 * i + 1]);
            if (RED_L == 3) sts32(red + (c.sb + SM_RED + c.w * 128), v[0]);
            else {
              float lo[8], hi[8];
#pragma unroll
              for (int i = 0; i < (8 >> RED_L); i++) { lo[i] = __uint_as_float(v[i] << 16); hi[i] = __uint_as_float(v[i] & 0xFFFF0000u); }
#pragma unroll
              for (int l = RED_L; l < 3; l++)
#pragma unroll
                for (int i = 0; i < (4 >> l); i++) { lo[i] = lo[2 * i] + lo[2 * i + 1]; hi[i] = hi[2 * i] + hi[2 * i + 1]; }
              sts64(red + (c.sb + SM_RED + c.w * 256), __float_as_uint(lo[0]), __float_as_uint(hi[0]));
            }
            if (ok) break;
            n++; CNT(0);
          }
          bar_sync(NB_HELP, 128);
          const uint32_t rd = red + (c.sb + SM_RED);
          if (!RED_P || c.w < 2) {
            if (RED_L == 3) st_pub_if(dst, sum4(lds32(rd), lds32(rd + 128), lds32(rd + 256), lds32(rd + 384)), c.w < 2);
            else {
              const uint2 p0 = lds64(rd), p1 = lds64(rd + 256), p2 = lds64(rd + 512), p3 = lds64(rd + 768);
              st_pub_if(dst, pack_bf16((__uint_as_float(p0.x) + __uint_as_float(p1.x)) + (__uint_as_float(p2.x) + __uint_as_float(p3.x)),
                                       (__uint_as_float(p0.y) + __uint_as_float(p1.y)) + (__uint_as_float(p2.y) + __uint_as_float(p3.y))), c.w < 2);
            }
          }
          t0 = clock_lo();
          mbar_arrive_warp(BAR(B_PUB));
          TRV(s, 15, n);
          mbar_wait(BAR(B_SPFREE), (s - 1) & 1);
        } else {
          if (tid_now() == 384) TL2(24);
          __syncwarp();
          if (!E30) mbar_wait(BAR(B_PROBE), 1);
          if (!WO_S) mbar_wait(BAR(B_WOFULL), 0);
          if (tid_now() == 384) TL2(19);
          __syncwarp();
          t0 = clock_lo() - DLY_E3;
        }
        TRV(s, 1, t0);
        {
          const uint32_t l16 = (tid_now() & 31) * 16, dst = vary(l16, s, c.sb) + (c.sb + SM_MEM + eh * 4096 + eq * 2048);
          const uint4 tb = lds128(tab + 16);
          st_pub_if(mk_ptr(tb.z | l16 >> 2, tb.w), SENT, c.w >= 2);
          const char* src = mk_ptr(tb.x | l16, tb.y);
          touch(src, dep(c.sb, dst, c.sb));
          delay_fine(t0 + (DLY_E3 + eh * DLY_E3B));
          uint32_t n = 0;
          while (true) {
            uint4 v[4];
#pragma unroll
            for (int i = 0; i < 4; i++) v[i] = ld_poll(src + i * 512);
#pragma unroll
            for (int i = 0; i < 4; i++) sts128(dst + i * 512, v[i]);
            if (arrive_if_all(max(max(v[0].x, v[1].x), max(v[2].x, v[3].x)) != SENT, NB_MEM + eh * 2 + eq, 160)) break;
            n++; CNT(1);
          }
          TR(s, 2); TRV(s, 14, n);
        }

        if (s == 1) CLK(1); if (s == 8) CLK(2); if (s == 56) CLK(3);
        if (c.w == 2 && s == 15) TRSYNC(8);
        if (c.w == 2 && s == 21) TRSYNC(10);
      }
      const int g = s + 1;
      auto load_v = [&]() {
        if (V_TMA && c.w == V_W) {
          mbar_expect_e(BAR(B_VFULL), (K_TMA ? 16384 : 8192) + (Q_TMA ? 2048 : 0));
          const char* src = c.mail + (uint32_t)(M_KVQ + (min(g, XEND - 1) & (NSLOT - 1)) * M_REG + c.h * 24576);
          bulk_load_e(c.sb + SM_V, src + 8192, 8192, BAR(B_VFULL));
          if (K_TMA > 1) delay_cycles(K_TMA);
          if (K_TMA) bulk_load_e(c.sb + SM_K, src, 8192, BAR(B_VFULL));
          if (Q_TMA > 1) delay_cycles(Q_TMA);
          if (Q_TMA) bulk_load_e(c.sb + SM_Q, src + (16384 + c.j * 2048), 2048, BAR(B_VFULL));
        }
      };
      if (XEND < NSEG && g >= XEND && g < NSEG) { mbar_wait(BAR(B_SC), s & 1); load_v(); }
      if (g < XEND) {
        const uint32_t tx_ = c.sb + SM_TAB + 1536 + (g & 3) * 128 + c.w * 32, tag = (g >> 2) & 1;
        if (c.w == 0) mbar_expect_e(BAR(B_LAND), EXP_PEER * 12288);
        auto load_x = [&]() {
          if (c.w == 3 && g + 1 < XEND) {
            mbar_wait(BAR(B_XEMPTY), g & 1);
            mbar_expect_e(BAR(B_XFULL), 16384 * EXP_NXT);
            for (int i = 0; i < EXP_NXT; i++) tma4d_e(c.sb + SM_XT + i * 16384, &tx, c.b * 8, (g + 1) * 4 + 2 * (c.b ^ i), BAR(B_XFULL));
          }
        };
        if (X_AT == 0 && g > 0) load_x();
        TR(s, 6);
        if (E30 && g == 0) mbar_idle(BAR(B_PROBE), 1);
        mbar_wait(BAR(B_LAND), g & 1);
        TR(s, 7);
        if (DLY_F && g > 0) delay_cycles(DLY_F);
        auto total = [&](int w, int lane, uint32_t o0, uint32_t o1) {
          const uint32_t a = c.sb + SM_LAND + land_off(w, lane);
          if (EXP_FL == 1) return make_uint4(a, a, a, a);
          const uint4 t = add4(lds128(a + o0), lds128(a + o1 + 2048));
          const uint32_t a2 = dep(dep(a, t.x ^ t.y ^ t.z, c.sb), t.w, c.sb);
          return add4(t, add4(lds128(a2 + o0 + 4096), lds128(a2 + o1 + 6144)));
        };
        auto get = [&](int e) {
          const int ln = tid_now() & 31;
          return e == 0 ? total(c.w, ln, 16384, 16384)
               : e == 1 ? total((c.w & 2) + ((ln >> 1) & 1), (ln & 1) * 16 + (c.w & 1) * 8 + (ln >> 2), 8192, 0)
                        : total((c.w & 2) + ((ln >> 1) & 1), (ln & 1) * 16 + (ln >> 3) * 4 + (c.w & 1) * 2 + ((ln >> 2) & 1), 0, 8192);
        };
        auto put = [&](int e, uint4 v) {
          const int ln = tid_now() & 31;
          const uint2 d = lds64(tx_ + e * 8);
          if (e < 2) {
            v.x = tagged(v.x, tag);
            st_pub4(mk_ptr(d.x | (e ? (ln & 24) * 32 + (ln & 7) * 16 : ln * 16), d.y), v);
          } else {
            char* dst = mk_ptr(d.x | ((ln & 7) * 16 + (ln >> 3) * 4), d.y);
            const uint32_t bit = ln < 8;
            st_pub(dst, put_tag(v.x, bit, tag)); st_pub(dst + 128, put_tag(v.y, bit, tag));
            st_pub(dst + 2048, put_tag(v.z, bit, tag)); st_pub(dst + 2176, put_tag(v.w, bit, tag));
          }
        };
        auto after_sc = [&]() { if (g > 0) { mbar_wait(BAR(B_SC), s & 1); if (DLY_FK) delay_cycles(DLY_FK); if (X_AT == 1) load_x(); } };
        if (FIN_AT == 5) {
          put(0, get(0));
          if (DLY_F2 && g > 0) delay_cycles(DLY_F2); else sched_fence(c.sb);
          const uint4 k = get(1);
          sched_fence(c.sb);
          const uint4 q = get(2);
          if (g > 0) mbar_wait(BAR(B_VST), s & 1);
          put(1, k); put(2, q);
          TR(s, 5);
          mbar_arrive_both(BAR(B_LFREE), c.b ^ 1);
          after_sc();
          load_v();
          continue;
        }
        if (FIN_AT < 3) {
          if (EXP_FIN & 1) put(0, get(0));
          TR(s, 3);
          if (FIN_AT == 1) after_sc();
          if (V_TMA == 1) load_v();
          if (EXP_FIN & 2) put(1, get(1));
        } else {
          const uint4 v = get(0);
          sched_fence(c.sb);
          const uint4 k = get(1);
          if (g > 0) { mbar_wait(BAR(B_VST), s & 1); if (DLY_FS) delay_cycles(DLY_FS); }
          put(0, v); put(1, k);
        }
        TR(s, 4);
        if (FIN_AT == 4) {
          const uint4 q = get(2);
          after_sc();
          load_v();
          put(2, q);
        } else {
          if (FIN_AT >= 2) after_sc();
          if (V_TMA == 2) load_v();
          if (EXP_FIN & 4) put(2, get(2));
        }
        mbar_arrive_both(BAR(B_LFREE), c.b ^ 1);
        if (V_TMA == 3) load_v();
        TR(s, 5);
        if (!FIN_AT && X_AT && g > 0) { mbar_wait(BAR(B_SC), s & 1); if (DLY_FK) delay_cycles(DLY_FK); load_x(); }
      }
    }
    const int tile = tile_of(c), s0 = (tile >> 3) * 4, n0 = (tile & 7) * 128;
    if (c.w == 1) {
      mbar_idle(BAR(B_PVDONE), 0);
      count_e(g_ctl + (EARLY2 ? C_LAST : C_EARLY));
      st_pub(c.mail + (uint32_t)((tid_now() & 6) * (M_REG / 2) + M_SEL + (tid_now() & 1) * 4096 + c.r * 4), 0);
      await_count(g_ctl + C_COLS, 4);
      if (K_TMA) mbar_idle(BAR(B_SC), 1);
      mbar_expect_e(BAR(B_TW), 8192);
      bulk_load_e(c.sb + SM_TW, g_tw, 8192, BAR(B_TW));
    } else if (c.w == 2) {
      const uint32_t ln = tid_now() & 31, rel = mapa(BAR(B_GEMPTY) + (ln >> 2) * 8, ln & 1);
      mbar_idle(BAR(B_VST), 1); mbar_idle(BAR(PRE_AT), 1);
      arrive_remote_if(rel, ln < 12);
      mbar_idle(BAR(B_E2TRIG), 1);
      if (GATE) mbar_wait(BAR(B_DONE), 0);
      arrive_remote_if(rel, ln >= 12 && ln < 20);
    } else {
      auto ahead = [&](int k) {
        if (c.w) { if (PF_A && (k & 3) == (tile >> 1 & 3)) prefetch3d_e(&ta, k * 32, s0 + 2 * c.b); }
        else if (PF_B && (k & 7) == (tile >> 4)) prefetch2d_e<(ONCE & 512) != 0>(&tw, n0 + (tile & 8) * 8, k * 64);
      };
#pragma unroll 1
      for (int k = 0; k < PF_D; k++) ahead(k);
      if (c.w == 3) await_count(g_ctl + C_EARLY, 128);
      const int skew = tile < 120 ? 0 : SKEW;
      uint32_t o = SM_XT, st = 0, ph = 0;
#pragma unroll 1
      for (int kb = 0; kb < 64 + skew; kb++, o = next_stage(o)) {
        const bool solo = kb < skew || kb >= 64;
        const uint32_t bar = BAR(B_GFULL + st), k = kb & 63;
        if (c.w && kb == skew) {
          if (tile >= 120) await_count(g_ctl + C_LAST, EARLY2 ? 640 : 512);
          if (tid_now() == 480) TL(10);
          __syncwarp();
        }
        mbar_wait(BAR(B_GEMPTY + st), ph);
        if (c.w) {
          const int r = solo ? (kb >> 5) + c.b : c.b * 2;
          tma3d_mc_e(c.sb + o + r * 4096, solo ? &ta32 : &ta, k * 32, s0 + r, bar);
        } else {
          mbar_expect_e(bar, solo ? 24576 : 32768);
          tma2d_o<(ONCE & 2) != 0>(c.sb + o + 16384, &tw, n0, k * 64, bar);
          tma2d_o<(ONCE & 2) != 0>(c.sb + o + 24576, &tw, n0 + 64, k * 64, bar);
        }
        if (kb + PF_D < 64) ahead(kb + PF_D);
        if (++st == 5) { st = 0; ph ^= 1; }
      }
    }
    return;
  } else if (c.m == 2) {
    asm volatile("setmaxnreg.dec.sync.aligned.u32 %0;" :: "n"(512 - 2 * REG_F - REG_H));
    c.lane = lane_id();
    {
      uint32_t tl = clock_lo() + (PACE0 + WO_AT * PACE);
      TR(-2, 0);
      sched_fence(i0 ^ i1);
      TR(-2, 7);
      int far1 = 0;
#pragma unroll 1
      for (int rep = EARLY; rep <= NPROBE; rep++) {
        const int lag = race_init(own + (rep & 1) * 4096, own + (~rep & 1) * 4096, SENT);
        if (rep) far1 += ((rep ^ c.r >> 5) & 1 ? 1 : -1) * min(lag, 200);
      }
      sts32(c.sb + SM_SEL + 512 + c.w * 4, (8 + far1 / (16 * NPROBE)) << 4 * c.w);
      TR(-2, 1);
      if (tid_now() == 256) TL2(14);
      __syncwarp();
      mbar_arrive_warp(BAR(B_PROBE));
      if (c.w == 0) {
        mbar_idle(BAR(B_PROBE), 0);
        const uint4 bits = lds128(c.sb + SM_SEL + 512);
        const uint32_t res = bits.x | bits.y | bits.z | bits.w;
        st_pub_if(c.mail + (uint32_t)((c.lane & 6) * (M_REG / 2) + M_SEL + (c.lane & 1) * 4096 + c.r * 4), res | tile_key(), c.lane < 8);
        const int q = (res >> 4 * ((c.lane + c.r) & 3) & 15) - 8, best = __reduce_max_sync(~0u, abs(q) * 64 + (c.lane & 3) * 16 + ((c.lane + c.r) & 3) * 2 + (q <= 0));
        const char* src = c.mail + (uint32_t)((best & 6) * (M_REG / 2) + M_SEL + (best & 1) * 4096 + c.lane * 16);
        if (SEL_AT) delay_until(tl - (PACE0 + WO_AT * PACE - SEL_AT));
        uint4 v; uint32_t n = 0;
        TR(-2, 4);
        while (true) {
          delay_cycles(DLY_SEL);
          TR(-2, 6);
          v = ld_poll(src);
          if (__all_sync(~0u, v.x && v.y && v.z && v.w)) break;
          watchdog(n, POLL_LIMIT);
        }
        TR(-2, 5);
        int ta = 0, tb = 0, pa = 0, pb = 0;
        uint32_t flip = 0;
#pragma unroll 1
        for (int i = 0; i < 4; i++) {
          const int a = (v.x >> 4 * i & 15) + (v.y >> 4 * i & 15) - 16, b = (v.z >> 4 * i & 15) + (v.w >> 4 * i & 15) - 16;
          const bool f = __reduce_add_sync(~0u, a * ta + b * tb) < 0;
          ta += f ? -a : a; tb += f ? -b : b; flip |= (uint32_t)f << i;
        }
#pragma unroll 1
        for (uint32_t g = 0; g < 8; g++) {
          const bool a = (v.x >> 16) - g * 256 < 120, b = (v.z >> 16) - g * 256 < 120;
          const int n = __reduce_add_sync(~0u, (a ? ta : 0) + (b ? tb : 0)) > 0 ? PRIOR : -PRIOR;
          if (a) pa = n;
          if (b) pb = n;
        }
        const uint32_t ka = AWARE && ta + pa > 0 ? ~flip : flip, kb = AWARE && tb + pb > 0 ? ~flip : flip;
        sts128(c.sb + SM_SEL + c.lane * 16, make_uint4(ka, ka, kb, kb));
        mbar_arrive_warp(BAR(B_SEL));
        const uint32_t key = __shfl_sync(~0u, c.a ? v.z : v.x, c.h);
        const int u = __popc(__ballot_sync(~0u, v.x < key)) + __popc(__ballot_sync(~0u, v.z < key));
        sts32(c.sb + SM_SEL + 528, (u & 32) * 2 + (u & 7) * 8 + (u >> 2 & 6) + c.b);
        TR(-2, 2);
        if (c.lane == 0) TL2(13);
        __syncwarp();
        bar_sync(14, 160);
        if (ZDLY) delay_cycles(ZDLY);
#pragma unroll 4
        for (int k = c.lane >> 3; k < (ZINIT ? 128 : 0); k += 4) {
          const int e = k & 7;
          const uint2 d = lds64(c.sb + SM_TAB + (e == 3 ? k - 1 : k) * 8);
          st_pub4(mk_ptr((d.x & ~127u) + (e < 2 ? (k & 8) * 32 : e == 3 ? 128 : 0) + (c.lane & 7) * 16, d.y), make_uint4(0, 0, 0, 0));
        }
        __syncwarp();
        if (c.lane < 4) asm volatile("mbarrier.arrive.shared::cta.b64 _, [%0];" :: "r"(BAR(B_PROBE)) : "memory");
        __syncwarp();
        TR(-2, 8);
      }
      if (c.w == 2) {
        mbar_idle(BAR(B_P1), 0);
        if (P1_AT) { mbar_idle(BAR(B_WFULL), 0); mbar_idle(BAR(B_WFULL + 1), 0); }
        st_pub_if(g_ctl + C_COLS + (c.r & 15) * 32 + c.lane, 0, c.r < (C_END - C_COLS) / 32);
        count_e(g_ctl + C_P1);
        TR(-2, 3);
      }
      if (c.w == 1) for (int i = 0; i < WO_N; i++) { delay_until(tl += WO_P * PACE); prefetch2d_e(&to, c.j * 256 + (i ^ WO_X) * 64, c.h * 128); }
      if (c.w == 3) {
        mbar_idle(BAR(B_WREAD0), 0);
        for (int i = 0; i < 2; i++) tma4d_e(c.sb + SM_WO + i * 16384, &tx, c.b * 8, 2 * (c.b ^ i), BAR(B_PFULL));
        mbar_expect_e(BAR(B_WOFULL), 65536);
#pragma unroll 1
        for (int i = 3; i >= 0; i--) {
          if (i & 1) mbar_idle(BAR(i < 2 ? B_XEMPTY : B_WREAD), 0);
          TMA_O(c.sb + SM_WO + i * 16384, &to, c.j * 256 + i * 64, c.h * 128, BAR(B_WOFULL));
        }
      }
    }
    asm volatile("barrier.cluster.wait;" ::: "memory");
    const int g = c.w, src0 = c.h * 4 + (g >> 1) * 2;
    mbar_wait(BAR(B_SEL), 0);
    c.sel = __shfl_sync(~0u, (e1_box(c, 0, src0 + (c.lane >> 5)) & 4096) | (e1_box(c, 1, src0) & 4096) * 2, 0);
    mbar_wait(BAR(B_WREAD), 0);
    uint32_t l16 = c.sb + g * 512 + c.lane * 16;
    auto lane = [&](uint32_t v) { l16 = dep(l16, v, c.sb); return (int)((l16 & 511) >> 4); };
    pad<PAD2>();
    for (int s = 0; s < NSEG; s++) {
      l16 = vary(l16, s, c.sb);
      int ln = (l16 & 511) >> 4;
      uint4 kf[4], qx;
      auto load_x = [&]() {
        if (X_AT >= 2 && g == 0 && s + 2 < XEND) {
          if (KL_AT != 2) mbar_wait(BAR(B_XEMPTY), ~s & 1);
          if (DLY_XL) delay_cycles(DLY_XL);
          mbar_expect_e(BAR(B_XFULL), 16384 * EXP_NXT);
          for (int i = 0; i < EXP_NXT; i++) tma4d_e(c.sb + SM_XT + i * 16384, &tx, c.b * 8, (s + 2) * 4 + 2 * (c.b ^ i), BAR(B_XFULL));
        }
      };
      {
        const int gs = min(s, XEND - 1);
        const char* pk = c.mail + (uint32_t)(M_KVQ + (gs & (NSLOT - 1)) * M_REG + c.h * 24576 + g * 2048 + ln * 16);
        const char* pq = pk + (16384 + c.j * 2048 - g * 1536);
        const uint32_t tg = (gs / NSLOT) & 1;
        touch(pk, c.sb); touch(pq, c.sb);
        TR(s, 0);
        mbar_wait(BAR(B_VFULL), s & 1);
        TR(s, 1);
        uint4 k[4];
        auto load_k = [&]() {
          if (Q_TMA && Q_AT == 0) qx = lds128(l16 + SM_Q);
          if (DLY_K) delay_cycles(DLY_K);
#pragma unroll
          for (int t = 0; t < 4; t++) k[t] = lds128(l16 + (g * 1536 + SM_K + t * 512));
          if (Q_TMA && Q_AT == 1) qx = lds128(l16 + SM_Q);
        };
        if (K_TMA && KL_AT == 1) load_k();
        if (Q_TMA && Q_AT == 2) qx = lds128(l16 + SM_Q);
        if (s > 0) mbar_wait(BAR(B_PUB), (s - 1) & 1);
        if (K_TMA) {
          if (!Q_TMA) qx = ld_poll(pq);
          if (KL_AT == 2) { mbar_spin_if(BAR(B_XEMPTY), ~s & 1, s + 1 < XEND); load_x(); }
          if (KL_AT != 1) load_k();
        }
        for (uint32_t n = 0; ; ) {
          if (!K_TMA) {
#pragma unroll
            for (int t = 0; t < 4; t++) k[t] = ld_poll(pk + t * 512);
            qx = ld_poll(pq);
          }
#pragma unroll
          for (int t = 0; t < 2; t++) {
            auto cp = [&](uint32_t v) { return dep(v, 0, c.sb); };
            kf[t] = make_uint4(cp(k[2 * t].x), cp(k[2 * t].y), cp(k[2 * t + 1].x), cp(k[2 * t + 1].y));
            kf[2 + t] = make_uint4(cp(k[2 * t].z), cp(k[2 * t].w), cp(k[2 * t + 1].z), cp(k[2 * t + 1].w));
          }
          if (all_clear(stale1(stale2(k[0].x, k[1].x, tg) | stale2(k[2].x, k[3].x, tg), qx.x, tg), EXP_CHK)) break;
          watchdog(n, POLL_LIMIT); CNT(4);
          if (K_TMA) {
#pragma unroll
            for (int t = 0; t < 4; t++) k[t] = ld_poll(pk + t * 512);
            qx = ld_poll(pq);
          }
        }
        TR(s, 2);
      }
      if (KL_AT != 2) load_x();
      ln = lane(kf[0].y);
      const char* pa = c.mail + (uint32_t)(box(s & 1, src0) + 8192 + (c.sel >> (s & 1) & 4096) + (g & 1) * 512 + (EXP_LIN ? ln * 16 : read_off(ln)));
      const uint32_t spw = c.sb + SM_SP + g * 1280 + (ln & 3) * 64 + ((((ln >> 3) ^ ln) & 2) << 4) + (ln & 4) * 4 + (ln & 8),
                     spr = c.sb + SM_SP + (ln & 4) * 80 + (ln >> 3) * 64 + (((ln & 3) ^ ((ln >> 3) & 2)) << 4), l8 = ln * 8;
      const uint32_t tg = s >> 1;
      float sx[2][4];
      uint32_t sm;
      uint4 km;
      auto causal = [&](uint32_t (&sc)[5], int l) {
        const int n = l >> 2, lim = 16 * (8 * c.j + (n & 4) + 2 * (n & 1) + ((n >> 1) & 1) - 2 * (l & 3) + 1);
#pragma unroll
        for (int w = 0; w < 4; w++) {
          uint32_t m; asm("shl.b32 %0, 0xffffffff, %1;" : "=r"(m) : "r"(max(lim - 128 * w, 0)));
          sc[1 + w] = (sc[1 + w] & ~m) | (0xD029D029u & m);
        }
      };
      if (SXP) {
        scores_x<false>(sx, kf, qx, 0);
        if (DLY_SA) { sched_fence(dep(c.sb, __float_as_uint(sx[1][0]), c.sb)); delay_cycles(DLY_SA); }
        store_scores(sx, spw + (SM_K - SM_SP + g * 768));
        if (DLY_SB) delay_cycles(DLY_SB);
        bar_sync(NB_ATT, 128);
        const uint32_t ax = spr + (SM_K - SM_SP);
        uint4 t = add4(lds128(ax), lds128(ax + 2048));
        const uint32_t ay = SXP == 2 ? dep(ax, t.x, c.sb) : ax;
        t = add4(add4(t, lds128(ay + 4096)), lds128(ay + 6144));
        uint32_t sc[5] = {0, t.x, t.y, t.z, t.w};
        causal(sc, ln);
        sts128(l16 + SM_OX, make_uint4(sc[1], sc[2], sc[3], sc[4]));
      }
      touch(pa, c.sb);
      mbar_wait(BAR(B_E1TRIG), s & 1);
      const uint32_t t0 = clock_lo();
      TRV(s, 3, t0);
      if (!SXP) {
        scores_x<false>(sx, kf, qx, 0);
        store_scores(sx, spw + 640);
      }
      if (DLY_E1) delay_fine(t0 + DLY_E1);
      uint32_t nr = 0;
      while (true) {
        const uint4 q0 = ld_poll(pa), q1 = ld_poll(pa + 2048), k0 = ld_poll(pa + 1024), k1 = ld_poll(pa + 3072);
        uint4 qm = add4(q0, q1);
        const uint32_t bq = stale2(q0.x, q1.x, tg);
        qm.x = dep(qm.x, bq, c.sb);
        scores_x<SC_F>(sx, kf, qm, c.sb);
        const uint32_t bk = stale2(k0.x, k1.x, tg);
        km = add4(k0, k1);
        km.x = dep(km.x, bk, c.sb);
        const bool ok = all_clear(bq | bk, 1);
        sm = scores_m(qm, km);
        store_scores(sx, spw);
        if (ok) break;
        nr++; CNT(2);
      }
      sts32(l8 + (c.sb + SM_SPM + (g >> 1) * 256 + (g & 1) * 4), sm);
      bar_sync(NB_ATT, 128);
      TR(s, 5); TRV(s, 13, nr);
      float o[2][4];
      uint32_t sp[5];
      uint4 vf[4];
      load_scores(sp, spr, l8 + (c.sb + SM_SPM));
      const uint32_t m5 = max5(sp);
      uint32_t m1;
      float off = row_off(m5, m1), f[10];
      l16 = dep(l16, VF_AT ? m1 : m5, c.sb);
#pragma unroll
      for (int t = 0; t < 4; t++) vf[(t >> 1) + 2 * (t & 1)] = lds128(l16 + SM_V + ((t >> 1) + 2 * (t & 1)) * 2048);
      qx.x = dep(qx.x, sp[0], c.sb);
      sts32(l8 + (c.sb + SM_SPM + 512 + (g >> 1) * 256 + (g & 1) * 4), scores_m(qx, km));
      mbar_arrive_warp(BAR(B_SC));
      unpack(f, sp);
      if (UP_F) sched_fence(c.sb);
      uint4 vm;
      if (VM_AT < 2) {
        bar_sync(NB_VM, 384);
        sp[1] = exp_pair(f, 1, off);
        const uint32_t av = dep(l8, VM_AT ? sp[1] : __float_as_uint(off), c.sb) + (c.sb + g * 512 + SM_VM);
        const uint2 vm0 = lds64(av), vm1 = lds64(av + 256);
        vm = make_uint4(vm0.x, vm0.y, vm1.x, vm1.y);
#pragma unroll
        for (int i = 2; i < 6; i++) sp[i % 5] = exp_pair(f, i % 5, off);
      } else {
#pragma unroll
        for (int i = 1; i < 6; i++) sp[i % 5] = exp_pair(f, i % 5, off);
        bar_sync(VM_AT == 2 ? dep(dep(0, sp[1] ^ sp[2], c.sb) + NB_VM, sp[0], c.sb) : dep(dep(0, sp[0] ^ sp[1] ^ sp[2], c.sb) + NB_VM, sp[3], c.sb), 384);
        const uint32_t av = l8 + (c.sb + g * 512 + SM_VM);
        const uint2 vm0 = lds64(av), vm1 = lds64(av + 256);
        vm = make_uint4(vm0.x, vm0.y, vm1.x, vm1.y);
      }
      uint2 u0, u1;
      uint4 sxx;
      auto load_sx = [&](uint32_t a8) { u0 = lds64(a8 + (c.sb + SM_SPM + 512)); u1 = lds64(a8 + (c.sb + SM_SPM + 768)); sxx = lds128(l16 + SM_OX); };
      if (SXP && XL_AT) load_sx(XL_AT == 2 ? dep(l8, vm.x, c.sb) : l8);
      float sum;
      auto rows_m = [&]() {
        const uint32_t tv = min(s, XEND - 1) / NSLOT;
        sum = pv(o, sp, vf, vm);
        stsm4<false>(l16 + SM_OM, pack_bf16(o[0][0], o[0][1]), pack_bf16(o[0][2], o[0][3]), pack_bf16(o[1][0], o[1][1]), pack_bf16(o[1][2], o[1][3]));
        sts32(c.sb + SM_SUM + ((l16 >> 4) & 28), __float_as_uint(sum));
        return arrive_if_clear(stale2(vf[0].x, vf[1].x, tv) | stale2(vf[2].x, vf[3].x, tv), EXP_CHK, NB_OM, 384);
      };
      if (!rows_m()) {
        const char* pv_ = c.mail + (uint32_t)(M_KVQ + (min(s, XEND - 1) & (NSLOT - 1)) * M_REG + c.h * 24576 + 8192 + (l16 - c.sb));
        uint32_t n = 0;
        do {
#pragma unroll
          for (int t = 0; t < 4; t++) vf[t] = ld_poll(pv_ + t * 2048);
          watchdog(n, POLL_LIMIT); CNT(5);
        } while (!rows_m());
        if (SXP && XL_AT) load_sx((l16 & 511) >> 1);
      }
      const uint32_t tom = clock_lo();
      TRV(s, 8, tom);
      sched_fence(c.sb);
      ln = lane(tom);
      const int n = ln >> 2, jj = ln & 3, tq_ = 8 * c.j + (n & 4) + 2 * (n & 1) + ((n >> 1) & 1);
      if (DLY_X) delay_until(tom + DLY_X);
      if (SXP) {
        if (!XL_AT) load_sx(ln * 8);
        sp[0] = sum4(u0.x, u0.y, u1.x, u1.y); sp[1] = sxx.x; sp[2] = sxx.y; sp[3] = sxx.z; sp[4] = sxx.w;
      } else {
        load_scores(sp, spr + 640, c.sb + SM_SPM + 512 + ln * 8);
        causal(sp, ln);
      }
      mbar_arrive_warp(dep(dep(0, sp[0], c.sb), sp[1], c.sb) + BAR(B_SPFREE));
      off = row_off(max5(sp), m1);
      unpack(f, sp);
#pragma unroll
      for (int i = 1; i < 6; i++) sp[i % 5] = exp_pair(f, i % 5, off);
      if (DLY_Y) { sched_fence(dep(dep(c.sb, sp[0] ^ sp[1] ^ sp[2], c.sb), sp[3] ^ sp[4], c.sb)); delay_until(tom + DLY_Y); }
      sum = pv(o, sp, vf, vm);
      TR(s, 7);
      sum = rcp(sum);
      const float i0 = __shfl_sync(~0u, sum, 8 * jj), i1 = __shfl_sync(~0u, sum, 8 * jj + 4);
      const uint32_t oxs = c.sb + SM_OX + g * 512;
      stsm4<true>(oxs + (ln & 7) * 64 + (((ln >> 3) ^ ((ln >> 1) & 3)) << 4),
                  pack_bf16(o[0][0] * i0, o[0][1] * i1), pack_bf16(o[0][2] * i0, o[0][3] * i1), pack_bf16(o[1][0] * i0, o[1][1] * i1), pack_bf16(o[1][2] * i0, o[1][3] * i1));
      __syncwarp();
      *(uint4*)(g_ox + ox_at(s, tq_, c.h * 4 + g, jj)) = lds128(oxs + n * 64 + ((jj ^ (n >> 1)) << 4));
      mbar_arrive_warp(BAR(B_PVDONE));
      TR(s, 9);
    }
    if (LASTM) {
      const int ln = tid_now() & 31, n = ln >> 2, jj = ln & 3, tq_ = 8 * c.j + (n & 4) + 2 * (n & 1) + ((n >> 1) & 1);
      store_count(g_ox + ox_at(NSEG - 1, tq_, c.h * 4 + g, jj), lds128(c.sb + SM_OX + g * 512 + n * 64 + ((jj ^ (n >> 1)) << 4)), (char*)(g_ctl + C_LAST) + (LASTM == 2 ? c.r * 4 + g : 0));
    } else count_e(g_ctl + C_LAST);
    mbar_arrive_warp(BAR(B_DONE));
    if (tid_now() == 256) TL(8);
    __syncwarp();
    mbar_wait(BAR(B_E2TRIG), 1); mbar_idle(BAR(B_DONE), 0); mbar_wait(BAR(B_TW), 0);
    asm volatile("setmaxnreg.inc.sync.aligned.u32 128;");
  } else {
    {
      const int w = c.m * 4 + c.w;
      mbar_expect_e(BAR(B_ROWS), 4096 + 256);
      for (int i = 0; i < 2; i++) bulk_load_e(c.sb + SM_FFT + (1024 + w * ROW_BUF) * 8 + i * 2048, x + (size_t)(z_row(c.r * 8 + w) + i * 1024) * D_, 2048, BAR(B_ROWS));
      bulk_load_e(c.sb + SM_GW + w * 256, gw + w * 128, 256, BAR(B_ROWS));
    }
    asm volatile("setmaxnreg.inc.sync.aligned.u32 %0;" :: "n"(REG_F));
    c.lane = lane_id();
    uint32_t wa[16][4], wb[16][4], wv[16][4];
    TR(-2, 4);
    fft_rows_fwd((float2*)(smraw + SM_FFT), (const __nv_bfloat16*)(smraw + SM_GW), c.r, threadIdx.x, BAR(B_ROWS), BAR(B_FREE), [&](int e) { TR(-2, e); }, [&]() {
      mbar_spin(BAR(B_PFULL), 0);
#pragma unroll
      for (int k = 0; k < NP; k++) ldsm4t(wa[k], c.sb + SM_POOL + c.m * NP * 2048 + frag_off(c.w, c.lane) + k * 2048);
      bar_sync(NB_XCH, 256);
#pragma unroll
      for (int k = 0; k < NP; k++) sts128(c.sb + SM_POOL + c.m * 2048 + c.w * 512 + c.lane * 16 + k * 4096, make_uint4(wa[k][0], wa[k][1], wa[k][2], wa[k][3]));
    });
    mbar_arrive_warp(BAR(B_P1));
    TR(-2, 0);
    if (tid_now() == 0) TL2(1);
    __syncwarp();
    mbar_spin(BAR(B_WFULL + c.m), 0);
    TR(-2, 1);
    if ((tid_now() & 127) == 0) TL2(16);
    __syncwarp();
    {
      const uint32_t st = c.sb + c.m * ST_WG + frag_off(c.w, c.lane);
#pragma unroll
      for (int k = 0; k < 16; k++) ldsm4t(wb[k], st + k * 2048);
#pragma unroll
      for (int k = NP; k < 16; k++) ldsm4t(wa[k], st + (16 + k - NP) * 2048);
#pragma unroll
      for (int k = 0; k < NV; k++) ldsm4t(wv[k], st + (32 - NP + k) * 2048);
      mbar_arrive_warp(BAR(B_WREAD));
      if (c.m == 0) mbar_arrive_warp(BAR(B_WREAD0));
#pragma unroll
      for (int k = 0; k < (LP_IN == 2 ? 0 : NP); k++) lds_frag(wa[k], c.sb + SM_POOL + c.m * 2048 + c.w * 512 + c.lane * 16 + k * 4096);
      TR(-2, 2);
    }
    TR(-2, 3);
    if (tid_now() == 0) TL2(12);
    __syncwarp();
    asm volatile("barrier.cluster.wait;" ::: "memory");
    uint32_t t16 = c.m * 2048 + c.w * 512 + c.lane * 16;
    uint32_t pk = (c.m * NHV * 2048 + frag_off(c.w, c.lane)) | (tile_off(2 * (c.w & 1), c.lane) << 16) | ((c.lane & 12) ? 0u : 0x80000000u);
    const uint32_t dx1 = desc_lo(c.sb + SM_XT + c.m * 4096), dh = desc_lo(c.sb + SM_HV + c.m * NHV * 2048);
    mbar_spin(BAR(B_PFULL), 1);
    pad<PAD0>();
    for (int s = -2; ; s++) {
      t16 = vary(t16, s, c.sb); pk = vary(pk, s, c.sb);
      const uint32_t dx = dx1 - (s == -2 ? (SM_XT - SM_WO) / 16 : 0);
      auto ldp = [&](int k0, int k1, int d, int back = 0) {
#pragma unroll
        for (int k = k0; k < k1; k++) lds_frag(wa[k], (k < k0 + d - back ? t16 : dep(t16, wa[k < d ? 0 : k - d][0], c.sb)) + (c.sb + SM_POOL + k * 4096));
      };
      if (s >= 0) {
        uint32_t af[16][4], bf[4][4], wo;
        const uint32_t tab = ((t16 >> 3) & 0x1C0) + (c.sb + SM_TAB + (s & 1) * 512);
        const char* pa;
        mem_proj(wa, wb, wv, af, wo, pa, tab, t16, pk, c, s);
        const uint32_t t0 = clock_lo();
        t16 = dep(t16, t0, c.sb);
        auto ldwo = [&](int f) { ldsm4t(af[f], (f < WO_D ? wo : dep(wo, af[f < WO_D ? 0 : f - WO_D][0], c.sb)) + (c.sb + SM_WO + (f & 1) * 32768 + (f >> 1) * 2048)); };
        {
          const uint32_t tg = s >> 1, vm = t16 >> 1, chk = (~t16 >> 4) & 1;
          if (WO_S && s == 0) {
            mbar_spin(BAR(B_WOFULL), 0);
#pragma unroll
            for (int f = 0; f < WO_0; f++) ldwo(f);
          }
#pragma unroll
          for (int f = WO_0; f < WO_1; f++) ldwo(f);
          if (DLY_V) delay_fine(t0 + DLY_V); else sched_fence(c.sb);
          uint2 v0 = ld_poll2(pa), v1 = ld_poll2(pa + 1024), v2 = ld_poll2(pa + 2048), v3 = ld_poll2(pa + 3072);
          TR(s, 3);
#pragma unroll
          for (int f = WO_1; f < 16 - WO_L; f++) ldwo(f);
          TR(s, 4);
          uint32_t n = 0;
          while (true) {
            sts64(vm + (c.sb + SM_VM), sum4(v0.x, v1.x, v2.x, v3.x), sum4(v0.y, v1.y, v2.y, v3.y));
            if (arrive_if_clear(stale1(stale1(stale2(v0.x, v1.x, tg), v2.x, tg), v3.x, tg), chk, NB_VM, 384)) break;
            v0 = ld_poll2(pa); v1 = ld_poll2(pa + 1024); v2 = ld_poll2(pa + 2048); v3 = ld_poll2(pa + 3072);
            n++; CNT(3);
          }
          TR(s, 12); TRV(s, 15, n);
        }
        const uint32_t ob = dep(dep(t16 & 511, af[14 - WO_L][0], c.sb), af[15 - WO_L][0], c.sb);
        uint32_t l4 = ob >> 2;
        const uint32_t bit = (t16 & 48) ? 0u : 1u;
        if (LF_AT) mbar_spin2_if(BAR(B_XFULL), BAR(B_LFREE), s & 1, s + 2 < XEND); else mbar_spin_if(BAR(B_XFULL), s & 1, s + 2 < XEND);
        bar_sync(NB_OM, 384);
        TR(s, 5);
#pragma unroll
        for (int i = 0; i < 4; i++) ldsm4t(bf[i], ob + (c.sb + SM_OM + i * 512));
        uint2 sum = lds64(((t16 >> 1) & 24) + (c.sb + SM_SUM));
        if (OM_F) sched_fence(c.sb);
        float d[WO_C][4] = {};
        uint4 d0, d1;
#pragma unroll
        for (int f = 0; f < 16; f++) {
          mma_a(d[f % WO_C], af[f], bf[f >> 2][f & 2], bf[f >> 2][(f & 2) + 1]);
          if (f >= WO_C && f < WO_C + WO_L) {
            const int l = 16 - WO_L + f - WO_C;
            ldsm4t(af[l], (WO_LD ? dep(wo, __float_as_uint(d[(f + 1) % WO_C][0]), c.sb) : wo) + (c.sb + SM_WO + (l & 1) * 32768 + (l >> 1) * 2048));
          }
          if (f == WO_T) {
            const uint32_t tb2 = dep((t16 >> 3) & 0x1C0, __float_as_uint(d[f % WO_C][0]), c.sb) + (c.sb + SM_TAB + (s & 1) * 512);
            d0 = lds128(tb2 + 32); d1 = lds128(tb2 + 48);
          }
          if (f >= PL_WA && f < PL_WA + PL_W) lds_frag(wa[f - PL_WA], (PL_WD ? dep(t16, __float_as_uint(d[(f + PL_WD) % WO_C][0]), c.sb) : t16) + (c.sb + SM_POOL + (f - PL_WA) * 4096));
          if (PL_W && PL_WF == 1 && f == PL_WA + PL_W - 1) sched_fence(c.sb);
          if (f == 4) { sum.x = dep(sum.x, __float_as_uint(d[0][0]), c.sb); sum.y = dep(sum.y, __float_as_uint(d[0][0]), c.sb); }
        }
        if (PL_W && !PL_WF) {
          uint32_t all = 0;
#pragma unroll
          for (int k = 0; k < PL_W; k++) all ^= wa[k][0];
          l4 = dep(l4, all, c.sb);
        }
        char* dst[4] = {mk_ptr(d0.x | l4, d0.y), mk_ptr(d0.z | l4, d0.w), mk_ptr(d1.x | l4, d1.y), mk_ptr(d1.z | l4, d1.w)};
        const float i0 = rcp(__uint_as_float(sum.x)), i1 = rcp(__uint_as_float(sum.y));
#pragma unroll
        for (int i = 0; i < 4; i++) {
          const int t = i >> 1, e = 2 * (i & 1);
          const float y0 = WO_C == 2 ? d[t][e] : d[t][e] + d[(t + 2) % WO_C][e], y1 = WO_C == 2 ? d[t][e + 1] : d[t][e + 1] + d[(t + 2) % WO_C][e + 1];
          st_pub(dst[i], put_tag(pack_bf16(y0 * i0, y1 * i1), bit, s >> 1));
        }
        if (ANCH2) sts32(c.sb + SM_SUM + 64, clock_lo());
        mbar_arrive_warp(BAR(B_E2TRIG));
        TR(s, 6);
        sched_fence(c.sb);
        if (W_E2 == 2) mbar_spin(BAR(B_E2TRIG), s & 1);
#pragma unroll
        for (int k = PL_A; k < PL_0; k++)
#pragma unroll
          for (int i = 0; i < 4; i++) wa[k][i] = af[16 - PL_0 + k][i];
      }
      if (__builtin_expect(s + 2 < XEND, 1)) {
        const uint32_t tg0 = DLY_P ? clock_lo() + DLY_P : 0;
        if (LP_IN) ldp(PL_W, PL_A, PL_D);
        if (PL_A < PL_0 && c.m != ASY) ldp(PL_A, PL_0, PL_D, PL_A > PL_W ? PL_D : 0);
        auto late = [&](int at) { if (PL_A < PL_0 && ASY_AT == at && c.m == ASY) ldp(PL_A, PL_0, PL_D1); };
        float xa[16];
        uint32_t q[4];
        if (W_E2 == 1 && s >= 0) mbar_spin(BAR(B_E2TRIG), s & 1);
        TR(s, 7);
        constexpr int S1 = ORDER ? 0 : 2, S2 = ORDER == 0 ? 0 : ORDER == 1 ? 2 : 1, S3 = ORDER == 2 ? 2 : 1;
        if (ORDER) issue_qk<0, 16>(xa, wb, vary(dx, s, c.sb)); else issue_v(xa, wv, vary(dx, s, c.sb), vary(dh, s, c.sb));
        if (DLY_P) delay_until(tg0); else if (IS_F) sched_fence(c.sb);
        ldp(PL_0, PL_1, PL_D1);
        const uint32_t land = (t16 ^ ((t16 >> 3) & 0x60)) + vary(c.sb + SM_LAND + c.b * 4096, s, c.sb);
        TR(s, 14);
        if (LF_AT == 1) mbar_spin_if(BAR(B_LFREE), s & 1, s < 0); else if (!LF_AT) mbar_spin(BAR(B_LFREE), s & 1);
        TR(s, 15);
        late(0);
        WG_WAIT(0);
        TR(s, 8);
        park_own<S1 == 2>(q, xa, land, S1, c.sb);
        late(1);
        if (W_PUB == 4 && s >= 0) mbar_spin(BAR(B_PUB), s & 1);
        if (ORDER == 1) issue_v(xa, wv, vary(dx, s, c.sb + 32), vary(dh, s, c.sb)); else issue_qk<0, 16>(xa, ORDER ? wa : wb, vary(dx, s, c.sb + 32));
        if (IS_F) sched_fence(c.sb);
        ldp(PL_1, PL_2, PL_D1);
        if (W_PUB == 1) mbar_spin_if(BAR(B_PUB), s & 1, s >= 0);
        uint32_t tp = clock_lo(), q1[4] = {q[0], q[1], q[2], q[3]};
        if (PL_2B) ldp(PL_2, NP - PL_L, PL_D1);
        late(2);
        if (W_PUB != 3) park_peer(q, land, S1, c);
        if (!PL_2B) ldp(PL_2, NP - PL_L, PL_D1);
        late(3);
        TR(s, 13);
        WG_WAIT(0);
        TR(s, 9);
        park_own<S2 == 2>(q, xa, land, S2, c.sb);
        late(4);
        if (ORDER == 2) issue_v(xa, wv, vary(dx, s, c.sb + 64), vary(dh, s, c.sb));
        else {
          issue_qk<0, PL_L ? NP - PL_L : 16>(xa, wa, vary(dx, s, c.sb + 64));
          ldp(NP - PL_L, NP, PL_E);
          if (PL_L) issue_qk<NP - PL_L, 16>(xa, wa, vary(dx, s, c.sb + 64));
        }
        if ((W_PUB == 2 || W_PUB == 3) && s >= 0) { mbar_spin(BAR(B_PUB), s & 1); tp = clock_lo(); }
        if (W_PUB == 3) park_peer(q1, land, S1, c);
        if (DLY_S && s >= 0) delay_until(tp + DLY_S);
        park_peer(q, land, S2, c);
        WG_WAIT(0);
        TR(s, 10);
        mbar_arrive_warp(BAR(B_XEMPTY));
        park_own<S3 == 2>(q, xa, land, S3, c.sb);
        park_peer(q, land, S3, c);
        TR(s, 11);
      } else {
        if (s == NSEG - 1) break;
        if (EARLY2 && (XEND == NSEG || s == NSEG - 2) && c.m * 4 + c.w == 0) count_e(g_ctl + C_EARLY);
        ldp(PL_W, NP, 2);
      }
    }
    asm volatile("setmaxnreg.dec.sync.aligned.u32 %0;" :: "n"(BPRE == 2 ? 176 : 128));
    const int tid = tid_now(), lane = tid & 31, tile = tile_of(c), m0 = (tile >> 3) * 128, n0 = (tile & 7) * 128;
    float acc[64];
#pragma unroll
    for (int i = 0; i < 64; i++) acc[i] = 0.f;
    const uint32_t rel = mapa(BAR(B_GEMPTY), lane & 1), la = desc_lo(c.sb + c.m * 8192), lb = ((c.sb + 16384) & 0x3FFFF) >> 4 | (8192 >> 4) << 16;
    bool relon = false;
    const int skew = tile < 120 ? 0 : SKEW, kend = 64 + skew - c.m * skew, hold = c.m * (65 - LEAD) - 1;
    const float g0 = __ldcg(g_gate + m0 + (tid >> 5) * 16 + (lane >> 2)), g1 = __ldcg(g_gate + m0 + (tid >> 5) * 16 + (lane >> 2) + 8);
    uint32_t o = SM_XT, st = 0, ph = 0, prev = 0;
    if (tid == 0) TL(9);
    __syncwarp();
    GT(0);
#pragma unroll 1
    for (int kb = -c.m * skew; kb < max(kend - 4, 64); kb++, o = next_stage(o)) {
      if (LEAD && kb == hold) bar_sync(15, 256);
      mbar_lim(BAR(B_GFULL + st), ph);
      if ((uint32_t)kb < 64) {
        WG_FENCE();
#pragma unroll
        for (int k = 0; k < 4; k++) wgmma_ss_n128_tb(acc, desc128(la + (o >> 4) + k * 2), desc128(lb + (o >> 4) + k * 128));
        WG_COMMIT();
        WG_WAIT(1);
      } else WG_WAIT(0);
      arrive_remote_if(rel + 8 * prev, relon && kb < kend - 4);
      relon = (tid & 127) < 2;
      prev = st;
      if (++st == 5) { st = 0; ph ^= 1; }
    }
    if (LEAD && c.m == 0) asm volatile("bar.arrive 15, 256;" ::: "memory");
    const uint32_t row = (tid >> 5) * 2048 + (lane & 15) * 128 + (((lane >> 4) ^ (lane & 7)) << 4);
    if (!BPRE) WG_WAIT(0);
    mbar_lim(BAR(B_BT), 0);
    uint32_t b[2][4][4];
    const uint32_t rb = (tid >> 5) * 2048 + (lane >> 2) * 128 + (((lane & 7) ^ (lane >> 2)) << 4);
#pragma unroll
    for (int i = 0; i < 8; i++) lds_frag(b[i & 1][i >> 1], (rb ^ (i & 2) * 32) + (c.sb + SM_BT + (i >> 2) * 16384 + (i & 1) * 1024));
    float bl[2][4][4], bh[2][4][4];
    if (BPRE == 2) {
#pragma unroll
      for (int i = 0; i < 32; i++) {
        asm volatile("shl.b32 %0, %1, 16;" : "=f"(bl[i >> 4][i >> 2 & 3][i & 3]) : "r"(b[i >> 4][i >> 2 & 3][i & 3]));
        asm volatile("and.b32 %0, %1, 0xffff0000;" : "=f"(bh[i >> 4][i >> 2 & 3][i & 3]) : "r"(b[i >> 4][i >> 2 & 3][i & 3]));
      }
    }
    if (BPRE) { sched_fence(c.sb); WG_WAIT(0); sched_fence(c.sb); }
#pragma unroll
    for (int i = 0; i < 64; i++) asm volatile("" : "+f"(acc[i]) :: "memory");
    GT(17);
    if (tid == 0) TL(4);
    __syncwarp();
#pragma unroll
    for (int hf = 0; hf < 2; hf++) {
#pragma unroll
      for (int t = 0; t < 4; t++) {
        uint32_t y[4];
#pragma unroll
        for (int i = 0; i < 4; i++) {
          const float* a = acc + 32 * hf + 8 * t + 2 * i, g = i & 1 ? g1 : g0;
          const uint32_t* q = b[i & 1][2 * (t & 1) + (i >> 1)] + hf;
          const float* f = (t & 2 ? bh : bl)[i & 1][2 * (t & 1) + (i >> 1)] + hf;
          if (BPRE == 2) y[i] = pack_bf16(fmaf(g, a[0], f[0]), fmaf(g, a[1], f[2])); else
          y[i] = pack_bf16(fmaf(g, a[0], __uint_as_float(t & 2 ? q[0] & 0xFFFF0000u : q[0] << 16)), fmaf(g, a[1], __uint_as_float(t & 2 ? q[2] & 0xFFFF0000u : q[2] << 16)));
        }
        stsm4<false>((row ^ t * 32) + (c.sb + SM_BT + hf * 16384), y[0], y[1], y[2], y[3]);
      }
      if (EP_F && !hf) { sched_fence(c.sb); for (int i = 32; i < 64; i++) asm volatile("" : "+f"(acc[i]) :: "memory"); }
      FENCE_ASYNC_SMEM();
      __syncwarp();
      tma2d_out_e(&tout, n0 + hf * 64, m0 + (c.m * 4 + c.w) * 16, c.sb + SM_BT + hf * 16384 + (c.m * 4 + c.w) * 2048);
    }
    asm volatile("cp.async.bulk.commit_group; cp.async.bulk.wait_group" WAITRD " 0;" ::: "memory");
    GT(18);
    if ((tid & 127) == 0) TL(11);
    return;
  }
  constexpr int NH = NQ < 106 ? 4 * (106 - NQ) : 0;
  const bool col = c.r >= 128;
  const int tile = col ? 0 : tile_of(c);
  const int q0 = col ? 256 - NQ + (c.r - 128) + c.m * 4 : tile < 120 ? tile : 256, u = (tile >> 1 & 32) | (tile >> 3 & 7) | (tile & 6) << 2, e = QSH == 2 ? 2 * (u - (u > 39) - (u > 47) - (NQ < 110 && u > 55)) + c.b : tile,
            dq = col ? 16 : QSH ? 120 + (e < NH ? e >> 1 : (e + NH) >> 2) - tile : 120, qe = col ? 256 : 256 - NQ,
            qw = col || !QSH || (e < NH ? c.w >> 1 == c.b : c.w == ((e + NH) & 3)) ? qe : 120;
  const uint32_t zs = c.sb + (col ? COL_Z + c.m * 32768 : SM_BT), zb = BAR(B_Z + c.m);
  auto load_z = [&](int q) { if (c.w == 0 && q < qe) { mbar_expect_e(zb, 32768); tma2d_o<(ONCE & 4) != 0>(zs, &tz, q * 64, 0, zb); } };
  asm volatile("fence.proxy.async.global;" ::: "memory");
  load_z(q0);
  uint32_t ph = 0;
#pragma unroll 1
  for (int q = q0; q < qe; q += dq, ph ^= 1) {
    mbar_lim(zb, ph);
    const int p = q * 4 + c.w;
    if (EXP_INV && q < qw) fft_rows_inv(zs, (float2*)(smraw + (col ? 8192 + c.m * INV_BUF * 32 : SM_MEM)) + c.w * INV_BUF, (const float2*)(smraw + (col ? 0 : SM_TW)), p, tid_now() & 31, g_b,
                              [&]() { bar_sync(5 + c.m, 128); load_z(q + dq); });
    else { bar_sync(5 + c.m, 128); load_z(q + dq); }
  }
  if (B_ST) asm volatile("cp.async.bulk.wait_group 0; fence.proxy.async.global;" ::: "memory");
  asm volatile("fence.acq_rel.gpu;" ::: "memory");
  __syncwarp();
  { const int q = q0 + (tid_now() & 31) * dq; if (q < qw) asm volatile("red.relaxed.gpu.global.add.u32 [%0], 1;" :: "l"(g_ctl + C_ROWS + (q >> 5) * 32) : "memory"); }
  if (tid_now() == 256) { if (col) TL(27); else TL(3); }
  __syncwarp();
  if (!col && c.w == 0) {
    await_count<AW_NS>(g_ctl + C_ROWS + ((tile >> 3) & 7) * 32, 128);
    mbar_expect_e(BAR(B_BT), 32768);
    for (int i = 0; i < 2; i++) tma2d_o<(ONCE & 8) != 0>(c.sb + SM_BT + i * 16384, &tb, (tile & 7) * 128 + i * 64, (tile >> 3) * 128, BAR(B_BT));
    if (tid_now() == 256) TL(5);
  }
}

typedef CUresult (*EncodeFn)(CUtensorMap*, CUtensorMapDataType, cuuint32_t, void*, const cuuint64_t*, const cuuint64_t*,
                             const cuuint32_t*, const cuuint32_t*, CUtensorMapInterleave, CUtensorMapSwizzle,
                             CUtensorMapL2promotion, CUtensorMapFloatOOBfill);

void make_map(EncodeFn enc, CUtensorMap* tm, const void* p, int rank, const cuuint64_t* dims, const cuuint64_t* strides, const cuuint32_t* box, bool swz = true) {
  const cuuint32_t es[4] = {1, 1, 1, 1};
  enc(tm, CU_TENSOR_MAP_DATA_TYPE_BFLOAT16, rank, (void*)p, dims, strides, box, es, CU_TENSOR_MAP_INTERLEAVE_NONE,
      swz ? CU_TENSOR_MAP_SWIZZLE_128B : CU_TENSOR_MAP_SWIZZLE_NONE, swz ? CU_TENSOR_MAP_L2_PROMOTION_L2_128B : W_PROMO, CU_TENSOR_MAP_FLOAT_OOB_FILL_NONE);
}
void make_map2(EncodeFn enc, CUtensorMap* tm, const void* p, uint64_t cols, uint64_t rows, uint32_t boxrows) {
  const cuuint64_t dims[2] = {cols, rows}, strides[1] = {cols * 2};
  const cuuint32_t box[2] = {64, boxrows};
  make_map(enc, tm, p, 2, dims, strides, box);
}

}

extern "C" void kernel_launch(void* const* d_in, const int* in_sizes, int n_in, void* d_out, int out_size) {
  (void)in_sizes; (void)n_in; (void)out_size;
  const __nv_bfloat16* x = (const __nv_bfloat16*)d_in[0];
  const __nv_bfloat16* mem0 = (const __nv_bfloat16*)d_in[1];
  const __nv_bfloat16* gw = (const __nv_bfloat16*)d_in[10];

  EncodeFn enc = nullptr;
  cudaDriverEntryPointQueryResult qr;
  cudaGetDriverEntryPoint("cuTensorMapEncodeTiled", (void**)&enc, cudaEnableDefault, &qr);
  void *p_ox, *p_b, *p_z, *p_mail;
  cudaGetSymbolAddress(&p_ox, g_ox); cudaGetSymbolAddress(&p_b, g_b); cudaGetSymbolAddress(&p_z, g_z); cudaGetSymbolAddress(&p_mail, g_mail);
  CUtensorMap tq, tk, tv, tv16, to, tx, twr, twi, ta, tw, tb, tout, tz, tzs, ta32;
  make_map2(enc, &tq, d_in[2], 4096, 1024, 64);
  make_map2(enc, &tk, d_in[3], 4096, 1024, 64);
  make_map2(enc, &tv, d_in[4], 4096, 1024, 64);
  make_map2(enc, &tv16, d_in[4], 4096, 1024, 16);
  make_map2(enc, &to, d_in[5], 1024, 4096, 128);
  make_map2(enc, &tw, d_in[5], 1024, 4096, 64);
  {
    const cuuint64_t dims[3] = {64, 2048, 64}, strides[2] = {128, 262144};
    const cuuint32_t box[3] = {64, 32, 2}, box1[3] = {64, 32, 1};
    make_map(enc, &ta, p_ox, 3, dims, strides, box);
    make_map(enc, &ta32, p_ox, 3, dims, strides, box1);
  }
  make_map2(enc, &tb, p_b, 1024, 2048, 128);
  make_map2(enc, &tout, d_out, 1024, 2048, 16);
  make_map2(enc, &tz, p_z, 16384, 257, 256);
  {
    const cuuint64_t dims[4] = {64, 8, 16, 256}, strides[3] = {2048, 128, 16384};
    const cuuint32_t box[4] = {64, 8, 8, 2};
    make_map(enc, &tx, x, 4, dims, strides, box);
  }
  {
    const cuuint64_t dims[2] = {512, 257 * 32}, strides[1] = {1024};
    const cuuint32_t box[2] = {128, 16};
    make_map(enc, &tzs, p_z, 2, dims, strides, box, false);
  }
  {
    const cuuint64_t dims[2] = {8 * 513, 256}, strides[1] = {8 * 513 * 2};
    const cuuint32_t box[2] = {8, 256};
    make_map(enc, &twr, d_in[8], 2, dims, strides, box, false);
    make_map(enc, &twi, d_in[9], 2, dims, strides, box, false);
  }
  cudaFuncSetAttribute(chain_kernel, cudaFuncAttributeMaxDynamicSharedMemorySize, CHAIN_SMEM);

  cudaStream_t st = cudaStreamPerThread;
  char* mail = (char*)(((uintptr_t)p_mail + M_REG - 1) & ~(uintptr_t)(M_REG - 1));
  chain_kernel<<<132, 512, CHAIN_SMEM, st>>>(tq, tk, tv, tv16, to, tx, twr, twi, ta, tw, tb, tout, tz, tzs, ta32, mem0, mail, x, gw);
}
```

```cpp
#include <cuda_runtime.h>
#include <cuda_bf16.h>
#include <cuda.h>
#include <stdint.h>

#define DLY_E1 220
#define DLY_V 330
#define DLY_E2 300
#define DLY_E3 440
#define DLY_X 0
#define DLY_S 100
#define DLY_F 130
#define VM_AT 3
#define OM_F 1
#define C1_AT 5
#define NLAG 2
#define WO_D 2
#define WO_0 3
#define WO_1 11
#define PL_0 10
#define PL_1 11
#define PL_D 2
#define PL_L 0
#define HV_D 4
#define DLY_FK 0
#define REG_F 216
#define REG_H 24
#define SC_F 1
#define E2_F 0
#define X_AT 2
#define PL_2 11
#define PL_E 2
#define ORDER 1
#define SSPOS 1
#define W_PUB 1
#define FIN_AT 5
#define AWARE 1
#define NPROBE 2
#define NP_ 12
#define DLY_GRP 1000
#define EXP_CHK 1
#define EXP_NXT 2
#define EXP_PEER 1
#define EXP_FIN 7
#define EXP_NWG 16
#define ANCH2 1
#define IS_F 1
#define PL_D1 1
#define W_E2 0
#define V_TMA 2
#define V_W 0
#define RED_L 3
#define RED_T 1
#define RED_P 1
#define DLY_E3B 100
#define HV_E 2
#define HV_R 5
#define HOLD 0
#define PACE 500
#define PACE0 0
#define EXP_ST 7
#define WO_AT 38
#define WO_P 2
#define DLY_SEL 300
#define P1_AT 1
#define TMA_W tma2d_once
#define TMA_O tma2d_once
#define PACE_Z 580
#define EXP_INV 1
#define VF_AT 1
#define UP_F 0
#define WO_L (12 - NP_)
#define WO_C 4
#define WO_T 3
#define WO_LD 0
#define EXP_LIN 0
#define PL_W 5
#define PL_WA 10
#define PL_WD 0
#define PL_WF 2
#define EXP_FL 0
#define DLY_FS 0
#define DLY_F2 40
#define PF_D 4
#define PF_A 1
#define PF_B 0
#define SIDE 1
#define ROLE 1
#define E1OFF 1
#define EPI 0
#define WAITRD ".read"
#define START 1000
#define WUNR 1
#define WO_N 0
#define PL_2B 1
#define DLY_P 0
#define LP_IN 1
#define LF_AT 1
#define FINE 0
#define E30 1
#define WO_S 1
#define POOL_AT 12
#define COL_DLY 0
#define PAD0 2
#define PAD2 0
#define PAD3 6
#define WO_X 0
#define PRIOR 12
#define EARLY 1
#define SEL_AT 3000
#define FUNR 0
#define ZINIT 1
#define ZDLY 0
#define NQ 92
#define GATE 0
#define LASTM 1
#define X_ONCE 1
#define ONCE 31
#define Z_PF 0
#define EXP_W 1
#define W_PROMO CU_TENSOR_MAP_L2_PROMOTION_L2_128B
#define Z_ST 1
#define W_FINE 0
#define X128 2
#define T128_ 1
#define W_AT 0
#define SKEW 7
#define AW_NS 0
#define QSH 2
#define EARLY2 1
#define LEAD 3
#define BPRE 2
#define EP_F 1
#define TQ_AT 0
#define LAG_0 4
#define LAG_G 0
#define LAG_S 0
#define O_AT 0
#define XB 1
#define V_E 1
#define LAG_T 0
#define E3M 0
#define B_ST 1
#define TW_L 1
#define K_TMA 1
#define KL_AT 0
#define DLY_K 350
#define Q_TMA 0
#define Q_AT 2
#define IDLE 1
#define PL_AN 4
#define PL_A (PL_0 - PL_AN < PL_W ? PL_W : PL_0 - PL_AN)
#define ASY 1
#define ASY_AT 2
#define DLY_XL 0
#define SXP 1
#define DLY_SA 0
#define DLY_SB 0
#define XL_AT 1
#define DLY_Y 0
#define LX_AT 0
#define X_W 2
#define PL_BN 2
#define PL_B (PL_A + PL_BN > PL_0 ? PL_0 : PL_A + PL_BN)
#define ASY_A 0
#define PL_DA 3
#define PRE_AT B_SC

namespace {
constexpr int wunr = WUNR;

constexpr int S_ = 2048, D_ = 1024, NSEG = 64;
constexpr uint32_t SENT = 0xFFFFFFFFu;
constexpr int NSLOT = 4;

constexpr uint32_t M_REG = 1 << 21, M_E3 = 64 * 16384, M_KVQ = M_E3 + 4 * 8192, M_SEL = M_KVQ + 32 * 24576;
__device__ __align__(1024) unsigned char g_mail[5 * M_REG];
constexpr int C_P1 = 0, C_COLS = C_P1 + 32, C_EARLY = C_COLS + 32, C_LAST = C_EARLY + 32, C_ROWS = C_LAST + 128, C_END = C_ROWS + 8 * 32;
__device__ __align__(1024) uint32_t g_ctl[C_END];
#define CLK(i)
#define TL(i)
#define TL2(i)
#define FT(i, v)
#define GT(i)
#define CNT(i)
__device__ __align__(1024) __nv_bfloat16 g_ox[S_ * 4096];
__device__ __align__(1024) float2 g_z[257 * 4096];
__device__ __align__(1024) __nv_bfloat16 g_b[S_ * D_];
__device__ float g_gate[S_];
__device__ __align__(1024) float2 g_tw[1024];

#define TRV(s, ev, val)
#define TR(s, ev)
#define TRSYNC(ev)
__device__ __forceinline__ uint32_t smem_u32(const void* p) { return (uint32_t)__cvta_generic_to_shared(p); }
__device__ __forceinline__ void watchdog(uint32_t& n, uint32_t limit) {
  asm volatile("{ .reg .pred p; add.u32 %0, %0, 1; setp.gt.u32 p, %0, %1; @p trap; }" : "+r"(n) : "r"(limit));
}
__device__ __forceinline__ void mbar_init(uint32_t bar, uint32_t cnt) {
  asm volatile("mbarrier.init.shared::cta.b64 [%0], %1;" :: "r"(bar), "r"(cnt) : "memory");
}
__device__ __forceinline__ void mbar_arrive_warp(uint32_t bar) {
  __syncwarp();
  asm volatile("{ .reg .pred p; elect.sync _|p, 0xffffffff; @p mbarrier.arrive.shared::cta.b64 _, [%0]; }" :: "r"(bar) : "memory");
}
__device__ __forceinline__ uint32_t clock_lo() {
  uint32_t r; asm volatile("{ .reg .u64 c; .reg .u32 h; mov.u64 c, %%clock64; mov.b64 {%0, h}, c; }" : "=r"(r) :: "memory"); return r;
}
__device__ __forceinline__ void delay_until(uint32_t t) {
  asm volatile("{ .reg .pred p; .reg .u64 c; .reg .u32 l, h;\n"
               "DLY: mov.u64 c, %%clock64; mov.b64 {l, h}, c; sub.s32 l, l, %0; setp.lt.s32 p, l, 0; @p bra.uni DLY; }" :: "r"(t) : "memory");
}
__device__ __forceinline__ void delay_fine(uint32_t t) {
  delay_until(t);
}
__device__ __forceinline__ void delay_cycles(uint32_t n) { delay_until(clock_lo() + n); }
__device__ __forceinline__ void sched_fence(uint32_t z) {
  asm volatile("{ .reg .pred p; setp.eq.u32 p, %0, 0x7fff0000; @p pmevent 1; }" :: "r"(z) : "memory");
}
__device__ __forceinline__ void pdl_wait() { asm volatile("griddepcontrol.wait;" ::: "memory"); }
__device__ __forceinline__ void pdl_launch() { asm volatile("griddepcontrol.launch_dependents;" ::: "memory"); }
__device__ __forceinline__ float ex2(float x) { float r; asm("ex2.approx.ftz.f32 %0, %1;" : "=f"(r) : "f"(x)); return r; }
__device__ __forceinline__ float rcp(float x) { float r; asm("rcp.approx.ftz.f32 %0, %1;" : "=f"(r) : "f"(x)); return r; }
__device__ __forceinline__ void mbar_expect(uint32_t bar, uint32_t bytes) {
  asm volatile("mbarrier.arrive.expect_tx.shared::cta.b64 _, [%0], %1;" :: "r"(bar), "r"(bytes) : "memory");
}
__device__ __forceinline__ bool mbar_try(uint32_t bar, uint32_t ph) {
  uint32_t ok;
  asm volatile("{ .reg .pred p; mbarrier.try_wait.parity.shared::cta.b64 p, [%1], %2; selp.u32 %0, 1, 0, p; }"
               : "=r"(ok) : "r"(bar), "r"(ph) : "memory");
  return ok;
}
__device__ __forceinline__ void mbar_wait(uint32_t bar, uint32_t ph) {
  uint32_t n = 0;
  while (!mbar_try(bar, ph)) { watchdog(n, (1u << 20)); }
}
__device__ __forceinline__ void mbar_spin(uint32_t bar, uint32_t ph) { while (!mbar_try(bar, ph)) {} }
__device__ __forceinline__ void mbar_idle(uint32_t bar, uint32_t ph) {
  if (!IDLE) { mbar_wait(bar, ph); return; }
  asm volatile("{ .reg .pred q; SPN: mbarrier.try_wait.parity.shared::cta.b64 q, [%0], %1; @!q bra.uni SPN; }" :: "r"(bar), "r"(ph) : "memory");
}
__device__ __forceinline__ void mbar_spin_if(uint32_t bar, uint32_t ph, bool on) {
  asm volatile("{ .reg .pred p, q; setp.ne.u32 p, %2, 0;\n"
               "SPN: setp.eq.u32 q, 0, 0; @p mbarrier.try_wait.parity.shared::cta.b64 q, [%0], %1; @!q bra.uni SPN; }" :: "r"(bar), "r"(ph), "r"((uint32_t)on) : "memory");
}
__device__ __forceinline__ void mbar_spin2_if(uint32_t bar, uint32_t bar2, uint32_t ph, bool on) {
  asm volatile("{ .reg .pred p, q, r; setp.ne.u32 p, %3, 0;\n"
               "SPN: setp.eq.u32 q, 0, 0; setp.eq.u32 r, 0, 0; @p mbarrier.try_wait.parity.shared::cta.b64 q, [%0], %2;\n"
               "@p mbarrier.try_wait.parity.shared::cta.b64 r, [%1], %2; and.pred q, q, r; @!q bra.uni SPN; }" :: "r"(bar), "r"(bar2), "r"(ph), "r"((uint32_t)on) : "memory");
}
__device__ __forceinline__ void mbar_spin_cluster(uint32_t bar, uint32_t ph) {
  uint32_t ok;
  do {
    asm volatile("{ .reg .pred p; mbarrier.try_wait.parity.acquire.cluster.shared::cta.b64 p, [%1], %2; selp.u32 %0, 1, 0, p; }"
                 : "=r"(ok) : "r"(bar), "r"(ph) : "memory");
  } while (!ok);
}
#define ONCE_H "mov.b64 h, 0x12F0000000000000; "
__device__ __forceinline__ void tma2d(uint32_t dst, const CUtensorMap* tm, int c0, int c1, uint32_t bar) {
  if (ONCE & 32) asm volatile("{ .reg .b64 h; " ONCE_H "cp.async.bulk.tensor.2d.shared::cluster.global.mbarrier::complete_tx::bytes.L2::cache_hint [%0], [%1, {%3, %4}], [%2], h; }"
               :: "r"(dst), "l"(tm), "r"(bar), "r"(c0), "r"(c1) : "memory");
  else asm volatile("cp.async.bulk.tensor.2d.shared::cluster.global.mbarrier::complete_tx::bytes [%0], [%1, {%3, %4}], [%2];"
               :: "r"(dst), "l"(tm), "r"(bar), "r"(c0), "r"(c1) : "memory");
}
__device__ __forceinline__ void mbar_expect_e(uint32_t bar, uint32_t bytes) {
  asm volatile("{ .reg .pred p; elect.sync _|p, 0xffffffff; @p mbarrier.arrive.expect_tx.shared::cta.b64 _, [%0], %1; }" :: "r"(bar), "r"(bytes) : "memory");
}
__device__ __forceinline__ void tma2d_e(uint32_t dst, const CUtensorMap* tm, int c0, int c1, uint32_t bar) {
  asm volatile("{ .reg .pred p; elect.sync _|p, 0xffffffff;\n"
               "@p cp.async.bulk.tensor.2d.shared::cluster.global.mbarrier::complete_tx::bytes [%0], [%1, {%3, %4}], [%2]; }"
               :: "r"(dst), "l"(tm), "r"(bar), "r"(c0), "r"(c1) : "memory");
}
__device__ __forceinline__ void tma2d_st_e(const CUtensorMap* tm, int c0, int c1, uint32_t src) {
  asm volatile("{ .reg .pred p; elect.sync _|p, 0xffffffff;\n"
               "@p cp.async.bulk.tensor.2d.global.shared::cta.bulk_group [%0, {%2, %3}], [%1]; }" :: "l"(tm), "r"(src), "r"(c0), "r"(c1) : "memory");
}
__device__ __forceinline__ void tma2d_out_e(const CUtensorMap* tm, int c0, int c1, uint32_t src) {
  if (EPI) asm volatile("{ .reg .pred p; elect.sync _|p, 0xffffffff;\n"
               "@p cp.reduce.async.bulk.tensor.2d.global.shared::cta.add.bulk_group [%0, {%2, %3}], [%1]; }" :: "l"(tm), "r"(src), "r"(c0), "r"(c1) : "memory");
  else if (ONCE & 16) asm volatile("{ .reg .pred p; .reg .b64 h; " ONCE_H "elect.sync _|p, 0xffffffff;\n"
               "@p cp.async.bulk.tensor.2d.global.shared::cta.bulk_group.L2::cache_hint [%0, {%2, %3}], [%1], h; }" :: "l"(tm), "r"(src), "r"(c0), "r"(c1) : "memory");
  else asm volatile("{ .reg .pred p; elect.sync _|p, 0xffffffff;\n"
               "@p cp.async.bulk.tensor.2d.global.shared::cta.bulk_group [%0, {%2, %3}], [%1]; }" :: "l"(tm), "r"(src), "r"(c0), "r"(c1) : "memory");
}
__device__ __forceinline__ void tma2d_once(uint32_t dst, const CUtensorMap* tm, int c0, int c1, uint32_t bar) {
  asm volatile("{ .reg .pred p; .reg .b64 h; " ONCE_H "elect.sync _|p, 0xffffffff;\n"
               "@p cp.async.bulk.tensor.2d.shared::cluster.global.mbarrier::complete_tx::bytes.L2::cache_hint [%0], [%1, {%3, %4}], [%2], h; }"
               :: "r"(dst), "l"(tm), "r"(bar), "r"(c0), "r"(c1) : "memory");
}
__device__ __forceinline__ void bulk_once(uint32_t dst, const void* src, uint32_t bytes, uint32_t bar) {
  asm volatile("{ .reg .pred p; .reg .b64 h; " ONCE_H "elect.sync _|p, 0xffffffff;\n"
               "@p cp.async.bulk.shared::cluster.global.mbarrier::complete_tx::bytes.L2::cache_hint [%0], [%1], %2, [%3], h; }"
               :: "r"(dst), "l"(src), "r"(bytes), "r"(bar) : "memory");
}
__device__ __forceinline__ void tma4d_e(uint32_t dst, const CUtensorMap* tm, int c2, int c3, uint32_t bar) {
  asm volatile("{ .reg .pred p; .reg .b64 h; " ONCE_H "elect.sync _|p, 0xffffffff;\n"
               "@p cp.async.bulk.tensor.4d.shared::cluster.global.mbarrier::complete_tx::bytes.L2::cache_hint [%0], [%1, {0, 0, %3, %4}], [%2], h; }"
               :: "r"(dst), "l"(tm), "r"(bar), "r"(c2), "r"(c3) : "memory");
}
__device__ __forceinline__ void bulk_load_e(uint32_t dst, const void* src, uint32_t bytes, uint32_t bar) {
  asm volatile("{ .reg .pred p; elect.sync _|p, 0xffffffff;\n"
               "@p cp.async.bulk.shared::cluster.global.mbarrier::complete_tx::bytes [%0], [%1], %2, [%3]; }"
               :: "r"(dst), "l"(src), "r"(bytes), "r"(bar) : "memory");
}
template<bool O> __device__ __forceinline__ void tma2d_o(uint32_t dst, const CUtensorMap* tm, int c0, int c1, uint32_t bar) {
  if (O) tma2d_once(dst, tm, c0, c1, bar); else tma2d_e(dst, tm, c0, c1, bar);
}
__device__ __forceinline__ float2 ld_once(const float2* p) {
  float2 v;
  if (ONCE & 64) asm volatile("{ .reg .b64 h; " ONCE_H "ld.global.cg.L2::cache_hint.v2.f32 {%0, %1}, [%2], h; }" : "=f"(v.x), "=f"(v.y) : "l"(p));
  else v = __ldcg(p);
  return v;
}
template<bool O = false> __device__ __forceinline__ void prefetch2d_e(const CUtensorMap* tm, int c0, int c1) {
  if (O) asm volatile("{ .reg .pred p; .reg .b64 h; " ONCE_H "elect.sync _|p, 0xffffffff;\n"
               "@p cp.async.bulk.prefetch.tensor.2d.L2.global.L2::cache_hint [%0, {%1, %2}], h; }" :: "l"(tm), "r"(c0), "r"(c1) : "memory");
  else asm volatile("{ .reg .pred p; elect.sync _|p, 0xffffffff;\n"
               "@p cp.async.bulk.prefetch.tensor.2d.L2.global [%0, {%1, %2}]; }" :: "l"(tm), "r"(c0), "r"(c1) : "memory");
}
__device__ __forceinline__ void st_pub4(void* p, uint4 v) {
  asm volatile("st.relaxed.gpu.global.v4.u32 [%0], {%1,%2,%3,%4};" :: "l"(p), "r"(v.x), "r"(v.y), "r"(v.z), "r"(v.w) : "memory");
}
__device__ __forceinline__ void st_pub_if(void* p, uint32_t v, bool on) {
  asm volatile("{ .reg .pred p; setp.ne.u32 p, %2, 0; @p st.relaxed.gpu.global.u32 [%0], %1; }" :: "l"(p), "r"(v), "r"((uint32_t)on) : "memory");
}
__device__ __forceinline__ uint32_t mapa(uint32_t a, uint32_t r) {
  uint32_t d; asm volatile("mapa.shared::cluster.u32 %0, %1, %2;" : "=r"(d) : "r"(a), "r"(r)); return d;
}
__device__ __forceinline__ void st_async4(uint32_t a, uint32_t x, uint32_t y, uint32_t z, uint32_t w, uint32_t bar) {
  asm volatile("st.async.shared::cluster.mbarrier::complete_tx::bytes.v4.u32 [%0], {%1,%2,%3,%4}, [%5];"
               :: "r"(a), "r"(x), "r"(y), "r"(z), "r"(w), "r"(bar) : "memory");
}
__device__ __forceinline__ uint4 ld_poll(const void* p) {
  uint4 v;
  asm volatile("ld.volatile.global.v4.u32 {%0,%1,%2,%3}, [%4];" : "=r"(v.x), "=r"(v.y), "=r"(v.z), "=r"(v.w) : "l"(p) : "memory");
  return v;
}
__device__ __forceinline__ uint2 ld_poll2(const void* p) {
  uint2 v; asm volatile("ld.volatile.global.v2.u32 {%0,%1}, [%2];" : "=r"(v.x), "=r"(v.y) : "l"(p) : "memory"); return v;
}
__device__ __forceinline__ void st_pub2(void* p, uint32_t a, uint32_t b) {
  asm volatile("st.relaxed.gpu.global.v2.u32 [%0], {%1,%2};" :: "l"(p), "r"(a), "r"(b) : "memory");
}
__device__ __forceinline__ uint32_t ld_poll1(const void* p) {
  uint32_t v; asm volatile("ld.volatile.global.u32 %0, [%1];" : "=r"(v) : "l"(p) : "memory"); return v;
}
__device__ __forceinline__ uint32_t ld_acquire(const uint32_t* p) {
  uint32_t v; asm volatile("ld.acquire.gpu.global.u32 %0, [%1];" : "=r"(v) : "l"(p) : "memory"); return v;
}
__device__ __forceinline__ void st_pub(void* p, uint32_t v) {
  asm volatile("st.relaxed.gpu.global.u32 [%0], %1;" :: "l"(p), "r"(v) : "memory");
}
__device__ __forceinline__ uint32_t lds32(uint32_t a) {
  uint32_t v; asm volatile("ld.shared.u32 %0, [%1];" : "=r"(v) : "r"(a) : "memory"); return v;
}
__device__ __forceinline__ int race_init(void* p0, void* p1, uint32_t val) {
  int t;
  asm volatile("{ .reg .pred r; .reg .u32 a, b, u, v;\n"
               "atom.relaxed.gpu.global.exch.b32 u, [%1], %3; atom.relaxed.gpu.global.exch.b32 v, [%2], %3;\n"
               "setp.eq.u32 r, u, 0x12345; @r pmevent 1; mov.u32 a, %%clock;\n"
               "setp.eq.u32 r, v, 0x12345; @r pmevent 1; mov.u32 b, %%clock; sub.u32 %0, b, a; }" : "=r"(t) : "l"(p0), "l"(p1), "r"(val) : "memory");
  return t;
}
__device__ __forceinline__ void race_init2(void* p0, void* p1, uint32_t val) {
  asm volatile("{ .reg .pred r; .reg .u32 a, b, u, v;\n"
               "atom.relaxed.gpu.global.exch.b32 u, [%0], %2; atom.relaxed.gpu.global.exch.b32 v, [%1], %2;\n"
               "atom.relaxed.gpu.global.exch.b32 a, [%0 + 4096], %2; atom.relaxed.gpu.global.exch.b32 b, [%1 + 4096], %2;\n"
               "lop3.b32 u, u, v, a, 0x96; setp.eq.u32 r, u, 0x12345; setp.eq.and.u32 r, b, u, r; @r pmevent 1; }" :: "l"(p0), "l"(p1), "r"(val) : "memory");
}
__device__ __forceinline__ uint4 lds128(uint32_t a) {
  uint4 v; asm volatile("ld.shared.v4.u32 {%0,%1,%2,%3}, [%4];" : "=r"(v.x), "=r"(v.y), "=r"(v.z), "=r"(v.w) : "r"(a) : "memory"); return v;
}
__device__ __forceinline__ uint2 lds64(uint32_t a) {
  uint2 v; asm volatile("ld.shared.v2.u32 {%0,%1}, [%2];" : "=r"(v.x), "=r"(v.y) : "r"(a) : "memory"); return v;
}
__device__ __forceinline__ void sts128(uint32_t a, uint4 v) {
  asm volatile("st.shared.v4.u32 [%0], {%1,%2,%3,%4};" :: "r"(a), "r"(v.x), "r"(v.y), "r"(v.z), "r"(v.w) : "memory");
}
__device__ __forceinline__ void sts64(uint32_t a, uint32_t x, uint32_t y) { asm volatile("st.shared.v2.u32 [%0], {%1,%2};" :: "r"(a), "r"(x), "r"(y) : "memory"); }
__device__ __forceinline__ void sts32(uint32_t a, uint32_t x) { asm volatile("st.shared.u32 [%0], %1;" :: "r"(a), "r"(x) : "memory"); }
__device__ __forceinline__ void ldsm4t(uint32_t (&r)[4], uint32_t a) {
  asm volatile("ldmatrix.sync.aligned.m8n8.x4.trans.shared.b16 {%0,%1,%2,%3}, [%4];"
               : "=r"(r[0]), "=r"(r[1]), "=r"(r[2]), "=r"(r[3]) : "r"(a) : "memory");
}
__device__ __forceinline__ void ldsm4(uint32_t (&r)[4], uint32_t a) {
  asm volatile("ldmatrix.sync.aligned.m8n8.x4.shared.b16 {%0,%1,%2,%3}, [%4];"
               : "=r"(r[0]), "=r"(r[1]), "=r"(r[2]), "=r"(r[3]) : "r"(a) : "memory");
}
template<bool TRANS> __device__ __forceinline__ void stsm4(uint32_t a, uint32_t r0, uint32_t r1, uint32_t r2, uint32_t r3) {
  if (TRANS) asm volatile("stmatrix.sync.aligned.m8n8.x4.trans.shared.b16 [%0], {%1,%2,%3,%4};" :: "r"(a), "r"(r0), "r"(r1), "r"(r2), "r"(r3) : "memory");
  else       asm volatile("stmatrix.sync.aligned.m8n8.x4.shared.b16 [%0], {%1,%2,%3,%4};" :: "r"(a), "r"(r0), "r"(r1), "r"(r2), "r"(r3) : "memory");
}
__device__ __forceinline__ void mma16816(float (&d)[4], uint32_t a0, uint32_t a1, uint32_t a2, uint32_t a3, uint32_t b0, uint32_t b1) {
  asm volatile("mma.sync.aligned.m16n8k16.row.col.f32.bf16.bf16.f32 {%0,%1,%2,%3}, {%4,%5,%6,%7}, {%8,%9}, {%0,%1,%2,%3};"
               : "+f"(d[0]), "+f"(d[1]), "+f"(d[2]), "+f"(d[3]) : "r"(a0), "r"(a1), "r"(a2), "r"(a3), "r"(b0), "r"(b1));
}
__device__ __forceinline__ void mma1688(float (&d)[4], uint32_t a0, uint32_t a1, uint32_t b0) {
  asm volatile("mma.sync.aligned.m16n8k8.row.col.f32.bf16.bf16.f32 {%0,%1,%2,%3}, {%4,%5}, {%6}, {%0,%1,%2,%3};"
               : "+f"(d[0]), "+f"(d[1]), "+f"(d[2]), "+f"(d[3]) : "r"(a0), "r"(a1), "r"(b0));
}
__device__ __forceinline__ uint32_t pack_bf16(float lo, float hi) {
  uint32_t r; asm("cvt.rn.bf16x2.f32 %0, %1, %2;" : "=r"(r) : "f"(hi), "f"(lo)); return r;
}
__device__ __forceinline__ uint32_t add_bf16x2(uint32_t a, uint32_t b) {
  uint32_t r; asm("add.rn.bf16x2 %0, %1, %2;" : "=r"(r) : "r"(a), "r"(b)); return r;
}
__device__ __forceinline__ uint32_t umax4(uint4 v) { return max(max(v.x, v.y), max(v.z, v.w)); }
__device__ __forceinline__ uint32_t opaque(uint32_t x) { uint32_t r; asm volatile("mov.u32 %0, %1;" : "=r"(r) : "r"(x)); return r; }
template<class T> __device__ __forceinline__ void pin(T*& p) { asm volatile("" : "+l"(p)); }
__device__ __forceinline__ void pin(uint32_t& v) { asm volatile("" : "+r"(v)); }
__device__ __forceinline__ uint32_t desc_lo(uint32_t addr) { return ((addr & 0x3FFFF) >> 4) | 0x10000; }
__device__ __forceinline__ uint64_t desc128(uint32_t lo) {
  uint64_t d; asm("mov.b64 %0, {%1, %2};" : "=l"(d) : "r"(lo), "r"(0x40000040)); return d;
}
#define WG_FENCE()  asm volatile("wgmma.fence.sync.aligned;" ::: "memory")
#define WG_COMMIT() asm volatile("wgmma.commit_group.sync.aligned;" ::: "memory")
#define WG_WAIT(n)  asm volatile("wgmma.wait_group.sync.aligned " #n ";" ::: "memory")
#define FENCE_ASYNC_SMEM() asm volatile("fence.proxy.async.shared::cta;" ::: "memory")
__device__ __forceinline__ void bar_sync(int id, int n) { asm volatile("bar.sync %0, %1;" :: "r"(id), "r"(n) : "memory"); }

#define D16(c) c(d[0]), c(d[1]), c(d[2]), c(d[3]), c(d[4]), c(d[5]), c(d[6]), c(d[7]), \
               c(d[8]), c(d[9]), c(d[10]), c(d[11]), c(d[12]), c(d[13]), c(d[14]), c(d[15])
template<bool FIRST> __device__ __forceinline__ void wgmma_rs_n32(float (&d)[16], const uint32_t (&a)[4], uint64_t b) {
  if (FIRST)
    asm volatile("wgmma.mma_async.sync.aligned.m64n32k16.f32.bf16.bf16 {%0,%1,%2,%3,%4,%5,%6,%7,%8,%9,%10,%11,%12,%13,%14,%15}, {%16,%17,%18,%19}, %20, 0, 1, 1, 0;"
      : D16("=f") : "r"(a[0]), "r"(a[1]), "r"(a[2]), "r"(a[3]), "l"(b));
  else
    asm volatile("wgmma.mma_async.sync.aligned.m64n32k16.f32.bf16.bf16 {%0,%1,%2,%3,%4,%5,%6,%7,%8,%9,%10,%11,%12,%13,%14,%15}, {%16,%17,%18,%19}, %20, 1, 1, 1, 0;"
      : D16("+f") : "r"(a[0]), "r"(a[1]), "r"(a[2]), "r"(a[3]), "l"(b));
}
template<bool FIRST> __device__ __forceinline__ void wgmma_ss_n32_ta(float (&d)[16], uint64_t a, uint64_t b) {
  if (FIRST)
    asm volatile("wgmma.mma_async.sync.aligned.m64n32k16.f32.bf16.bf16 {%0,%1,%2,%3,%4,%5,%6,%7,%8,%9,%10,%11,%12,%13,%14,%15}, %16, %17, 0, 1, 1, 1, 0;"
      : D16("=f") : "l"(a), "l"(b));
  else
    asm volatile("wgmma.mma_async.sync.aligned.m64n32k16.f32.bf16.bf16 {%0,%1,%2,%3,%4,%5,%6,%7,%8,%9,%10,%11,%12,%13,%14,%15}, %16, %17, 1, 1, 1, 1, 0;"
      : D16("+f") : "l"(a), "l"(b));
}
__device__ __forceinline__ void wgmma_ss_n128_tb(float (&d)[64], uint64_t a, uint64_t b) {
  asm volatile("wgmma.mma_async.sync.aligned.m64n128k16.f32.bf16.bf16 "
    "{%0,%1,%2,%3,%4,%5,%6,%7,%8,%9,%10,%11,%12,%13,%14,%15,%16,%17,%18,%19,%20,%21,%22,%23,%24,%25,%26,%27,%28,%29,%30,%31,"
    "%32,%33,%34,%35,%36,%37,%38,%39,%40,%41,%42,%43,%44,%45,%46,%47,%48,%49,%50,%51,%52,%53,%54,%55,%56,%57,%58,%59,%60,%61,%62,%63}, "
    "%64, %65, 1, 1, 1, 0, 1;"
    : "+f"(d[0]), "+f"(d[1]), "+f"(d[2]), "+f"(d[3]), "+f"(d[4]), "+f"(d[5]), "+f"(d[6]), "+f"(d[7]),
      "+f"(d[8]), "+f"(d[9]), "+f"(d[10]), "+f"(d[11]), "+f"(d[12]), "+f"(d[13]), "+f"(d[14]), "+f"(d[15]),
      "+f"(d[16]), "+f"(d[17]), "+f"(d[18]), "+f"(d[19]), "+f"(d[20]), "+f"(d[21]), "+f"(d[22]), "+f"(d[23]),
      "+f"(d[24]), "+f"(d[25]), "+f"(d[26]), "+f"(d[27]), "+f"(d[28]), "+f"(d[29]), "+f"(d[30]), "+f"(d[31]),
      "+f"(d[32]), "+f"(d[33]), "+f"(d[34]), "+f"(d[35]), "+f"(d[36]), "+f"(d[37]), "+f"(d[38]), "+f"(d[39]),
      "+f"(d[40]), "+f"(d[41]), "+f"(d[42]), "+f"(d[43]), "+f"(d[44]), "+f"(d[45]), "+f"(d[46]), "+f"(d[47]),
      "+f"(d[48]), "+f"(d[49]), "+f"(d[50]), "+f"(d[51]), "+f"(d[52]), "+f"(d[53]), "+f"(d[54]), "+f"(d[55]),
      "+f"(d[56]), "+f"(d[57]), "+f"(d[58]), "+f"(d[59]), "+f"(d[60]), "+f"(d[61]), "+f"(d[62]), "+f"(d[63])
    : "l"(a), "l"(b));
}

__device__ __forceinline__ void tma3d_mc_e(uint32_t dst, const CUtensorMap* tm, int c1, int c2, uint32_t bar) {
  asm volatile("{ .reg .pred p; .reg .b64 h; " ONCE_H "elect.sync _|p, 0xffffffff;\n"
               "@p cp.async.bulk.tensor.3d.shared::cluster.global.mbarrier::complete_tx::bytes.multicast::cluster.L2::cache_hint [%0], [%1, {0, %3, %4}], [%2], %5, h; }"
               :: "r"(dst), "l"(tm), "r"(bar), "r"(c1), "r"(c2), "h"((uint16_t)3) : "memory");
}
__device__ __forceinline__ void prefetch3d_e(const CUtensorMap* tm, int c1, int c2) {
  asm volatile("{ .reg .pred p; elect.sync _|p, 0xffffffff;\n"
               "@p cp.async.bulk.prefetch.tensor.3d.L2.global [%0, {0, %1, %2}]; }" :: "l"(tm), "r"(c1), "r"(c2) : "memory");
}

__device__ __forceinline__ void count_e(uint32_t* p) {
  asm volatile("fence.acq_rel.gpu;" ::: "memory");
  __syncwarp();
  asm volatile("{ .reg .pred p; elect.sync _|p, 0xffffffff; @p red.relaxed.gpu.global.add.u32 [%0], 1; }" :: "l"(p) : "memory");
}
template<int NS = 0> __device__ __forceinline__ void await_count(const uint32_t* p, uint32_t n) {
  for (uint32_t i = 0; ld_acquire(p) < n && i < (1u << 22); i++) { if (NS) __nanosleep(NS); }
  asm volatile("fence.proxy.async.global;" ::: "memory");
}
__device__ __forceinline__ void await_flags(const uint32_t* p) {
  for (uint32_t i = 0; i < (1u << 22); i++) {
    uint4 v;
    asm volatile("ld.acquire.gpu.global.v4.u32 {%0,%1,%2,%3}, [%4];" : "=r"(v.x), "=r"(v.y), "=r"(v.z), "=r"(v.w) : "l"(p) : "memory");
    if (__all_sync(~0u, (v.x & v.y & v.z & v.w) == 0x01010101u)) break;
  }
  asm volatile("fence.proxy.async.global;" ::: "memory");
}
__device__ __forceinline__ void mbar_lim(uint32_t bar, uint32_t ph) { for (uint32_t i = 0; !mbar_try(bar, ph) && i < (1u << 20); i++) {} }

struct cf { float x, y; };
__host__ __device__ constexpr float cos64(int k) {
  return k == 0 ? 1.0f : k == 1 ? 0.99518472667219689f : k == 2 ? 0.98078528040323045f : k == 3 ? 0.95694033573220887f :
         k == 4 ? 0.92387953251128676f : k == 5 ? 0.88192126434835503f : k == 6 ? 0.83146961230254524f : k == 7 ? 0.77301045336273696f :
         k == 8 ? 0.70710678118654752f : k == 9 ? 0.63439328416364550f : k == 10 ? 0.55557023301960222f : k == 11 ? 0.47139673682599765f :
         k == 12 ? 0.38268343236508977f : k == 13 ? 0.29028467725446236f : k == 14 ? 0.19509032201612827f : k == 15 ? 0.09801714032956060f : 0.0f;
}
__host__ __device__ constexpr float c64(int k) { return k <= 16 ? cos64(k) : -cos64(32 - k); }
__host__ __device__ constexpr float s64(int k) { return k <= 16 ? cos64(16 - k) : cos64(k - 16); }

template<int N, int ST, bool INV> struct Fft {
  template<int K> static __device__ __forceinline__ void bf(const cf* e, const cf* o, cf* out) {
    if constexpr (K < N / 2) {
      constexpr int idx = K * (64 / N);
      const cf a = e[K], b = o[K];
      if constexpr (idx == 0) {
        out[K] = {a.x + b.x, a.y + b.y}; out[K + N / 2] = {a.x - b.x, a.y - b.y};
      } else if constexpr (idx == 16) {
        if constexpr (INV) { out[K] = {a.x - b.y, a.y + b.x}; out[K + N / 2] = {a.x + b.y, a.y - b.x}; }
        else               { out[K] = {a.x + b.y, a.y - b.x}; out[K + N / 2] = {a.x - b.y, a.y + b.x}; }
      } else {
        constexpr float c = c64(idx), s = INV ? s64(idx) : -s64(idx);
        cf p; p.x = fmaf(-s, b.y, fmaf(c, b.x, a.x)); p.y = fmaf(s, b.x, fmaf(c, b.y, a.y));
        out[K] = p; out[K + N / 2] = {fmaf(2.0f, a.x, -p.x), fmaf(2.0f, a.y, -p.y)};
      }
      bf<K + 1>(e, o, out);
    }
  }
  static __device__ __forceinline__ void run(const cf* in, cf* out) {
    cf e[N / 2], o[N / 2];
    Fft<N / 2, 2 * ST, INV>::run(in, e);
    Fft<N / 2, 2 * ST, INV>::run(in + ST, o);
    bf<0>(e, o, out);
  }
};
template<int ST, bool INV> struct Fft<1, ST, INV> {
  static __device__ __forceinline__ void run(const cf* in, cf* out) { out[0] = in[0]; }
};
template<bool INV> __device__ __forceinline__ void fft32(cf (&v)[32]) {
  cf o[32]; Fft<32, 1, INV>::run(v, o);
#pragma unroll
  for (int i = 0; i < 32; i++) v[i] = o[i];
}
__device__ __forceinline__ cf cmul(cf a, float c, float s) { return {fmaf(-a.y, s, a.x * c), fmaf(a.x, s, a.y * c)}; }
__device__ __forceinline__ float bf2f(__nv_bfloat16 v) { return __bfloat162float(v); }

__device__ __forceinline__ int tw_at(int i) { return (i & ~63) | (i & 31) << 1 | (i >> 5 & 1); }
template<bool INV, bool T128 = true> __device__ __forceinline__ void twiddles(cf (&v)[32], const float4* __restrict__ tw) {
#pragma unroll
  for (int j = 0; j < 32; j += 2) {
    float4 w;
    if (T128) w = tw[j * 16];
    else { const uint2 a = lds64(smem_u32(tw + j * 16)), b = lds64(smem_u32(tw + j * 16) + 8); w = make_float4(__uint_as_float(a.x), __uint_as_float(a.y), __uint_as_float(b.x), __uint_as_float(b.y)); }
    if (j) v[j] = cmul(v[j], w.x, INV ? -w.y : w.y);
    v[j + 1] = cmul(v[j + 1], w.z, INV ? -w.w : w.w);
  }
}
template<bool INV, class F> __device__ __forceinline__ void warp_fft1024(cf (&v)[32], float2* __restrict__ buf, const float2* __restrict__ tw, int t, int u, F mid) {
#pragma unroll 1
  for (uint32_t h = 0; h < 2; h++) {
    fft32<INV>(v);
    if (FUNR ? h : opaque(h)) continue;
    twiddles<INV>(v, (const float4*)tw + u);
    if (INV) {
      float* f = (float*)buf;
#pragma unroll
      for (int j = 0; j < 32; j++) f[j * 36 + t] = v[j].x;
      __syncwarp();
#pragma unroll
      for (int j = 0; j < 32; j += 4) { const float4 r = *(const float4*)(f + u * 36 + j); v[j].x = r.x; v[j + 1].x = r.y; v[j + 2].x = r.z; v[j + 3].x = r.w; }
      __syncwarp();
#pragma unroll
      for (int j = 0; j < 32; j++) f[j * 36 + t] = v[j].y;
      __syncwarp();
#pragma unroll
      for (int j = 0; j < 32; j += 4) { const float4 r = *(const float4*)(f + u * 36 + j); v[j].y = r.x; v[j + 1].y = r.y; v[j + 2].y = r.z; v[j + 3].y = r.w; }
    } else {
#pragma unroll
      for (int j = 0; j < 32; j++) buf[j * 33 + t] = make_float2(v[j].x, v[j].y);
      __syncwarp();
#pragma unroll
      for (int j = 0; j < 32; j++) { const float2 r = buf[u * 33 + j]; v[j] = {r.x, r.y}; }
    }
    __syncwarp();
    mid();
  }
}
constexpr int ROW_BUF = 32 * 33, INV_BUF = 32 * 18;

__device__ __forceinline__ int z_row(int p) { return (p & ~31) | (p & 7) << 2 | (p & 31) >> 3; }
__device__ __forceinline__ int inv_lane(int t) { return (t & ~14) | (t & 12) >> 1 | (t & 2) << 2; }
__device__ __forceinline__ float2 twiddle(int i) { float s, c; sincospif(-(float)((i >> 5) * (i & 31)) * (1.0f / 512.0f), &s, &c); return make_float2(c, s); }
template<class F, class G> __device__ __forceinline__ void fft_rows_fwd(float2* sm2, const __nv_bfloat16* gw, int cta, int tid, uint32_t full_bar, uint32_t release_bar, F ev, G extra) {
  const int t = tid & 31, w = tid >> 5, n = z_row(cta * 8 + w);
#pragma unroll 1
  for (int i = tid; i < 1024; i += 256) sm2[tw_at(i)] = twiddle(i);
  ev(5);
  mbar_spin(full_bar, 0);
  if (tid == 0) TL2(6);
  __syncwarp();
  const __nv_bfloat16* xa = (const __nv_bfloat16*)(sm2 + 1024 + w * ROW_BUF) + t;
  cf v[32];
  float ga = 0.f, gb = 0.f;
#pragma unroll
  for (int j = 0; j < 32; j++) {
    v[j] = {bf2f(xa[32 * j]), bf2f(xa[D_ + 32 * j])};
    const float g = bf2f(gw[32 * j + t]); ga = fmaf(v[j].x, g, ga); gb = fmaf(v[j].y, g, gb);
  }
#pragma unroll
  for (int o = 16; o; o >>= 1) { ga += __shfl_xor_sync(~0u, ga, o); gb += __shfl_xor_sync(~0u, gb, o); }
  if (t < 2) g_gate[n + 1024 * t] = __fdividef(1.0f, 1.0f + __expf(-(t ? gb : ga)));
  ev(6);
  bar_sync(13, 256);
  warp_fft1024<false>(v, sm2 + 1024 + w * ROW_BUF, sm2, t, t, [&]() { FENCE_ASYNC_SMEM(); mbar_arrive_warp(release_bar); });
  float ws, wc; sincospif(-(float)n * (1.0f / 1024.0f), &ws, &wc);
  ev(12);
  uint32_t tz = clock_lo();
  float4* z = (float4*)g_z + ((size_t)(t >> 1) * 1024 + cta * 8 + w) * 2 + (t & 1);
#pragma unroll
  for (int j = 0; j < 17; j++) {
    cf q = v[(32 - j) & 31];
    if (j < 16) {
      const cf r = {__shfl_sync(~0u, v[31 - j].x, 32 - t), __shfl_sync(~0u, v[31 - j].y, 32 - t)};
      if (t != 0) q = r;
    }
    const cf a = {v[j].x + q.x, v[j].y - q.y}, b = {v[j].y + q.y, q.x - v[j].x};
    const cf d = cmul({a.x - b.x, a.y - b.y}, wc, ws);
    if (j == POOL_AT) extra();
    if (PACE_Z && j && j < 16) delay_until(tz += PACE_Z);
    if ((j < 16 || t == 0) && ((EXP_ST & 4) || d.x == 123.f)) z[j * 32768] = make_float4(a.x + b.x, a.y + b.y, d.x, d.y);
  }
}
constexpr int CP = X128 == 0 ? 33 : X128 == 2 ? 34 : 36, COL_FS = 32 * 36 + 8, COL_W = (8192 + 16 * COL_FS * 4 + 127) & ~127, COL_SMEM = COL_W + 131072 + 128;

__device__ __forceinline__ void fft_cols(float2* sm2, int cta, const CUtensorMap* twr, const CUtensorMap* twi, const CUtensorMap* tzs) {
  const int grp = __shfl_sync(~0u, (int)(threadIdx.x >> 7), 0), tid = threadIdx.x & 127, tp = tid >> 2, w = __shfl_sync(~0u, tid >> 5, 0);
  float* buf = (float*)(sm2 + 1024) + (grp * 4 + (tid & 3)) * COL_FS;
  const uint32_t wsm = smem_u32(sm2) + COL_W, wbar = wsm + 131072 + (W_FINE ? w * 32 : 0);
  const int res = w * 2 + (tid & 1), el = res + grp * 2 + ((tid >> 1) & 1);
  uint32_t wa = (el >> 3) * 65536 + res * 4096 + (tp & 7) * 16 + (el & 7) * 2;
  auto load_w = [&](int q) {
    const uint32_t bar = wbar + (q & 1) * 8;
    mbar_expect(bar, W_FINE ? 16384 : 65536);
#pragma unroll 1
    for (int i = W_FINE ? 4 * w : 0; i < (W_FINE ? 4 * w + 4 : 16); i++) tma2d(wsm + (q & 1) * 65536 + (i & 1) * 32768 + (i >> 1) * 4096, i & 1 ? twi : twr, (i >> 1) * 512 + q * 8, 0, bar);
  };
  const bool lead = (tid & (W_FINE ? 31 : 127)) == 0, first = grp < 2 && lead;
  if (first) { mbar_init(wbar + grp * 8, 1); sts32(wbar + 16 + grp * 4, grp ? 0 : w); asm volatile("fence.mbarrier_init.release.cluster;" ::: "memory"); }
#pragma unroll 1
  for (int i = threadIdx.x; i < 1024; i += 512) {
    const float2 t = twiddle(z_row(i));
    sm2[tw_at(i)] = t;
    if (cta == 0) g_tw[tw_at(inv_lane(z_row(i)))] = t;
  }
  for (uint32_t n = 0; ld_acquire(g_ctl + C_P1) < 128; ) { watchdog(n, 1u << 22); __nanosleep(200); }
  if (COL_DLY) delay_cycles(COL_DLY);
  if (first) load_w(cta * 16 + grp);
  __syncthreads();
  delay_cycles(1 + grp * DLY_GRP);
  mbar_wait(wbar, 0);
  const int end = cta * 64 + 64 + (cta == 3);
  for (int item = cta * 64 + grp; item < end; item += 4, wa ^= 65536) {
    float2* zp = g_z + (size_t)item * 4096;
    auto next_w = [&]() {
      const int q = (item >> 2) + (W_FINE && grp + w > 3);
      uint32_t n; asm volatile("atom.shared.inc.u32 %0, [%1], 3;" : "=r"(n) : "r"(wbar + 16 + (q & 1) * 4) : "memory");
      if (EXP_W && n == 3 && q < (cta * 16 + 15)) load_w(q + 2);
    };
    cf v[32];
#pragma unroll
    for (int j = 0; j < 32; j++) { const float2 a = ld_once(zp + tid + j * 128); v[j] = {a.x, a.y}; }
#pragma unroll 1
    for (int ph = 0; ; ph++) {
      fft32<false>(v);
      twiddles<false, T128_>(v, (const float4*)sm2 + tp);
      if (Z_ST) asm volatile("cp.async.bulk.wait_group.read 0;" ::: "memory");
      bar_sync(1 + grp, 128);
      if (lead) {
        if (ph) {
          if (!W_AT) next_w();
        } else if (Z_PF && item + 4 < end) asm volatile("cp.async.bulk.prefetch.L2.global [%0], %1;" :: "l"(zp + 4 * 4096 + w * 1024), "n"(W_FINE ? 8192 : 32768) : "memory");
      }
      __syncwarp();
#pragma unroll
      for (int j = 0; j < 32; j++) buf[((j & 3) * 8 + (j >> 2)) * CP + tp] = v[j].x;
      bar_sync(1 + grp, 128);
      if (X128 == 0) {
#pragma unroll
        for (int j = 0; j < 32; j++) v[j].x = buf[tp * CP + (j & 3) * 8 + (j >> 2)];
      } else if (X128 == 2) {
#pragma unroll
        for (int j = 0; j < 16; j++) { const float2 r = *(const float2*)(buf + tp * CP + 2 * j); cf* d = v + (j & 3) * 8 + (j >> 2); d[0].x = r.x; d[4].x = r.y; }
      } else
#pragma unroll
      for (int j = 0; j < 8; j++) {
        const float4 r = *(const float4*)(buf + tp * 36 + 4 * j);
        cf* d = v + (j & 1) * 16 + (j >> 1);
        d[0].x = r.x; d[4].x = r.y; d[8].x = r.z; d[12].x = r.w;
      }
      bar_sync(1 + grp, 128);
#pragma unroll
      for (int j = 0; j < 32; j++) buf[((j & 3) * 8 + (j >> 2)) * CP + tp] = v[j].y;
      bar_sync(1 + grp, 128);
      if (X128 == 0) {
#pragma unroll
        for (int j = 0; j < 32; j++) v[j].y = buf[tp * CP + (j & 3) * 8 + (j >> 2)];
      } else if (X128 == 2) {
#pragma unroll
        for (int j = 0; j < 16; j++) { const float2 r = *(const float2*)(buf + tp * CP + 2 * j); cf* d = v + (j & 3) * 8 + (j >> 2); d[0].y = r.x; d[4].y = r.y; }
      } else
#pragma unroll
      for (int j = 0; j < 8; j++) {
        const float4 r = *(const float4*)(buf + tp * 36 + 4 * j);
        cf* d = v + (j & 1) * 16 + (j >> 1);
        d[0].y = r.x; d[4].y = r.y; d[8].y = r.z; d[12].y = r.w;
      }
      fft32<false>(v);
      if (ph) break;
      const int q = min((item >> 2) + (!W_FINE || grp + w >= 3), 64);
      if (EXP_W) mbar_wait(wbar + (q & 1) * 8, (q >> 1) & 1);
#pragma unroll
      for (int j = 0; j < 32; j++) {
        uint32_t re, im;
        asm volatile("ld.shared.u16 %0, [%1];" : "=r"(re) : "r"(wsm + wa + j * 128) : "memory");
        asm volatile("ld.shared.u16 %0, [%1];" : "=r"(im) : "r"(wsm + wa + 32768 + j * 128) : "memory");
        const cf r = cmul(v[j], __uint_as_float(re << 16), __uint_as_float(im << 16));
        v[j] = {r.y, r.x};
      }
    }
    if (Z_ST) {
      float2* st = sm2 + 1024 + grp * (COL_FS * 2) + w * 512;
      bar_sync(1 + grp, 128);
#pragma unroll
      for (int h = 0; h < 2; h++) {
        if (h && Z_ST == 2) {
#pragma unroll
          for (int j = 16; j < 32; j++) zp[tid + j * 128] = make_float2(v[j].y, v[j].x);
          break;
        }
        if (h) { asm volatile("cp.async.bulk.wait_group.read 0;" ::: "memory"); __syncwarp(); }
#pragma unroll
        for (int j = 0; j < 16; j++) st[j * 32 + (tid & 31)] = make_float2(v[h * 16 + j].y, v[h * 16 + j].x);
        FENCE_ASYNC_SMEM();
        __syncwarp();
        tma2d_st_e(tzs, w * 128, item * 32 + h * 16, smem_u32(st));
        asm volatile("cp.async.bulk.commit_group;" ::: "memory");
      }
    } else {
#pragma unroll
      for (int j = 0; j < 32; j++) zp[tid + j * 128] = make_float2(v[j].y, v[j].x);
    }
    if (W_AT) { if (lead) next_w(); __syncwarp(); }
  }
  if (Z_ST) asm volatile("cp.async.bulk.wait_group 0; fence.proxy.async.global;" ::: "memory");
  const float4 t = ((const float4*)sm2)[threadIdx.x];
  __syncthreads();
  if (TW_L) ((float4*)sm2)[inv_lane(z_row(threadIdx.x))] = t;
  if (threadIdx.x < 32) {
    count_e(g_ctl + C_COLS);
    await_count(g_ctl + C_COLS, 4);
    g_ctl[C_P1] = 0;
  }
  __syncthreads();
  if (!TW_L) {
    ((float4*)sm2)[threadIdx.x] = __ldcg((const float4*)g_tw + threadIdx.x);
    __syncthreads();
  }
}

template<class F> __device__ __forceinline__ void fft_rows_inv(uint32_t zs, float2* buf, const float2* tw, int p, int lane, __nv_bfloat16* out, F read) {
  const int n = z_row(p), t = (lane & 17) | (lane & 6) << 1 | (lane & 8) >> 2, src = inv_lane(-t & 31);
  const uint32_t z = zs + (t >> 1) * 128 + ((((p & 3) * 2 + (t & 1)) ^ (t >> 1 & 7)) << 4);
  FT(0, 0.f);
  float4 e[17];
  uint32_t all = 0;
  e[16] = __ldcg((const float4*)g_z + ((size_t)256 * 1024 + p) * 2);
  const float g0 = __ldcg(g_gate + n), g1 = __ldcg(g_gate + n + 1024);
#pragma unroll
  for (int j = 0; j < 16; j++) { const uint4 u = lds128(z + j * 2048); e[j] = make_float4(__uint_as_float(u.x), __uint_as_float(u.y), __uint_as_float(u.z), __uint_as_float(u.w)); all |= u.x; }
  sched_fence(all);
  read();
  float ws, wc; sincospif((float)n * (1.0f / 1024.0f), &ws, &wc);
  cf v[32], q[17];
#pragma unroll
  for (int j = 0; j < 17; j++) {
    const cf d = cmul({e[j].z, e[j].w}, wc, ws);
    cf a = {e[j].x + d.x, e[j].y + d.y}, b = {e[j].x - d.x, e[j].y - d.y};
    if (j == 16 || (j == 0 && t == 0)) { a.y = 0.f; b.y = 0.f; }
    if (j < 16) v[j] = {a.x - b.y, a.y + b.x};
    q[j] = {a.x + b.y, b.x - a.y};
  }
#pragma unroll
  for (int j = 16; j < 32; j++) {
    v[j] = {__shfl_sync(~0u, q[31 - j].x, src), __shfl_sync(~0u, q[31 - j].y, src)};
    if (t == 0) v[j] = q[32 - j];
  }
  FT(1, v[0].x + v[16].x + v[31].x);
  if (B_ST) { asm volatile("cp.async.bulk.wait_group.read 0;" ::: "memory"); __syncwarp(); }
  warp_fft1024<true>(v, buf, tw, t, lane, []() {});
  FT(3, v[31].y + v[0].x);
  const float sc = 0.5f / (2048.0f * 1024.0f), s0 = (1.f - g0) * sc, s1 = (1.f - g1) * sc;
  uint2* o = (B_ST ? (uint2*)buf : (uint2*)(out + (size_t)n * D_)) + (lane ^ (n & 1) << 3);
#pragma unroll
  for (int j = 0; j < 32; j += 4) {
    o[8 * j] = make_uint2(pack_bf16(v[j].x * s0, v[j + 1].x * s0), pack_bf16(v[j + 2].x * s0, v[j + 3].x * s0));
    o[(B_ST ? 256 : 256 * D_) + 8 * j] = make_uint2(pack_bf16(v[j].y * s1, v[j + 1].y * s1), pack_bf16(v[j + 2].y * s1, v[j + 3].y * s1));
  }
  if (B_ST) {
    FENCE_ASYNC_SMEM();
    __syncwarp();
    asm volatile("{ .reg .pred p; setp.lt.u32 p, %2, 2; @p cp.async.bulk.global.shared::cta.bulk_group [%0], [%1], 2048; cp.async.bulk.commit_group; }"
                 :: "l"(out + (size_t)(n + 1024 * (lane & 1)) * D_), "r"(smem_u32(buf) + (lane & 1) * 2048), "r"(lane) : "memory");
  }
  FT(4, 0.f);
}

constexpr int NP = NP_, NHV = REG_F == 216 ? 5 : 7, NV = 16 - NHV;
constexpr int XEND = NSEG;
constexpr uint32_t SM_WO = 0, SM_V = 65536, SM_LAND = SM_V + 8192, SM_MEM = SM_LAND + 24576, SM_SP = SM_MEM, SM_SPM = SM_MEM + 5120, SM_OM = SM_MEM + 6144,
                   SM_OX = SM_MEM + 8192, SM_RED = SM_OX + 2048, SM_XCH = SM_RED + 1024, SM_SUM = SM_XCH + 4096, SM_VM = SM_SUM + 128, SM_TAB = SM_VM + 2048, SM_TRACE = SM_TAB + 2048, SM_K = SM_TRACE,
                   ST_WG = (32 - NP + NV) * 2048,
                   SM_XT = 2 * ST_WG, SM_POOL = SM_XT + 32768, SM_HV = SM_POOL + 2 * NP * 2048,
                   SM_BAR = SM_HV + 2 * NHV * 2048, SM_SEL = SM_BAR + 320, SM_Q = SM_SEL + 576, CHAIN_SMEM = SM_Q + (Q_TMA ? 2048 : 1024);
constexpr uint32_t SM_FFT = 49152, SM_GW = SM_XT - 2048;
static_assert(NP % 4 == 0 && NV == 11 && SM_TRACE + 8192 <= SM_XT, "shared memory layout");
static_assert(CHAIN_SMEM <= 232448 && COL_SMEM <= SM_BAR && SM_FFT + (1024 + 8 * ROW_BUF) * 8 <= SM_GW && NP == 12, "shared memory budget");
enum { B_WFULL = 0, B_WREAD = 2, B_WOFULL, B_XFULL, B_XEMPTY, B_E1TRIG, B_E2TRIG, B_PVDONE, B_PUB, B_SC, B_PFULL, B_SPFREE,
       B_LAND, B_LFREE, B_DONE, B_SEL, B_PROBE, B_FREE, B_P1, B_ROWS, B_VFULL, B_VST, B_TW, B_BT, B_WREAD0, B_Z, B_GFULL = B_Z + 4, B_GEMPTY = B_GFULL + 5, B_END = B_GEMPTY + 5 };
static_assert(B_END * 8 <= 320, "barriers");
__host__ __device__ constexpr uint32_t bar_codes(int g) {
  uint32_t r = 0;
  for (int i = 16 * g; i < 16 * g + 16; i++)
    r |= (i == B_LAND ? 3u : i == B_WREAD || i == B_XEMPTY || i == B_E1TRIG || i == B_E2TRIG || i == B_LFREE || i == B_FREE || i == B_VST || i == B_P1 || i == B_ROWS ? 2u :
          i >= B_GEMPTY || i == B_WREAD0 || i == B_PROBE || i == B_DONE || i == B_PVDONE || i == B_PUB || i == B_SC || i == B_SPFREE ? 1u : 0u) << 2 * (i & 15);
  return r;
}
constexpr uint32_t SM_BT = 65536, SM_TW = SM_XT - 8192, COL_Z = 80 * 1024;
static_assert(SM_XT + 3 * 32768 <= SM_BAR && SM_BT + 32768 <= SM_MEM && SM_TRACE <= SM_TW && SM_MEM + 4 * INV_BUF * 8 <= SM_TRACE &&
              8192 + 16 * INV_BUF * 8 <= COL_Z && COL_Z + 131072 <= SM_BAR, "shared memory layout");
__device__ __forceinline__ uint32_t next_stage(uint32_t o) { return o == SM_XT + 65536 ? 0 : o == 32768 ? SM_XT : o + 32768; }

struct ChainCtx { char* mail; uint32_t sb, sel; int r, h, a, b, j, m, w, lane; };
#define BAR(i) (c.sb + SM_BAR + 8 * (i))

__device__ __forceinline__ uint32_t tile_off(int line, int lane) {
  return line * 128 + (((lane & 3) ^ line) << 5) + (lane >> 2) * 4;
}
__device__ __forceinline__ uint32_t read_off(int lane) {
  const int n = lane >> 2, jj = lane & 3, l = 2 * (jj >> 1) + (n & 1);
  return l * 128 + (((n >> 1) ^ l) << 5) + (jj & 1) * 16;
}
__device__ __forceinline__ uint32_t frag_off(int w, int lane) {
  const int mi = lane >> 3, r = lane & 7;
  return ((mi >> 1) * 8 + r) * 128 + (((2 * w + (mi & 1)) ^ r) << 4);
}
__device__ __forceinline__ uint32_t land_off(int w, int lane) { return w * 512 + ((lane ^ (((lane >> 4) | ((w & 1) << 1)) << 1)) << 4); }
__device__ __forceinline__ uint32_t tagged(uint32_t v, uint32_t tag) { return (v | 1u) ^ tag; }
__device__ __forceinline__ void mma_a(float (&d)[4], const uint32_t (&a)[4], uint32_t b0, uint32_t b1) { mma16816(d, a[0], a[1], a[2], a[3], b0, b1); }
__device__ __forceinline__ void mma_q(float (&d)[4], const uint4& a, uint32_t b0, uint32_t b1) { mma16816(d, a.x, a.y, a.z, a.w, b0, b1); }
__device__ __forceinline__ uint4 add4(uint4 a, uint4 b) {
  return make_uint4(add_bf16x2(a.x, b.x), add_bf16x2(a.y, b.y), add_bf16x2(a.z, b.z), add_bf16x2(a.w, b.w));
}
__device__ __forceinline__ void mbar_arrive_both(uint32_t bar, int peer) {
  __syncwarp();
  asm volatile("{ .reg .pred p; .reg .u32 a; mapa.shared::cluster.u32 a, %0, %1; elect.sync _|p, 0xffffffff;\n"
               "@p mbarrier.arrive.shared::cta.b64 _, [%0]; @p mbarrier.arrive.shared::cluster.b64 _, [a]; }" :: "r"(bar), "r"(peer) : "memory");
}

__device__ __forceinline__ void arrive_remote_if(uint32_t a, bool on) {
  asm volatile("{ .reg .pred p; setp.ne.u32 p, %1, 0; @p mbarrier.arrive.shared::cluster.b64 _, [%0]; }" :: "r"(a), "r"((uint32_t)on) : "memory");
}
__device__ __forceinline__ void store_count(void* p, uint4 v, void* cnt) {
  asm volatile("{ .reg .pred p, q; .reg .b128 a, b; .reg .b64 l, h; mov.b64 l, {%1, %2}; mov.b64 h, {%3, %4}; mov.b128 a, {l, h};\n"
               "atom.relaxed.gpu.global.exch.b128 b, [%0], a; mov.b128 {l, h}, b; setp.eq.u64 q, l, 0x7fc17fc17fc17fc1; @q pmevent 1;\n"
               "elect.sync _|p, 0xffffffff; @p red.relaxed.gpu.global.add.u32 [%5], 1; }"
               :: "l"(p), "r"(v.x), "r"(v.y), "r"(v.z), "r"(v.w), "l"(cnt) : "memory");
}

template<int N> __device__ __forceinline__ void pad() {
#pragma unroll
  for (int i = 0; i < N; i++) asm volatile("pmevent 3;");
}
__device__ __forceinline__ int lane_id() {
  int l; asm volatile("{ .reg .u32 t; mov.u32 t, %%laneid; shfl.sync.idx.b32 %0, t, t, 31, 0xffffffff; }" : "=r"(l)); return l;
}
__device__ __forceinline__ uint32_t tid_now() { uint32_t t; asm volatile("mov.u32 %0, %%tid.x;" : "=r"(t)); return t; }
enum { NB_ATT = 1, NB_OM = 2, NB_VM = 3, NB_XCH = 4, NB_MEM = 8, NB_HELP = 12 };
__device__ __forceinline__ uint32_t dep(uint32_t a, uint32_t v, uint32_t z) { uint32_t r; asm("shf.l.wrap.b32 %0, %2, %1, %3;" : "=r"(r) : "r"(a), "r"(v), "r"(z)); return r; }
__device__ __forceinline__ uint32_t vary(uint32_t a, int s, uint32_t z) { return dep(a, 0, z + 32 * s); }
__device__ __forceinline__ char* mk_ptr(uint32_t lo, uint32_t hi) { uint64_t r; asm("mov.b64 %0, {%1, %2};" : "=l"(r) : "r"(lo), "r"(hi)); return (char*)r; }
__device__ __forceinline__ void lds_frag(uint32_t (&r)[4], uint32_t a) {
  asm volatile("ld.shared.v4.u32 {%0,%1,%2,%3}, [%4];" : "=r"(r[0]), "=r"(r[1]), "=r"(r[2]), "=r"(r[3]) : "r"(a) : "memory");
}
__device__ __forceinline__ uint32_t stale2(uint32_t a, uint32_t b, uint32_t t) { uint32_t r; asm("lop3.b32 %0, %1, %2, %3, 0xbd;" : "=r"(r) : "r"(a), "r"(b), "r"(t)); return r; }
__device__ __forceinline__ uint32_t stale1(uint32_t acc, uint32_t a, uint32_t t) { uint32_t r; asm("lop3.b32 %0, %1, %2, %3, 0xf9;" : "=r"(r) : "r"(acc), "r"(a), "r"(t)); return r; }
__device__ __forceinline__ bool all_clear(uint32_t x, uint32_t m) {
  uint32_t r;
  asm volatile("{ .reg .pred p; .reg .u32 t; and.b32 t, %1, %2; setp.eq.u32 p, t, 0; vote.sync.all.pred p, p, 0xffffffff; selp.u32 %0, 1, 0, p; }" : "=r"(r) : "r"(x), "r"(m));
  return r;
}
__device__ __forceinline__ bool arrive_if_all(bool ok, int id, int n) {
  uint32_t r;
  asm volatile("{ .reg .pred p, q; setp.ne.u32 p, %1, 0; vote.sync.all.pred q, p, 0xffffffff; @q bar.arrive %2, %3; selp.u32 %0, 1, 0, q; }"
               : "=r"(r) : "r"((uint32_t)ok), "r"(id), "r"(n) : "memory");
  return r;
}
__device__ __forceinline__ bool arrive_if_clear(uint32_t x, uint32_t m, int id, int n) {
  uint32_t r;
  asm volatile("{ .reg .pred p; .reg .u32 t; and.b32 t, %1, %2; setp.eq.u32 p, t, 0; vote.sync.all.pred p, p, 0xffffffff; @p bar.arrive %3, %4; selp.u32 %0, 1, 0, p; }"
               : "=r"(r) : "r"(x), "r"(m), "r"(id), "r"(n) : "memory");
  return r;
}
__device__ __forceinline__ void touch(const void* p, uint32_t z) {
  asm volatile("{ .reg .pred p; setp.eq.u32 p, %1, 0x7fff0000; @p prefetch.global.L2 [%0]; }" :: "l"(p), "r"(z) : "memory");
}

__device__ __forceinline__ uint64_t desc_x(uint32_t lo, int k) {
  uint64_t d; asm("mov.b64 %0, {%1, %2};" : "=l"(d) : "r"(lo + (k >> 2) * 64 + (k & 3) * 2), "r"(0x40000200)); return d;
}
template<int K0, int K1> __device__ __forceinline__ void issue_qk(float (&xa)[16], const uint32_t (&wt)[16][4], uint32_t lo) {
  WG_FENCE();
#pragma unroll
  for (int k = K0; k < K1; k++) {
    if (k >= EXP_NWG) continue;
    if (k == 0) wgmma_rs_n32<true>(xa, wt[0], desc_x(lo, 0));
    else wgmma_rs_n32<false>(xa, wt[k], desc_x(lo, k));
  }
  WG_COMMIT();
}
__host__ __device__ constexpr int v_order(int i) { return SSPOS == 0 ? i : SSPOS == 2 ? (i + NV) % 16 : NHV == 5 ? (i % 3 == 2 ? NV + i / 3 : i - i / 3) : (i == 15 ? NV - 1 : i % 2 ? NV + i / 2 : i / 2); }
__device__ __forceinline__ void issue_v(float (&xa)[16], const uint32_t (&wv)[16][4], uint32_t lo, uint32_t la) {
  WG_FENCE();
#pragma unroll
  for (int i = 0; i < EXP_NWG; i++) {
    const int k = v_order(i);
    const uint64_t b = desc_x(lo, k);
    if (k < NV) { if (i == 0) wgmma_rs_n32<true>(xa, wv[k], b); else wgmma_rs_n32<false>(xa, wv[k], b); }
    else        { if (i == 0) wgmma_ss_n32_ta<true>(xa, desc128(la + (k - NV) * 128), b); else wgmma_ss_n32_ta<false>(xa, desc128(la + (k - NV) * 128), b); }
  }
  WG_COMMIT();
}
template<bool ISV> __device__ __forceinline__ void park_own(uint32_t (&q)[4], float (&xa)[16], uint32_t dst, int slot, uint32_t z) {
  uint32_t p[8];
#pragma unroll
  for (int i = 0; i < 16; i++) asm volatile("" : "+f"(xa[i]) :: "memory");
#pragma unroll
  for (int i = 0; i < 2; i++) {
    const float* k = xa + 8 * i;
    if (ISV) { p[4 * i] = pack_bf16(k[0], k[1]); p[4 * i + 1] = pack_bf16(k[2], k[3]); p[4 * i + 2] = pack_bf16(k[4], k[5]); p[4 * i + 3] = pack_bf16(k[6], k[7]); }
    else     { p[4 * i] = pack_bf16(k[0], k[2]); p[4 * i + 1] = pack_bf16(k[1], k[3]); p[4 * i + 2] = pack_bf16(k[4], k[6]); p[4 * i + 3] = pack_bf16(k[5], k[7]); }
  }
  sts128(dep(dep(dst, p[4] ^ p[5] ^ p[6], z), p[7], z) + slot * 8192, make_uint4(p[0], p[1], p[2], p[3]));
#pragma unroll
  for (int i = 0; i < 4; i++) q[i] = p[4 + i];
}
__device__ __forceinline__ void park_peer(const uint32_t (&q)[4], uint32_t dst, int slot, const ChainCtx& c) {
  const uint32_t bar = BAR(B_LAND);
  if (EXP_PEER) st_async4(mapa(dst + slot * 8192, c.b ^ 1), q[0], q[1], q[2], q[3], mapa(bar, c.b ^ 1));
  else touch((void*)(uintptr_t)(q[0] ^ q[1] ^ q[2] ^ q[3]), c.sb);
  mbar_arrive_warp(bar);
}
__device__ __forceinline__ uint32_t put_tag(uint32_t v, uint32_t bit, uint32_t t) {
  uint32_t r; asm("lop3.b32 %0, %1, %2, %3, 0x74;" : "=r"(r) : "r"(v), "r"(bit), "r"(t)); return r;
}
__device__ __forceinline__ void mem_proj(const uint32_t (&wa)[16][4], const uint32_t (&wb)[16][4], uint32_t (&wv)[16][4], uint32_t (&af)[16][4],
                                         uint32_t& wo, const char*& pa, uint32_t tab, uint32_t t16, uint32_t pk, const ChainCtx& c, int s) {
  const uint32_t mp = t16 & ~0x600u, id = NB_MEM + (t16 >> 11);
  uint32_t r[8][4];
  float la[4][4] = {}, lg[NLAG][4] = {}, lv[4][4] = {};
  auto lead = [&](int k) { mma_a(la[k & 3], wa[k], r[k >> 1][2 * (k & 1)], r[k >> 1][2 * (k & 1) + 1]); };
  auto lag = [&](int k) { mma_a(lg[k % NLAG], wb[k], r[k >> 1][2 * (k & 1)], r[k >> 1][2 * (k & 1) + 1]); };
  auto sum = [](const float (&d)[4][4], int i) { return (d[0][i] + d[1][i]) + (d[2][i] + d[3][i]); };
  bar_sync(id, 160);
  TR(s, 0);
#pragma unroll
  for (int i = 0; i < 4; i++) ldsm4t(r[i], mp + (c.sb + SM_MEM + i * 512));
  uint4 tq;
  if (!TQ_AT) tq = lds128(tab);
  bar_sync(id + 2, 160);
  uint32_t first = 0;
#pragma unroll
  for (int k = 0; k < 8; k++) { lead(k); if (k == C1_AT - 4) first = dep(mp, __float_as_uint(la[k & 3][0]), c.sb); }
  uint32_t ta, tb;
  if (!TQ_AT) { ta = tq.x | ((pk >> 16) & 511); tb = tq.z ^ ((pk >> 16) & 511); }
  const uint32_t mp1 = C1_AT >= 4 ? (TQ_AT ? first : dep(first, ta ^ tb, c.sb)) : dep(mp, __float_as_uint(la[C1_AT & 3][0]) ^ (TQ_AT ? 0 : ta ^ tb), c.sb);
#pragma unroll
  for (int i = 4; i < 8; i++) ldsm4t(r[i], mp1 + (c.sb + SM_MEM + 2048 + i * 512));
  if (TQ_AT) { tq = lds128(tab); ta = tq.x | ((pk >> 16) & 511); tb = tq.z ^ ((pk >> 16) & 511); }
  char* dst = mk_ptr(ta, tq.y);
  char* dst2 = mk_ptr(tb, tq.w);
  const uint32_t hv = pk & 0xFFFF;
#pragma unroll
  for (int k = NV; k < NV + HV_E; k++) ldsm4t(wv[k], dep(hv, r[HV_R][0], c.sb) + (c.sb + SM_HV + (k - NV) * 2048));
#pragma unroll
  for (int k = 0; k < LAG_0; k++) lag(k);
#pragma unroll
  for (int k = 8; k < 16; k++) lead(k);
  const uint32_t s0 = __float_as_uint(sum(la, 0)), s3 = __float_as_uint(sum(la, 3));
  sts128((HV_E ? dep(t16, wv[NV][0] ^ wv[NV + HV_E / 2][1] ^ wv[NV + HV_E - (HV_E > 0)][2], c.sb) : TQ_AT ? dep(t16, ta ^ tb, c.sb) : t16) + (c.sb + SM_XCH),
         make_uint4(s0, __float_as_uint(sum(la, 1)), __float_as_uint(sum(la, 2)), s3));
  if (XB) bar_sync(NB_XCH, 256); else bar_sync(NB_XCH | ((t16 >> 9) & 3), 64);
#pragma unroll
  for (int k = LAG_0; k < LAG_0 + LAG_G; k++) r[k >> 1][2 * (k & 1)] = dep(r[k >> 1][2 * (k & 1)], LAG_S == 0 ? s3 : __float_as_uint(la[LAG_S - 1][0]), c.sb);
#pragma unroll
  for (int k = LAG_0; k < O_AT; k++) lag(k);
  const uint4 o = lds128((O_AT > LAG_0 ? dep(t16 ^ 2048, __float_as_uint(lg[(O_AT - 1) % NLAG][0]), c.sb) : t16 ^ 2048) + (c.sb + SM_XCH));
#pragma unroll
  for (int k = O_AT > LAG_0 ? O_AT : LAG_0; k < 16; k++) lag(k);
#pragma unroll
  for (int k = 0; k < V_E; k++) mma_a(lv[k & 3], wv[k], r[k >> 1][2 * (k & 1)], r[k >> 1][2 * (k & 1) + 1]);
  float t[4];
#pragma unroll
  for (int i = 0; i < 4; i++) {
    const float oi = __uint_as_float(i == 0 ? o.x : i == 1 ? o.y : i == 2 ? o.z : o.w);
    t[i] = NLAG == 4 ? (LAG_T ? ((lg[0][i] + lg[1][i]) + oi) + (lg[2 % NLAG][i] + lg[3 % NLAG][i]) : (((lg[0][i] + lg[1][i]) + lg[2 % NLAG][i]) + lg[3 % NLAG][i]) + oi) : LAG_T && NLAG == 2 ? (lg[0][i] + lg[1][i]) + oi : NLAG == 3 ? (lg[1][i] + lg[2 % NLAG][i]) + (lg[0][i] + oi) : (lg[0][i] + oi) + lg[1][i];
  }
  const uint32_t y0 = put_tag(pack_bf16(t[0], t[2]), pk >> 31, s >> 1), y1 = put_tag(pack_bf16(t[1], t[3]), pk >> 31, s >> 1);
  st_pub(dst, y0); st_pub(dst2, y1);
  mbar_arrive_warp(BAR(B_E1TRIG));
  TR(s, 1);
  sched_fence(c.sb);
  const uint4 tv = lds128(tab + 16);
#pragma unroll
  for (int k = NV + HV_E; k < 16; k++) ldsm4t(wv[k], (k < NV + HV_E + HV_D ? hv : dep(hv, k == NV + HV_E + HV_D ? wv[k - HV_D][0] ^ tv.x : wv[k - HV_D][0], c.sb)) + (c.sb + SM_HV + (k - NV) * 2048));
  wo = (hv & 2047) | ((t16 & 2048) << 3);
  const uint32_t l8 = (t16 >> 1) & 255;
  char* dv = mk_ptr(tv.x | l8, tv.y);
  pa = mk_ptr(tv.z | l8, tv.w);
#pragma unroll
  for (int f = 0; f < WO_0; f++) ldsm4t(af[f], dep(wo, f < WO_D ? wv[16 - WO_D + f][0] : af[f < WO_D ? 0 : f - WO_D][0], c.sb) + (c.sb + SM_WO + (f & 1) * 32768 + (f >> 1) * 2048));
#pragma unroll
  for (int k = V_E; k < 16; k++) mma_a(lv[k & 3], wv[k], r[k >> 1][2 * (k & 1)], r[k >> 1][2 * (k & 1) + 1]);
  const uint32_t z0 = put_tag(pack_bf16(sum(lv, 0), sum(lv, 1)), (~t16 >> 4) & 1, s >> 1), z1 = pack_bf16(sum(lv, 2), sum(lv, 3));
  st_pub2(dv, z0, z1);
  if (FIN_AT >= 3) mbar_arrive_warp(BAR(B_VST));
  TR(s, 2);
}
__device__ __forceinline__ uint32_t max_bf16x2(uint32_t a, uint32_t b) { uint32_t r; asm("max.bf16x2 %0, %1, %2;" : "=r"(r) : "r"(a), "r"(b)); return r; }
constexpr float SCL = 0.08838834764831845f * 1.4426950408889634f;
__device__ __forceinline__ uint32_t max5(const uint32_t (&sc)[5]) { return max_bf16x2(max_bf16x2(max_bf16x2(max_bf16x2(sc[0], sc[1]), sc[2]), sc[3]), sc[4]); }
__device__ __forceinline__ float row_off(uint32_t m, uint32_t& m1) {
  m1 = __shfl_xor_sync(~0u, m, 1);
  const uint32_t m2 = __shfl_xor_sync(~0u, m, 2), m3 = __shfl_xor_sync(~0u, m, 3);
  const uint32_t mm = max_bf16x2(max_bf16x2(max_bf16x2(m, m1), m2), m3);
  return -SCL * fmaxf(__uint_as_float(mm << 16), __uint_as_float(mm & 0xFFFF0000u));
}
__device__ __forceinline__ void unpack(float (&f)[10], const uint32_t (&sc)[5]) {
#pragma unroll
  for (int i = 0; i < 5; i++) {
    asm volatile("shl.b32 %0, %1, 16;" : "=f"(f[2 * i]) : "r"(sc[i]));
    asm volatile("and.b32 %0, %1, 0xffff0000;" : "=f"(f[2 * i + 1]) : "r"(sc[i]));
  }
}
__device__ __forceinline__ uint32_t exp_pair(const float (&f)[10], int i, float off) {
  return pack_bf16(ex2(fmaf(f[2 * i], SCL, off)), ex2(fmaf(f[2 * i + 1], SCL, off)));
}
template<bool SPLIT> __device__ __forceinline__ void scores_x(float (&a)[2][4], const uint4 (&kf)[4], const uint4& q, uint32_t z) {
#pragma unroll
  for (int t = 0; t < 2; t++) { a[t][0] = a[t][1] = a[t][2] = a[t][3] = 0.f; }
  mma_q(a[0], kf[0], q.x, q.y); mma_q(a[1], kf[2], q.x, q.y);
  if (SPLIT) sched_fence(z);
  mma_q(a[0], kf[1], q.z, q.w); mma_q(a[1], kf[3], q.z, q.w);
}
__device__ __forceinline__ uint32_t scores_m(const uint4& q, const uint4& k) {
  float a[4] = {}, b[4] = {};
  mma_q(a, q, k.x, k.z); mma_q(b, q, k.y, k.w);
  return pack_bf16(a[0] + b[2], a[1] + b[3]);
}
__device__ __forceinline__ void store_scores(const float (&a)[2][4], uint32_t dst) {
  sts64(dst, pack_bf16(a[0][0], a[0][2]), pack_bf16(a[1][0], a[1][2]));
  sts64(dst + 320, pack_bf16(a[0][1], a[0][3]), pack_bf16(a[1][1], a[1][3]));
}
__device__ __forceinline__ uint32_t sum4(uint32_t a, uint32_t b, uint32_t d, uint32_t e) { return add_bf16x2(add_bf16x2(a, b), add_bf16x2(d, e)); }
__device__ __forceinline__ void load_scores(uint32_t (&sc)[5], uint32_t ax, uint32_t am) {
  uint4 p[4];
#pragma unroll
  for (int i = 0; i < 4; i++) p[i] = lds128(ax + i * 1280);
  const uint2 m0 = lds64(am), m1 = lds64(am + 256);
  const uint4 t = add4(add4(add4(p[0], p[1]), p[2]), p[3]);
  sc[1] = t.x; sc[2] = t.y; sc[3] = t.z; sc[4] = t.w;
  sc[0] = sum4(m0.x, m0.y, m1.x, m1.y);
}
constexpr uint32_t ONES = 0x3F803F80u;
__device__ __forceinline__ float pv(float (&o)[2][4], const uint32_t (&p)[5], const uint4 (&vf)[4], const uint4& vm) {
  float a[4] = {}, b[4] = {};
#pragma unroll
  for (int t = 0; t < 2; t++) { o[t][0] = o[t][1] = o[t][2] = o[t][3] = 0.f; }
  mma_q(o[0], vf[0], p[1], p[2]); mma_q(o[1], vf[2], p[1], p[2]);
  mma_q(o[0], vf[1], p[3], p[4]); mma_q(o[1], vf[3], p[3], p[4]);
  mma16816(a, p[1], p[2], p[3], p[4], ONES, ONES);
  mma1688(o[0], vm.x, vm.y, p[0]); mma1688(o[1], vm.z, vm.w, p[0]);
  mma1688(b, p[0], ONES, ONES);
  return (a[0] + a[2]) + b[0];
}
constexpr uint32_t POLL_LIMIT = 1u << 21;
__device__ __forceinline__ uint32_t box(int slot, int cta) { return (slot * 2 + (cta >> 6)) * M_REG + (cta & 63) * 16384; }
__device__ __forceinline__ uint32_t near_page(const ChainCtx& c, int cta, uint32_t off) {
  return off + (((lds32(c.sb + SM_SEL + cta * 4) >> (off >> 21)) ^ __popc(off & 0xB2000)) & 1) * 4096;
}
__device__ __forceinline__ uint32_t e1_box(const ChainCtx& c, int slot, int cta) { return near_page(c, E1OFF ? cta ^ 2 : cta, box(slot, cta) + 8192) ^ (E1OFF ? 0 : 4096); }
__device__ __forceinline__ uint32_t tile_key() {
  uint32_t sm; asm volatile("mov.u32 %0, %%smid;" : "=r"(sm));
  return (sm < 64 ? sm / 2 % 8 : sm < 120 ? 1 + (sm / 2 - 32) % 7 : 0) << 24 | sm << 16;
}
__device__ __forceinline__ uint32_t ox_at(int s, int row, int g, int jj) { return s * 131072 + ((g >> 1) * 32 + row) * 64 + (g & 1) * 32 + 8 * jj; }
__device__ __forceinline__ int tile_of(const ChainCtx& c) { return SIDE ? __shfl_sync(~0u, lds32(c.sb + SM_SEL + 528), 0) : c.r; }

__global__ void __cluster_dims__(2, 1, 1) __launch_bounds__(512, 1)
chain_kernel(const __grid_constant__ CUtensorMap tq, const __grid_constant__ CUtensorMap tk, const __grid_constant__ CUtensorMap tv,
             const __grid_constant__ CUtensorMap tv16, const __grid_constant__ CUtensorMap to, const __grid_constant__ CUtensorMap tx,
             const __grid_constant__ CUtensorMap twr, const __grid_constant__ CUtensorMap twi,
             const __grid_constant__ CUtensorMap ta, const __grid_constant__ CUtensorMap tw,
             const __grid_constant__ CUtensorMap tb, const __grid_constant__ CUtensorMap tout, const __grid_constant__ CUtensorMap tz,
             const __grid_constant__ CUtensorMap tzs, const __grid_constant__ CUtensorMap ta32,
             const __nv_bfloat16* __restrict__ mem0, char* __restrict__ mail, const __nv_bfloat16* __restrict__ x,
             const __nv_bfloat16* __restrict__ gw) {
  extern __shared__ __align__(1024) unsigned char smraw[];
  if (threadIdx.x == 0) TL(0);
  ChainCtx c;
  c.sb = __shfl_sync(~0u, smem_u32(smraw), 0);
  c.mail = mail; c.sel = 0; c.r = blockIdx.x;
  if (ROLE) {
    const uint32_t u = blockIdx.x >> 1, n = u < 36 ? 8 : 7, k = u - (u < 36 ? 4 : 36), q = k * (u < 36 ? 32 : 37) >> 8;
    c.r = __shfl_sync(~0u, 2 * (u - 4 < 60 ? u + k - q * n - (q & 1) * (n - 1) : u) + (blockIdx.x & 1) + (threadIdx.x >> 9), 0);
  }
  c.h = c.r >> 2; c.a = (c.r >> 1) & 1; c.b = c.r & 1; c.j = c.r & 3;
  c.m = __shfl_sync(~0u, (int)(threadIdx.x >> 7), 0); c.w = __shfl_sync(~0u, (int)((threadIdx.x >> 5) & 3), 0);
  char* own = c.mail + (uint32_t)(c.w * M_REG + M_E3 + (c.r >> 5) * 8192 + (c.r & 31) * 128 + (threadIdx.x & 31) * 4);
  uint32_t i0 = 0, i1 = 0;
  if (EARLY) asm volatile("{ .reg .pred p; setp.ne.u32 p, %4, 0; @p atom.relaxed.gpu.global.exch.b32 %0, [%2], %3; @p atom.relaxed.gpu.global.exch.b32 %1, [%2 + 4096], %3; }"
               : "+r"(i0), "+r"(i1) : "l"(own), "r"(SENT), "r"((uint32_t)(c.m == 2 && c.r < 128)) : "memory");
#pragma unroll
  for (int g = 0; g < 3; g++) {
    const int i = c.m * 4 + c.w;
    if (g < 2 || i < B_END - 32)
      asm volatile("{ .reg .pred p; elect.sync _|p, 0xffffffff; @p mbarrier.init.shared::cta.b64 [%0], %1; }"
                   :: "r"(BAR(g * 16 + i)), "r"(0x19080401u >> (bar_codes(g) >> 2 * i & 3) * 8 & 255) : "memory");
  }
  asm volatile("fence.mbarrier_init.release.cluster;" ::: "memory");
  __syncthreads();
  asm volatile("barrier.cluster.arrive.relaxed.aligned;" ::: "memory");

  if (c.r >= 128) {
    fft_cols((float2*)smraw, c.r - 128, &twr, &twi, &tzs);
    if ((threadIdx.x & 127) == 0) TL(7);
    __syncwarp();
  } else if (c.m == 3) {
    asm volatile("setmaxnreg.dec.sync.aligned.u32 %0;" :: "n"(REG_H));
    c.lane = lane_id();
    if (c.sb & 1023) asm volatile("trap;");
    const int col = c.h * 128 + c.a * 64, eq = E3M ? c.w & 1 : c.w >> 1, eh = E3M == 1 ? (c.w >> 1) ^ 1 : E3M ? c.w >> 1 : c.w & 1;
    uint32_t tl = clock_lo();
    TR(-2, 3);
    if (c.w == 0) {
      if (START) delay_until(tl + START);
      if (HOLD == 2) mbar_wait(BAR(B_PROBE), 0);
      if (HOLD == 3) mbar_wait(BAR(B_SEL), 0);
      if (HOLD == 1) mbar_wait(BAR(B_PROBE), 0);
      TR(-2, 4);
      tl = clock_lo();
      mbar_expect_e(BAR(B_PFULL), 2 * NP * 2048);
      mbar_expect_e(BAR(B_WFULL), (48 - NP) * 2048);
      mbar_expect_e(BAR(B_WFULL + 1), (48 - NP) * 2048);
    }
    auto dst_x = [&](int e, int w) {
      const uint32_t g2 = 2 * c.a + (w >> 1), u = w & 1;
      return M_KVQ + c.h * 24576 + (e == 0 ? 8192 + (2 * u + c.b) * 2048 + g2 * 512 : e == 1 ? g2 * 2048 + u * 1024 + c.b * 128 : 16384 + c.b * 4096 + g2 * 512 + u * 256);
    };
    if (c.w == 0) {
      tl += PACE0;
#pragma unroll wunr
      for (int i = 0; i < 24; i++) {
        const int m = i < 4 || i >= 16, k = i < 4 ? i : m ? i - 12 : i - 4;
        const int row = c.b * 512 + m * 256;
        const uint32_t st = c.sb + m * ST_WG, bar = BAR(k < 3 ? B_PFULL : B_WFULL + m);
        if (PACE) delay_until(tl += PACE);
        if (i == 14) { mbar_idle(BAR(B_FREE), 0); if (c.lane == 0) TL2(2); __syncwarp(); }
        if (k < 11) TMA_W(k < 3 ? c.sb + SM_POOL + m * NP * 2048 + k * 8192 : k == 3 ? c.sb + SM_HV + (m * NHV + 1) * 2048 : st + (k - 4) * 8192,
                          k == 3 || k > 8 ? &tv : (k >> 2 & 1) == m ? &tk : &tq, col, row + (k < 8 ? k & 3 : (k - 9) & 3) * 64, bar);
        else {
#pragma unroll 1
          for (int j = 8; j < 12; j++) TMA_W(j < NV ? st + (32 - NP + j) * 2048 : c.sb + SM_HV + m * NHV * 2048, &tv16, col, row + j * 16, bar);
        }
      }
      TR(-2, 7);
    } else if (c.w == 2) {
      const unsigned short* mp = (const unsigned short*)mem0 + (2 * (c.lane & 3)) * D_ + 8 * c.r + (c.lane >> 2);
      uint32_t mv = (uint32_t)mp[0] | (uint32_t)mp[D_] << 16;
      if (mv == SENT) mv = 0x7FFF7FFFu;
      mbar_idle(BAR(B_PROBE), 0);
      char* dst = c.mail + (uint32_t)(M_E3 + (c.r >> 5) * 8192 + (c.r & 31) * 128 + c.lane * 4);
      st_pub(dst, mv); st_pub(dst + 4096, mv);
    } else if (c.w == 3) {
      mbar_idle(BAR(B_FREE), 0);
      mbar_idle(BAR(B_PFULL), 0);
      mbar_expect_e(BAR(B_PFULL), 65536);
      for (int i = 0; i < 2; i++) tma4d_e(c.sb + SM_XT + i * 16384, &tx, c.b * 8, 4 + 2 * (c.b ^ i), BAR(B_PFULL));
    }
    {
      mbar_idle(BAR(B_SEL), 0);
      const int i = tid_now() & 127, sl = i & 3, e = (i >> 2) & 3;
      uint32_t ox = dst_x(e, i >> 5) + sl * M_REG;
      uint32_t oh = e & 1 ? (sl ^ (e & 2)) * M_REG + M_E3 + (c.r >> 5) * 8192 + (c.w & 1) * 4096 + (c.r & 31) * 128
                          : near_page(c, c.r, e ? sl * M_REG + M_E3 + (c.b * 2 + eq) * 8192 : box(~sl & 1, c.r)) + (e ? eh * 2048 : c.w * 1024), of;
      {
        const int e = i & 7, w = (i >> 3) & 3, m = (i >> 5) & 1, sl = i >> 6;
        const int cta = e < 2 ? c.r & ~1 : e == 2 ? c.r | 1 : e == 3 ? c.h * 4 + 2 * m + 1 : c.j * 32 + m * 8 + 2 * w + (e & 2) * 8 + (e & 1);
        const uint32_t off = e < 2 ? c.b * 2048 + m * 1024 + (w >> 1) * 512 + e * 160 : e == 2 ? c.b * 2048 + m * 1024 + w * 256 : e == 3 ? w * 256 : c.h * 128;
        of = (e < 4 ? e1_box(c, sl, cta) : near_page(c, cta, box(sl, cta))) + off;
      }
      char *px = c.mail + ox, *ph = c.mail + oh, *pf = c.mail + of;
      uint32_t at = sl * 128 + (i >> 5) * 32 + e * 8, af = i * 8;
      pin(px); pin(ph); pin(pf); pin(at); pin(af);
      asm volatile("barrier.cluster.wait;" ::: "memory");
      TR(-2, 0);
      mbar_idle(BAR(B_WREAD), 0);
      TR(-2, 1);
      mbar_arrive_both(BAR(B_LFREE), c.b ^ 1);
      sts64(at + (c.sb + SM_TAB + 1536), (uint32_t)(uintptr_t)px, (uint32_t)((uintptr_t)px >> 32));
      sts64(at + (c.sb + SM_TAB + 1024), (uint32_t)(uintptr_t)ph, (uint32_t)((uintptr_t)ph >> 32));
      sts64(af + (c.sb + SM_TAB), (uint32_t)(uintptr_t)pf, (uint32_t)((uintptr_t)pf >> 32));
      TR(-2, 2);
      if (tid_now() == 384) TL2(25);
      __syncwarp();
      bar_sync(14, 160);
    }
    pad<PAD3>();
    for (int s = -1; s < NSEG; s++) {
      if (E30 ? s != 0 : s >= 0) {
        const uint32_t tab = c.sb + SM_TAB + 1024 + (max(s, 0) & 3) * 128 + c.w * 32;
        uint32_t t0;
        if (s > 0) {
          const uint32_t ln = tid_now() & 31;
          const uint4 ta = lds128(tab);
          const char* src = mk_ptr(ta.x | ln * 4, ta.y);
          char* dst = mk_ptr(ta.z | ln * 4, ta.w);
          const uint32_t tg = (s - 1) >> 1, chk = (ln & 3) ? 0u : 1u, red = ln * (RED_L == 3 ? 4 : 8);
          touch(src, dep(c.sb, chk, c.sb)); touch(dst, dep(c.sb, red, c.sb));
          mbar_wait(BAR(B_E2TRIG), (s - 1) & 1);
          TR(s, 0);
          if (ANCH2) delay_fine(lds32(c.sb + SM_SUM + 64) + DLY_E2); else delay_cycles(DLY_E2);
          uint32_t n = 0;
          while (true) {
            uint32_t v[8];
#pragma unroll
            for (int i = 0; i < 8; i++) v[i] = ld_poll1(src + i * 128);
            if (E2_F) sched_fence(c.sb);
            const uint32_t bad = RED_T ? (stale2(v[0], v[1], tg) | stale2(v[2], v[3], tg) | stale2(v[4], v[5], tg)) | stale2(v[6], v[7], tg)
                                       : stale1(stale1(stale2(v[0], v[1], tg), v[2], tg), v[3], tg) | stale1(stale1(stale2(v[4], v[5], tg), v[6], tg), v[7], tg);
            const bool ok = all_clear(bad, chk);
#pragma unroll
            for (int l = 0; l < RED_L; l++)
#pragma unroll
              for (int i = 0; i < (4 >> l); i++) v[i] = add_bf16x2(v[2 * i], v[2 * i + 1]);
            if (RED_L == 3) sts32(red + (c.sb + SM_RED + c.w * 128), v[0]);
            else {
              float lo[8], hi[8];
#pragma unroll
              for (int i = 0; i < (8 >> RED_L); i++) { lo[i] = __uint_as_float(v[i] << 16); hi[i] = __uint_as_float(v[i] & 0xFFFF0000u); }
#pragma unroll
              for (int l = RED_L; l < 3; l++)
#pragma unroll
                for (int i = 0; i < (4 >> l); i++) { lo[i] = lo[2 * i] + lo[2 * i + 1]; hi[i] = hi[2 * i] + hi[2 * i + 1]; }
              sts64(red + (c.sb + SM_RED + c.w * 256), __float_as_uint(lo[0]), __float_as_uint(hi[0]));
            }
            if (ok) break;
            n++; CNT(0);
          }
          bar_sync(NB_HELP, 128);
          const uint32_t rd = red + (c.sb + SM_RED);
          if (!RED_P || c.w < 2) {
            if (RED_L == 3) st_pub_if(dst, sum4(lds32(rd), lds32(rd + 128), lds32(rd + 256), lds32(rd + 384)), c.w < 2);
            else {
              const uint2 p0 = lds64(rd), p1 = lds64(rd + 256), p2 = lds64(rd + 512), p3 = lds64(rd + 768);
              st_pub_if(dst, pack_bf16((__uint_as_float(p0.x) + __uint_as_float(p1.x)) + (__uint_as_float(p2.x) + __uint_as_float(p3.x)),
                                       (__uint_as_float(p0.y) + __uint_as_float(p1.y)) + (__uint_as_float(p2.y) + __uint_as_float(p3.y))), c.w < 2);
            }
          }
          t0 = clock_lo();
          mbar_arrive_warp(BAR(B_PUB));
          TRV(s, 15, n);
          mbar_wait(BAR(B_SPFREE), (s - 1) & 1);
        } else {
          if (tid_now() == 384) TL2(24);
          __syncwarp();
          if (!E30) mbar_wait(BAR(B_PROBE), 1);
          if (!WO_S) mbar_wait(BAR(B_WOFULL), 0);
          if (tid_now() == 384) TL2(19);
          __syncwarp();
          t0 = clock_lo() - DLY_E3;
        }
        TRV(s, 1, t0);
        {
          const uint32_t l16 = (tid_now() & 31) * 16, dst = vary(l16, s, c.sb) + (c.sb + SM_MEM + eh * 4096 + eq * 2048);
          const uint4 tb = lds128(tab + 16);
          st_pub_if(mk_ptr(tb.z | l16 >> 2, tb.w), SENT, c.w >= 2);
          const char* src = mk_ptr(tb.x | l16, tb.y);
          touch(src, dep(c.sb, dst, c.sb));
          delay_fine(t0 + (DLY_E3 + eh * DLY_E3B));
          uint32_t n = 0;
          while (true) {
            uint4 v[4];
#pragma unroll
            for (int i = 0; i < 4; i++) v[i] = ld_poll(src + i * 512);
#pragma unroll
            for (int i = 0; i < 4; i++) sts128(dst + i * 512, v[i]);
            if (arrive_if_all(max(max(v[0].x, v[1].x), max(v[2].x, v[3].x)) != SENT, NB_MEM + eh * 2 + eq, 160)) break;
            n++; CNT(1);
          }
          TR(s, 2); TRV(s, 14, n);
        }

        if (s == 1) CLK(1); if (s == 8) CLK(2); if (s == 56) CLK(3);
        if (c.w == 2 && s == 15) TRSYNC(8);
        if (c.w == 2 && s == 21) TRSYNC(10);
      }
      const int g = s + 1;
      auto load_v = [&]() {
        if (V_TMA && c.w == V_W) {
          mbar_expect_e(BAR(B_VFULL), (K_TMA ? 16384 : 8192) + (Q_TMA ? 2048 : 0));
          const char* src = c.mail + (uint32_t)(M_KVQ + (min(g, XEND - 1) & (NSLOT - 1)) * M_REG + c.h * 24576);
          bulk_load_e(c.sb + SM_V, src + 8192, 8192, BAR(B_VFULL));
          if (K_TMA > 1) delay_cycles(K_TMA);
          if (K_TMA) bulk_load_e(c.sb + SM_K, src, 8192, BAR(B_VFULL));
          if (Q_TMA > 1) delay_cycles(Q_TMA);
          if (Q_TMA) bulk_load_e(c.sb + SM_Q, src + (16384 + c.j * 2048), 2048, BAR(B_VFULL));
        }
      };
      if (XEND < NSEG && g >= XEND && g < NSEG) { mbar_wait(BAR(B_SC), s & 1); load_v(); }
      if (g < XEND) {
        const uint32_t tx_ = c.sb + SM_TAB + 1536 + (g & 3) * 128 + c.w * 32, tag = (g >> 2) & 1;
        if (c.w == 0) mbar_expect_e(BAR(B_LAND), EXP_PEER * 12288);
        auto load_x = [&]() {
          if (c.w == 3 && g + 1 < XEND) {
            mbar_wait(BAR(B_XEMPTY), g & 1);
            mbar_expect_e(BAR(B_XFULL), 16384 * EXP_NXT);
            for (int i = 0; i < EXP_NXT; i++) tma4d_e(c.sb + SM_XT + i * 16384, &tx, c.b * 8, (g + 1) * 4 + 2 * (c.b ^ i), BAR(B_XFULL));
          }
        };
        if (X_AT == 0 && g > 0) load_x();
        TR(s, 6);
        if (E30 && g == 0) mbar_idle(BAR(B_PROBE), 1);
        mbar_wait(BAR(B_LAND), g & 1);
        TR(s, 7);
        if (DLY_F && g > 0) delay_cycles(DLY_F);
        auto total = [&](int w, int lane, uint32_t o0, uint32_t o1) {
          const uint32_t a = c.sb + SM_LAND + land_off(w, lane);
          if (EXP_FL == 1) return make_uint4(a, a, a, a);
          const uint4 t = add4(lds128(a + o0), lds128(a + o1 + 2048));
          const uint32_t a2 = dep(dep(a, t.x ^ t.y ^ t.z, c.sb), t.w, c.sb);
          return add4(t, add4(lds128(a2 + o0 + 4096), lds128(a2 + o1 + 6144)));
        };
        auto get = [&](int e) {
          const int ln = tid_now() & 31;
          return e == 0 ? total(c.w, ln, 16384, 16384)
               : e == 1 ? total((c.w & 2) + ((ln >> 1) & 1), (ln & 1) * 16 + (c.w & 1) * 8 + (ln >> 2), 8192, 0)
                        : total((c.w & 2) + ((ln >> 1) & 1), (ln & 1) * 16 + (ln >> 3) * 4 + (c.w & 1) * 2 + ((ln >> 2) & 1), 0, 8192);
        };
        auto put = [&](int e, uint4 v) {
          const int ln = tid_now() & 31;
          const uint2 d = lds64(tx_ + e * 8);
          if (e < 2) {
            v.x = tagged(v.x, tag);
            st_pub4(mk_ptr(d.x | (e ? (ln & 24) * 32 + (ln & 7) * 16 : ln * 16), d.y), v);
          } else {
            char* dst = mk_ptr(d.x | ((ln & 7) * 16 + (ln >> 3) * 4), d.y);
            const uint32_t bit = ln < 8;
            st_pub(dst, put_tag(v.x, bit, tag)); st_pub(dst + 128, put_tag(v.y, bit, tag));
            st_pub(dst + 2048, put_tag(v.z, bit, tag)); st_pub(dst + 2176, put_tag(v.w, bit, tag));
          }
        };
        auto after_sc = [&]() { if (g > 0) { mbar_wait(BAR(B_SC), s & 1); if (DLY_FK) delay_cycles(DLY_FK); if (X_AT == 1) load_x(); } };
        if (FIN_AT == 5) {
          put(0, get(0));
          if (DLY_F2 && g > 0) delay_cycles(DLY_F2); else sched_fence(c.sb);
          const uint4 k = get(1);
          sched_fence(c.sb);
          const uint4 q = get(2);
          if (g > 0) mbar_wait(BAR(B_VST), s & 1);
          put(1, k); put(2, q);
          TR(s, 5);
          mbar_arrive_both(BAR(B_LFREE), c.b ^ 1);
          after_sc();
          load_v();
          continue;
        }
        if (FIN_AT < 3) {
          if (EXP_FIN & 1) put(0, get(0));
          TR(s, 3);
          if (FIN_AT == 1) after_sc();
          if (V_TMA == 1) load_v();
          if (EXP_FIN & 2) put(1, get(1));
        } else {
          const uint4 v = get(0);
          sched_fence(c.sb);
          const uint4 k = get(1);
          if (g > 0) { mbar_wait(BAR(B_VST), s & 1); if (DLY_FS) delay_cycles(DLY_FS); }
          put(0, v); put(1, k);
        }
        TR(s, 4);
        if (FIN_AT == 4) {
          const uint4 q = get(2);
          after_sc();
          load_v();
          put(2, q);
        } else {
          if (FIN_AT >= 2) after_sc();
          if (V_TMA == 2) load_v();
          if (EXP_FIN & 4) put(2, get(2));
        }
        mbar_arrive_both(BAR(B_LFREE), c.b ^ 1);
        if (V_TMA == 3) load_v();
        TR(s, 5);
        if (!FIN_AT && X_AT && g > 0) { mbar_wait(BAR(B_SC), s & 1); if (DLY_FK) delay_cycles(DLY_FK); load_x(); }
      }
    }
    const int tile = tile_of(c), s0 = (tile >> 3) * 4, n0 = (tile & 7) * 128;
    if (c.w == 1) {
      mbar_idle(BAR(B_PVDONE), 0);
      count_e(g_ctl + (EARLY2 ? C_LAST : C_EARLY));
      st_pub(c.mail + (uint32_t)((tid_now() & 6) * (M_REG / 2) + M_SEL + (tid_now() & 1) * 4096 + c.r * 4), 0);
      await_count(g_ctl + C_COLS, 4);
      if (K_TMA) mbar_idle(BAR(B_SC), 1);
      mbar_expect_e(BAR(B_TW), 8192);
      bulk_load_e(c.sb + SM_TW, g_tw, 8192, BAR(B_TW));
    } else if (c.w == 2) {
      const uint32_t ln = tid_now() & 31, rel = mapa(BAR(B_GEMPTY) + (ln >> 2) * 8, ln & 1);
      mbar_idle(BAR(B_VST), 1); mbar_idle(BAR(PRE_AT), 1);
      arrive_remote_if(rel, ln < 12);
      mbar_idle(BAR(B_E2TRIG), 1);
      if (GATE) mbar_wait(BAR(B_DONE), 0);
      arrive_remote_if(rel, ln >= 12 && ln < 20);
    } else {
      auto ahead = [&](int k) {
        if (c.w) { if (PF_A && (k & 3) == (tile >> 1 & 3)) prefetch3d_e(&ta, k * 32, s0 + 2 * c.b); }
        else if (PF_B && (k & 7) == (tile >> 4)) prefetch2d_e<(ONCE & 512) != 0>(&tw, n0 + (tile & 8) * 8, k * 64);
      };
#pragma unroll 1
      for (int k = 0; k < PF_D; k++) ahead(k);
      if (c.w == 3) await_count(g_ctl + C_EARLY, 128);
      const int skew = tile < 120 ? 0 : SKEW;
      uint32_t o = SM_XT, st = 0, ph = 0;
#pragma unroll 1
      for (int kb = 0; kb < 64 + skew; kb++, o = next_stage(o)) {
        const bool solo = kb < skew || kb >= 64;
        const uint32_t bar = BAR(B_GFULL + st), k = kb & 63;
        if (c.w && kb == skew) {
          if (tile >= 120) await_count(g_ctl + C_LAST, EARLY2 ? 640 : 512);
          if (tid_now() == 480) TL(10);
          __syncwarp();
        }
        mbar_wait(BAR(B_GEMPTY + st), ph);
        if (c.w) {
          const int r = solo ? (kb >> 5) + c.b : c.b * 2;
          tma3d_mc_e(c.sb + o + r * 4096, solo ? &ta32 : &ta, k * 32, s0 + r, bar);
        } else {
          mbar_expect_e(bar, solo ? 24576 : 32768);
          tma2d_o<(ONCE & 2) != 0>(c.sb + o + 16384, &tw, n0, k * 64, bar);
          tma2d_o<(ONCE & 2) != 0>(c.sb + o + 24576, &tw, n0 + 64, k * 64, bar);
        }
        if (kb + PF_D < 64) ahead(kb + PF_D);
        if (++st == 5) { st = 0; ph ^= 1; }
      }
    }
    return;
  } else if (c.m == 2) {
    asm volatile("setmaxnreg.dec.sync.aligned.u32 %0;" :: "n"(512 - 2 * REG_F - REG_H));
    c.lane = lane_id();
    {
      uint32_t tl = clock_lo() + (PACE0 + WO_AT * PACE);
      TR(-2, 0);
      sched_fence(i0 ^ i1);
      TR(-2, 7);
      int far1 = 0;
#pragma unroll 1
      for (int rep = EARLY; rep <= NPROBE; rep++) {
        const int lag = race_init(own + (rep & 1) * 4096, own + (~rep & 1) * 4096, SENT);
        if (rep) far1 += ((rep ^ c.r >> 5) & 1 ? 1 : -1) * min(lag, 200);
      }
      sts32(c.sb + SM_SEL + 512 + c.w * 4, (8 + far1 / (16 * NPROBE)) << 4 * c.w);
      TR(-2, 1);
      if (tid_now() == 256) TL2(14);
      __syncwarp();
      mbar_arrive_warp(BAR(B_PROBE));
      if (c.w == 0) {
        mbar_idle(BAR(B_PROBE), 0);
        const uint4 bits = lds128(c.sb + SM_SEL + 512);
        const uint32_t res = bits.x | bits.y | bits.z | bits.w;
        st_pub_if(c.mail + (uint32_t)((c.lane & 6) * (M_REG / 2) + M_SEL + (c.lane & 1) * 4096 + c.r * 4), res | tile_key(), c.lane < 8);
        const int q = (res >> 4 * ((c.lane + c.r) & 3) & 15) - 8, best = __reduce_max_sync(~0u, abs(q) * 64 + (c.lane & 3) * 16 + ((c.lane + c.r) & 3) * 2 + (q <= 0));
        const char* src = c.mail + (uint32_t)((best & 6) * (M_REG / 2) + M_SEL + (best & 1) * 4096 + c.lane * 16);
        if (SEL_AT) delay_until(tl - (PACE0 + WO_AT * PACE - SEL_AT));
        uint4 v; uint32_t n = 0;
        TR(-2, 4);
        while (true) {
          delay_cycles(DLY_SEL);
          TR(-2, 6);
          v = ld_poll(src);
          if (__all_sync(~0u, v.x && v.y && v.z && v.w)) break;
          watchdog(n, POLL_LIMIT);
        }
        TR(-2, 5);
        int ta = 0, tb = 0, pa = 0, pb = 0;
        uint32_t flip = 0;
#pragma unroll 1
        for (int i = 0; i < 4; i++) {
          const int a = (v.x >> 4 * i & 15) + (v.y >> 4 * i & 15) - 16, b = (v.z >> 4 * i & 15) + (v.w >> 4 * i & 15) - 16;
          const bool f = __reduce_add_sync(~0u, a * ta + b * tb) < 0;
          ta += f ? -a : a; tb += f ? -b : b; flip |= (uint32_t)f << i;
        }
#pragma unroll 1
        for (uint32_t g = 0; g < 8; g++) {
          const bool a = (v.x >> 16) - g * 256 < 120, b = (v.z >> 16) - g * 256 < 120;
          const int n = __reduce_add_sync(~0u, (a ? ta : 0) + (b ? tb : 0)) > 0 ? PRIOR : -PRIOR;
          if (a) pa = n;
          if (b) pb = n;
        }
        const uint32_t ka = AWARE && ta + pa > 0 ? ~flip : flip, kb = AWARE && tb + pb > 0 ? ~flip : flip;
        sts128(c.sb + SM_SEL + c.lane * 16, make_uint4(ka, ka, kb, kb));
        mbar_arrive_warp(BAR(B_SEL));
        const uint32_t key = __shfl_sync(~0u, c.a ? v.z : v.x, c.h);
        const int u = __popc(__ballot_sync(~0u, v.x < key)) + __popc(__ballot_sync(~0u, v.z < key));
        sts32(c.sb + SM_SEL + 528, (u & 32) * 2 + (u & 7) * 8 + (u >> 2 & 6) + c.b);
        TR(-2, 2);
        if (c.lane == 0) TL2(13);
        __syncwarp();
        bar_sync(14, 160);
        if (ZDLY) delay_cycles(ZDLY);
#pragma unroll 4
        for (int k = c.lane >> 3; k < (ZINIT ? 128 : 0); k += 4) {
          const int e = k & 7;
          const uint2 d = lds64(c.sb + SM_TAB + (e == 3 ? k - 1 : k) * 8);
          st_pub4(mk_ptr((d.x & ~127u) + (e < 2 ? (k & 8) * 32 : e == 3 ? 128 : 0) + (c.lane & 7) * 16, d.y), make_uint4(0, 0, 0, 0));
        }
        __syncwarp();
        if (c.lane < 4) asm volatile("mbarrier.arrive.shared::cta.b64 _, [%0];" :: "r"(BAR(B_PROBE)) : "memory");
        __syncwarp();
        TR(-2, 8);
      }
      if (c.w == 2) {
        mbar_idle(BAR(B_P1), 0);
        if (P1_AT) { mbar_idle(BAR(B_WFULL), 0); mbar_idle(BAR(B_WFULL + 1), 0); }
        st_pub_if(g_ctl + C_COLS + (c.r & 15) * 32 + c.lane, 0, c.r < (C_END - C_COLS) / 32);
        count_e(g_ctl + C_P1);
        TR(-2, 3);
      }
      if (c.w == 1) for (int i = 0; i < WO_N; i++) { delay_until(tl += WO_P * PACE); prefetch2d_e(&to, c.j * 256 + (i ^ WO_X) * 64, c.h * 128); }
      if (c.w == 3) {
        mbar_idle(BAR(B_WREAD0), 0);
        for (int i = 0; i < 2; i++) tma4d_e(c.sb + SM_WO + i * 16384, &tx, c.b * 8, 2 * (c.b ^ i), BAR(B_PFULL));
        mbar_expect_e(BAR(B_WOFULL), 65536);
#pragma unroll 1
        for (int i = 3; i >= 0; i--) {
          if (i & 1) mbar_idle(BAR(i < 2 ? B_XEMPTY : B_WREAD), 0);
          TMA_O(c.sb + SM_WO + i * 16384, &to, c.j * 256 + i * 64, c.h * 128, BAR(B_WOFULL));
        }
      }
    }
    asm volatile("barrier.cluster.wait;" ::: "memory");
    const int g = c.w, src0 = c.h * 4 + (g >> 1) * 2;
    mbar_wait(BAR(B_SEL), 0);
    c.sel = __shfl_sync(~0u, (e1_box(c, 0, src0 + (c.lane >> 5)) & 4096) | (e1_box(c, 1, src0) & 4096) * 2, 0);
    mbar_wait(BAR(B_WREAD), 0);
    uint32_t l16 = c.sb + g * 512 + c.lane * 16;
    auto lane = [&](uint32_t v) { l16 = dep(l16, v, c.sb); return (int)((l16 & 511) >> 4); };
    pad<PAD2>();
    for (int s = 0; s < NSEG; s++) {
      l16 = vary(l16, s, c.sb);
      int ln = (l16 & 511) >> 4;
      uint4 kf[4], qx;
      auto load_x = [&]() {
        if (X_AT >= 2 && g == X_W && s + 2 < XEND) {
          if (KL_AT != 2) mbar_wait(BAR(B_XEMPTY), ~s & 1);
          if (DLY_XL) delay_cycles(DLY_XL);
          mbar_expect_e(BAR(B_XFULL), 16384 * EXP_NXT);
          for (int i = 0; i < EXP_NXT; i++) tma4d_e(c.sb + SM_XT + i * 16384, &tx, c.b * 8, (s + 2) * 4 + 2 * (c.b ^ i), BAR(B_XFULL));
        }
      };
      {
        const int gs = min(s, XEND - 1);
        const char* pk = c.mail + (uint32_t)(M_KVQ + (gs & (NSLOT - 1)) * M_REG + c.h * 24576 + g * 2048 + ln * 16);
        const char* pq = pk + (16384 + c.j * 2048 - g * 1536);
        const uint32_t tg = (gs / NSLOT) & 1;
        touch(pk, c.sb); touch(pq, c.sb);
        TR(s, 0);
        mbar_wait(BAR(B_VFULL), s & 1);
        TR(s, 1);
        uint4 k[4];
        auto load_k = [&]() {
          if (Q_TMA && Q_AT == 0) qx = lds128(l16 + SM_Q);
          if (DLY_K) delay_cycles(DLY_K);
#pragma unroll
          for (int t = 0; t < 4; t++) k[t] = lds128(l16 + (g * 1536 + SM_K + t * 512));
          if (Q_TMA && Q_AT == 1) qx = lds128(l16 + SM_Q);
        };
        if (K_TMA && KL_AT == 1) load_k();
        if (Q_TMA && Q_AT == 2) qx = lds128(l16 + SM_Q);
        if (s > 0) mbar_wait(BAR(B_PUB), (s - 1) & 1);
        if (K_TMA) {
          if (!Q_TMA) qx = ld_poll(pq);
          if (KL_AT == 2) { mbar_spin_if(BAR(B_XEMPTY), ~s & 1, s + 1 < XEND); load_x(); }
          if (KL_AT != 1) load_k();
        }
        for (uint32_t n = 0; ; ) {
          if (!K_TMA) {
#pragma unroll
            for (int t = 0; t < 4; t++) k[t] = ld_poll(pk + t * 512);
            qx = ld_poll(pq);
          }
#pragma unroll
          for (int t = 0; t < 2; t++) {
            auto cp = [&](uint32_t v) { return dep(v, 0, c.sb); };
            kf[t] = make_uint4(cp(k[2 * t].x), cp(k[2 * t].y), cp(k[2 * t + 1].x), cp(k[2 * t + 1].y));
            kf[2 + t] = make_uint4(cp(k[2 * t].z), cp(k[2 * t].w), cp(k[2 * t + 1].z), cp(k[2 * t + 1].w));
          }
          if (all_clear(stale1(stale2(k[0].x, k[1].x, tg) | stale2(k[2].x, k[3].x, tg), qx.x, tg), EXP_CHK)) break;
          watchdog(n, POLL_LIMIT); CNT(4);
          if (K_TMA) {
#pragma unroll
            for (int t = 0; t < 4; t++) k[t] = ld_poll(pk + t * 512);
            qx = ld_poll(pq);
          }
        }
        TR(s, 2);
      }
      if (KL_AT != 2 && !LX_AT) load_x();
      ln = lane(kf[0].y);
      const char* pa = c.mail + (uint32_t)(box(s & 1, src0) + 8192 + (c.sel >> (s & 1) & 4096) + (g & 1) * 512 + (EXP_LIN ? ln * 16 : read_off(ln)));
      const uint32_t spw = c.sb + SM_SP + g * 1280 + (ln & 3) * 64 + ((((ln >> 3) ^ ln) & 2) << 4) + (ln & 4) * 4 + (ln & 8),
                     spr = c.sb + SM_SP + (ln & 4) * 80 + (ln >> 3) * 64 + (((ln & 3) ^ ((ln >> 3) & 2)) << 4), l8 = ln * 8;
      const uint32_t tg = s >> 1;
      float sx[2][4];
      uint32_t sm;
      uint4 km;
      auto causal = [&](uint32_t (&sc)[5], int l) {
        const int n = l >> 2, lim = 16 * (8 * c.j + (n & 4) + 2 * (n & 1) + ((n >> 1) & 1) - 2 * (l & 3) + 1);
#pragma unroll
        for (int w = 0; w < 4; w++) {
          uint32_t m; asm("shl.b32 %0, 0xffffffff, %1;" : "=r"(m) : "r"(max(lim - 128 * w, 0)));
          sc[1 + w] = (sc[1 + w] & ~m) | (0xD029D029u & m);
        }
      };
      if (SXP) {
        scores_x<false>(sx, kf, qx, 0);
        if (DLY_SA) { sched_fence(dep(c.sb, __float_as_uint(sx[1][0]), c.sb)); delay_cycles(DLY_SA); }
        store_scores(sx, spw + (SM_K - SM_SP + g * 768));
        if (LX_AT == 1) load_x();
        if (DLY_SB) delay_cycles(DLY_SB);
        bar_sync(NB_ATT, 128);
        const uint32_t ax = spr + (SM_K - SM_SP);
        uint4 t = add4(lds128(ax), lds128(ax + 2048));
        const uint32_t ay = SXP == 2 ? dep(ax, t.x, c.sb) : ax;
        t = add4(add4(t, lds128(ay + 4096)), lds128(ay + 6144));
        uint32_t sc[5] = {0, t.x, t.y, t.z, t.w};
        causal(sc, ln);
        sts128(l16 + SM_OX, make_uint4(sc[1], sc[2], sc[3], sc[4]));
      }
      touch(pa, c.sb);
      mbar_wait(BAR(B_E1TRIG), s & 1);
      const uint32_t t0 = clock_lo();
      TRV(s, 3, t0);
      if (!SXP) {
        scores_x<false>(sx, kf, qx, 0);
        store_scores(sx, spw + 640);
      }
      if (DLY_E1) delay_fine(t0 + DLY_E1);
      uint32_t nr = 0;
      while (true) {
        const uint4 q0 = ld_poll(pa), q1 = ld_poll(pa + 2048), k0 = ld_poll(pa + 1024), k1 = ld_poll(pa + 3072);
        uint4 qm = add4(q0, q1);
        const uint32_t bq = stale2(q0.x, q1.x, tg);
        qm.x = dep(qm.x, bq, c.sb);
        scores_x<SC_F>(sx, kf, qm, c.sb);
        const uint32_t bk = stale2(k0.x, k1.x, tg);
        km = add4(k0, k1);
        km.x = dep(km.x, bk, c.sb);
        const bool ok = all_clear(bq | bk, 1);
        sm = scores_m(qm, km);
        store_scores(sx, spw);
        if (ok) break;
        nr++; CNT(2);
      }
      sts32(l8 + (c.sb + SM_SPM + (g >> 1) * 256 + (g & 1) * 4), sm);
      bar_sync(NB_ATT, 128);
      TR(s, 5); TRV(s, 13, nr);
      float o[2][4];
      uint32_t sp[5];
      uint4 vf[4];
      load_scores(sp, spr, l8 + (c.sb + SM_SPM));
      const uint32_t m5 = max5(sp);
      uint32_t m1;
      float off = row_off(m5, m1), f[10];
      l16 = dep(l16, VF_AT ? m1 : m5, c.sb);
#pragma unroll
      for (int t = 0; t < 4; t++) vf[(t >> 1) + 2 * (t & 1)] = lds128(l16 + SM_V + ((t >> 1) + 2 * (t & 1)) * 2048);
      qx.x = dep(qx.x, sp[0], c.sb);
      sts32(l8 + (c.sb + SM_SPM + 512 + (g >> 1) * 256 + (g & 1) * 4), scores_m(qx, km));
      mbar_arrive_warp(BAR(B_SC));
      unpack(f, sp);
      if (UP_F) sched_fence(c.sb);
      uint4 vm;
      if (VM_AT < 2) {
        bar_sync(NB_VM, 384);
        sp[1] = exp_pair(f, 1, off);
        const uint32_t av = dep(l8, VM_AT ? sp[1] : __float_as_uint(off), c.sb) + (c.sb + g * 512 + SM_VM);
        const uint2 vm0 = lds64(av), vm1 = lds64(av + 256);
        vm = make_uint4(vm0.x, vm0.y, vm1.x, vm1.y);
#pragma unroll
        for (int i = 2; i < 6; i++) sp[i % 5] = exp_pair(f, i % 5, off);
      } else {
#pragma unroll
        for (int i = 1; i < 6; i++) sp[i % 5] = exp_pair(f, i % 5, off);
        bar_sync(VM_AT == 2 ? dep(dep(0, sp[1] ^ sp[2], c.sb) + NB_VM, sp[0], c.sb) : dep(dep(0, sp[0] ^ sp[1] ^ sp[2], c.sb) + NB_VM, sp[3], c.sb), 384);
        const uint32_t av = l8 + (c.sb + g * 512 + SM_VM);
        const uint2 vm0 = lds64(av), vm1 = lds64(av + 256);
        vm = make_uint4(vm0.x, vm0.y, vm1.x, vm1.y);
      }
      uint2 u0, u1;
      uint4 sxx;
      auto load_sx = [&](uint32_t a8) { u0 = lds64(a8 + (c.sb + SM_SPM + 512)); u1 = lds64(a8 + (c.sb + SM_SPM + 768)); sxx = lds128(l16 + SM_OX); };
      if (SXP && XL_AT) load_sx(XL_AT == 2 ? dep(l8, vm.x, c.sb) : l8);
      float sum;
      auto rows_m = [&]() {
        const uint32_t tv = min(s, XEND - 1) / NSLOT;
        sum = pv(o, sp, vf, vm);
        stsm4<false>(l16 + SM_OM, pack_bf16(o[0][0], o[0][1]), pack_bf16(o[0][2], o[0][3]), pack_bf16(o[1][0], o[1][1]), pack_bf16(o[1][2], o[1][3]));
        sts32(c.sb + SM_SUM + ((l16 >> 4) & 28), __float_as_uint(sum));
        return arrive_if_clear(stale2(vf[0].x, vf[1].x, tv) | stale2(vf[2].x, vf[3].x, tv), EXP_CHK, NB_OM, 384);
      };
      if (!rows_m()) {
        const char* pv_ = c.mail + (uint32_t)(M_KVQ + (min(s, XEND - 1) & (NSLOT - 1)) * M_REG + c.h * 24576 + 8192 + (l16 - c.sb));
        uint32_t n = 0;
        do {
#pragma unroll
          for (int t = 0; t < 4; t++) vf[t] = ld_poll(pv_ + t * 2048);
          watchdog(n, POLL_LIMIT); CNT(5);
        } while (!rows_m());
        if (SXP && XL_AT) load_sx((l16 & 511) >> 1);
      }
      const uint32_t tom = clock_lo();
      TRV(s, 8, tom);
      sched_fence(c.sb);
      ln = lane(tom);
      const int n = ln >> 2, jj = ln & 3, tq_ = 8 * c.j + (n & 4) + 2 * (n & 1) + ((n >> 1) & 1);
      if (DLY_X) delay_until(tom + DLY_X);
      if (SXP) {
        if (!XL_AT) load_sx(ln * 8);
        sp[0] = sum4(u0.x, u0.y, u1.x, u1.y); sp[1] = sxx.x; sp[2] = sxx.y; sp[3] = sxx.z; sp[4] = sxx.w;
      } else {
        load_scores(sp, spr + 640, c.sb + SM_SPM + 512 + ln * 8);
        causal(sp, ln);
      }
      mbar_arrive_warp(dep(dep(0, sp[0], c.sb), sp[1], c.sb) + BAR(B_SPFREE));
      off = row_off(max5(sp), m1);
      unpack(f, sp);
#pragma unroll
      for (int i = 1; i < 6; i++) sp[i % 5] = exp_pair(f, i % 5, off);
      if (DLY_Y) { sched_fence(dep(dep(c.sb, sp[0] ^ sp[1] ^ sp[2], c.sb), sp[3] ^ sp[4], c.sb)); delay_until(tom + DLY_Y); }
      sum = pv(o, sp, vf, vm);
      TR(s, 7);
      sum = rcp(sum);
      const float i0 = __shfl_sync(~0u, sum, 8 * jj), i1 = __shfl_sync(~0u, sum, 8 * jj + 4);
      const uint32_t oxs = c.sb + SM_OX + g * 512;
      stsm4<true>(oxs + (ln & 7) * 64 + (((ln >> 3) ^ ((ln >> 1) & 3)) << 4),
                  pack_bf16(o[0][0] * i0, o[0][1] * i1), pack_bf16(o[0][2] * i0, o[0][3] * i1), pack_bf16(o[1][0] * i0, o[1][1] * i1), pack_bf16(o[1][2] * i0, o[1][3] * i1));
      __syncwarp();
      *(uint4*)(g_ox + ox_at(s, tq_, c.h * 4 + g, jj)) = lds128(oxs + n * 64 + ((jj ^ (n >> 1)) << 4));
      mbar_arrive_warp(BAR(B_PVDONE));
      TR(s, 9);
    }
    if (LASTM) {
      const int ln = tid_now() & 31, n = ln >> 2, jj = ln & 3, tq_ = 8 * c.j + (n & 4) + 2 * (n & 1) + ((n >> 1) & 1);
      store_count(g_ox + ox_at(NSEG - 1, tq_, c.h * 4 + g, jj), lds128(c.sb + SM_OX + g * 512 + n * 64 + ((jj ^ (n >> 1)) << 4)), (char*)(g_ctl + C_LAST) + (LASTM == 2 ? c.r * 4 + g : 0));
    } else count_e(g_ctl + C_LAST);
    mbar_arrive_warp(BAR(B_DONE));
    if (tid_now() == 256) TL(8);
    __syncwarp();
    mbar_wait(BAR(B_E2TRIG), 1); mbar_idle(BAR(B_DONE), 0); mbar_wait(BAR(B_TW), 0);
    asm volatile("setmaxnreg.inc.sync.aligned.u32 128;");
  } else {
    {
      const int w = c.m * 4 + c.w;
      mbar_expect_e(BAR(B_ROWS), 4096 + 256);
      for (int i = 0; i < 2; i++) bulk_load_e(c.sb + SM_FFT + (1024 + w * ROW_BUF) * 8 + i * 2048, x + (size_t)(z_row(c.r * 8 + w) + i * 1024) * D_, 2048, BAR(B_ROWS));
      bulk_load_e(c.sb + SM_GW + w * 256, gw + w * 128, 256, BAR(B_ROWS));
    }
    asm volatile("setmaxnreg.inc.sync.aligned.u32 %0;" :: "n"(REG_F));
    c.lane = lane_id();
    uint32_t wa[16][4], wb[16][4], wv[16][4];
    TR(-2, 4);
    fft_rows_fwd((float2*)(smraw + SM_FFT), (const __nv_bfloat16*)(smraw + SM_GW), c.r, threadIdx.x, BAR(B_ROWS), BAR(B_FREE), [&](int e) { TR(-2, e); }, [&]() {
      mbar_spin(BAR(B_PFULL), 0);
#pragma unroll
      for (int k = 0; k < NP; k++) ldsm4t(wa[k], c.sb + SM_POOL + c.m * NP * 2048 + frag_off(c.w, c.lane) + k * 2048);
      bar_sync(NB_XCH, 256);
#pragma unroll
      for (int k = 0; k < NP; k++) sts128(c.sb + SM_POOL + c.m * 2048 + c.w * 512 + c.lane * 16 + k * 4096, make_uint4(wa[k][0], wa[k][1], wa[k][2], wa[k][3]));
    });
    mbar_arrive_warp(BAR(B_P1));
    TR(-2, 0);
    if (tid_now() == 0) TL2(1);
    __syncwarp();
    mbar_spin(BAR(B_WFULL + c.m), 0);
    TR(-2, 1);
    if ((tid_now() & 127) == 0) TL2(16);
    __syncwarp();
    {
      const uint32_t st = c.sb + c.m * ST_WG + frag_off(c.w, c.lane);
#pragma unroll
      for (int k = 0; k < 16; k++) ldsm4t(wb[k], st + k * 2048);
#pragma unroll
      for (int k = NP; k < 16; k++) ldsm4t(wa[k], st + (16 + k - NP) * 2048);
#pragma unroll
      for (int k = 0; k < NV; k++) ldsm4t(wv[k], st + (32 - NP + k) * 2048);
      mbar_arrive_warp(BAR(B_WREAD));
      if (c.m == 0) mbar_arrive_warp(BAR(B_WREAD0));
#pragma unroll
      for (int k = 0; k < (LP_IN == 2 ? 0 : NP); k++) lds_frag(wa[k], c.sb + SM_POOL + c.m * 2048 + c.w * 512 + c.lane * 16 + k * 4096);
      TR(-2, 2);
    }
    TR(-2, 3);
    if (tid_now() == 0) TL2(12);
    __syncwarp();
    asm volatile("barrier.cluster.wait;" ::: "memory");
    uint32_t t16 = c.m * 2048 + c.w * 512 + c.lane * 16;
    uint32_t pk = (c.m * NHV * 2048 + frag_off(c.w, c.lane)) | (tile_off(2 * (c.w & 1), c.lane) << 16) | ((c.lane & 12) ? 0u : 0x80000000u);
    const uint32_t dx1 = desc_lo(c.sb + SM_XT + c.m * 4096), dh = desc_lo(c.sb + SM_HV + c.m * NHV * 2048);
    mbar_spin(BAR(B_PFULL), 1);
    pad<PAD0>();
    for (int s = -2; ; s++) {
      t16 = vary(t16, s, c.sb); pk = vary(pk, s, c.sb);
      const uint32_t dx = dx1 - (s == -2 ? (SM_XT - SM_WO) / 16 : 0);
      auto ldp = [&](int k0, int k1, int d, int back = 0) {
#pragma unroll
        for (int k = k0; k < k1; k++) lds_frag(wa[k], (k < k0 + d - back ? t16 : dep(t16, wa[k < d ? 0 : k - d][0], c.sb)) + (c.sb + SM_POOL + k * 4096));
      };
      if (s >= 0) {
        uint32_t af[16][4], bf[4][4], wo;
        const uint32_t tab = ((t16 >> 3) & 0x1C0) + (c.sb + SM_TAB + (s & 1) * 512);
        const char* pa;
        mem_proj(wa, wb, wv, af, wo, pa, tab, t16, pk, c, s);
        const uint32_t t0 = clock_lo();
        t16 = dep(t16, t0, c.sb);
        auto ldwo = [&](int f) { ldsm4t(af[f], (f < WO_D ? wo : dep(wo, af[f < WO_D ? 0 : f - WO_D][0], c.sb)) + (c.sb + SM_WO + (f & 1) * 32768 + (f >> 1) * 2048)); };
        {
          const uint32_t tg = s >> 1, vm = t16 >> 1, chk = (~t16 >> 4) & 1;
          if (WO_S && s == 0) {
            mbar_spin(BAR(B_WOFULL), 0);
#pragma unroll
            for (int f = 0; f < WO_0; f++) ldwo(f);
          }
#pragma unroll
          for (int f = WO_0; f < WO_1; f++) ldwo(f);
          if (DLY_V) delay_fine(t0 + DLY_V); else sched_fence(c.sb);
          uint2 v0 = ld_poll2(pa), v1 = ld_poll2(pa + 1024), v2 = ld_poll2(pa + 2048), v3 = ld_poll2(pa + 3072);
          TR(s, 3);
#pragma unroll
          for (int f = WO_1; f < 16 - WO_L; f++) ldwo(f);
          TR(s, 4);
          uint32_t n = 0;
          while (true) {
            sts64(vm + (c.sb + SM_VM), sum4(v0.x, v1.x, v2.x, v3.x), sum4(v0.y, v1.y, v2.y, v3.y));
            if (arrive_if_clear(stale1(stale1(stale2(v0.x, v1.x, tg), v2.x, tg), v3.x, tg), chk, NB_VM, 384)) break;
            v0 = ld_poll2(pa); v1 = ld_poll2(pa + 1024); v2 = ld_poll2(pa + 2048); v3 = ld_poll2(pa + 3072);
            n++; CNT(3);
          }
          TR(s, 12); TRV(s, 15, n);
        }
        const uint32_t ob = dep(dep(t16 & 511, af[14 - WO_L][0], c.sb), af[15 - WO_L][0], c.sb);
        uint32_t l4 = ob >> 2;
        const uint32_t bit = (t16 & 48) ? 0u : 1u;
        if (LF_AT) mbar_spin2_if(BAR(B_XFULL), BAR(B_LFREE), s & 1, s + 2 < XEND); else mbar_spin_if(BAR(B_XFULL), s & 1, s + 2 < XEND);
        bar_sync(NB_OM, 384);
        TR(s, 5);
#pragma unroll
        for (int i = 0; i < 4; i++) ldsm4t(bf[i], ob + (c.sb + SM_OM + i * 512));
        uint2 sum = lds64(((t16 >> 1) & 24) + (c.sb + SM_SUM));
        if (OM_F) sched_fence(c.sb);
        float d[WO_C][4] = {};
        uint4 d0, d1;
#pragma unroll
        for (int f = 0; f < 16; f++) {
          mma_a(d[f % WO_C], af[f], bf[f >> 2][f & 2], bf[f >> 2][(f & 2) + 1]);
          if (f >= WO_C && f < WO_C + WO_L) {
            const int l = 16 - WO_L + f - WO_C;
            ldsm4t(af[l], (WO_LD ? dep(wo, __float_as_uint(d[(f + 1) % WO_C][0]), c.sb) : wo) + (c.sb + SM_WO + (l & 1) * 32768 + (l >> 1) * 2048));
          }
          if (f == WO_T) {
            const uint32_t tb2 = dep((t16 >> 3) & 0x1C0, __float_as_uint(d[f % WO_C][0]), c.sb) + (c.sb + SM_TAB + (s & 1) * 512);
            d0 = lds128(tb2 + 32); d1 = lds128(tb2 + 48);
          }
          if (f >= PL_WA && f < PL_WA + PL_W) lds_frag(wa[f - PL_WA], (PL_WD ? dep(t16, __float_as_uint(d[(f + PL_WD) % WO_C][0]), c.sb) : t16) + (c.sb + SM_POOL + (f - PL_WA) * 4096));
          if (PL_W && PL_WF == 1 && f == PL_WA + PL_W - 1) sched_fence(c.sb);
          if (f == 4) { sum.x = dep(sum.x, __float_as_uint(d[0][0]), c.sb); sum.y = dep(sum.y, __float_as_uint(d[0][0]), c.sb); }
        }
        if (PL_W && !PL_WF) {
          uint32_t all = 0;
#pragma unroll
          for (int k = 0; k < PL_W; k++) all ^= wa[k][0];
          l4 = dep(l4, all, c.sb);
        }
        char* dst[4] = {mk_ptr(d0.x | l4, d0.y), mk_ptr(d0.z | l4, d0.w), mk_ptr(d1.x | l4, d1.y), mk_ptr(d1.z | l4, d1.w)};
        const float i0 = rcp(__uint_as_float(sum.x)), i1 = rcp(__uint_as_float(sum.y));
#pragma unroll
        for (int i = 0; i < 4; i++) {
          const int t = i >> 1, e = 2 * (i & 1);
          const float y0 = WO_C == 2 ? d[t][e] : d[t][e] + d[(t + 2) % WO_C][e], y1 = WO_C == 2 ? d[t][e + 1] : d[t][e + 1] + d[(t + 2) % WO_C][e + 1];
          st_pub(dst[i], put_tag(pack_bf16(y0 * i0, y1 * i1), bit, s >> 1));
        }
        if (ANCH2) sts32(c.sb + SM_SUM + 64, clock_lo());
        mbar_arrive_warp(BAR(B_E2TRIG));
        TR(s, 6);
        sched_fence(c.sb);
        if (W_E2 == 2) mbar_spin(BAR(B_E2TRIG), s & 1);
#pragma unroll
        for (int k = PL_A; k < PL_0; k++)
#pragma unroll
          for (int i = 0; i < 4; i++) wa[k][i] = af[16 - PL_0 + k][i];
      }
      if (__builtin_expect(s + 2 < XEND, 1)) {
        const uint32_t tg0 = DLY_P ? clock_lo() + DLY_P : 0;
        if (LP_IN) ldp(PL_W, PL_A, PL_D);
        if (PL_A < PL_0 && c.m != ASY) ldp(PL_A, PL_0, PL_D, PL_A > PL_W ? PL_D : 0);
        auto late = [&](int at) {
          if (PL_A < PL_B && ASY_A == at && c.m == ASY) ldp(PL_A, PL_B, PL_DA);
          if (PL_B < PL_0 && ASY_AT == at && c.m == ASY) ldp(PL_B, PL_0, PL_DA);
        };
        float xa[16];
        uint32_t q[4];
        if (W_E2 == 1 && s >= 0) mbar_spin(BAR(B_E2TRIG), s & 1);
        TR(s, 7);
        constexpr int S1 = ORDER ? 0 : 2, S2 = ORDER == 0 ? 0 : ORDER == 1 ? 2 : 1, S3 = ORDER == 2 ? 2 : 1;
        if (ORDER) issue_qk<0, 16>(xa, wb, vary(dx, s, c.sb)); else issue_v(xa, wv, vary(dx, s, c.sb), vary(dh, s, c.sb));
        if (DLY_P) delay_until(tg0); else if (IS_F) sched_fence(c.sb);
        ldp(PL_0, PL_1, PL_D1);
        const uint32_t land = (t16 ^ ((t16 >> 3) & 0x60)) + vary(c.sb + SM_LAND + c.b * 4096, s, c.sb);
        TR(s, 14);
        if (LF_AT == 1) mbar_spin_if(BAR(B_LFREE), s & 1, s < 0); else if (!LF_AT) mbar_spin(BAR(B_LFREE), s & 1);
        TR(s, 15);
        late(0);
        WG_WAIT(0);
        TR(s, 8);
        park_own<S1 == 2>(q, xa, land, S1, c.sb);
        late(1);
        if (W_PUB == 4 && s >= 0) mbar_spin(BAR(B_PUB), s & 1);
        if (ORDER == 1) issue_v(xa, wv, vary(dx, s, c.sb + 32), vary(dh, s, c.sb)); else issue_qk<0, 16>(xa, ORDER ? wa : wb, vary(dx, s, c.sb + 32));
        if (IS_F) sched_fence(c.sb);
        ldp(PL_1, PL_2, PL_D1);
        if (W_PUB == 1) mbar_spin_if(BAR(B_PUB), s & 1, s >= 0);
        uint32_t tp = clock_lo(), q1[4] = {q[0], q[1], q[2], q[3]};
        if (PL_2B) ldp(PL_2, NP - PL_L, PL_D1);
        late(2);
        if (W_PUB != 3) park_peer(q, land, S1, c);
        if (!PL_2B) ldp(PL_2, NP - PL_L, PL_D1);
        late(3);
        TR(s, 13);
        WG_WAIT(0);
        TR(s, 9);
        park_own<S2 == 2>(q, xa, land, S2, c.sb);
        late(4);
        if (ORDER == 2) issue_v(xa, wv, vary(dx, s, c.sb + 64), vary(dh, s, c.sb));
        else {
          issue_qk<0, PL_L ? NP - PL_L : 16>(xa, wa, vary(dx, s, c.sb + 64));
          ldp(NP - PL_L, NP, PL_E);
          if (PL_L) issue_qk<NP - PL_L, 16>(xa, wa, vary(dx, s, c.sb + 64));
        }
        if ((W_PUB == 2 || W_PUB == 3) && s >= 0) { mbar_spin(BAR(B_PUB), s & 1); tp = clock_lo(); }
        if (W_PUB == 3) park_peer(q1, land, S1, c);
        if (DLY_S && s >= 0) delay_until(tp + DLY_S);
        park_peer(q, land, S2, c);
        WG_WAIT(0);
        TR(s, 10);
        mbar_arrive_warp(BAR(B_XEMPTY));
        park_own<S3 == 2>(q, xa, land, S3, c.sb);
        park_peer(q, land, S3, c);
        TR(s, 11);
      } else {
        if (s == NSEG - 1) break;
        if (EARLY2 && (XEND == NSEG || s == NSEG - 2) && c.m * 4 + c.w == 0) count_e(g_ctl + C_EARLY);
        ldp(PL_W, NP, 2);
      }
    }
    asm volatile("setmaxnreg.dec.sync.aligned.u32 %0;" :: "n"(BPRE == 2 ? 176 : 128));
    const int tid = tid_now(), lane = tid & 31, tile = tile_of(c), m0 = (tile >> 3) * 128, n0 = (tile & 7) * 128;
    float acc[64];
#pragma unroll
    for (int i = 0; i < 64; i++) acc[i] = 0.f;
    const uint32_t rel = mapa(BAR(B_GEMPTY), lane & 1), la = desc_lo(c.sb + c.m * 8192), lb = ((c.sb + 16384) & 0x3FFFF) >> 4 | (8192 >> 4) << 16;
    bool relon = false;
    const int skew = tile < 120 ? 0 : SKEW, kend = 64 + skew - c.m * skew, hold = c.m * (65 - LEAD) - 1;
    const float g0 = __ldcg(g_gate + m0 + (tid >> 5) * 16 + (lane >> 2)), g1 = __ldcg(g_gate + m0 + (tid >> 5) * 16 + (lane >> 2) + 8);
    uint32_t o = SM_XT, st = 0, ph = 0, prev = 0;
    if (tid == 0) TL(9);
    __syncwarp();
    GT(0);
#pragma unroll 1
    for (int kb = -c.m * skew; kb < max(kend - 4, 64); kb++, o = next_stage(o)) {
      if (LEAD && kb == hold) bar_sync(15, 256);
      mbar_lim(BAR(B_GFULL + st), ph);
      if ((uint32_t)kb < 64) {
        WG_FENCE();
#pragma unroll
        for (int k = 0; k < 4; k++) wgmma_ss_n128_tb(acc, desc128(la + (o >> 4) + k * 2), desc128(lb + (o >> 4) + k * 128));
        WG_COMMIT();
        WG_WAIT(1);
      } else WG_WAIT(0);
      arrive_remote_if(rel + 8 * prev, relon && kb < kend - 4);
      relon = (tid & 127) < 2;
      prev = st;
      if (++st == 5) { st = 0; ph ^= 1; }
    }
    if (LEAD && c.m == 0) asm volatile("bar.arrive 15, 256;" ::: "memory");
    const uint32_t row = (tid >> 5) * 2048 + (lane & 15) * 128 + (((lane >> 4) ^ (lane & 7)) << 4);
    if (!BPRE) WG_WAIT(0);
    mbar_lim(BAR(B_BT), 0);
    uint32_t b[2][4][4];
    const uint32_t rb = (tid >> 5) * 2048 + (lane >> 2) * 128 + (((lane & 7) ^ (lane >> 2)) << 4);
#pragma unroll
    for (int i = 0; i < 8; i++) lds_frag(b[i & 1][i >> 1], (rb ^ (i & 2) * 32) + (c.sb + SM_BT + (i >> 2) * 16384 + (i & 1) * 1024));
    float bl[2][4][4], bh[2][4][4];
    if (BPRE == 2) {
#pragma unroll
      for (int i = 0; i < 32; i++) {
        asm volatile("shl.b32 %0, %1, 16;" : "=f"(bl[i >> 4][i >> 2 & 3][i & 3]) : "r"(b[i >> 4][i >> 2 & 3][i & 3]));
        asm volatile("and.b32 %0, %1, 0xffff0000;" : "=f"(bh[i >> 4][i >> 2 & 3][i & 3]) : "r"(b[i >> 4][i >> 2 & 3][i & 3]));
      }
    }
    if (BPRE) { sched_fence(c.sb); WG_WAIT(0); sched_fence(c.sb); }
#pragma unroll
    for (int i = 0; i < 64; i++) asm volatile("" : "+f"(acc[i]) :: "memory");
    GT(17);
    if (tid == 0) TL(4);
    __syncwarp();
#pragma unroll
    for (int hf = 0; hf < 2; hf++) {
#pragma unroll
      for (int t = 0; t < 4; t++) {
        uint32_t y[4];
#pragma unroll
        for (int i = 0; i < 4; i++) {
          const float* a = acc + 32 * hf + 8 * t + 2 * i, g = i & 1 ? g1 : g0;
          const uint32_t* q = b[i & 1][2 * (t & 1) + (i >> 1)] + hf;
          const float* f = (t & 2 ? bh : bl)[i & 1][2 * (t & 1) + (i >> 1)] + hf;
          if (BPRE == 2) y[i] = pack_bf16(fmaf(g, a[0], f[0]), fmaf(g, a[1], f[2])); else
          y[i] = pack_bf16(fmaf(g, a[0], __uint_as_float(t & 2 ? q[0] & 0xFFFF0000u : q[0] << 16)), fmaf(g, a[1], __uint_as_float(t & 2 ? q[2] & 0xFFFF0000u : q[2] << 16)));
        }
        stsm4<false>((row ^ t * 32) + (c.sb + SM_BT + hf * 16384), y[0], y[1], y[2], y[3]);
      }
      if (EP_F && !hf) { sched_fence(c.sb); for (int i = 32; i < 64; i++) asm volatile("" : "+f"(acc[i]) :: "memory"); }
      FENCE_ASYNC_SMEM();
      __syncwarp();
      tma2d_out_e(&tout, n0 + hf * 64, m0 + (c.m * 4 + c.w) * 16, c.sb + SM_BT + hf * 16384 + (c.m * 4 + c.w) * 2048);
    }
    asm volatile("cp.async.bulk.commit_group; cp.async.bulk.wait_group" WAITRD " 0;" ::: "memory");
    GT(18);
    if ((tid & 127) == 0) TL(11);
    return;
  }
  constexpr int NH = NQ < 106 ? 4 * (106 - NQ) : 0;
  const bool col = c.r >= 128;
  const int tile = col ? 0 : tile_of(c);
  const int q0 = col ? 256 - NQ + (c.r - 128) + c.m * 4 : tile < 120 ? tile : 256, u = (tile >> 1 & 32) | (tile >> 3 & 7) | (tile & 6) << 2, e = QSH == 2 ? 2 * (u - (u > 39) - (u > 47) - (NQ < 110 && u > 55)) + c.b : tile,
            dq = col ? 16 : QSH ? 120 + (e < NH ? e >> 1 : (e + NH) >> 2) - tile : 120, qe = col ? 256 : 256 - NQ,
            qw = col || !QSH || (e < NH ? c.w >> 1 == c.b : c.w == ((e + NH) & 3)) ? qe : 120;
  const uint32_t zs = c.sb + (col ? COL_Z + c.m * 32768 : SM_BT), zb = BAR(B_Z + c.m);
  auto load_z = [&](int q) { if (c.w == 0 && q < qe) { mbar_expect_e(zb, 32768); tma2d_o<(ONCE & 4) != 0>(zs, &tz, q * 64, 0, zb); } };
  asm volatile("fence.proxy.async.global;" ::: "memory");
  load_z(q0);
  uint32_t ph = 0;
#pragma unroll 1
  for (int q = q0; q < qe; q += dq, ph ^= 1) {
    mbar_lim(zb, ph);
    const int p = q * 4 + c.w;
    if (EXP_INV && q < qw) fft_rows_inv(zs, (float2*)(smraw + (col ? 8192 + c.m * INV_BUF * 32 : SM_MEM)) + c.w * INV_BUF, (const float2*)(smraw + (col ? 0 : SM_TW)), p, tid_now() & 31, g_b,
                              [&]() { bar_sync(5 + c.m, 128); load_z(q + dq); });
    else { bar_sync(5 + c.m, 128); load_z(q + dq); }
  }
  if (B_ST) asm volatile("cp.async.bulk.wait_group 0; fence.proxy.async.global;" ::: "memory");
  asm volatile("fence.acq_rel.gpu;" ::: "memory");
  __syncwarp();
  { const int q = q0 + (tid_now() & 31) * dq; if (q < qw) asm volatile("red.relaxed.gpu.global.add.u32 [%0], 1;" :: "l"(g_ctl + C_ROWS + (q >> 5) * 32) : "memory"); }
  if (tid_now() == 256) { if (col) TL(27); else TL(3); }
  __syncwarp();
  if (!col && c.w == 0) {
    await_count<AW_NS>(g_ctl + C_ROWS + ((tile >> 3) & 7) * 32, 128);
    mbar_expect_e(BAR(B_BT), 32768);
    for (int i = 0; i < 2; i++) tma2d_o<(ONCE & 8) != 0>(c.sb + SM_BT + i * 16384, &tb, (tile & 7) * 128 + i * 64, (tile >> 3) * 128, BAR(B_BT));
    if (tid_now() == 256) TL(5);
  }
}

typedef CUresult (*EncodeFn)(CUtensorMap*, CUtensorMapDataType, cuuint32_t, void*, const cuuint64_t*, const cuuint64_t*,
                             const cuuint32_t*, const cuuint32_t*, CUtensorMapInterleave, CUtensorMapSwizzle,
                             CUtensorMapL2promotion, CUtensorMapFloatOOBfill);

void make_map(EncodeFn enc, CUtensorMap* tm, const void* p, int rank, const cuuint64_t* dims, const cuuint64_t* strides, const cuuint32_t* box, bool swz = true) {
  const cuuint32_t es[4] = {1, 1, 1, 1};
  enc(tm, CU_TENSOR_MAP_DATA_TYPE_BFLOAT16, rank, (void*)p, dims, strides, box, es, CU_TENSOR_MAP_INTERLEAVE_NONE,
      swz ? CU_TENSOR_MAP_SWIZZLE_128B : CU_TENSOR_MAP_SWIZZLE_NONE, swz ? CU_TENSOR_MAP_L2_PROMOTION_L2_128B : W_PROMO, CU_TENSOR_MAP_FLOAT_OOB_FILL_NONE);
}
void make_map2(EncodeFn enc, CUtensorMap* tm, const void* p, uint64_t cols, uint64_t rows, uint32_t boxrows) {
  const cuuint64_t dims[2] = {cols, rows}, strides[1] = {cols * 2};
  const cuuint32_t box[2] = {64, boxrows};
  make_map(enc, tm, p, 2, dims, strides, box);
}

}

extern "C" void kernel_launch(void* const* d_in, const int* in_sizes, int n_in, void* d_out, int out_size) {
  (void)in_sizes; (void)n_in; (void)out_size;
  const __nv_bfloat16* x = (const __nv_bfloat16*)d_in[0];
  const __nv_bfloat16* mem0 = (const __nv_bfloat16*)d_in[1];
  const __nv_bfloat16* gw = (const __nv_bfloat16*)d_in[10];

  EncodeFn enc = nullptr;
  cudaDriverEntryPointQueryResult qr;
  cudaGetDriverEntryPoint("cuTensorMapEncodeTiled", (void**)&enc, cudaEnableDefault, &qr);
  void *p_ox, *p_b, *p_z, *p_mail;
  cudaGetSymbolAddress(&p_ox, g_ox); cudaGetSymbolAddress(&p_b, g_b); cudaGetSymbolAddress(&p_z, g_z); cudaGetSymbolAddress(&p_mail, g_mail);
  CUtensorMap tq, tk, tv, tv16, to, tx, twr, twi, ta, tw, tb, tout, tz, tzs, ta32;
  make_map2(enc, &tq, d_in[2], 4096, 1024, 64);
  make_map2(enc, &tk, d_in[3], 4096, 1024, 64);
  make_map2(enc, &tv, d_in[4], 4096, 1024, 64);
  make_map2(enc, &tv16, d_in[4], 4096, 1024, 16);
  make_map2(enc, &to, d_in[5], 1024, 4096, 128);
  make_map2(enc, &tw, d_in[5], 1024, 4096, 64);
  {
    const cuuint64_t dims[3] = {64, 2048, 64}, strides[2] = {128, 262144};
    const cuuint32_t box[3] = {64, 32, 2}, box1[3] = {64, 32, 1};
    make_map(enc, &ta, p_ox, 3, dims, strides, box);
    make_map(enc, &ta32, p_ox, 3, dims, strides, box1);
  }
  make_map2(enc, &tb, p_b, 1024, 2048, 128);
  make_map2(enc, &tout, d_out, 1024, 2048, 16);
  make_map2(enc, &tz, p_z, 16384, 257, 256);
  {
    const cuuint64_t dims[4] = {64, 8, 16, 256}, strides[3] = {2048, 128, 16384};
    const cuuint32_t box[4] = {64, 8, 8, 2};
    make_map(enc, &tx, x, 4, dims, strides, box);
  }
  {
    const cuuint64_t dims[2] = {512, 257 * 32}, strides[1] = {1024};
    const cuuint32_t box[2] = {128, 16};
    make_map(enc, &tzs, p_z, 2, dims, strides, box, false);
  }
  {
    const cuuint64_t dims[2] = {8 * 513, 256}, strides[1] = {8 * 513 * 2};
    const cuuint32_t box[2] = {8, 256};
    make_map(enc, &twr, d_in[8], 2, dims, strides, box, false);
    make_map(enc, &twi, d_in[9], 2, dims, strides, box, false);
  }
  cudaFuncSetAttribute(chain_kernel, cudaFuncAttributeMaxDynamicSharedMemorySize, CHAIN_SMEM);

  cudaStream_t st = cudaStreamPerThread;
  char* mail = (char*)(((uintptr_t)p_mail + M_REG - 1) & ~(uintptr_t)(M_REG - 1));
  chain_kernel<<<132, 512, CHAIN_SMEM, st>>>(tq, tk, tv, tv16, to, tx, twr, twi, ta, tw, tb, tout, tz, tzs, ta32, mem0, mail, x, gw);
}
```

```cpp
#include <cuda_runtime.h>
#include <cuda_bf16.h>
#include <cuda.h>
#include <stdint.h>

#define DLY_E1 220
#define DLY_V 330
#define DLY_E2 300
#define DLY_E3 440
#define DLY_X 0
#define DLY_S 100
#define DLY_F 150
#define VM_AT 3
#define OM_F 1
#define C1_AT 5
#define NLAG 2
#define WO_D 2
#define WO_0 3
#define WO_1 11
#define PL_0 10
#define PL_1 11
#define PL_D 2
#define PL_L 0
#define HV_D 4
#define DLY_FK 0
#define REG_F 216
#define REG_H 24
#define SC_F 1
#define E2_F 0
#define X_AT 2
#define PL_2 11
#define PL_E 2
#define ORDER 1
#define SSPOS 1
#define W_PUB 1
#define FIN_AT 5
#define AWARE 1
#define NPROBE 2
#define NP_ 12
#define DLY_GRP 1000
#define EXP_CHK 1
#define EXP_NXT 2
#define EXP_PEER 1
#define EXP_FIN 7
#define EXP_NWG 16
#define ANCH2 1
#define IS_F 1
#define PL_D1 1
#define W_E2 0
#define V_TMA 2
#define V_W 3
#define RED_L 3
#define RED_T 1
#define RED_P 1
#define DLY_E3B 100
#define HV_E 2
#define HV_R 5
#define HOLD 0
#define PACE 500
#define PACE0 0
#define EXP_ST 7
#define WO_AT 38
#define WO_P 2
#define DLY_SEL 300
#define P1_AT 0
#define TMA_W tma2d_once
#define TMA_O tma2d_once
#define PACE_Z 580
#define EXP_INV 1
#define VF_AT 1
#define UP_F 0
#define WO_L (12 - NP_)
#define WO_C 4
#define WO_T 3
#define WO_LD 0
#define EXP_LIN 0
#define PL_W 5
#define PL_WA 10
#define PL_WD 0
#define PL_WF 2
#define EXP_FL 0
#define DLY_FS 0
#define DLY_F2 40
#define PF_D 4
#define PF_A 0
#define PF_B 0
#define SIDE 1
#define ROLE 1
#define E1OFF 1
#define EPI 0
#define WAITRD ".read"
#define START 1000
#define WUNR 1
#define WO_N 0
#define PL_2B 1
#define DLY_P 0
#define LP_IN 1
#define LF_AT 1
#define FINE 0
#define E30 1
#define WO_S 1
#define POOL_AT 12
#define COL_DLY 0
#define PAD0 2
#define PAD2 0
#define PAD3 6
#define WO_X 0
#define PRIOR 12
#define EARLY 1
#define SEL_AT 3000
#define FUNR 0
#define ZINIT 1
#define ZDLY 0
#define NQ 84
#define GATE 0
#define LASTM 1
#define X_ONCE 1
#define ONCE 31
#define Z_PF 0
#define EXP_W 1
#define W_PROMO CU_TENSOR_MAP_L2_PROMOTION_L2_128B
#define Z_ST 1
#define W_FINE 0
#define X128 2
#define T128_ 1
#define W_AT 0
#define SKEW 7
#define AW_NS 0
#define QSH 2
#define EARLY2 1
#define LEAD 3
#define BPRE 2
#define EP_F 1
#define TQ_AT 0
#define LAG_0 4
#define LAG_G 0
#define LAG_S 0
#define O_AT 0
#define XB 1
#define V_E 1
#define LAG_T 0
#define E3M 0
#define B_ST 1
#define TW_L 1
#define K_TMA 1
#define KL_AT 0
#define DLY_K 350
#define Q_TMA 0
#define Q_AT 2
#define IDLE 1
#define PL_AN 4
#define PL_A (PL_0 - PL_AN < PL_W ? PL_W : PL_0 - PL_AN)
#define ASY 1
#define ASY_AT 2
#define DLY_XL 0
#define SXP 1
#define DLY_SA 0
#define DLY_SB 0
#define XL_AT 1
#define DLY_Y 0
#define LX_AT 0
#define X_W 2
#define PL_BN 2
#define PL_B (PL_A + PL_BN > PL_0 ? PL_0 : PL_A + PL_BN)
#define ASY_A 0
#define PL_DA 3
#define XR_F 0
#define RDX 1
#define DLY_Z 0
#define DLY_O 0
#define OX_AT 0
#define OX_L 0
#define PRE_AT B_SC

namespace {
constexpr int wunr = WUNR;

constexpr int S_ = 2048, D_ = 1024, NSEG = 64;
constexpr uint32_t SENT = 0xFFFFFFFFu;
constexpr int NSLOT = 4;

constexpr uint32_t M_REG = 1 << 21, M_E3 = 64 * 16384, M_KVQ = M_E3 + 4 * 8192, M_SEL = M_KVQ + 32 * 24576;
__device__ __align__(1024) unsigned char g_mail[5 * M_REG];
constexpr int C_P1 = 0, C_COLS = C_P1 + 32, C_EARLY = C_COLS + 32, C_LAST = C_EARLY + 32, C_ROWS = C_LAST + 128, C_END = C_ROWS + 8 * 32;
__device__ __align__(1024) uint32_t g_ctl[C_END];
#define CLK(i)
#define TL(i)
#define TL2(i)
#define FT(i, v)
#define GT(i)
#define CNT(i)
__device__ __align__(1024) __nv_bfloat16 g_ox[S_ * 4096];
__device__ __align__(1024) float2 g_z[257 * 4096];
__device__ __align__(1024) __nv_bfloat16 g_b[S_ * D_];
__device__ float g_gate[S_];
__device__ __align__(1024) float2 g_tw[1024];

#define TRV(s, ev, val)
#define TR(s, ev)
#define TRSYNC(ev)
__device__ __forceinline__ uint32_t smem_u32(const void* p) { return (uint32_t)__cvta_generic_to_shared(p); }
__device__ __forceinline__ void watchdog(uint32_t& n, uint32_t limit) {
  asm volatile("{ .reg .pred p; add.u32 %0, %0, 1; setp.gt.u32 p, %0, %1; @p trap; }" : "+r"(n) : "r"(limit));
}
__device__ __forceinline__ void mbar_init(uint32_t bar, uint32_t cnt) {
  asm volatile("mbarrier.init.shared::cta.b64 [%0], %1;" :: "r"(bar), "r"(cnt) : "memory");
}
__device__ __forceinline__ void mbar_arrive_warp(uint32_t bar) {
  __syncwarp();
  asm volatile("{ .reg .pred p; elect.sync _|p, 0xffffffff; @p mbarrier.arrive.shared::cta.b64 _, [%0]; }" :: "r"(bar) : "memory");
}
__device__ __forceinline__ uint32_t clock_lo() {
  uint32_t r; asm volatile("{ .reg .u64 c; .reg .u32 h; mov.u64 c, %%clock64; mov.b64 {%0, h}, c; }" : "=r"(r) :: "memory"); return r;
}
__device__ __forceinline__ void delay_until(uint32_t t) {
  asm volatile("{ .reg .pred p; .reg .u64 c; .reg .u32 l, h;\n"
               "DLY: mov.u64 c, %%clock64; mov.b64 {l, h}, c; sub.s32 l, l, %0; setp.lt.s32 p, l, 0; @p bra.uni DLY; }" :: "r"(t) : "memory");
}
__device__ __forceinline__ void delay_fine(uint32_t t) {
  delay_until(t);
}
__device__ __forceinline__ void delay_cycles(uint32_t n) { delay_until(clock_lo() + n); }
__device__ __forceinline__ void sched_fence(uint32_t z) {
  asm volatile("{ .reg .pred p; setp.eq.u32 p, %0, 0x7fff0000; @p pmevent 1; }" :: "r"(z) : "memory");
}
__device__ __forceinline__ void pdl_wait() { asm volatile("griddepcontrol.wait;" ::: "memory"); }
__device__ __forceinline__ void pdl_launch() { asm volatile("griddepcontrol.launch_dependents;" ::: "memory"); }
__device__ __forceinline__ float ex2(float x) { float r; asm("ex2.approx.ftz.f32 %0, %1;" : "=f"(r) : "f"(x)); return r; }
__device__ __forceinline__ float rcp(float x) { float r; asm("rcp.approx.ftz.f32 %0, %1;" : "=f"(r) : "f"(x)); return r; }
__device__ __forceinline__ void mbar_expect(uint32_t bar, uint32_t bytes) {
  asm volatile("mbarrier.arrive.expect_tx.shared::cta.b64 _, [%0], %1;" :: "r"(bar), "r"(bytes) : "memory");
}
__device__ __forceinline__ bool mbar_try(uint32_t bar, uint32_t ph) {
  uint32_t ok;
  asm volatile("{ .reg .pred p; mbarrier.try_wait.parity.shared::cta.b64 p, [%1], %2; selp.u32 %0, 1, 0, p; }"
               : "=r"(ok) : "r"(bar), "r"(ph) : "memory");
  return ok;
}
__device__ __forceinline__ void mbar_wait(uint32_t bar, uint32_t ph) {
  uint32_t n = 0;
  while (!mbar_try(bar, ph)) { watchdog(n, (1u << 20)); }
}
__device__ __forceinline__ void mbar_spin(uint32_t bar, uint32_t ph) { while (!mbar_try(bar, ph)) {} }
__device__ __forceinline__ void mbar_idle(uint32_t bar, uint32_t ph) {
  if (!IDLE) { mbar_wait(bar, ph); return; }
  asm volatile("{ .reg .pred q; SPN: mbarrier.try_wait.parity.shared::cta.b64 q, [%0], %1; @!q bra.uni SPN; }" :: "r"(bar), "r"(ph) : "memory");
}
__device__ __forceinline__ void mbar_spin_if(uint32_t bar, uint32_t ph, bool on) {
  asm volatile("{ .reg .pred p, q; setp.ne.u32 p, %2, 0;\n"
               "SPN: setp.eq.u32 q, 0, 0; @p mbarrier.try_wait.parity.shared::cta.b64 q, [%0], %1; @!q bra.uni SPN; }" :: "r"(bar), "r"(ph), "r"((uint32_t)on) : "memory");
}
__device__ __forceinline__ void mbar_spin2_if(uint32_t bar, uint32_t bar2, uint32_t ph, bool on) {
  asm volatile("{ .reg .pred p, q, r; setp.ne.u32 p, %3, 0;\n"
               "SPN: setp.eq.u32 q, 0, 0; setp.eq.u32 r, 0, 0; @p mbarrier.try_wait.parity.shared::cta.b64 q, [%0], %2;\n"
               "@p mbarrier.try_wait.parity.shared::cta.b64 r, [%1], %2; and.pred q, q, r; @!q bra.uni SPN; }" :: "r"(bar), "r"(bar2), "r"(ph), "r"((uint32_t)on) : "memory");
}
__device__ __forceinline__ void mbar_spin_cluster(uint32_t bar, uint32_t ph) {
  uint32_t ok;
  do {
    asm volatile("{ .reg .pred p; mbarrier.try_wait.parity.acquire.cluster.shared::cta.b64 p, [%1], %2; selp.u32 %0, 1, 0, p; }"
                 : "=r"(ok) : "r"(bar), "r"(ph) : "memory");
  } while (!ok);
}
#define ONCE_H "mov.b64 h, 0x12F0000000000000; "
__device__ __forceinline__ void tma2d(uint32_t dst, const CUtensorMap* tm, int c0, int c1, uint32_t bar) {
  if (ONCE & 32) asm volatile("{ .reg .b64 h; " ONCE_H "cp.async.bulk.tensor.2d.shared::cluster.global.mbarrier::complete_tx::bytes.L2::cache_hint [%0], [%1, {%3, %4}], [%2], h; }"
               :: "r"(dst), "l"(tm), "r"(bar), "r"(c0), "r"(c1) : "memory");
  else asm volatile("cp.async.bulk.tensor.2d.shared::cluster.global.mbarrier::complete_tx::bytes [%0], [%1, {%3, %4}], [%2];"
               :: "r"(dst), "l"(tm), "r"(bar), "r"(c0), "r"(c1) : "memory");
}
__device__ __forceinline__ void mbar_expect_e(uint32_t bar, uint32_t bytes) {
  asm volatile("{ .reg .pred p; elect.sync _|p, 0xffffffff; @p mbarrier.arrive.expect_tx.shared::cta.b64 _, [%0], %1; }" :: "r"(bar), "r"(bytes) : "memory");
}
__device__ __forceinline__ void tma2d_e(uint32_t dst, const CUtensorMap* tm, int c0, int c1, uint32_t bar) {
  asm volatile("{ .reg .pred p; elect.sync _|p, 0xffffffff;\n"
               "@p cp.async.bulk.tensor.2d.shared::cluster.global.mbarrier::complete_tx::bytes [%0], [%1, {%3, %4}], [%2]; }"
               :: "r"(dst), "l"(tm), "r"(bar), "r"(c0), "r"(c1) : "memory");
}
__device__ __forceinline__ void tma2d_st_e(const CUtensorMap* tm, int c0, int c1, uint32_t src) {
  asm volatile("{ .reg .pred p; elect.sync _|p, 0xffffffff;\n"
               "@p cp.async.bulk.tensor.2d.global.shared::cta.bulk_group [%0, {%2, %3}], [%1]; }" :: "l"(tm), "r"(src), "r"(c0), "r"(c1) : "memory");
}
__device__ __forceinline__ void tma2d_out_e(const CUtensorMap* tm, int c0, int c1, uint32_t src) {
  if (EPI) asm volatile("{ .reg .pred p; elect.sync _|p, 0xffffffff;\n"
               "@p cp.reduce.async.bulk.tensor.2d.global.shared::cta.add.bulk_group [%0, {%2, %3}], [%1]; }" :: "l"(tm), "r"(src), "r"(c0), "r"(c1) : "memory");
  else if (ONCE & 16) asm volatile("{ .reg .pred p; .reg .b64 h; " ONCE_H "elect.sync _|p, 0xffffffff;\n"
               "@p cp.async.bulk.tensor.2d.global.shared::cta.bulk_group.L2::cache_hint [%0, {%2, %3}], [%1], h; }" :: "l"(tm), "r"(src), "r"(c0), "r"(c1) : "memory");
  else asm volatile("{ .reg .pred p; elect.sync _|p, 0xffffffff;\n"
               "@p cp.async.bulk.tensor.2d.global.shared::cta.bulk_group [%0, {%2, %3}], [%1]; }" :: "l"(tm), "r"(src), "r"(c0), "r"(c1) : "memory");
}
__device__ __forceinline__ void tma2d_once(uint32_t dst, const CUtensorMap* tm, int c0, int c1, uint32_t bar) {
  asm volatile("{ .reg .pred p; .reg .b64 h; " ONCE_H "elect.sync _|p, 0xffffffff;\n"
               "@p cp.async.bulk.tensor.2d.shared::cluster.global.mbarrier::complete_tx::bytes.L2::cache_hint [%0], [%1, {%3, %4}], [%2], h; }"
               :: "r"(dst), "l"(tm), "r"(bar), "r"(c0), "r"(c1) : "memory");
}
__device__ __forceinline__ void bulk_once(uint32_t dst, const void* src, uint32_t bytes, uint32_t bar) {
  asm volatile("{ .reg .pred p; .reg .b64 h; " ONCE_H "elect.sync _|p, 0xffffffff;\n"
               "@p cp.async.bulk.shared::cluster.global.mbarrier::complete_tx::bytes.L2::cache_hint [%0], [%1], %2, [%3], h; }"
               :: "r"(dst), "l"(src), "r"(bytes), "r"(bar) : "memory");
}
__device__ __forceinline__ void tma4d_e(uint32_t dst, const CUtensorMap* tm, int c2, int c3, uint32_t bar) {
  asm volatile("{ .reg .pred p; .reg .b64 h; " ONCE_H "elect.sync _|p, 0xffffffff;\n"
               "@p cp.async.bulk.tensor.4d.shared::cluster.global.mbarrier::complete_tx::bytes.L2::cache_hint [%0], [%1, {0, 0, %3, %4}], [%2], h; }"
               :: "r"(dst), "l"(tm), "r"(bar), "r"(c2), "r"(c3) : "memory");
}
__device__ __forceinline__ void bulk_load_e(uint32_t dst, const void* src, uint32_t bytes, uint32_t bar) {
  asm volatile("{ .reg .pred p; elect.sync _|p, 0xffffffff;\n"
               "@p cp.async.bulk.shared::cluster.global.mbarrier::complete_tx::bytes [%0], [%1], %2, [%3]; }"
               :: "r"(dst), "l"(src), "r"(bytes), "r"(bar) : "memory");
}
template<bool O> __device__ __forceinline__ void tma2d_o(uint32_t dst, const CUtensorMap* tm, int c0, int c1, uint32_t bar) {
  if (O) tma2d_once(dst, tm, c0, c1, bar); else tma2d_e(dst, tm, c0, c1, bar);
}
__device__ __forceinline__ float2 ld_once(const float2* p) {
  float2 v;
  if (ONCE & 64) asm volatile("{ .reg .b64 h; " ONCE_H "ld.global.cg.L2::cache_hint.v2.f32 {%0, %1}, [%2], h; }" : "=f"(v.x), "=f"(v.y) : "l"(p));
  else v = __ldcg(p);
  return v;
}
template<bool O = false> __device__ __forceinline__ void prefetch2d_e(const CUtensorMap* tm, int c0, int c1) {
  if (O) asm volatile("{ .reg .pred p; .reg .b64 h; " ONCE_H "elect.sync _|p, 0xffffffff;\n"
               "@p cp.async.bulk.prefetch.tensor.2d.L2.global.L2::cache_hint [%0, {%1, %2}], h; }" :: "l"(tm), "r"(c0), "r"(c1) : "memory");
  else asm volatile("{ .reg .pred p; elect.sync _|p, 0xffffffff;\n"
               "@p cp.async.bulk.prefetch.tensor.2d.L2.global [%0, {%1, %2}]; }" :: "l"(tm), "r"(c0), "r"(c1) : "memory");
}
__device__ __forceinline__ void st_pub4(void* p, uint4 v) {
  asm volatile("st.relaxed.gpu.global.v4.u32 [%0], {%1,%2,%3,%4};" :: "l"(p), "r"(v.x), "r"(v.y), "r"(v.z), "r"(v.w) : "memory");
}
__device__ __forceinline__ void st_pub_if(void* p, uint32_t v, bool on) {
  asm volatile("{ .reg .pred p; setp.ne.u32 p, %2, 0; @p st.relaxed.gpu.global.u32 [%0], %1; }" :: "l"(p), "r"(v), "r"((uint32_t)on) : "memory");
}
__device__ __forceinline__ uint32_t mapa(uint32_t a, uint32_t r) {
  uint32_t d; asm volatile("mapa.shared::cluster.u32 %0, %1, %2;" : "=r"(d) : "r"(a), "r"(r)); return d;
}
__device__ __forceinline__ void st_async4(uint32_t a, uint32_t x, uint32_t y, uint32_t z, uint32_t w, uint32_t bar) {
  asm volatile("st.async.shared::cluster.mbarrier::complete_tx::bytes.v4.u32 [%0], {%1,%2,%3,%4}, [%5];"
               :: "r"(a), "r"(x), "r"(y), "r"(z), "r"(w), "r"(bar) : "memory");
}
__device__ __forceinline__ uint4 ld_poll(const void* p) {
  uint4 v;
  asm volatile("ld.volatile.global.v4.u32 {%0,%1,%2,%3}, [%4];" : "=r"(v.x), "=r"(v.y), "=r"(v.z), "=r"(v.w) : "l"(p) : "memory");
  return v;
}
__device__ __forceinline__ uint2 ld_poll2(const void* p) {
  uint2 v; asm volatile("ld.volatile.global.v2.u32 {%0,%1}, [%2];" : "=r"(v.x), "=r"(v.y) : "l"(p) : "memory"); return v;
}
__device__ __forceinline__ void st_pub2(void* p, uint32_t a, uint32_t b) {
  asm volatile("st.relaxed.gpu.global.v2.u32 [%0], {%1,%2};" :: "l"(p), "r"(a), "r"(b) : "memory");
}
__device__ __forceinline__ uint32_t ld_poll1(const void* p) {
  uint32_t v; asm volatile("ld.volatile.global.u32 %0, [%1];" : "=r"(v) : "l"(p) : "memory"); return v;
}
__device__ __forceinline__ uint32_t ld_acquire(const uint32_t* p) {
  uint32_t v; asm volatile("ld.acquire.gpu.global.u32 %0, [%1];" : "=r"(v) : "l"(p) : "memory"); return v;
}
__device__ __forceinline__ void st_pub(void* p, uint32_t v) {
  asm volatile("st.relaxed.gpu.global.u32 [%0], %1;" :: "l"(p), "r"(v) : "memory");
}
__device__ __forceinline__ uint32_t lds32(uint32_t a) {
  uint32_t v; asm volatile("ld.shared.u32 %0, [%1];" : "=r"(v) : "r"(a) : "memory"); return v;
}
__device__ __forceinline__ int race_init(void* p0, void* p1, uint32_t val) {
  int t;
  asm volatile("{ .reg .pred r; .reg .u32 a, b, u, v;\n"
               "atom.relaxed.gpu.global.exch.b32 u, [%1], %3; atom.relaxed.gpu.global.exch.b32 v, [%2], %3;\n"
               "setp.eq.u32 r, u, 0x12345; @r pmevent 1; mov.u32 a, %%clock;\n"
               "setp.eq.u32 r, v, 0x12345; @r pmevent 1; mov.u32 b, %%clock; sub.u32 %0, b, a; }" : "=r"(t) : "l"(p0), "l"(p1), "r"(val) : "memory");
  return t;
}
__device__ __forceinline__ void race_init2(void* p0, void* p1, uint32_t val) {
  asm volatile("{ .reg .pred r; .reg .u32 a, b, u, v;\n"
               "atom.relaxed.gpu.global.exch.b32 u, [%0], %2; atom.relaxed.gpu.global.exch.b32 v, [%1], %2;\n"
               "atom.relaxed.gpu.global.exch.b32 a, [%0 + 4096], %2; atom.relaxed.gpu.global.exch.b32 b, [%1 + 4096], %2;\n"
               "lop3.b32 u, u, v, a, 0x96; setp.eq.u32 r, u, 0x12345; setp.eq.and.u32 r, b, u, r; @r pmevent 1; }" :: "l"(p0), "l"(p1), "r"(val) : "memory");
}
__device__ __forceinline__ uint4 lds128(uint32_t a) {
  uint4 v; asm volatile("ld.shared.v4.u32 {%0,%1,%2,%3}, [%4];" : "=r"(v.x), "=r"(v.y), "=r"(v.z), "=r"(v.w) : "r"(a) : "memory"); return v;
}
__device__ __forceinline__ uint2 lds64(uint32_t a) {
  uint2 v; asm volatile("ld.shared.v2.u32 {%0,%1}, [%2];" : "=r"(v.x), "=r"(v.y) : "r"(a) : "memory"); return v;
}
__device__ __forceinline__ void sts128(uint32_t a, uint4 v) {
  asm volatile("st.shared.v4.u32 [%0], {%1,%2,%3,%4};" :: "r"(a), "r"(v.x), "r"(v.y), "r"(v.z), "r"(v.w) : "memory");
}
__device__ __forceinline__ void sts64(uint32_t a, uint32_t x, uint32_t y) { asm volatile("st.shared.v2.u32 [%0], {%1,%2};" :: "r"(a), "r"(x), "r"(y) : "memory"); }
__device__ __forceinline__ void sts32(uint32_t a, uint32_t x) { asm volatile("st.shared.u32 [%0], %1;" :: "r"(a), "r"(x) : "memory"); }
__device__ __forceinline__ void ldsm4t(uint32_t (&r)[4], uint32_t a) {
  asm volatile("ldmatrix.sync.aligned.m8n8.x4.trans.shared.b16 {%0,%1,%2,%3}, [%4];"
               : "=r"(r[0]), "=r"(r[1]), "=r"(r[2]), "=r"(r[3]) : "r"(a) : "memory");
}
__device__ __forceinline__ void ldsm4(uint32_t (&r)[4], uint32_t a) {
  asm volatile("ldmatrix.sync.aligned.m8n8.x4.shared.b16 {%0,%1,%2,%3}, [%4];"
               : "=r"(r[0]), "=r"(r[1]), "=r"(r[2]), "=r"(r[3]) : "r"(a) : "memory");
}
template<bool TRANS> __device__ __forceinline__ void stsm4(uint32_t a, uint32_t r0, uint32_t r1, uint32_t r2, uint32_t r3) {
  if (TRANS) asm volatile("stmatrix.sync.aligned.m8n8.x4.trans.shared.b16 [%0], {%1,%2,%3,%4};" :: "r"(a), "r"(r0), "r"(r1), "r"(r2), "r"(r3) : "memory");
  else       asm volatile("stmatrix.sync.aligned.m8n8.x4.shared.b16 [%0], {%1,%2,%3,%4};" :: "r"(a), "r"(r0), "r"(r1), "r"(r2), "r"(r3) : "memory");
}
__device__ __forceinline__ void mma16816(float (&d)[4], uint32_t a0, uint32_t a1, uint32_t a2, uint32_t a3, uint32_t b0, uint32_t b1) {
  asm volatile("mma.sync.aligned.m16n8k16.row.col.f32.bf16.bf16.f32 {%0,%1,%2,%3}, {%4,%5,%6,%7}, {%8,%9}, {%0,%1,%2,%3};"
               : "+f"(d[0]), "+f"(d[1]), "+f"(d[2]), "+f"(d[3]) : "r"(a0), "r"(a1), "r"(a2), "r"(a3), "r"(b0), "r"(b1));
}
__device__ __forceinline__ void mma1688(float (&d)[4], uint32_t a0, uint32_t a1, uint32_t b0) {
  asm volatile("mma.sync.aligned.m16n8k8.row.col.f32.bf16.bf16.f32 {%0,%1,%2,%3}, {%4,%5}, {%6}, {%0,%1,%2,%3};"
               : "+f"(d[0]), "+f"(d[1]), "+f"(d[2]), "+f"(d[3]) : "r"(a0), "r"(a1), "r"(b0));
}
__device__ __forceinline__ uint32_t pack_bf16(float lo, float hi) {
  uint32_t r; asm("cvt.rn.bf16x2.f32 %0, %1, %2;" : "=r"(r) : "f"(hi), "f"(lo)); return r;
}
__device__ __forceinline__ uint32_t add_bf16x2(uint32_t a, uint32_t b) {
  uint32_t r; asm("add.rn.bf16x2 %0, %1, %2;" : "=r"(r) : "r"(a), "r"(b)); return r;
}
__device__ __forceinline__ uint32_t umax4(uint4 v) { return max(max(v.x, v.y), max(v.z, v.w)); }
__device__ __forceinline__ uint32_t opaque(uint32_t x) { uint32_t r; asm volatile("mov.u32 %0, %1;" : "=r"(r) : "r"(x)); return r; }
template<class T> __device__ __forceinline__ void pin(T*& p) { asm volatile("" : "+l"(p)); }
__device__ __forceinline__ void pin(uint32_t& v) { asm volatile("" : "+r"(v)); }
__device__ __forceinline__ uint32_t desc_lo(uint32_t addr) { return ((addr & 0x3FFFF) >> 4) | 0x10000; }
__device__ __forceinline__ uint64_t desc128(uint32_t lo) {
  uint64_t d; asm("mov.b64 %0, {%1, %2};" : "=l"(d) : "r"(lo), "r"(0x40000040)); return d;
}
#define WG_FENCE()  asm volatile("wgmma.fence.sync.aligned;" ::: "memory")
#define WG_COMMIT() asm volatile("wgmma.commit_group.sync.aligned;" ::: "memory")
#define WG_WAIT(n)  asm volatile("wgmma.wait_group.sync.aligned " #n ";" ::: "memory")
#define FENCE_ASYNC_SMEM() asm volatile("fence.proxy.async.shared::cta;" ::: "memory")
__device__ __forceinline__ void bar_sync(int id, int n) { asm volatile("bar.sync %0, %1;" :: "r"(id), "r"(n) : "memory"); }

#define D16(c) c(d[0]), c(d[1]), c(d[2]), c(d[3]), c(d[4]), c(d[5]), c(d[6]), c(d[7]), \
               c(d[8]), c(d[9]), c(d[10]), c(d[11]), c(d[12]), c(d[13]), c(d[14]), c(d[15])
template<bool FIRST> __device__ __forceinline__ void wgmma_rs_n32(float (&d)[16], const uint32_t (&a)[4], uint64_t b) {
  if (FIRST)
    asm volatile("wgmma.mma_async.sync.aligned.m64n32k16.f32.bf16.bf16 {%0,%1,%2,%3,%4,%5,%6,%7,%8,%9,%10,%11,%12,%13,%14,%15}, {%16,%17,%18,%19}, %20, 0, 1, 1, 0;"
      : D16("=f") : "r"(a[0]), "r"(a[1]), "r"(a[2]), "r"(a[3]), "l"(b));
  else
    asm volatile("wgmma.mma_async.sync.aligned.m64n32k16.f32.bf16.bf16 {%0,%1,%2,%3,%4,%5,%6,%7,%8,%9,%10,%11,%12,%13,%14,%15}, {%16,%17,%18,%19}, %20, 1, 1, 1, 0;"
      : D16("+f") : "r"(a[0]), "r"(a[1]), "r"(a[2]), "r"(a[3]), "l"(b));
}
template<bool FIRST> __device__ __forceinline__ void wgmma_ss_n32_ta(float (&d)[16], uint64_t a, uint64_t b) {
  if (FIRST)
    asm volatile("wgmma.mma_async.sync.aligned.m64n32k16.f32.bf16.bf16 {%0,%1,%2,%3,%4,%5,%6,%7,%8,%9,%10,%11,%12,%13,%14,%15}, %16, %17, 0, 1, 1, 1, 0;"
      : D16("=f") : "l"(a), "l"(b));
  else
    asm volatile("wgmma.mma_async.sync.aligned.m64n32k16.f32.bf16.bf16 {%0,%1,%2,%3,%4,%5,%6,%7,%8,%9,%10,%11,%12,%13,%14,%15}, %16, %17, 1, 1, 1, 1, 0;"
      : D16("+f") : "l"(a), "l"(b));
}
__device__ __forceinline__ void wgmma_ss_n128_tb(float (&d)[64], uint64_t a, uint64_t b) {
  asm volatile("wgmma.mma_async.sync.aligned.m64n128k16.f32.bf16.bf16 "
    "{%0,%1,%2,%3,%4,%5,%6,%7,%8,%9,%10,%11,%12,%13,%14,%15,%16,%17,%18,%19,%20,%21,%22,%23,%24,%25,%26,%27,%28,%29,%30,%31,"
    "%32,%33,%34,%35,%36,%37,%38,%39,%40,%41,%42,%43,%44,%45,%46,%47,%48,%49,%50,%51,%52,%53,%54,%55,%56,%57,%58,%59,%60,%61,%62,%63}, "
    "%64, %65, 1, 1, 1, 0, 1;"
    : "+f"(d[0]), "+f"(d[1]), "+f"(d[2]), "+f"(d[3]), "+f"(d[4]), "+f"(d[5]), "+f"(d[6]), "+f"(d[7]),
      "+f"(d[8]), "+f"(d[9]), "+f"(d[10]), "+f"(d[11]), "+f"(d[12]), "+f"(d[13]), "+f"(d[14]), "+f"(d[15]),
      "+f"(d[16]), "+f"(d[17]), "+f"(d[18]), "+f"(d[19]), "+f"(d[20]), "+f"(d[21]), "+f"(d[22]), "+f"(d[23]),
      "+f"(d[24]), "+f"(d[25]), "+f"(d[26]), "+f"(d[27]), "+f"(d[28]), "+f"(d[29]), "+f"(d[30]), "+f"(d[31]),
      "+f"(d[32]), "+f"(d[33]), "+f"(d[34]), "+f"(d[35]), "+f"(d[36]), "+f"(d[37]), "+f"(d[38]), "+f"(d[39]),
      "+f"(d[40]), "+f"(d[41]), "+f"(d[42]), "+f"(d[43]), "+f"(d[44]), "+f"(d[45]), "+f"(d[46]), "+f"(d[47]),
      "+f"(d[48]), "+f"(d[49]), "+f"(d[50]), "+f"(d[51]), "+f"(d[52]), "+f"(d[53]), "+f"(d[54]), "+f"(d[55]),
      "+f"(d[56]), "+f"(d[57]), "+f"(d[58]), "+f"(d[59]), "+f"(d[60]), "+f"(d[61]), "+f"(d[62]), "+f"(d[63])
    : "l"(a), "l"(b));
}

__device__ __forceinline__ void tma3d_mc_e(uint32_t dst, const CUtensorMap* tm, int c1, int c2, uint32_t bar) {
  asm volatile("{ .reg .pred p; .reg .b64 h; " ONCE_H "elect.sync _|p, 0xffffffff;\n"
               "@p cp.async.bulk.tensor.3d.shared::cluster.global.mbarrier::complete_tx::bytes.multicast::cluster.L2::cache_hint [%0], [%1, {0, %3, %4}], [%2], %5, h; }"
               :: "r"(dst), "l"(tm), "r"(bar), "r"(c1), "r"(c2), "h"((uint16_t)3) : "memory");
}
__device__ __forceinline__ void prefetch3d_e(const CUtensorMap* tm, int c1, int c2) {
  asm volatile("{ .reg .pred p; elect.sync _|p, 0xffffffff;\n"
               "@p cp.async.bulk.prefetch.tensor.3d.L2.global [%0, {0, %1, %2}]; }" :: "l"(tm), "r"(c1), "r"(c2) : "memory");
}

__device__ __forceinline__ void count_e(uint32_t* p) {
  asm volatile("fence.acq_rel.gpu;" ::: "memory");
  __syncwarp();
  asm volatile("{ .reg .pred p; elect.sync _|p, 0xffffffff; @p red.relaxed.gpu.global.add.u32 [%0], 1; }" :: "l"(p) : "memory");
}
template<int NS = 0> __device__ __forceinline__ void await_count(const uint32_t* p, uint32_t n) {
  for (uint32_t i = 0; ld_acquire(p) < n && i < (1u << 22); i++) { if (NS) __nanosleep(NS); }
  asm volatile("fence.proxy.async.global;" ::: "memory");
}
__device__ __forceinline__ void await_flags(const uint32_t* p) {
  for (uint32_t i = 0; i < (1u << 22); i++) {
    uint4 v;
    asm volatile("ld.acquire.gpu.global.v4.u32 {%0,%1,%2,%3}, [%4];" : "=r"(v.x), "=r"(v.y), "=r"(v.z), "=r"(v.w) : "l"(p) : "memory");
    if (__all_sync(~0u, (v.x & v.y & v.z & v.w) == 0x01010101u)) break;
  }
  asm volatile("fence.proxy.async.global;" ::: "memory");
}
__device__ __forceinline__ void mbar_lim(uint32_t bar, uint32_t ph) { for (uint32_t i = 0; !mbar_try(bar, ph) && i < (1u << 20); i++) {} }

struct cf { float x, y; };
__host__ __device__ constexpr float cos64(int k) {
  return k == 0 ? 1.0f : k == 1 ? 0.99518472667219689f : k == 2 ? 0.98078528040323045f : k == 3 ? 0.95694033573220887f :
         k == 4 ? 0.92387953251128676f : k == 5 ? 0.88192126434835503f : k == 6 ? 0.83146961230254524f : k == 7 ? 0.77301045336273696f :
         k == 8 ? 0.70710678118654752f : k == 9 ? 0.63439328416364550f : k == 10 ? 0.55557023301960222f : k == 11 ? 0.47139673682599765f :
         k == 12 ? 0.38268343236508977f : k == 13 ? 0.29028467725446236f : k == 14 ? 0.19509032201612827f : k == 15 ? 0.09801714032956060f : 0.0f;
}
__host__ __device__ constexpr float c64(int k) { return k <= 16 ? cos64(k) : -cos64(32 - k); }
__host__ __device__ constexpr float s64(int k) { return k <= 16 ? cos64(16 - k) : cos64(k - 16); }

template<int N, int ST, bool INV> struct Fft {
  template<int K> static __device__ __forceinline__ void bf(const cf* e, const cf* o, cf* out) {
    if constexpr (K < N / 2) {
      constexpr int idx = K * (64 / N);
      const cf a = e[K], b = o[K];
      if constexpr (idx == 0) {
        out[K] = {a.x + b.x, a.y + b.y}; out[K + N / 2] = {a.x - b.x, a.y - b.y};
      } else if constexpr (idx == 16) {
        if constexpr (INV) { out[K] = {a.x - b.y, a.y + b.x}; out[K + N / 2] = {a.x + b.y, a.y - b.x}; }
        else               { out[K] = {a.x + b.y, a.y - b.x}; out[K + N / 2] = {a.x - b.y, a.y + b.x}; }
      } else {
        constexpr float c = c64(idx), s = INV ? s64(idx) : -s64(idx);
        cf p; p.x = fmaf(-s, b.y, fmaf(c, b.x, a.x)); p.y = fmaf(s, b.x, fmaf(c, b.y, a.y));
        out[K] = p; out[K + N / 2] = {fmaf(2.0f, a.x, -p.x), fmaf(2.0f, a.y, -p.y)};
      }
      bf<K + 1>(e, o, out);
    }
  }
  static __device__ __forceinline__ void run(const cf* in, cf* out) {
    cf e[N / 2], o[N / 2];
    Fft<N / 2, 2 * ST, INV>::run(in, e);
    Fft<N / 2, 2 * ST, INV>::run(in + ST, o);
    bf<0>(e, o, out);
  }
};
template<int ST, bool INV> struct Fft<1, ST, INV> {
  static __device__ __forceinline__ void run(const cf* in, cf* out) { out[0] = in[0]; }
};
template<bool INV> __device__ __forceinline__ void fft32(cf (&v)[32]) {
  cf o[32]; Fft<32, 1, INV>::run(v, o);
#pragma unroll
  for (int i = 0; i < 32; i++) v[i] = o[i];
}
__device__ __forceinline__ cf cmul(cf a, float c, float s) { return {fmaf(-a.y, s, a.x * c), fmaf(a.x, s, a.y * c)}; }
__device__ __forceinline__ float bf2f(__nv_bfloat16 v) { return __bfloat162float(v); }

__device__ __forceinline__ int tw_at(int i) { return (i & ~63) | (i & 31) << 1 | (i >> 5 & 1); }
template<bool INV, bool T128 = true> __device__ __forceinline__ void twiddles(cf (&v)[32], const float4* __restrict__ tw) {
#pragma unroll
  for (int j = 0; j < 32; j += 2) {
    float4 w;
    if (T128) w = tw[j * 16];
    else { const uint2 a = lds64(smem_u32(tw + j * 16)), b = lds64(smem_u32(tw + j * 16) + 8); w = make_float4(__uint_as_float(a.x), __uint_as_float(a.y), __uint_as_float(b.x), __uint_as_float(b.y)); }
    if (j) v[j] = cmul(v[j], w.x, INV ? -w.y : w.y);
    v[j + 1] = cmul(v[j + 1], w.z, INV ? -w.w : w.w);
  }
}
template<bool INV, class F> __device__ __forceinline__ void warp_fft1024(cf (&v)[32], float2* __restrict__ buf, const float2* __restrict__ tw, int t, int u, F mid) {
#pragma unroll 1
  for (uint32_t h = 0; h < 2; h++) {
    fft32<INV>(v);
    if (FUNR ? h : opaque(h)) continue;
    twiddles<INV>(v, (const float4*)tw + u);
    if (INV) {
      float* f = (float*)buf;
#pragma unroll
      for (int j = 0; j < 32; j++) f[j * 36 + t] = v[j].x;
      __syncwarp();
#pragma unroll
      for (int j = 0; j < 32; j += 4) { const float4 r = *(const float4*)(f + u * 36 + j); v[j].x = r.x; v[j + 1].x = r.y; v[j + 2].x = r.z; v[j + 3].x = r.w; }
      __syncwarp();
#pragma unroll
      for (int j = 0; j < 32; j++) f[j * 36 + t] = v[j].y;
      __syncwarp();
#pragma unroll
      for (int j = 0; j < 32; j += 4) { const float4 r = *(const float4*)(f + u * 36 + j); v[j].y = r.x; v[j + 1].y = r.y; v[j + 2].y = r.z; v[j + 3].y = r.w; }
    } else {
#pragma unroll
      for (int j = 0; j < 32; j++) buf[j * 33 + t] = make_float2(v[j].x, v[j].y);
      __syncwarp();
#pragma unroll
      for (int j = 0; j < 32; j++) { const float2 r = buf[u * 33 + j]; v[j] = {r.x, r.y}; }
    }
    __syncwarp();
    mid();
  }
}
constexpr int ROW_BUF = 32 * 33, INV_BUF = 32 * 18;

__device__ __forceinline__ int z_row(int p) { return (p & ~31) | (p & 7) << 2 | (p & 31) >> 3; }
__device__ __forceinline__ int inv_lane(int t) { return (t & ~14) | (t & 12) >> 1 | (t & 2) << 2; }
__device__ __forceinline__ float2 twiddle(int i) { float s, c; sincospif(-(float)((i >> 5) * (i & 31)) * (1.0f / 512.0f), &s, &c); return make_float2(c, s); }
template<class F, class G> __device__ __forceinline__ void fft_rows_fwd(float2* sm2, const __nv_bfloat16* gw, int cta, int tid, uint32_t full_bar, uint32_t release_bar, F ev, G extra) {
  const int t = tid & 31, w = tid >> 5, n = z_row(cta * 8 + w);
#pragma unroll 1
  for (int i = tid; i < 1024; i += 256) sm2[tw_at(i)] = twiddle(i);
  ev(5);
  mbar_spin(full_bar, 0);
  if (tid == 0) TL2(6);
  __syncwarp();
  const __nv_bfloat16* xa = (const __nv_bfloat16*)(sm2 + 1024 + w * ROW_BUF) + t;
  cf v[32];
  float ga = 0.f, gb = 0.f;
#pragma unroll
  for (int j = 0; j < 32; j++) {
    v[j] = {bf2f(xa[32 * j]), bf2f(xa[D_ + 32 * j])};
    const float g = bf2f(gw[32 * j + t]); ga = fmaf(v[j].x, g, ga); gb = fmaf(v[j].y, g, gb);
  }
#pragma unroll
  for (int o = 16; o; o >>= 1) { ga += __shfl_xor_sync(~0u, ga, o); gb += __shfl_xor_sync(~0u, gb, o); }
  if (t < 2) g_gate[n + 1024 * t] = __fdividef(1.0f, 1.0f + __expf(-(t ? gb : ga)));
  ev(6);
  bar_sync(13, 256);
  warp_fft1024<false>(v, sm2 + 1024 + w * ROW_BUF, sm2, t, t, [&]() { FENCE_ASYNC_SMEM(); mbar_arrive_warp(release_bar); });
  float ws, wc; sincospif(-(float)n * (1.0f / 1024.0f), &ws, &wc);
  ev(12);
  uint32_t tz = clock_lo();
  float4* z = (float4*)g_z + ((size_t)(t >> 1) * 1024 + cta * 8 + w) * 2 + (t & 1);
#pragma unroll
  for (int j = 0; j < 17; j++) {
    cf q = v[(32 - j) & 31];
    if (j < 16) {
      const cf r = {__shfl_sync(~0u, v[31 - j].x, 32 - t), __shfl_sync(~0u, v[31 - j].y, 32 - t)};
      if (t != 0) q = r;
    }
    const cf a = {v[j].x + q.x, v[j].y - q.y}, b = {v[j].y + q.y, q.x - v[j].x};
    const cf d = cmul({a.x - b.x, a.y - b.y}, wc, ws);
    if (j == POOL_AT) extra();
    if (PACE_Z && j && j < 16) delay_until(tz += PACE_Z);
    if ((j < 16 || t == 0) && ((EXP_ST & 4) || d.x == 123.f)) z[j * 32768] = make_float4(a.x + b.x, a.y + b.y, d.x, d.y);
  }
}
constexpr int CP = X128 == 0 ? 33 : X128 == 2 ? 34 : 36, COL_FS = 32 * 36 + 8, COL_W = (8192 + 16 * COL_FS * 4 + 127) & ~127, COL_SMEM = COL_W + 131072 + 128;

__device__ __forceinline__ void fft_cols(float2* sm2, int cta, const CUtensorMap* twr, const CUtensorMap* twi, const CUtensorMap* tzs) {
  const int grp = __shfl_sync(~0u, (int)(threadIdx.x >> 7), 0), tid = threadIdx.x & 127, tp = tid >> 2, w = __shfl_sync(~0u, tid >> 5, 0);
  float* buf = (float*)(sm2 + 1024) + (grp * 4 + (tid & 3)) * COL_FS;
  const uint32_t wsm = smem_u32(sm2) + COL_W, wbar = wsm + 131072 + (W_FINE ? w * 32 : 0);
  const int res = w * 2 + (tid & 1), el = res + grp * 2 + ((tid >> 1) & 1);
  uint32_t wa = (el >> 3) * 65536 + res * 4096 + (tp & 7) * 16 + (el & 7) * 2;
  auto load_w = [&](int q) {
    const uint32_t bar = wbar + (q & 1) * 8;
    mbar_expect(bar, W_FINE ? 16384 : 65536);
#pragma unroll 1
    for (int i = W_FINE ? 4 * w : 0; i < (W_FINE ? 4 * w + 4 : 16); i++) tma2d(wsm + (q & 1) * 65536 + (i & 1) * 32768 + (i >> 1) * 4096, i & 1 ? twi : twr, (i >> 1) * 512 + q * 8, 0, bar);
  };
  const bool lead = (tid & (W_FINE ? 31 : 127)) == 0, first = grp < 2 && lead;
  if (first) { mbar_init(wbar + grp * 8, 1); sts32(wbar + 16 + grp * 4, grp ? 0 : w); asm volatile("fence.mbarrier_init.release.cluster;" ::: "memory"); }
#pragma unroll 1
  for (int i = threadIdx.x; i < 1024; i += 512) {
    const float2 t = twiddle(z_row(i));
    sm2[tw_at(i)] = t;
    if (cta == 0) g_tw[tw_at(inv_lane(z_row(i)))] = t;
  }
  for (uint32_t n = 0; ld_acquire(g_ctl + C_P1) < 128; ) { watchdog(n, 1u << 22); __nanosleep(200); }
  if (COL_DLY) delay_cycles(COL_DLY);
  if (first) load_w(cta * 16 + grp);
  __syncthreads();
  delay_cycles(1 + grp * DLY_GRP);
  mbar_wait(wbar, 0);
  const int end = cta * 64 + 64 + (cta == 3);
  for (int item = cta * 64 + grp; item < end; item += 4, wa ^= 65536) {
    float2* zp = g_z + (size_t)item * 4096;
    auto next_w = [&]() {
      const int q = (item >> 2) + (W_FINE && grp + w > 3);
      uint32_t n; asm volatile("atom.shared.inc.u32 %0, [%1], 3;" : "=r"(n) : "r"(wbar + 16 + (q & 1) * 4) : "memory");
      if (EXP_W && n == 3 && q < (cta * 16 + 15)) load_w(q + 2);
    };
    cf v[32];
#pragma unroll
    for (int j = 0; j < 32; j++) { const float2 a = ld_once(zp + tid + j * 128); v[j] = {a.x, a.y}; }
#pragma unroll 1
    for (int ph = 0; ; ph++) {
      fft32<false>(v);
      twiddles<false, T128_>(v, (const float4*)sm2 + tp);
      if (Z_ST) asm volatile("cp.async.bulk.wait_group.read 0;" ::: "memory");
      bar_sync(1 + grp, 128);
      if (lead) {
        if (ph) {
          if (!W_AT) next_w();
        } else if (Z_PF && item + 4 < end) asm volatile("cp.async.bulk.prefetch.L2.global [%0], %1;" :: "l"(zp + 4 * 4096 + w * 1024), "n"(W_FINE ? 8192 : 32768) : "memory");
      }
      __syncwarp();
#pragma unroll
      for (int j = 0; j < 32; j++) buf[((j & 3) * 8 + (j >> 2)) * CP + tp] = v[j].x;
      bar_sync(1 + grp, 128);
      if (X128 == 0) {
#pragma unroll
        for (int j = 0; j < 32; j++) v[j].x = buf[tp * CP + (j & 3) * 8 + (j >> 2)];
      } else if (X128 == 2) {
#pragma unroll
        for (int j = 0; j < 16; j++) { const float2 r = *(const float2*)(buf + tp * CP + 2 * j); cf* d = v + (j & 3) * 8 + (j >> 2); d[0].x = r.x; d[4].x = r.y; }
      } else
#pragma unroll
      for (int j = 0; j < 8; j++) {
        const float4 r = *(const float4*)(buf + tp * 36 + 4 * j);
        cf* d = v + (j & 1) * 16 + (j >> 1);
        d[0].x = r.x; d[4].x = r.y; d[8].x = r.z; d[12].x = r.w;
      }
      bar_sync(1 + grp, 128);
#pragma unroll
      for (int j = 0; j < 32; j++) buf[((j & 3) * 8 + (j >> 2)) * CP + tp] = v[j].y;
      bar_sync(1 + grp, 128);
      if (X128 == 0) {
#pragma unroll
        for (int j = 0; j < 32; j++) v[j].y = buf[tp * CP + (j & 3) * 8 + (j >> 2)];
      } else if (X128 == 2) {
#pragma unroll
        for (int j = 0; j < 16; j++) { const float2 r = *(const float2*)(buf + tp * CP + 2 * j); cf* d = v + (j & 3) * 8 + (j >> 2); d[0].y = r.x; d[4].y = r.y; }
      } else
#pragma unroll
      for (int j = 0; j < 8; j++) {
        const float4 r = *(const float4*)(buf + tp * 36 + 4 * j);
        cf* d = v + (j & 1) * 16 + (j >> 1);
        d[0].y = r.x; d[4].y = r.y; d[8].y = r.z; d[12].y = r.w;
      }
      fft32<false>(v);
      if (ph) break;
      const int q = min((item >> 2) + (!W_FINE || grp + w >= 3), 64);
      if (EXP_W) mbar_wait(wbar + (q & 1) * 8, (q >> 1) & 1);
#pragma unroll
      for (int j = 0; j < 32; j++) {
        uint32_t re, im;
        asm volatile("ld.shared.u16 %0, [%1];" : "=r"(re) : "r"(wsm + wa + j * 128) : "memory");
        asm volatile("ld.shared.u16 %0, [%1];" : "=r"(im) : "r"(wsm + wa + 32768 + j * 128) : "memory");
        const cf r = cmul(v[j], __uint_as_float(re << 16), __uint_as_float(im << 16));
        v[j] = {r.y, r.x};
      }
    }
    if (Z_ST) {
      float2* st = sm2 + 1024 + grp * (COL_FS * 2) + w * 512;
      bar_sync(1 + grp, 128);
#pragma unroll
      for (int h = 0; h < 2; h++) {
        if (h && Z_ST == 2) {
#pragma unroll
          for (int j = 16; j < 32; j++) zp[tid + j * 128] = make_float2(v[j].y, v[j].x);
          break;
        }
        if (h) { asm volatile("cp.async.bulk.wait_group.read 0;" ::: "memory"); __syncwarp(); }
#pragma unroll
        for (int j = 0; j < 16; j++) st[j * 32 + (tid & 31)] = make_float2(v[h * 16 + j].y, v[h * 16 + j].x);
        FENCE_ASYNC_SMEM();
        __syncwarp();
        tma2d_st_e(tzs, w * 128, item * 32 + h * 16, smem_u32(st));
        asm volatile("cp.async.bulk.commit_group;" ::: "memory");
      }
    } else {
#pragma unroll
      for (int j = 0; j < 32; j++) zp[tid + j * 128] = make_float2(v[j].y, v[j].x);
    }
    if (W_AT) { if (lead) next_w(); __syncwarp(); }
  }
  if (Z_ST) asm volatile("cp.async.bulk.wait_group 0; fence.proxy.async.global;" ::: "memory");
  const float4 t = ((const float4*)sm2)[threadIdx.x];
  __syncthreads();
  if (TW_L) ((float4*)sm2)[inv_lane(z_row(threadIdx.x))] = t;
  if (threadIdx.x < 32) {
    count_e(g_ctl + C_COLS);
    await_count(g_ctl + C_COLS, 4);
    g_ctl[C_P1] = 0;
  }
  __syncthreads();
  if (!TW_L) {
    ((float4*)sm2)[threadIdx.x] = __ldcg((const float4*)g_tw + threadIdx.x);
    __syncthreads();
  }
}

template<class F> __device__ __forceinline__ void fft_rows_inv(uint32_t zs, float2* buf, const float2* tw, int p, int lane, __nv_bfloat16* out, F read) {
  const int n = z_row(p), t = (lane & 17) | (lane & 6) << 1 | (lane & 8) >> 2, src = inv_lane(-t & 31);
  const uint32_t z = zs + (t >> 1) * 128 + ((((p & 3) * 2 + (t & 1)) ^ (t >> 1 & 7)) << 4);
  FT(0, 0.f);
  float4 e[17];
  uint32_t all = 0;
  e[16] = __ldcg((const float4*)g_z + ((size_t)256 * 1024 + p) * 2);
  const float g0 = __ldcg(g_gate + n), g1 = __ldcg(g_gate + n + 1024);
#pragma unroll
  for (int j = 0; j < 16; j++) { const uint4 u = lds128(z + j * 2048); e[j] = make_float4(__uint_as_float(u.x), __uint_as_float(u.y), __uint_as_float(u.z), __uint_as_float(u.w)); all |= u.x; }
  sched_fence(all);
  read();
  float ws, wc; sincospif((float)n * (1.0f / 1024.0f), &ws, &wc);
  cf v[32], q[17];
#pragma unroll
  for (int j = 0; j < 17; j++) {
    const cf d = cmul({e[j].z, e[j].w}, wc, ws);
    cf a = {e[j].x + d.x, e[j].y + d.y}, b = {e[j].x - d.x, e[j].y - d.y};
    if (j == 16 || (j == 0 && t == 0)) { a.y = 0.f; b.y = 0.f; }
    if (j < 16) v[j] = {a.x - b.y, a.y + b.x};
    q[j] = {a.x + b.y, b.x - a.y};
  }
#pragma unroll
  for (int j = 16; j < 32; j++) {
    v[j] = {__shfl_sync(~0u, q[31 - j].x, src), __shfl_sync(~0u, q[31 - j].y, src)};
    if (t == 0) v[j] = q[32 - j];
  }
  FT(1, v[0].x + v[16].x + v[31].x);
  if (B_ST) { asm volatile("cp.async.bulk.wait_group.read 0;" ::: "memory"); __syncwarp(); }
  warp_fft1024<true>(v, buf, tw, t, lane, []() {});
  FT(3, v[31].y + v[0].x);
  const float sc = 0.5f / (2048.0f * 1024.0f), s0 = (1.f - g0) * sc, s1 = (1.f - g1) * sc;
  uint2* o = (B_ST ? (uint2*)buf : (uint2*)(out + (size_t)n * D_)) + (lane ^ (n & 1) << 3);
#pragma unroll
  for (int j = 0; j < 32; j += 4) {
    o[8 * j] = make_uint2(pack_bf16(v[j].x * s0, v[j + 1].x * s0), pack_bf16(v[j + 2].x * s0, v[j + 3].x * s0));
    o[(B_ST ? 256 : 256 * D_) + 8 * j] = make_uint2(pack_bf16(v[j].y * s1, v[j + 1].y * s1), pack_bf16(v[j + 2].y * s1, v[j + 3].y * s1));
  }
  if (B_ST) {
    FENCE_ASYNC_SMEM();
    __syncwarp();
    asm volatile("{ .reg .pred p; setp.lt.u32 p, %2, 2; @p cp.async.bulk.global.shared::cta.bulk_group [%0], [%1], 2048; cp.async.bulk.commit_group; }"
                 :: "l"(out + (size_t)(n + 1024 * (lane & 1)) * D_), "r"(smem_u32(buf) + (lane & 1) * 2048), "r"(lane) : "memory");
  }
  FT(4, 0.f);
}

constexpr int NP = NP_, NHV = REG_F == 216 ? 5 : 7, NV = 16 - NHV;
constexpr int XEND = NSEG;
constexpr uint32_t SM_WO = 0, SM_V = 65536, SM_LAND = SM_V + 8192, SM_MEM = SM_LAND + 24576, SM_SP = SM_MEM, SM_SPM = SM_MEM + 5120, SM_OM = SM_MEM + 6144,
                   SM_OX = SM_MEM + 8192, SM_RED = SM_OX + 2048, SM_XCH = SM_RED + 1024, SM_SUM = SM_XCH + 4096, SM_VM = SM_SUM + 128, SM_TAB = SM_VM + 2048, SM_TRACE = SM_TAB + 2048, SM_K = SM_TRACE,
                   ST_WG = (32 - NP + NV) * 2048,
                   SM_XT = 2 * ST_WG, SM_POOL = SM_XT + 32768, SM_HV = SM_POOL + 2 * NP * 2048,
                   SM_BAR = SM_HV + 2 * NHV * 2048, SM_SEL = SM_BAR + 320, SM_Q = SM_SEL + 576, CHAIN_SMEM = SM_Q + (Q_TMA ? 2048 : 1024);
constexpr uint32_t SM_FFT = 49152, SM_GW = SM_XT - 2048;
static_assert((!OX_L || (XB && !OX_AT)) && (OX_AT < 3 || SXP >= 3) && (!OX_AT || LASTM) && NP % 4 == 0 && NV == 11 && SM_TRACE + 8192 <= SM_XT, "shared memory layout");
static_assert(CHAIN_SMEM <= 232448 && COL_SMEM <= SM_BAR && SM_FFT + (1024 + 8 * ROW_BUF) * 8 <= SM_GW && NP == 12, "shared memory budget");
enum { B_WFULL = 0, B_WREAD = 2, B_WOFULL, B_XFULL, B_XEMPTY, B_E1TRIG, B_E2TRIG, B_PVDONE, B_PUB, B_SC, B_PFULL, B_SPFREE,
       B_LAND, B_LFREE, B_DONE, B_SEL, B_PROBE, B_FREE, B_P1, B_ROWS, B_VFULL, B_VST, B_TW, B_BT, B_WREAD0, B_Z, B_GFULL = B_Z + 4, B_GEMPTY = B_GFULL + 5, B_END = B_GEMPTY + 5 };
static_assert(B_END * 8 <= 320, "barriers");
__host__ __device__ constexpr uint32_t bar_codes(int g) {
  uint32_t r = 0;
  for (int i = 16 * g; i < 16 * g + 16; i++)
    r |= (i == B_LAND ? 3u : i == B_WREAD || i == B_XEMPTY || i == B_E1TRIG || i == B_E2TRIG || i == B_LFREE || i == B_FREE || i == B_VST || i == B_P1 || i == B_ROWS ? 2u :
          i >= B_GEMPTY || i == B_WREAD0 || i == B_PROBE || i == B_DONE || i == B_PVDONE || i == B_PUB || i == B_SC || i == B_SPFREE ? 1u : 0u) << 2 * (i & 15);
  return r;
}
constexpr uint32_t SM_BT = 65536, SM_TW = SM_XT - 8192, COL_Z = 80 * 1024;
static_assert(SM_XT + 3 * 32768 <= SM_BAR && SM_BT + 32768 <= SM_MEM && SM_TRACE <= SM_TW && SM_MEM + 4 * INV_BUF * 8 <= SM_TRACE &&
              8192 + 16 * INV_BUF * 8 <= COL_Z && COL_Z + 131072 <= SM_BAR, "shared memory layout");
__device__ __forceinline__ uint32_t next_stage(uint32_t o) { return o == SM_XT + 65536 ? 0 : o == 32768 ? SM_XT : o + 32768; }

struct ChainCtx { char* mail; uint32_t sb, sel; int r, h, a, b, j, m, w, lane; };
#define BAR(i) (c.sb + SM_BAR + 8 * (i))

__device__ __forceinline__ uint32_t tile_off(int line, int lane) {
  return line * 128 + (((lane & 3) ^ line) << 5) + (lane >> 2) * 4;
}
__device__ __forceinline__ uint32_t read_off(int lane) {
  const int n = lane >> 2, jj = lane & 3, l = 2 * (jj >> 1) + (n & 1);
  return l * 128 + (((n >> 1) ^ l) << 5) + (jj & 1) * 16;
}
__device__ __forceinline__ uint32_t frag_off(int w, int lane) {
  const int mi = lane >> 3, r = lane & 7;
  return ((mi >> 1) * 8 + r) * 128 + (((2 * w + (mi & 1)) ^ r) << 4);
}
__device__ __forceinline__ uint32_t land_off(int w, int lane) { return w * 512 + ((lane ^ (((lane >> 4) | ((w & 1) << 1)) << 1)) << 4); }
__device__ __forceinline__ uint32_t tagged(uint32_t v, uint32_t tag) { return (v | 1u) ^ tag; }
__device__ __forceinline__ void mma_a(float (&d)[4], const uint32_t (&a)[4], uint32_t b0, uint32_t b1) { mma16816(d, a[0], a[1], a[2], a[3], b0, b1); }
__device__ __forceinline__ void mma_q(float (&d)[4], const uint4& a, uint32_t b0, uint32_t b1) { mma16816(d, a.x, a.y, a.z, a.w, b0, b1); }
__device__ __forceinline__ uint4 add4(uint4 a, uint4 b) {
  return make_uint4(add_bf16x2(a.x, b.x), add_bf16x2(a.y, b.y), add_bf16x2(a.z, b.z), add_bf16x2(a.w, b.w));
}
__device__ __forceinline__ void mbar_arrive_both(uint32_t bar, int peer) {
  __syncwarp();
  asm volatile("{ .reg .pred p; .reg .u32 a; mapa.shared::cluster.u32 a, %0, %1; elect.sync _|p, 0xffffffff;\n"
               "@p mbarrier.arrive.shared::cta.b64 _, [%0]; @p mbarrier.arrive.shared::cluster.b64 _, [a]; }" :: "r"(bar), "r"(peer) : "memory");
}

__device__ __forceinline__ void arrive_remote_if(uint32_t a, bool on) {
  asm volatile("{ .reg .pred p; setp.ne.u32 p, %1, 0; @p mbarrier.arrive.shared::cluster.b64 _, [%0]; }" :: "r"(a), "r"((uint32_t)on) : "memory");
}
__device__ __forceinline__ void store_count(void* p, uint4 v, void* cnt) {
  asm volatile("{ .reg .pred p, q; .reg .b128 a, b; .reg .b64 l, h; mov.b64 l, {%1, %2}; mov.b64 h, {%3, %4}; mov.b128 a, {l, h};\n"
               "atom.relaxed.gpu.global.exch.b128 b, [%0], a; mov.b128 {l, h}, b; setp.eq.u64 q, l, 0x7fc17fc17fc17fc1; @q pmevent 1;\n"
               "elect.sync _|p, 0xffffffff; @p red.relaxed.gpu.global.add.u32 [%5], 1; }"
               :: "l"(p), "r"(v.x), "r"(v.y), "r"(v.z), "r"(v.w), "l"(cnt) : "memory");
}

template<int N> __device__ __forceinline__ void pad() {
#pragma unroll
  for (int i = 0; i < N; i++) asm volatile("pmevent 3;");
}
__device__ __forceinline__ int lane_id() {
  int l; asm volatile("{ .reg .u32 t; mov.u32 t, %%laneid; shfl.sync.idx.b32 %0, t, t, 31, 0xffffffff; }" : "=r"(l)); return l;
}
__device__ __forceinline__ uint32_t tid_now() { uint32_t t; asm volatile("mov.u32 %0, %%tid.x;" : "=r"(t)); return t; }
enum { NB_ATT = 1, NB_OM = 2, NB_VM = 3, NB_XCH = 4, NB_MEM = 8, NB_HELP = 12 };
__device__ __forceinline__ uint32_t dep(uint32_t a, uint32_t v, uint32_t z) { uint32_t r; asm("shf.l.wrap.b32 %0, %2, %1, %3;" : "=r"(r) : "r"(a), "r"(v), "r"(z)); return r; }
__device__ __forceinline__ uint32_t vary(uint32_t a, int s, uint32_t z) { return dep(a, 0, z + 32 * s); }
__device__ __forceinline__ char* mk_ptr(uint32_t lo, uint32_t hi) { uint64_t r; asm("mov.b64 %0, {%1, %2};" : "=l"(r) : "r"(lo), "r"(hi)); return (char*)r; }
__device__ __forceinline__ void lds_frag(uint32_t (&r)[4], uint32_t a) {
  asm volatile("ld.shared.v4.u32 {%0,%1,%2,%3}, [%4];" : "=r"(r[0]), "=r"(r[1]), "=r"(r[2]), "=r"(r[3]) : "r"(a) : "memory");
}
__device__ __forceinline__ uint32_t stale2(uint32_t a, uint32_t b, uint32_t t) { uint32_t r; asm("lop3.b32 %0, %1, %2, %3, 0xbd;" : "=r"(r) : "r"(a), "r"(b), "r"(t)); return r; }
__device__ __forceinline__ uint32_t stale1(uint32_t acc, uint32_t a, uint32_t t) { uint32_t r; asm("lop3.b32 %0, %1, %2, %3, 0xf9;" : "=r"(r) : "r"(acc), "r"(a), "r"(t)); return r; }
__device__ __forceinline__ bool all_clear(uint32_t x, uint32_t m) {
  uint32_t r;
  asm volatile("{ .reg .pred p; .reg .u32 t; and.b32 t, %1, %2; setp.eq.u32 p, t, 0; vote.sync.all.pred p, p, 0xffffffff; selp.u32 %0, 1, 0, p; }" : "=r"(r) : "r"(x), "r"(m));
  return r;
}
__device__ __forceinline__ bool arrive_if_all(bool ok, int id, int n) {
  uint32_t r;
  asm volatile("{ .reg .pred p, q; setp.ne.u32 p, %1, 0; vote.sync.all.pred q, p, 0xffffffff; @q bar.arrive %2, %3; selp.u32 %0, 1, 0, q; }"
               : "=r"(r) : "r"((uint32_t)ok), "r"(id), "r"(n) : "memory");
  return r;
}
__device__ __forceinline__ bool arrive_if_clear(uint32_t x, uint32_t m, int id, int n) {
  uint32_t r;
  asm volatile("{ .reg .pred p; .reg .u32 t; and.b32 t, %1, %2; setp.eq.u32 p, t, 0; vote.sync.all.pred p, p, 0xffffffff; @p bar.arrive %3, %4; selp.u32 %0, 1, 0, p; }"
               : "=r"(r) : "r"(x), "r"(m), "r"(id), "r"(n) : "memory");
  return r;
}
__device__ __forceinline__ void touch(const void* p, uint32_t z) {
  asm volatile("{ .reg .pred p; setp.eq.u32 p, %1, 0x7fff0000; @p prefetch.global.L2 [%0]; }" :: "l"(p), "r"(z) : "memory");
}

__device__ __forceinline__ uint64_t desc_x(uint32_t lo, int k) {
  uint64_t d; asm("mov.b64 %0, {%1, %2};" : "=l"(d) : "r"(lo + (k >> 2) * 64 + (k & 3) * 2), "r"(0x40000200)); return d;
}
template<int K0, int K1> __device__ __forceinline__ void issue_qk(float (&xa)[16], const uint32_t (&wt)[16][4], uint32_t lo) {
  WG_FENCE();
#pragma unroll
  for (int k = K0; k < K1; k++) {
    if (k >= EXP_NWG) continue;
    if (k == 0) wgmma_rs_n32<true>(xa, wt[0], desc_x(lo, 0));
    else wgmma_rs_n32<false>(xa, wt[k], desc_x(lo, k));
  }
  WG_COMMIT();
}
__host__ __device__ constexpr int v_order(int i) { return SSPOS == 0 ? i : SSPOS == 2 ? (i + NV) % 16 : NHV == 5 ? (i % 3 == 2 ? NV + i / 3 : i - i / 3) : (i == 15 ? NV - 1 : i % 2 ? NV + i / 2 : i / 2); }
__device__ __forceinline__ void issue_v(float (&xa)[16], const uint32_t (&wv)[16][4], uint32_t lo, uint32_t la) {
  WG_FENCE();
#pragma unroll
  for (int i = 0; i < EXP_NWG; i++) {
    const int k = v_order(i);
    const uint64_t b = desc_x(lo, k);
    if (k < NV) { if (i == 0) wgmma_rs_n32<true>(xa, wv[k], b); else wgmma_rs_n32<false>(xa, wv[k], b); }
    else        { if (i == 0) wgmma_ss_n32_ta<true>(xa, desc128(la + (k - NV) * 128), b); else wgmma_ss_n32_ta<false>(xa, desc128(la + (k - NV) * 128), b); }
  }
  WG_COMMIT();
}
template<bool ISV> __device__ __forceinline__ void park_own(uint32_t (&q)[4], float (&xa)[16], uint32_t dst, int slot, uint32_t z) {
  uint32_t p[8];
#pragma unroll
  for (int i = 0; i < 16; i++) asm volatile("" : "+f"(xa[i]) :: "memory");
#pragma unroll
  for (int i = 0; i < 2; i++) {
    const float* k = xa + 8 * i;
    if (ISV) { p[4 * i] = pack_bf16(k[0], k[1]); p[4 * i + 1] = pack_bf16(k[2], k[3]); p[4 * i + 2] = pack_bf16(k[4], k[5]); p[4 * i + 3] = pack_bf16(k[6], k[7]); }
    else     { p[4 * i] = pack_bf16(k[0], k[2]); p[4 * i + 1] = pack_bf16(k[1], k[3]); p[4 * i + 2] = pack_bf16(k[4], k[6]); p[4 * i + 3] = pack_bf16(k[5], k[7]); }
  }
  sts128(dep(dep(dst, p[4] ^ p[5] ^ p[6], z), p[7], z) + slot * 8192, make_uint4(p[0], p[1], p[2], p[3]));
#pragma unroll
  for (int i = 0; i < 4; i++) q[i] = p[4 + i];
}
__device__ __forceinline__ void park_peer(const uint32_t (&q)[4], uint32_t dst, int slot, const ChainCtx& c) {
  const uint32_t bar = BAR(B_LAND);
  if (EXP_PEER) st_async4(mapa(dst + slot * 8192, c.b ^ 1), q[0], q[1], q[2], q[3], mapa(bar, c.b ^ 1));
  else touch((void*)(uintptr_t)(q[0] ^ q[1] ^ q[2] ^ q[3]), c.sb);
  mbar_arrive_warp(bar);
}
__device__ __forceinline__ uint32_t put_tag(uint32_t v, uint32_t bit, uint32_t t) {
  uint32_t r; asm("lop3.b32 %0, %1, %2, %3, 0x74;" : "=r"(r) : "r"(v), "r"(bit), "r"(t)); return r;
}
__device__ __forceinline__ void mem_proj(const uint32_t (&wa)[16][4], const uint32_t (&wb)[16][4], uint32_t (&wv)[16][4], uint32_t (&af)[16][4],
                                         uint32_t& wo, const char*& pa, uint32_t tab, uint32_t t16, uint32_t pk, const ChainCtx& c, int s) {
  const uint32_t mp = t16 & ~0x600u, id = NB_MEM + (t16 >> 11);
  uint32_t r[8][4];
  float la[4][4] = {}, lg[NLAG][4] = {}, lv[4][4] = {};
  auto lead = [&](int k) { mma_a(la[k & 3], wa[k], r[k >> 1][2 * (k & 1)], r[k >> 1][2 * (k & 1) + 1]); };
  auto lag = [&](int k) { mma_a(lg[k % NLAG], wb[k], r[k >> 1][2 * (k & 1)], r[k >> 1][2 * (k & 1) + 1]); };
  auto sum = [](const float (&d)[4][4], int i) { return (d[0][i] + d[1][i]) + (d[2][i] + d[3][i]); };
  bar_sync(id, 160);
  TR(s, 0);
#pragma unroll
  for (int i = 0; i < 4; i++) ldsm4t(r[i], mp + (c.sb + SM_MEM + i * 512));
  uint4 tq;
  if (!TQ_AT) tq = lds128(tab);
  bar_sync(id + 2, 160);
  uint32_t first = 0;
#pragma unroll
  for (int k = 0; k < 8; k++) { lead(k); if (k == C1_AT - 4) first = dep(mp, __float_as_uint(la[k & 3][0]), c.sb); }
  uint32_t ta, tb;
  if (!TQ_AT) { ta = tq.x | ((pk >> 16) & 511); tb = tq.z ^ ((pk >> 16) & 511); }
  const uint32_t mp1 = C1_AT >= 4 ? (TQ_AT ? first : dep(first, ta ^ tb, c.sb)) : dep(mp, __float_as_uint(la[C1_AT & 3][0]) ^ (TQ_AT ? 0 : ta ^ tb), c.sb);
#pragma unroll
  for (int i = 4; i < 8; i++) ldsm4t(r[i], mp1 + (c.sb + SM_MEM + 2048 + i * 512));
  if (TQ_AT) { tq = lds128(tab); ta = tq.x | ((pk >> 16) & 511); tb = tq.z ^ ((pk >> 16) & 511); }
  char* dst = mk_ptr(ta, tq.y);
  char* dst2 = mk_ptr(tb, tq.w);
  const uint32_t hv = pk & 0xFFFF;
#pragma unroll
  for (int k = NV; k < NV + HV_E; k++) ldsm4t(wv[k], dep(hv, r[HV_R][0], c.sb) + (c.sb + SM_HV + (k - NV) * 2048));
#pragma unroll
  for (int k = 0; k < LAG_0; k++) lag(k);
#pragma unroll
  for (int k = 8; k < 16; k++) lead(k);
  const uint32_t s0 = __float_as_uint(sum(la, 0)), s3 = __float_as_uint(sum(la, 3));
  sts128((HV_E ? dep(t16, wv[NV][0] ^ wv[NV + HV_E / 2][1] ^ wv[NV + HV_E - (HV_E > 0)][2], c.sb) : TQ_AT ? dep(t16, ta ^ tb, c.sb) : t16) + (c.sb + SM_XCH),
         make_uint4(s0, __float_as_uint(sum(la, 1)), __float_as_uint(sum(la, 2)), s3));
  if (XB) bar_sync(NB_XCH, 256); else bar_sync(NB_XCH | ((t16 >> 9) & 3), 64);
#pragma unroll
  for (int k = LAG_0; k < LAG_0 + LAG_G; k++) r[k >> 1][2 * (k & 1)] = dep(r[k >> 1][2 * (k & 1)], LAG_S == 0 ? s3 : __float_as_uint(la[LAG_S - 1][0]), c.sb);
#pragma unroll
  for (int k = LAG_0; k < O_AT; k++) lag(k);
  const uint4 o = lds128((O_AT > LAG_0 ? dep(t16 ^ 2048, __float_as_uint(lg[(O_AT - 1) % NLAG][0]), c.sb) : t16 ^ 2048) + (c.sb + SM_XCH));
#pragma unroll
  for (int k = O_AT > LAG_0 ? O_AT : LAG_0; k < 16; k++) lag(k);
#pragma unroll
  for (int k = 0; k < V_E; k++) mma_a(lv[k & 3], wv[k], r[k >> 1][2 * (k & 1)], r[k >> 1][2 * (k & 1) + 1]);
  float t[4];
#pragma unroll
  for (int i = 0; i < 4; i++) {
    const float oi = __uint_as_float(i == 0 ? o.x : i == 1 ? o.y : i == 2 ? o.z : o.w);
    t[i] = NLAG == 4 ? (LAG_T ? ((lg[0][i] + lg[1][i]) + oi) + (lg[2 % NLAG][i] + lg[3 % NLAG][i]) : (((lg[0][i] + lg[1][i]) + lg[2 % NLAG][i]) + lg[3 % NLAG][i]) + oi) : LAG_T && NLAG == 2 ? (lg[0][i] + lg[1][i]) + oi : NLAG == 3 ? (lg[1][i] + lg[2 % NLAG][i]) + (lg[0][i] + oi) : (lg[0][i] + oi) + lg[1][i];
  }
  const uint32_t y0 = put_tag(pack_bf16(t[0], t[2]), pk >> 31, s >> 1), y1 = put_tag(pack_bf16(t[1], t[3]), pk >> 31, s >> 1);
  st_pub(dst, y0); st_pub(dst2, y1);
  mbar_arrive_warp(BAR(B_E1TRIG));
  TR(s, 1);
  sched_fence(c.sb);
  const uint4 tv = lds128(tab + 16);
#pragma unroll
  for (int k = NV + HV_E; k < 16; k++) ldsm4t(wv[k], (k < NV + HV_E + HV_D ? hv : dep(hv, k == NV + HV_E + HV_D ? wv[k - HV_D][0] ^ tv.x : wv[k - HV_D][0], c.sb)) + (c.sb + SM_HV + (k - NV) * 2048));
  wo = (hv & 2047) | ((t16 & 2048) << 3);
  const uint32_t l8 = (t16 >> 1) & 255;
  char* dv = mk_ptr(tv.x | l8, tv.y);
  pa = mk_ptr(tv.z | l8, tv.w);
#pragma unroll
  for (int f = 0; f < WO_0; f++) ldsm4t(af[f], dep(wo, f < WO_D ? wv[16 - WO_D + f][0] : af[f < WO_D ? 0 : f - WO_D][0], c.sb) + (c.sb + SM_WO + (f & 1) * 32768 + (f >> 1) * 2048));
#pragma unroll
  for (int k = V_E; k < 16; k++) mma_a(lv[k & 3], wv[k], r[k >> 1][2 * (k & 1)], r[k >> 1][2 * (k & 1) + 1]);
  const uint32_t z0 = put_tag(pack_bf16(sum(lv, 0), sum(lv, 1)), (~t16 >> 4) & 1, s >> 1), z1 = pack_bf16(sum(lv, 2), sum(lv, 3));
  st_pub2(dv, z0, z1);
  if (FIN_AT >= 3) mbar_arrive_warp(BAR(B_VST));
  TR(s, 2);
}
__device__ __forceinline__ uint32_t max_bf16x2(uint32_t a, uint32_t b) { uint32_t r; asm("max.bf16x2 %0, %1, %2;" : "=r"(r) : "r"(a), "r"(b)); return r; }
constexpr float SCL = 0.08838834764831845f * 1.4426950408889634f;
__device__ __forceinline__ uint32_t max5(const uint32_t (&sc)[5]) { return max_bf16x2(max_bf16x2(max_bf16x2(max_bf16x2(sc[0], sc[1]), sc[2]), sc[3]), sc[4]); }
__device__ __forceinline__ float row_off(uint32_t m, uint32_t& m1) {
  m1 = __shfl_xor_sync(~0u, m, 1);
  const uint32_t m2 = __shfl_xor_sync(~0u, m, 2), m3 = __shfl_xor_sync(~0u, m, 3);
  const uint32_t mm = max_bf16x2(max_bf16x2(max_bf16x2(m, m1), m2), m3);
  return -SCL * fmaxf(__uint_as_float(mm << 16), __uint_as_float(mm & 0xFFFF0000u));
}
__device__ __forceinline__ void unpack(float (&f)[10], const uint32_t (&sc)[5]) {
#pragma unroll
  for (int i = 0; i < 5; i++) {
    asm volatile("shl.b32 %0, %1, 16;" : "=f"(f[2 * i]) : "r"(sc[i]));
    asm volatile("and.b32 %0, %1, 0xffff0000;" : "=f"(f[2 * i + 1]) : "r"(sc[i]));
  }
}
__device__ __forceinline__ uint32_t exp_pair(const float (&f)[10], int i, float off) {
  return pack_bf16(ex2(fmaf(f[2 * i], SCL, off)), ex2(fmaf(f[2 * i + 1], SCL, off)));
}
template<bool SPLIT> __device__ __forceinline__ void scores_x(float (&a)[2][4], const uint4 (&kf)[4], const uint4& q, uint32_t z) {
#pragma unroll
  for (int t = 0; t < 2; t++) { a[t][0] = a[t][1] = a[t][2] = a[t][3] = 0.f; }
  mma_q(a[0], kf[0], q.x, q.y); mma_q(a[1], kf[2], q.x, q.y);
  if (SPLIT) sched_fence(z);
  mma_q(a[0], kf[1], q.z, q.w); mma_q(a[1], kf[3], q.z, q.w);
}
__device__ __forceinline__ uint32_t scores_m(const uint4& q, const uint4& k) {
  float a[4] = {}, b[4] = {};
  mma_q(a, q, k.x, k.z); mma_q(b, q, k.y, k.w);
  return pack_bf16(a[0] + b[2], a[1] + b[3]);
}
__device__ __forceinline__ void store_scores(const float (&a)[2][4], uint32_t dst) {
  sts64(dst, pack_bf16(a[0][0], a[0][2]), pack_bf16(a[1][0], a[1][2]));
  sts64(dst + 320, pack_bf16(a[0][1], a[0][3]), pack_bf16(a[1][1], a[1][3]));
}
__device__ __forceinline__ uint32_t sum4(uint32_t a, uint32_t b, uint32_t d, uint32_t e) { return add_bf16x2(add_bf16x2(a, b), add_bf16x2(d, e)); }
__device__ __forceinline__ void load_scores(uint32_t (&sc)[5], uint32_t ax, uint32_t am) {
  uint4 p[4];
#pragma unroll
  for (int i = 0; i < 4; i++) p[i] = lds128(ax + i * 1280);
  const uint2 m0 = lds64(am), m1 = lds64(am + 256);
  const uint4 t = add4(add4(add4(p[0], p[1]), p[2]), p[3]);
  sc[1] = t.x; sc[2] = t.y; sc[3] = t.z; sc[4] = t.w;
  sc[0] = sum4(m0.x, m0.y, m1.x, m1.y);
}
constexpr uint32_t ONES = 0x3F803F80u;
__device__ __forceinline__ float pv(float (&o)[2][4], const uint32_t (&p)[5], const uint4 (&vf)[4], const uint4& vm) {
  float a[4] = {}, b[4] = {};
#pragma unroll
  for (int t = 0; t < 2; t++) { o[t][0] = o[t][1] = o[t][2] = o[t][3] = 0.f; }
  mma_q(o[0], vf[0], p[1], p[2]); mma_q(o[1], vf[2], p[1], p[2]);
  mma_q(o[0], vf[1], p[3], p[4]); mma_q(o[1], vf[3], p[3], p[4]);
  mma16816(a, p[1], p[2], p[3], p[4], ONES, ONES);
  mma1688(o[0], vm.x, vm.y, p[0]); mma1688(o[1], vm.z, vm.w, p[0]);
  mma1688(b, p[0], ONES, ONES);
  return (a[0] + a[2]) + b[0];
}
constexpr uint32_t POLL_LIMIT = 1u << 21;
__device__ __forceinline__ uint32_t box(int slot, int cta) { return (slot * 2 + (cta >> 6)) * M_REG + (cta & 63) * 16384; }
__device__ __forceinline__ uint32_t near_page(const ChainCtx& c, int cta, uint32_t off) {
  return off + (((lds32(c.sb + SM_SEL + cta * 4) >> (off >> 21)) ^ __popc(off & 0xB2000)) & 1) * 4096;
}
__device__ __forceinline__ uint32_t e1_box(const ChainCtx& c, int slot, int cta) { return near_page(c, E1OFF ? cta ^ 2 : cta, box(slot, cta) + 8192) ^ (E1OFF ? 0 : 4096); }
__device__ __forceinline__ uint32_t tile_key() {
  uint32_t sm; asm volatile("mov.u32 %0, %%smid;" : "=r"(sm));
  return (sm < 64 ? sm / 2 % 8 : sm < 120 ? 1 + (sm / 2 - 32) % 7 : 0) << 24 | sm << 16;
}
__device__ __forceinline__ uint32_t ox_at(int s, int row, int g, int jj) { return s * 131072 + ((g >> 1) * 32 + row) * 64 + (g & 1) * 32 + 8 * jj; }
__device__ __forceinline__ int tile_of(const ChainCtx& c) { return SIDE ? __shfl_sync(~0u, lds32(c.sb + SM_SEL + 528), 0) : c.r; }

__global__ void __cluster_dims__(2, 1, 1) __launch_bounds__(512, 1)
chain_kernel(const __grid_constant__ CUtensorMap tq, const __grid_constant__ CUtensorMap tk, const __grid_constant__ CUtensorMap tv,
             const __grid_constant__ CUtensorMap tv16, const __grid_constant__ CUtensorMap to, const __grid_constant__ CUtensorMap tx,
             const __grid_constant__ CUtensorMap twr, const __grid_constant__ CUtensorMap twi,
             const __grid_constant__ CUtensorMap ta, const __grid_constant__ CUtensorMap tw,
             const __grid_constant__ CUtensorMap tb, const __grid_constant__ CUtensorMap tout, const __grid_constant__ CUtensorMap tz,
             const __grid_constant__ CUtensorMap tzs, const __grid_constant__ CUtensorMap ta32,
             const __nv_bfloat16* __restrict__ mem0, char* __restrict__ mail, const __nv_bfloat16* __restrict__ x,
             const __nv_bfloat16* __restrict__ gw) {
  extern __shared__ __align__(1024) unsigned char smraw[];
  if (threadIdx.x == 0) TL(0);
  ChainCtx c;
  c.sb = __shfl_sync(~0u, smem_u32(smraw), 0);
  c.mail = mail; c.sel = 0; c.r = blockIdx.x;
  if (ROLE) {
    const uint32_t u = blockIdx.x >> 1, n = u < 36 ? 8 : 7, k = u - (u < 36 ? 4 : 36), q = k * (u < 36 ? 32 : 37) >> 8;
    c.r = __shfl_sync(~0u, 2 * (u - 4 < 60 ? u + k - q * n - (q & 1) * (n - 1) : u) + (blockIdx.x & 1) + (threadIdx.x >> 9), 0);
  }
  c.h = c.r >> 2; c.a = (c.r >> 1) & 1; c.b = c.r & 1; c.j = c.r & 3;
  c.m = __shfl_sync(~0u, (int)(threadIdx.x >> 7), 0); c.w = __shfl_sync(~0u, (int)((threadIdx.x >> 5) & 3), 0);
  char* own = c.mail + (uint32_t)(c.w * M_REG + M_E3 + (c.r >> 5) * 8192 + (c.r & 31) * 128 + (threadIdx.x & 31) * 4);
  uint32_t i0 = 0, i1 = 0;
  if (EARLY) asm volatile("{ .reg .pred p; setp.ne.u32 p, %4, 0; @p atom.relaxed.gpu.global.exch.b32 %0, [%2], %3; @p atom.relaxed.gpu.global.exch.b32 %1, [%2 + 4096], %3; }"
               : "+r"(i0), "+r"(i1) : "l"(own), "r"(SENT), "r"((uint32_t)(c.m == 2 && c.r < 128)) : "memory");
#pragma unroll
  for (int g = 0; g < 3; g++) {
    const int i = c.m * 4 + c.w;
    if (g < 2 || i < B_END - 32)
      asm volatile("{ .reg .pred p; elect.sync _|p, 0xffffffff; @p mbarrier.init.shared::cta.b64 [%0], %1; }"
                   :: "r"(BAR(g * 16 + i)), "r"(0x19080401u >> (bar_codes(g) >> 2 * i & 3) * 8 & 255) : "memory");
  }
  asm volatile("fence.mbarrier_init.release.cluster;" ::: "memory");
  __syncthreads();
  asm volatile("barrier.cluster.arrive.relaxed.aligned;" ::: "memory");

  if (c.r >= 128) {
    fft_cols((float2*)smraw, c.r - 128, &twr, &twi, &tzs);
    if ((threadIdx.x & 127) == 0) TL(7);
    __syncwarp();
  } else if (c.m == 3) {
    asm volatile("setmaxnreg.dec.sync.aligned.u32 %0;" :: "n"(REG_H));
    c.lane = lane_id();
    if (c.sb & 1023) asm volatile("trap;");
    const int col = c.h * 128 + c.a * 64, eq = E3M ? c.w & 1 : c.w >> 1, eh = E3M == 1 ? (c.w >> 1) ^ 1 : E3M ? c.w >> 1 : c.w & 1;
    uint32_t tl = clock_lo();
    TR(-2, 3);
    if (c.w == 0) {
      if (START) delay_until(tl + START);
      if (HOLD == 2) mbar_wait(BAR(B_PROBE), 0);
      if (HOLD == 3) mbar_wait(BAR(B_SEL), 0);
      if (HOLD == 1) mbar_wait(BAR(B_PROBE), 0);
      TR(-2, 4);
      tl = clock_lo();
      mbar_expect_e(BAR(B_PFULL), 2 * NP * 2048);
      mbar_expect_e(BAR(B_WFULL), (48 - NP) * 2048);
      mbar_expect_e(BAR(B_WFULL + 1), (48 - NP) * 2048);
    }
    auto dst_x = [&](int e, int w) {
      const uint32_t g2 = 2 * c.a + (w >> 1), u = w & 1;
      return M_KVQ + c.h * 24576 + (e == 0 ? 8192 + (2 * u + c.b) * 2048 + g2 * 512 : e == 1 ? g2 * 2048 + u * 1024 + c.b * 128 : 16384 + c.b * 4096 + g2 * 512 + u * 256);
    };
    if (c.w == 0) {
      tl += PACE0;
#pragma unroll wunr
      for (int i = 0; i < 24; i++) {
        const int m = i < 4 || i >= 16, k = i < 4 ? i : m ? i - 12 : i - 4;
        const int row = c.b * 512 + m * 256;
        const uint32_t st = c.sb + m * ST_WG, bar = BAR(k < 3 ? B_PFULL : B_WFULL + m);
        if (PACE) delay_until(tl += PACE);
        if (i == 14) { mbar_idle(BAR(B_FREE), 0); if (c.lane == 0) TL2(2); __syncwarp(); }
        if (k < 11) TMA_W(k < 3 ? c.sb + SM_POOL + m * NP * 2048 + k * 8192 : k == 3 ? c.sb + SM_HV + (m * NHV + 1) * 2048 : st + (k - 4) * 8192,
                          k == 3 || k > 8 ? &tv : (k >> 2 & 1) == m ? &tk : &tq, col, row + (k < 8 ? k & 3 : (k - 9) & 3) * 64, bar);
        else {
#pragma unroll 1
          for (int j = 8; j < 12; j++) TMA_W(j < NV ? st + (32 - NP + j) * 2048 : c.sb + SM_HV + m * NHV * 2048, &tv16, col, row + j * 16, bar);
        }
      }
      TR(-2, 7);
    } else if (c.w == 2) {
      const unsigned short* mp = (const unsigned short*)mem0 + (2 * (c.lane & 3)) * D_ + 8 * c.r + (c.lane >> 2);
      uint32_t mv = (uint32_t)mp[0] | (uint32_t)mp[D_] << 16;
      if (mv == SENT) mv = 0x7FFF7FFFu;
      mbar_idle(BAR(B_PROBE), 0);
      char* dst = c.mail + (uint32_t)(M_E3 + (c.r >> 5) * 8192 + (c.r & 31) * 128 + c.lane * 4);
      st_pub(dst, mv); st_pub(dst + 4096, mv);
    } else if (c.w == 3) {
      mbar_idle(BAR(B_FREE), 0);
      mbar_idle(BAR(B_PFULL), 0);
      mbar_expect_e(BAR(B_PFULL), 65536);
      for (int i = 0; i < 2; i++) tma4d_e(c.sb + SM_XT + i * 16384, &tx, c.b * 8, 4 + 2 * (c.b ^ i), BAR(B_PFULL));
    }
    {
      mbar_idle(BAR(B_SEL), 0);
      const int i = tid_now() & 127, sl = i & 3, e = (i >> 2) & 3;
      uint32_t ox = dst_x(e, i >> 5) + sl * M_REG;
      uint32_t oh = e & 1 ? (sl ^ (e & 2)) * M_REG + M_E3 + (c.r >> 5) * 8192 + (c.w & 1) * 4096 + (c.r & 31) * 128
                          : near_page(c, c.r, e ? sl * M_REG + M_E3 + (c.b * 2 + eq) * 8192 : box(~sl & 1, c.r)) + (e ? eh * 2048 : c.w * 1024), of;
      {
        const int e = i & 7, w = (i >> 3) & 3, m = (i >> 5) & 1, sl = i >> 6;
        const int cta = e < 2 ? c.r & ~1 : e == 2 ? c.r | 1 : e == 3 ? c.h * 4 + 2 * m + 1 : c.j * 32 + m * 8 + 2 * w + (e & 2) * 8 + (e & 1);
        const uint32_t off = e < 2 ? c.b * 2048 + m * 1024 + (w >> 1) * 512 + e * 160 : e == 2 ? c.b * 2048 + m * 1024 + w * 256 : e == 3 ? w * 256 : c.h * 128;
        of = (e < 4 ? e1_box(c, sl, cta) : near_page(c, cta, box(sl, cta))) + off;
      }
      char *px = c.mail + ox, *ph = c.mail + oh, *pf = c.mail + of;
      uint32_t at = sl * 128 + (i >> 5) * 32 + e * 8, af = i * 8;
      pin(px); pin(ph); pin(pf); pin(at); pin(af);
      asm volatile("barrier.cluster.wait;" ::: "memory");
      TR(-2, 0);
      mbar_idle(BAR(B_WREAD), 0);
      TR(-2, 1);
      mbar_arrive_both(BAR(B_LFREE), c.b ^ 1);
      sts64(at + (c.sb + SM_TAB + 1536), (uint32_t)(uintptr_t)px, (uint32_t)((uintptr_t)px >> 32));
      sts64(at + (c.sb + SM_TAB + 1024), (uint32_t)(uintptr_t)ph, (uint32_t)((uintptr_t)ph >> 32));
      sts64(af + (c.sb + SM_TAB), (uint32_t)(uintptr_t)pf, (uint32_t)((uintptr_t)pf >> 32));
      TR(-2, 2);
      if (tid_now() == 384) TL2(25);
      __syncwarp();
      bar_sync(14, 160);
    }
    pad<PAD3>();
    for (int s = -1; s < NSEG; s++) {
      if (E30 ? s != 0 : s >= 0) {
        const uint32_t tab = c.sb + SM_TAB + 1024 + (max(s, 0) & 3) * 128 + c.w * 32;
        uint32_t t0;
        if (s > 0) {
          const uint32_t ln = tid_now() & 31;
          const uint4 ta = lds128(tab);
          const char* src = mk_ptr(ta.x | ln * 4, ta.y);
          char* dst = mk_ptr(ta.z | ln * 4, ta.w);
          const uint32_t tg = (s - 1) >> 1, chk = (ln & 3) ? 0u : 1u, red = ln * (RED_L == 3 ? 4 : 8);
          touch(src, dep(c.sb, chk, c.sb)); touch(dst, dep(c.sb, red, c.sb));
          mbar_wait(BAR(B_E2TRIG), (s - 1) & 1);
          TR(s, 0);
          if (ANCH2) delay_fine(lds32(c.sb + SM_SUM + 64) + DLY_E2); else delay_cycles(DLY_E2);
          uint32_t n = 0;
          while (true) {
            uint32_t v[8];
#pragma unroll
            for (int i = 0; i < 8; i++) v[i] = ld_poll1(src + i * 128);
            if (E2_F) sched_fence(c.sb);
            const uint32_t bad = RED_T ? (stale2(v[0], v[1], tg) | stale2(v[2], v[3], tg) | stale2(v[4], v[5], tg)) | stale2(v[6], v[7], tg)
                                       : stale1(stale1(stale2(v[0], v[1], tg), v[2], tg), v[3], tg) | stale1(stale1(stale2(v[4], v[5], tg), v[6], tg), v[7], tg);
            const bool ok = all_clear(bad, chk);
#pragma unroll
            for (int l = 0; l < RED_L; l++)
#pragma unroll
              for (int i = 0; i < (4 >> l); i++) v[i] = add_bf16x2(v[2 * i], v[2 * i + 1]);
            if (RED_L == 3) sts32(red + (c.sb + SM_RED + c.w * 128), v[0]);
            else {
              float lo[8], hi[8];
#pragma unroll
              for (int i = 0; i < (8 >> RED_L); i++) { lo[i] = __uint_as_float(v[i] << 16); hi[i] = __uint_as_float(v[i] & 0xFFFF0000u); }
#pragma unroll
              for (int l = RED_L; l < 3; l++)
#pragma unroll
                for (int i = 0; i < (4 >> l); i++) { lo[i] = lo[2 * i] + lo[2 * i + 1]; hi[i] = hi[2 * i] + hi[2 * i + 1]; }
              sts64(red + (c.sb + SM_RED + c.w * 256), __float_as_uint(lo[0]), __float_as_uint(hi[0]));
            }
            if (ok) break;
            n++; CNT(0);
          }
          bar_sync(NB_HELP, 128);
          const uint32_t rd = red + (c.sb + SM_RED);
          if (!RED_P || c.w < 2) {
            if (RED_L == 3) st_pub_if(dst, sum4(lds32(rd), lds32(rd + 128), lds32(rd + 256), lds32(rd + 384)), c.w < 2);
            else {
              const uint2 p0 = lds64(rd), p1 = lds64(rd + 256), p2 = lds64(rd + 512), p3 = lds64(rd + 768);
              st_pub_if(dst, pack_bf16((__uint_as_float(p0.x) + __uint_as_float(p1.x)) + (__uint_as_float(p2.x) + __uint_as_float(p3.x)),
                                       (__uint_as_float(p0.y) + __uint_as_float(p1.y)) + (__uint_as_float(p2.y) + __uint_as_float(p3.y))), c.w < 2);
            }
          }
          t0 = clock_lo();
          mbar_arrive_warp(BAR(B_PUB));
          TRV(s, 15, n);
          mbar_wait(BAR(B_SPFREE), (s - 1) & 1);
        } else {
          if (tid_now() == 384) TL2(24);
          __syncwarp();
          if (!E30) mbar_wait(BAR(B_PROBE), 1);
          if (!WO_S) mbar_wait(BAR(B_WOFULL), 0);
          if (tid_now() == 384) TL2(19);
          __syncwarp();
          t0 = clock_lo() - DLY_E3;
        }
        TRV(s, 1, t0);
        {
          const uint32_t l16 = (tid_now() & 31) * 16, dst = vary(l16, s, c.sb) + (c.sb + SM_MEM + eh * 4096 + eq * 2048);
          const uint4 tb = lds128(tab + 16);
          st_pub_if(mk_ptr(tb.z | l16 >> 2, tb.w), SENT, c.w >= 2);
          const char* src = mk_ptr(tb.x | l16, tb.y);
          touch(src, dep(c.sb, dst, c.sb));
          delay_fine(t0 + (DLY_E3 + eh * DLY_E3B));
          uint32_t n = 0;
          while (true) {
            uint4 v[4];
#pragma unroll
            for (int i = 0; i < 4; i++) v[i] = ld_poll(src + i * 512);
#pragma unroll
            for (int i = 0; i < 4; i++) sts128(dst + i * 512, v[i]);
            if (arrive_if_all(max(max(v[0].x, v[1].x), max(v[2].x, v[3].x)) != SENT, NB_MEM + eh * 2 + eq, 160)) break;
            n++; CNT(1);
          }
          TR(s, 2); TRV(s, 14, n);
        }

        if (s == 1) CLK(1); if (s == 8) CLK(2); if (s == 56) CLK(3);
        if (c.w == 2 && s == 15) TRSYNC(8);
        if (c.w == 2 && s == 21) TRSYNC(10);
      }
      const int g = s + 1;
      auto load_v = [&]() {
        if (V_TMA && c.w == V_W) {
          mbar_expect_e(BAR(B_VFULL), (K_TMA ? 16384 : 8192) + (Q_TMA ? 2048 : 0));
          const char* src = c.mail + (uint32_t)(M_KVQ + (min(g, XEND - 1) & (NSLOT - 1)) * M_REG + c.h * 24576);
          bulk_load_e(c.sb + SM_V, src + 8192, 8192, BAR(B_VFULL));
          if (K_TMA > 1) delay_cycles(K_TMA);
          if (K_TMA) bulk_load_e(c.sb + SM_K, src, 8192, BAR(B_VFULL));
          if (Q_TMA > 1) delay_cycles(Q_TMA);
          if (Q_TMA) bulk_load_e(c.sb + SM_Q, src + (16384 + c.j * 2048), 2048, BAR(B_VFULL));
        }
      };
      if (XEND < NSEG && g >= XEND && g < NSEG) { mbar_wait(BAR(B_SC), s & 1); load_v(); }
      if (g < XEND) {
        const uint32_t tx_ = c.sb + SM_TAB + 1536 + (g & 3) * 128 + c.w * 32, tag = (g >> 2) & 1;
        if (c.w == 0) mbar_expect_e(BAR(B_LAND), EXP_PEER * 12288);
        auto load_x = [&]() {
          if (c.w == 3 && g + 1 < XEND) {
            mbar_wait(BAR(B_XEMPTY), g & 1);
            mbar_expect_e(BAR(B_XFULL), 16384 * EXP_NXT);
            for (int i = 0; i < EXP_NXT; i++) tma4d_e(c.sb + SM_XT + i * 16384, &tx, c.b * 8, (g + 1) * 4 + 2 * (c.b ^ i), BAR(B_XFULL));
          }
        };
        if (X_AT == 0 && g > 0) load_x();
        TR(s, 6);
        if (E30 && g == 0) mbar_idle(BAR(B_PROBE), 1);
        mbar_wait(BAR(B_LAND), g & 1);
        TR(s, 7);
        if (DLY_F && g > 0) delay_cycles(DLY_F);
        auto total = [&](int w, int lane, uint32_t o0, uint32_t o1) {
          const uint32_t a = c.sb + SM_LAND + land_off(w, lane);
          if (EXP_FL == 1) return make_uint4(a, a, a, a);
          const uint4 t = add4(lds128(a + o0), lds128(a + o1 + 2048));
          const uint32_t a2 = dep(dep(a, t.x ^ t.y ^ t.z, c.sb), t.w, c.sb);
          return add4(t, add4(lds128(a2 + o0 + 4096), lds128(a2 + o1 + 6144)));
        };
        auto get = [&](int e) {
          const int ln = tid_now() & 31;
          return e == 0 ? total(c.w, ln, 16384, 16384)
               : e == 1 ? total((c.w & 2) + ((ln >> 1) & 1), (ln & 1) * 16 + (c.w & 1) * 8 + (ln >> 2), 8192, 0)
                        : total((c.w & 2) + ((ln >> 1) & 1), (ln & 1) * 16 + (ln >> 3) * 4 + (c.w & 1) * 2 + ((ln >> 2) & 1), 0, 8192);
        };
        auto put = [&](int e, uint4 v) {
          const int ln = tid_now() & 31;
          const uint2 d = lds64(tx_ + e * 8);
          if (e < 2) {
            v.x = tagged(v.x, tag);
            st_pub4(mk_ptr(d.x | (e ? (ln & 24) * 32 + (ln & 7) * 16 : ln * 16), d.y), v);
          } else {
            char* dst = mk_ptr(d.x | ((ln & 7) * 16 + (ln >> 3) * 4), d.y);
            const uint32_t bit = ln < 8;
            st_pub(dst, put_tag(v.x, bit, tag)); st_pub(dst + 128, put_tag(v.y, bit, tag));
            st_pub(dst + 2048, put_tag(v.z, bit, tag)); st_pub(dst + 2176, put_tag(v.w, bit, tag));
          }
        };
        auto after_sc = [&]() { if (g > 0) { mbar_wait(BAR(B_SC), s & 1); if (DLY_FK) delay_cycles(DLY_FK); if (X_AT == 1) load_x(); } };
        if (FIN_AT == 5) {
          put(0, get(0));
          if (DLY_F2 && g > 0) delay_cycles(DLY_F2); else sched_fence(c.sb);
          const uint4 k = get(1);
          sched_fence(c.sb);
          const uint4 q = get(2);
          if (g > 0) mbar_wait(BAR(B_VST), s & 1);
          put(1, k); put(2, q);
          TR(s, 5);
          mbar_arrive_both(BAR(B_LFREE), c.b ^ 1);
          after_sc();
          load_v();
          continue;
        }
        if (FIN_AT < 3) {
          if (EXP_FIN & 1) put(0, get(0));
          TR(s, 3);
          if (FIN_AT == 1) after_sc();
          if (V_TMA == 1) load_v();
          if (EXP_FIN & 2) put(1, get(1));
        } else {
          const uint4 v = get(0);
          sched_fence(c.sb);
          const uint4 k = get(1);
          if (g > 0) { mbar_wait(BAR(B_VST), s & 1); if (DLY_FS) delay_cycles(DLY_FS); }
          put(0, v); put(1, k);
        }
        TR(s, 4);
        if (FIN_AT == 4) {
          const uint4 q = get(2);
          after_sc();
          load_v();
          put(2, q);
        } else {
          if (FIN_AT >= 2) after_sc();
          if (V_TMA == 2) load_v();
          if (EXP_FIN & 4) put(2, get(2));
        }
        mbar_arrive_both(BAR(B_LFREE), c.b ^ 1);
        if (V_TMA == 3) load_v();
        TR(s, 5);
        if (!FIN_AT && X_AT && g > 0) { mbar_wait(BAR(B_SC), s & 1); if (DLY_FK) delay_cycles(DLY_FK); load_x(); }
      }
    }
    const int tile = tile_of(c), s0 = (tile >> 3) * 4, n0 = (tile & 7) * 128;
    if (c.w == 1) {
      mbar_idle(BAR(B_PVDONE), 0);
      count_e(g_ctl + (EARLY2 ? C_LAST : C_EARLY));
      st_pub(c.mail + (uint32_t)((tid_now() & 6) * (M_REG / 2) + M_SEL + (tid_now() & 1) * 4096 + c.r * 4), 0);
      await_count(g_ctl + C_COLS, 4);
      if (K_TMA) mbar_idle(BAR(B_SC), 1);
      mbar_expect_e(BAR(B_TW), 8192);
      bulk_load_e(c.sb + SM_TW, g_tw, 8192, BAR(B_TW));
    } else if (c.w == 2) {
      const uint32_t ln = tid_now() & 31, rel = mapa(BAR(B_GEMPTY) + (ln >> 2) * 8, ln & 1);
      mbar_idle(BAR(B_VST), 1); mbar_idle(BAR(PRE_AT), 1);
      arrive_remote_if(rel, ln < 12);
      mbar_idle(BAR(B_E2TRIG), 1);
      if (GATE) mbar_wait(BAR(B_DONE), 0);
      arrive_remote_if(rel, ln >= 12 && ln < 20);
    } else {
      auto ahead = [&](int k) {
        if (c.w) { if (PF_A && (k & 3) == (tile >> 1 & 3)) prefetch3d_e(&ta, k * 32, s0 + 2 * c.b); }
        else if (PF_B && (k & 7) == (tile >> 4)) prefetch2d_e<(ONCE & 512) != 0>(&tw, n0 + (tile & 8) * 8, k * 64);
      };
#pragma unroll 1
      for (int k = 0; k < PF_D; k++) ahead(k);
      if (c.w == 3) await_count(g_ctl + C_EARLY, 128);
      const int skew = tile < 120 ? 0 : SKEW;
      uint32_t o = SM_XT, st = 0, ph = 0;
#pragma unroll 1
      for (int kb = 0; kb < 64 + skew; kb++, o = next_stage(o)) {
        const bool solo = kb < skew || kb >= 64;
        const uint32_t bar = BAR(B_GFULL + st), k = kb & 63;
        if (c.w && kb == skew) {
          if (tile >= 120) await_count(g_ctl + C_LAST, EARLY2 ? 640 : 512);
          if (tid_now() == 480) TL(10);
          __syncwarp();
        }
        mbar_wait(BAR(B_GEMPTY + st), ph);
        if (c.w) {
          const int r = solo ? (kb >> 5) + c.b : c.b * 2;
          tma3d_mc_e(c.sb + o + r * 4096, solo ? &ta32 : &ta, k * 32, s0 + r, bar);
        } else {
          mbar_expect_e(bar, solo ? 24576 : 32768);
          tma2d_o<(ONCE & 2) != 0>(c.sb + o + 16384, &tw, n0, k * 64, bar);
          tma2d_o<(ONCE & 2) != 0>(c.sb + o + 24576, &tw, n0 + 64, k * 64, bar);
        }
        if (kb + PF_D < 64) ahead(kb + PF_D);
        if (++st == 5) { st = 0; ph ^= 1; }
      }
    }
    return;
  } else if (c.m == 2) {
    asm volatile("setmaxnreg.dec.sync.aligned.u32 %0;" :: "n"(512 - 2 * REG_F - REG_H));
    c.lane = lane_id();
    {
      uint32_t tl = clock_lo() + (PACE0 + WO_AT * PACE);
      TR(-2, 0);
      sched_fence(i0 ^ i1);
      TR(-2, 7);
      int far1 = 0;
#pragma unroll 1
      for (int rep = EARLY; rep <= NPROBE; rep++) {
        const int lag = race_init(own + (rep & 1) * 4096, own + (~rep & 1) * 4096, SENT);
        if (rep) far1 += ((rep ^ c.r >> 5) & 1 ? 1 : -1) * min(lag, 200);
      }
      sts32(c.sb + SM_SEL + 512 + c.w * 4, (8 + far1 / (16 * NPROBE)) << 4 * c.w);
      TR(-2, 1);
      if (tid_now() == 256) TL2(14);
      __syncwarp();
      mbar_arrive_warp(BAR(B_PROBE));
      if (c.w == 0) {
        mbar_idle(BAR(B_PROBE), 0);
        const uint4 bits = lds128(c.sb + SM_SEL + 512);
        const uint32_t res = bits.x | bits.y | bits.z | bits.w;
        st_pub_if(c.mail + (uint32_t)((c.lane & 6) * (M_REG / 2) + M_SEL + (c.lane & 1) * 4096 + c.r * 4), res | tile_key(), c.lane < 8);
        const int q = (res >> 4 * ((c.lane + c.r) & 3) & 15) - 8, best = __reduce_max_sync(~0u, abs(q) * 64 + (c.lane & 3) * 16 + ((c.lane + c.r) & 3) * 2 + (q <= 0));
        const char* src = c.mail + (uint32_t)((best & 6) * (M_REG / 2) + M_SEL + (best & 1) * 4096 + c.lane * 16);
        if (SEL_AT) delay_until(tl - (PACE0 + WO_AT * PACE - SEL_AT));
        uint4 v; uint32_t n = 0;
        TR(-2, 4);
        while (true) {
          delay_cycles(DLY_SEL);
          TR(-2, 6);
          v = ld_poll(src);
          if (__all_sync(~0u, v.x && v.y && v.z && v.w)) break;
          watchdog(n, POLL_LIMIT);
        }
        TR(-2, 5);
        int ta = 0, tb = 0, pa = 0, pb = 0;
        uint32_t flip = 0;
#pragma unroll 1
        for (int i = 0; i < 4; i++) {
          const int a = (v.x >> 4 * i & 15) + (v.y >> 4 * i & 15) - 16, b = (v.z >> 4 * i & 15) + (v.w >> 4 * i & 15) - 16;
          const bool f = __reduce_add_sync(~0u, a * ta + b * tb) < 0;
          ta += f ? -a : a; tb += f ? -b : b; flip |= (uint32_t)f << i;
        }
#pragma unroll 1
        for (uint32_t g = 0; g < 8; g++) {
          const bool a = (v.x >> 16) - g * 256 < 120, b = (v.z >> 16) - g * 256 < 120;
          const int n = __reduce_add_sync(~0u, (a ? ta : 0) + (b ? tb : 0)) > 0 ? PRIOR : -PRIOR;
          if (a) pa = n;
          if (b) pb = n;
        }
        const uint32_t ka = AWARE && ta + pa > 0 ? ~flip : flip, kb = AWARE && tb + pb > 0 ? ~flip : flip;
        sts128(c.sb + SM_SEL + c.lane * 16, make_uint4(ka, ka, kb, kb));
        mbar_arrive_warp(BAR(B_SEL));
        const uint32_t key = __shfl_sync(~0u, c.a ? v.z : v.x, c.h);
        const int u = __popc(__ballot_sync(~0u, v.x < key)) + __popc(__ballot_sync(~0u, v.z < key));
        sts32(c.sb + SM_SEL + 528, (u & 32) * 2 + (u & 7) * 8 + (u >> 2 & 6) + c.b);
        TR(-2, 2);
        if (c.lane == 0) TL2(13);
        __syncwarp();
        bar_sync(14, 160);
        if (ZDLY) delay_cycles(ZDLY);
#pragma unroll 4
        for (int k = c.lane >> 3; k < (ZINIT ? 128 : 0); k += 4) {
          const int e = k & 7;
          const uint2 d = lds64(c.sb + SM_TAB + (e == 3 ? k - 1 : k) * 8);
          st_pub4(mk_ptr((d.x & ~127u) + (e < 2 ? (k & 8) * 32 : e == 3 ? 128 : 0) + (c.lane & 7) * 16, d.y), make_uint4(0, 0, 0, 0));
        }
        __syncwarp();
        if (c.lane < 4) asm volatile("mbarrier.arrive.shared::cta.b64 _, [%0];" :: "r"(BAR(B_PROBE)) : "memory");
        __syncwarp();
        TR(-2, 8);
      }
      if (c.w == 2) {
        mbar_idle(BAR(B_P1), 0);
        if (P1_AT) { mbar_idle(BAR(B_WFULL), 0); mbar_idle(BAR(B_WFULL + 1), 0); }
        st_pub_if(g_ctl + C_COLS + (c.r & 15) * 32 + c.lane, 0, c.r < (C_END - C_COLS) / 32);
        count_e(g_ctl + C_P1);
        TR(-2, 3);
      }
      if (c.w == 1) for (int i = 0; i < WO_N; i++) { delay_until(tl += WO_P * PACE); prefetch2d_e(&to, c.j * 256 + (i ^ WO_X) * 64, c.h * 128); }
      if (c.w == 3) {
        mbar_idle(BAR(B_WREAD0), 0);
        for (int i = 0; i < 2; i++) tma4d_e(c.sb + SM_WO + i * 16384, &tx, c.b * 8, 2 * (c.b ^ i), BAR(B_PFULL));
        mbar_expect_e(BAR(B_WOFULL), 65536);
#pragma unroll 1
        for (int i = 3; i >= 0; i--) {
          if (i & 1) mbar_idle(BAR(i < 2 ? B_XEMPTY : B_WREAD), 0);
          TMA_O(c.sb + SM_WO + i * 16384, &to, c.j * 256 + i * 64, c.h * 128, BAR(B_WOFULL));
        }
      }
    }
    asm volatile("barrier.cluster.wait;" ::: "memory");
    const int g = c.w, src0 = c.h * 4 + (g >> 1) * 2;
    mbar_wait(BAR(B_SEL), 0);
    c.sel = __shfl_sync(~0u, (e1_box(c, 0, src0 + (c.lane >> 5)) & 4096) | (e1_box(c, 1, src0) & 4096) * 2, 0);
    mbar_wait(BAR(B_WREAD), 0);
    uint32_t l16 = c.sb + g * 512 + c.lane * 16;
    auto lane = [&](uint32_t v) { l16 = dep(l16, v, c.sb); return (int)((l16 & 511) >> 4); };
    pad<PAD2>();
    for (int s = 0; s < NSEG; s++) {
      l16 = vary(l16, s, c.sb);
      int ln = (l16 & 511) >> 4;
      uint4 kf[4], qx;
      auto load_x = [&]() {
        if (X_AT >= 2 && g == X_W && s + 2 < XEND) {
          if (KL_AT != 2) mbar_wait(BAR(B_XEMPTY), ~s & 1);
          if (DLY_XL) delay_cycles(DLY_XL);
          mbar_expect_e(BAR(B_XFULL), 16384 * EXP_NXT);
          for (int i = 0; i < EXP_NXT; i++) tma4d_e(c.sb + SM_XT + i * 16384, &tx, c.b * 8, (s + 2) * 4 + 2 * (c.b ^ i), BAR(B_XFULL));
        }
      };
      {
        const int gs = min(s, XEND - 1);
        const char* pk = c.mail + (uint32_t)(M_KVQ + (gs & (NSLOT - 1)) * M_REG + c.h * 24576 + g * 2048 + ln * 16);
        const char* pq = pk + (16384 + c.j * 2048 - g * 1536);
        const uint32_t tg = (gs / NSLOT) & 1;
        touch(pk, c.sb); touch(pq, c.sb);
        TR(s, 0);
        mbar_wait(BAR(B_VFULL), s & 1);
        TR(s, 1);
        uint4 k[4];
        auto load_k = [&]() {
          if (Q_TMA && Q_AT == 0) qx = lds128(l16 + SM_Q);
          if (DLY_K) delay_cycles(DLY_K);
#pragma unroll
          for (int t = 0; t < 4; t++) k[t] = lds128(l16 + (g * 1536 + SM_K + t * 512));
          if (Q_TMA && Q_AT == 1) qx = lds128(l16 + SM_Q);
        };
        if (K_TMA && KL_AT == 1) load_k();
        if (Q_TMA && Q_AT == 2) qx = lds128(l16 + SM_Q);
        if (s > 0) mbar_wait(BAR(B_PUB), (s - 1) & 1);
        if (K_TMA) {
          if (!Q_TMA) qx = ld_poll(pq);
          if (KL_AT == 2) { mbar_spin_if(BAR(B_XEMPTY), ~s & 1, s + 1 < XEND); load_x(); }
          if (KL_AT != 1) load_k();
        }
        for (uint32_t n = 0; ; ) {
          if (!K_TMA) {
#pragma unroll
            for (int t = 0; t < 4; t++) k[t] = ld_poll(pk + t * 512);
            qx = ld_poll(pq);
          }
#pragma unroll
          for (int t = 0; t < 2; t++) {
            auto cp = [&](uint32_t v) { return dep(v, 0, c.sb); };
            kf[t] = make_uint4(cp(k[2 * t].x), cp(k[2 * t].y), cp(k[2 * t + 1].x), cp(k[2 * t + 1].y));
            kf[2 + t] = make_uint4(cp(k[2 * t].z), cp(k[2 * t].w), cp(k[2 * t + 1].z), cp(k[2 * t + 1].w));
          }
          if (all_clear(stale1(stale2(k[0].x, k[1].x, tg) | stale2(k[2].x, k[3].x, tg), qx.x, tg), EXP_CHK)) break;
          watchdog(n, POLL_LIMIT); CNT(4);
          if (K_TMA) {
#pragma unroll
            for (int t = 0; t < 4; t++) k[t] = ld_poll(pk + t * 512);
            qx = ld_poll(pq);
          }
        }
        TR(s, 2);
      }
      if (KL_AT != 2 && !LX_AT) load_x();
      ln = lane(kf[0].y);
      const char* pa = c.mail + (uint32_t)(box(s & 1, src0) + 8192 + (c.sel >> (s & 1) & 4096) + (g & 1) * 512 + (EXP_LIN ? ln * 16 : read_off(ln)));
      const uint32_t spw = c.sb + SM_SP + g * 1280 + (ln & 3) * 64 + ((((ln >> 3) ^ ln) & 2) << 4) + (ln & 4) * 4 + (ln & 8),
                     spr = c.sb + SM_SP + (ln & 4) * 80 + (ln >> 3) * 64 + (((ln & 3) ^ ((ln >> 3) & 2)) << 4), l8 = ln * 8;
      const uint32_t tg = s >> 1;
      float sx[2][4];
      uint32_t sm;
      uint4 km;
      auto causal = [&](uint32_t (&sc)[5], int l) {
        const int n = l >> 2, lim = 16 * (8 * c.j + (n & 4) + 2 * (n & 1) + ((n >> 1) & 1) - 2 * (l & 3) + 1);
#pragma unroll
        for (int w = 0; w < 4; w++) {
          uint32_t m; asm("shl.b32 %0, 0xffffffff, %1;" : "=r"(m) : "r"(max(lim - 128 * w, 0)));
          sc[1 + w] = (sc[1 + w] & ~m) | (0xD029D029u & m);
        }
      };
      auto put_rows = [&]() {
        if (s == 0) return;
        const int n = ln >> 2;
        *(uint4*)(g_ox + ox_at(s - 1, 8 * c.j + (n & 4) + 2 * (n & 1) + ((n >> 1) & 1), c.h * 4 + g, ln & 3)) = lds128((l16 ^ (ln & 24) * 2) + SM_OX);
        mbar_arrive_warp(BAR(B_PVDONE));
      };
      if (OX_AT == 1) put_rows();
      if (SXP) {
        scores_x<false>(sx, kf, qx, 0);
        if (DLY_SA) { sched_fence(dep(c.sb, __float_as_uint(sx[1][0]), c.sb)); delay_cycles(DLY_SA); }
        store_scores(sx, spw + (SM_K - SM_SP + g * 768));
        if (LX_AT == 1) load_x();
        if (OX_AT == 2) put_rows();
        if (DLY_SB) delay_cycles(DLY_SB);
        bar_sync(NB_ATT, 128);
        if (SXP >= 3) {
          const uint32_t t4 = (l16 - c.sb) >> 2, a = (t4 & 64) * 5 + ((t4 & 60) ^ (t4 >> 3 & 32)) + (t4 >> 1 & 192) + (c.sb + SM_K);
          const uint32_t t = add_bf16x2(add_bf16x2(add_bf16x2(lds32(a), lds32(a + 2048)), lds32(a + 4096)), lds32(a + 6144));
          const int lim = (int)((t4 >> 2 & 64) + (t4 >> 3 & 16) + (t4 >> 1 & 32) - (t4 * 2 & 96) - (t4 * 32 & 384)) + (128 * c.j + 16);
          uint32_t m; asm("shl.b32 %0, 0xffffffff, %1;" : "=r"(m) : "r"(max(lim, 0)));
          uint32_t y = (t & ~m) | (0xD029D029u & m);
          if (SXP == 4) {
            const float y0 = __uint_as_float(y << 16), y1 = __uint_as_float(y & 0xFFFF0000u);
            float mx = fmaxf(y0, y1);
            if (RDX) {
              int k = __float_as_int(mx); k ^= k >> 31 & 0x7FFFFFFF;
              const int k0 = __reduce_max_sync(~0u, t4 & 64 ? INT32_MIN : k), k1 = __reduce_max_sync(~0u, t4 & 64 ? k : INT32_MIN);
              k = t4 & 64 ? k1 : k0; mx = __int_as_float(k ^ (k >> 31 & 0x7FFFFFFF));
            } else {
#pragma unroll
              for (int d = 1; d < 16; d *= 2) mx = fmaxf(mx, __shfl_xor_sync(~0u, mx, d));
            }
            mx *= -SCL;
            y = pack_bf16(ex2(fmaf(y0, SCL, mx)), ex2(fmaf(y1, SCL, mx)));
            sts32((t4 >> 4 & 28) + (c.sb + SM_Q + 512), __float_as_uint(mx));
          }
          sts32(t4 + (c.sb + SM_Q), y);
        } else {
        const uint32_t ax = spr + (SM_K - SM_SP);
        uint4 t = add4(lds128(ax), lds128(ax + 2048));
        const uint32_t ay = SXP == 2 ? dep(ax, t.x, c.sb) : ax;
        t = add4(add4(t, lds128(ay + 4096)), lds128(ay + 6144));
        uint32_t sc[5] = {0, t.x, t.y, t.z, t.w};
        causal(sc, ln);
        sts128(l16 + SM_OX, make_uint4(sc[1], sc[2], sc[3], sc[4]));
        }
      }
      if (OX_AT == 3) { if (DLY_O) delay_cycles(DLY_O); put_rows(); }
      touch(pa, c.sb);
      mbar_wait(BAR(B_E1TRIG), s & 1);
      const uint32_t t0 = clock_lo();
      TRV(s, 3, t0);
      if (!SXP) {
        scores_x<false>(sx, kf, qx, 0);
        store_scores(sx, spw + 640);
      }
      if (DLY_E1) delay_fine(t0 + DLY_E1);
      uint32_t nr = 0;
      while (true) {
        const uint4 q0 = ld_poll(pa), q1 = ld_poll(pa + 2048), k0 = ld_poll(pa + 1024), k1 = ld_poll(pa + 3072);
        uint4 qm = add4(q0, q1);
        const uint32_t bq = stale2(q0.x, q1.x, tg);
        qm.x = dep(qm.x, bq, c.sb);
        scores_x<SC_F>(sx, kf, qm, c.sb);
        const uint32_t bk = stale2(k0.x, k1.x, tg);
        km = add4(k0, k1);
        km.x = dep(km.x, bk, c.sb);
        const bool ok = all_clear(bq | bk, 1);
        sm = scores_m(qm, km);
        store_scores(sx, spw);
        if (ok) break;
        nr++; CNT(2);
      }
      sts32(l8 + (c.sb + SM_SPM + (g >> 1) * 256 + (g & 1) * 4), sm);
      bar_sync(NB_ATT, 128);
      TR(s, 5); TRV(s, 13, nr);
      float o[2][4];
      uint32_t sp[5];
      uint4 vf[4];
      load_scores(sp, spr, l8 + (c.sb + SM_SPM));
      const uint32_t m5 = max5(sp);
      uint32_t m1;
      float off = row_off(m5, m1), f[10];
      l16 = dep(l16, VF_AT ? m1 : m5, c.sb);
#pragma unroll
      for (int t = 0; t < 4; t++) vf[(t >> 1) + 2 * (t & 1)] = lds128(l16 + SM_V + ((t >> 1) + 2 * (t & 1)) * 2048);
      qx.x = dep(qx.x, sp[0], c.sb);
      sts32(l8 + (c.sb + SM_SPM + 512 + (g >> 1) * 256 + (g & 1) * 4), scores_m(qx, km));
      mbar_arrive_warp(BAR(B_SC));
      unpack(f, sp);
      if (UP_F) sched_fence(c.sb);
      uint4 vm;
      if (VM_AT < 2) {
        bar_sync(NB_VM, 384);
        sp[1] = exp_pair(f, 1, off);
        const uint32_t av = dep(l8, VM_AT ? sp[1] : __float_as_uint(off), c.sb) + (c.sb + g * 512 + SM_VM);
        const uint2 vm0 = lds64(av), vm1 = lds64(av + 256);
        vm = make_uint4(vm0.x, vm0.y, vm1.x, vm1.y);
#pragma unroll
        for (int i = 2; i < 6; i++) sp[i % 5] = exp_pair(f, i % 5, off);
      } else {
#pragma unroll
        for (int i = 1; i < 6; i++) sp[i % 5] = exp_pair(f, i % 5, off);
        bar_sync(VM_AT == 2 ? dep(dep(0, sp[1] ^ sp[2], c.sb) + NB_VM, sp[0], c.sb) : dep(dep(0, sp[0] ^ sp[1] ^ sp[2], c.sb) + NB_VM, sp[3], c.sb), 384);
        const uint32_t av = l8 + (c.sb + g * 512 + SM_VM);
        const uint2 vm0 = lds64(av), vm1 = lds64(av + 256);
        vm = make_uint4(vm0.x, vm0.y, vm1.x, vm1.y);
      }
      uint2 u0, u1;
      uint4 sxx;
      auto load_sx = [&](uint32_t a8, int part = 3) {
        if (part & 1) { u0 = lds64(a8 + (c.sb + SM_SPM + 512)); u1 = lds64(a8 + (c.sb + SM_SPM + 768)); }
        if (part & 2) sxx = lds128(SXP >= 3 ? a8 * 2 + (c.sb + SM_Q) : l16 + SM_OX);
      };
      if (SXP && XL_AT && XL_AT < 4) load_sx(XL_AT == 2 ? dep(l8, vm.x, c.sb) : l8, XL_AT == 3 ? 1 : 3);
      float sum;
      auto rows_m = [&]() {
        const uint32_t tv = min(s, XEND - 1) / NSLOT;
        sum = pv(o, sp, vf, vm);
        stsm4<false>(l16 + SM_OM, pack_bf16(o[0][0], o[0][1]), pack_bf16(o[0][2], o[0][3]), pack_bf16(o[1][0], o[1][1]), pack_bf16(o[1][2], o[1][3]));
        sts32(c.sb + SM_SUM + ((l16 >> 4) & 28), __float_as_uint(sum));
        return arrive_if_clear(stale2(vf[0].x, vf[1].x, tv) | stale2(vf[2].x, vf[3].x, tv), EXP_CHK, NB_OM, 384);
      };
      const bool done = rows_m();
      if (SXP && XL_AT >= 3) load_sx(l8, XL_AT == 3 ? 2 : 3);
      if (!done) {
        const char* pv_ = c.mail + (uint32_t)(M_KVQ + (min(s, XEND - 1) & (NSLOT - 1)) * M_REG + c.h * 24576 + 8192 + (l16 - c.sb));
        uint32_t n = 0;
        do {
#pragma unroll
          for (int t = 0; t < 4; t++) vf[t] = ld_poll(pv_ + t * 2048);
          watchdog(n, POLL_LIMIT); CNT(5);
        } while (!rows_m());
        if (SXP && XL_AT) load_sx((l16 & 511) >> 1);
      }
      const uint32_t tom = clock_lo();
      TRV(s, 8, tom);
      if (XR_F) sched_fence(c.sb);
      ln = lane(tom);
      const int n = ln >> 2, jj = ln & 3, tq_ = 8 * c.j + (n & 4) + 2 * (n & 1) + ((n >> 1) & 1);
      if (DLY_X) delay_until(tom + DLY_X);
      if (SXP) {
        if (!XL_AT) load_sx(ln * 8);
        sp[0] = sum4(u0.x, u0.y, u1.x, u1.y); sp[1] = sxx.x; sp[2] = sxx.y; sp[3] = sxx.z; sp[4] = sxx.w;
      } else {
        load_scores(sp, spr + 640, c.sb + SM_SPM + 512 + ln * 8);
        causal(sp, ln);
      }
      mbar_arrive_warp(dep(dep(0, sp[0], c.sb), sp[1], c.sb) + BAR(B_SPFREE));
      float i0, i1;
      if (SXP == 4) {
        const float ox = __uint_as_float(lds32((ln & 28) + (c.sb + SM_Q + 512)));
        float sa[4] = {}, sb[4] = {}, om[2][4] = {};
#pragma unroll
        for (int t = 0; t < 2; t++) { o[t][0] = o[t][1] = o[t][2] = o[t][3] = 0.f; }
        off = row_off(sp[0], m1);
        mma_q(o[0], vf[0], sp[1], sp[2]); mma_q(o[1], vf[2], sp[1], sp[2]);
        mma16816(sa, sp[1], sp[2], sp[3], sp[4], ONES, ONES);
        mma_q(o[0], vf[1], sp[3], sp[4]); mma_q(o[1], vf[3], sp[3], sp[4]);
        off = fminf(off, ox);
        const uint32_t p0 = pack_bf16(ex2(fmaf(__uint_as_float(sp[0] << 16), SCL, off)), ex2(fmaf(__uint_as_float(sp[0] & 0xFFFF0000u), SCL, off)));
        float wx = ex2(off - ox);
        mma1688(sb, p0, ONES, ONES);
        mma1688(om[0], vm.x, vm.y, p0); mma1688(om[1], vm.z, vm.w, p0);
        if (DLY_Z) { sched_fence(dep(dep(c.sb, __float_as_uint(om[0][0]) ^ __float_as_uint(om[1][0]) ^ __float_as_uint(sb[0]), c.sb), __float_as_uint(o[0][0]) ^ __float_as_uint(o[1][0]) ^ __float_as_uint(sa[0]), c.sb)); delay_until(tom + DLY_Z); }
        const float j0 = __shfl_sync(~0u, wx, 8 * jj), j1 = __shfl_sync(~0u, wx, 8 * jj + 4);
        sum = fmaf(wx, sa[0] + sa[2], sb[0]);
#pragma unroll
        for (int i = 0; i < 8; i++) o[i >> 2][i & 3] = fmaf(o[i >> 2][i & 3], i & 1 ? j1 : j0, om[i >> 2][i & 3]);
      } else {
      off = row_off(max5(sp), m1);
      unpack(f, sp);
#pragma unroll
      for (int i = 1; i < 6; i++) sp[i % 5] = exp_pair(f, i % 5, off);
      if (DLY_Y) { sched_fence(dep(dep(c.sb, sp[0] ^ sp[1] ^ sp[2], c.sb), sp[3] ^ sp[4], c.sb)); delay_until(tom + DLY_Y); }
      sum = pv(o, sp, vf, vm);
      }
      TR(s, 7);
      sum = rcp(sum);
      i0 = __shfl_sync(~0u, sum, 8 * jj), i1 = __shfl_sync(~0u, sum, 8 * jj + 4);
      const uint32_t oxs = c.sb + SM_OX + g * 512;
      stsm4<true>(oxs + ((ln & 7) ^ (OX_L & l16 >> 9)) * 64 + (((ln >> 3) ^ ((ln >> 1) & 3)) << 4),
                  pack_bf16(o[0][0] * i0, o[0][1] * i1), pack_bf16(o[0][2] * i0, o[0][3] * i1), pack_bf16(o[1][0] * i0, o[1][1] * i1), pack_bf16(o[1][2] * i0, o[1][3] * i1));
      __syncwarp();
      if (OX_L) {
        const int r = l16 >> 7 & 7, hi = ln >> 2 & 1;
        bar_sync(5 + ((l16 - c.sb) >> 10), 64);
        *(uint4*)(g_ox + ox_at(s, 8 * c.j + (r & 4) + 2 * (r & 1) + ((r >> 1) & 1), c.h * 4 + g, (ln & 7) - (r & 4))) =
          lds128((l16 & ~1023u) + hi * 512 + (r ^ hi) * 64 + ((jj ^ (r >> 1)) << 4) + SM_OX);
        mbar_arrive_warp(BAR(B_PVDONE));
      } else if (!OX_AT) {
        *(uint4*)(g_ox + ox_at(s, tq_, c.h * 4 + g, jj)) = lds128(oxs + n * 64 + ((jj ^ (n >> 1)) << 4));
        mbar_arrive_warp(BAR(B_PVDONE));
      }
      TR(s, 9);
    }
    if (LASTM) {
      const int ln = tid_now() & 31, n = ln >> 2, jj = ln & 3, tq_ = 8 * c.j + (n & 4) + 2 * (n & 1) + ((n >> 1) & 1);
      store_count(g_ox + ox_at(NSEG - 1, tq_, c.h * 4 + g, jj), lds128(c.sb + SM_OX + g * 512 + (n ^ (OX_L & g)) * 64 + ((jj ^ (n >> 1)) << 4)), (char*)(g_ctl + C_LAST) + (LASTM == 2 ? c.r * 4 + g : 0));
    } else count_e(g_ctl + C_LAST);
    mbar_arrive_warp(BAR(B_DONE));
    if (tid_now() == 256) TL(8);
    __syncwarp();
    mbar_wait(BAR(B_E2TRIG), 1); mbar_idle(BAR(B_DONE), 0); mbar_wait(BAR(B_TW), 0);
    asm volatile("setmaxnreg.inc.sync.aligned.u32 128;");
  } else {
    {
      const int w = c.m * 4 + c.w;
      mbar_expect_e(BAR(B_ROWS), 4096 + 256);
      for (int i = 0; i < 2; i++) bulk_load_e(c.sb + SM_FFT + (1024 + w * ROW_BUF) * 8 + i * 2048, x + (size_t)(z_row(c.r * 8 + w) + i * 1024) * D_, 2048, BAR(B_ROWS));
      bulk_load_e(c.sb + SM_GW + w * 256, gw + w * 128, 256, BAR(B_ROWS));
    }
    asm volatile("setmaxnreg.inc.sync.aligned.u32 %0;" :: "n"(REG_F));
    c.lane = lane_id();
    uint32_t wa[16][4], wb[16][4], wv[16][4];
    TR(-2, 4);
    fft_rows_fwd((float2*)(smraw + SM_FFT), (const __nv_bfloat16*)(smraw + SM_GW), c.r, threadIdx.x, BAR(B_ROWS), BAR(B_FREE), [&](int e) { TR(-2, e); }, [&]() {
      mbar_spin(BAR(B_PFULL), 0);
#pragma unroll
      for (int k = 0; k < NP; k++) ldsm4t(wa[k], c.sb + SM_POOL + c.m * NP * 2048 + frag_off(c.w, c.lane) + k * 2048);
      bar_sync(NB_XCH, 256);
#pragma unroll
      for (int k = 0; k < NP; k++) sts128(c.sb + SM_POOL + c.m * 2048 + c.w * 512 + c.lane * 16 + k * 4096, make_uint4(wa[k][0], wa[k][1], wa[k][2], wa[k][3]));
    });
    mbar_arrive_warp(BAR(B_P1));
    TR(-2, 0);
    if (tid_now() == 0) TL2(1);
    __syncwarp();
    mbar_spin(BAR(B_WFULL + c.m), 0);
    TR(-2, 1);
    if ((tid_now() & 127) == 0) TL2(16);
    __syncwarp();
    {
      const uint32_t st = c.sb + c.m * ST_WG + frag_off(c.w, c.lane);
#pragma unroll
      for (int k = 0; k < 16; k++) ldsm4t(wb[k], st + k * 2048);
#pragma unroll
      for (int k = NP; k < 16; k++) ldsm4t(wa[k], st + (16 + k - NP) * 2048);
#pragma unroll
      for (int k = 0; k < NV; k++) ldsm4t(wv[k], st + (32 - NP + k) * 2048);
      mbar_arrive_warp(BAR(B_WREAD));
      if (c.m == 0) mbar_arrive_warp(BAR(B_WREAD0));
#pragma unroll
      for (int k = 0; k < (LP_IN == 2 ? 0 : NP); k++) lds_frag(wa[k], c.sb + SM_POOL + c.m * 2048 + c.w * 512 + c.lane * 16 + k * 4096);
      TR(-2, 2);
    }
    TR(-2, 3);
    if (tid_now() == 0) TL2(12);
    __syncwarp();
    asm volatile("barrier.cluster.wait;" ::: "memory");
    uint32_t t16 = c.m * 2048 + c.w * 512 + c.lane * 16;
    uint32_t pk = (c.m * NHV * 2048 + frag_off(c.w, c.lane)) | (tile_off(2 * (c.w & 1), c.lane) << 16) | ((c.lane & 12) ? 0u : 0x80000000u);
    const uint32_t dx1 = desc_lo(c.sb + SM_XT + c.m * 4096), dh = desc_lo(c.sb + SM_HV + c.m * NHV * 2048);
    mbar_spin(BAR(B_PFULL), 1);
    pad<PAD0>();
    for (int s = -2; ; s++) {
      t16 = vary(t16, s, c.sb); pk = vary(pk, s, c.sb);
      const uint32_t dx = dx1 - (s == -2 ? (SM_XT - SM_WO) / 16 : 0);
      auto ldp = [&](int k0, int k1, int d, int back = 0) {
#pragma unroll
        for (int k = k0; k < k1; k++) lds_frag(wa[k], (k < k0 + d - back ? t16 : dep(t16, wa[k < d ? 0 : k - d][0], c.sb)) + (c.sb + SM_POOL + k * 4096));
      };
      if (s >= 0) {
        uint32_t af[16][4], bf[4][4], wo;
        const uint32_t tab = ((t16 >> 3) & 0x1C0) + (c.sb + SM_TAB + (s & 1) * 512);
        const char* pa;
        mem_proj(wa, wb, wv, af, wo, pa, tab, t16, pk, c, s);
        const uint32_t t0 = clock_lo();
        t16 = dep(t16, t0, c.sb);
        auto ldwo = [&](int f) { ldsm4t(af[f], (f < WO_D ? wo : dep(wo, af[f < WO_D ? 0 : f - WO_D][0], c.sb)) + (c.sb + SM_WO + (f & 1) * 32768 + (f >> 1) * 2048)); };
        {
          const uint32_t tg = s >> 1, vm = t16 >> 1, chk = (~t16 >> 4) & 1;
          if (WO_S && s == 0) {
            mbar_spin(BAR(B_WOFULL), 0);
#pragma unroll
            for (int f = 0; f < WO_0; f++) ldwo(f);
          }
#pragma unroll
          for (int f = WO_0; f < WO_1; f++) ldwo(f);
          if (DLY_V) delay_fine(t0 + DLY_V); else sched_fence(c.sb);
          uint2 v0 = ld_poll2(pa), v1 = ld_poll2(pa + 1024), v2 = ld_poll2(pa + 2048), v3 = ld_poll2(pa + 3072);
          TR(s, 3);
#pragma unroll
          for (int f = WO_1; f < 16 - WO_L; f++) ldwo(f);
          TR(s, 4);
          uint32_t n = 0;
          while (true) {
            sts64(vm + (c.sb + SM_VM), sum4(v0.x, v1.x, v2.x, v3.x), sum4(v0.y, v1.y, v2.y, v3.y));
            if (arrive_if_clear(stale1(stale1(stale2(v0.x, v1.x, tg), v2.x, tg), v3.x, tg), chk, NB_VM, 384)) break;
            v0 = ld_poll2(pa); v1 = ld_poll2(pa + 1024); v2 = ld_poll2(pa + 2048); v3 = ld_poll2(pa + 3072);
            n++; CNT(3);
          }
          TR(s, 12); TRV(s, 15, n);
        }
        const uint32_t ob = dep(dep(t16 & 511, af[14 - WO_L][0], c.sb), af[15 - WO_L][0], c.sb);
        uint32_t l4 = ob >> 2;
        const uint32_t bit = (t16 & 48) ? 0u : 1u;
        if (LF_AT) mbar_spin2_if(BAR(B_XFULL), BAR(B_LFREE), s & 1, s + 2 < XEND); else mbar_spin_if(BAR(B_XFULL), s & 1, s + 2 < XEND);
        bar_sync(NB_OM, 384);
        TR(s, 5);
#pragma unroll
        for (int i = 0; i < 4; i++) ldsm4t(bf[i], ob + (c.sb + SM_OM + i * 512));
        uint2 sum = lds64(((t16 >> 1) & 24) + (c.sb + SM_SUM));
        if (OM_F) sched_fence(c.sb);
        float d[WO_C][4] = {};
        uint4 d0, d1;
#pragma unroll
        for (int f = 0; f < 16; f++) {
          mma_a(d[f % WO_C], af[f], bf[f >> 2][f & 2], bf[f >> 2][(f & 2) + 1]);
          if (f >= WO_C && f < WO_C + WO_L) {
            const int l = 16 - WO_L + f - WO_C;
            ldsm4t(af[l], (WO_LD ? dep(wo, __float_as_uint(d[(f + 1) % WO_C][0]), c.sb) : wo) + (c.sb + SM_WO + (l & 1) * 32768 + (l >> 1) * 2048));
          }
          if (f == WO_T) {
            const uint32_t tb2 = dep((t16 >> 3) & 0x1C0, __float_as_uint(d[f % WO_C][0]), c.sb) + (c.sb + SM_TAB + (s & 1) * 512);
            d0 = lds128(tb2 + 32); d1 = lds128(tb2 + 48);
          }
          if (f >= PL_WA && f < PL_WA + PL_W) lds_frag(wa[f - PL_WA], (PL_WD ? dep(t16, __float_as_uint(d[(f + PL_WD) % WO_C][0]), c.sb) : t16) + (c.sb + SM_POOL + (f - PL_WA) * 4096));
          if (PL_W && PL_WF == 1 && f == PL_WA + PL_W - 1) sched_fence(c.sb);
          if (f == 4) { sum.x = dep(sum.x, __float_as_uint(d[0][0]), c.sb); sum.y = dep(sum.y, __float_as_uint(d[0][0]), c.sb); }
        }
        if (PL_W && !PL_WF) {
          uint32_t all = 0;
#pragma unroll
          for (int k = 0; k < PL_W; k++) all ^= wa[k][0];
          l4 = dep(l4, all, c.sb);
        }
        char* dst[4] = {mk_ptr(d0.x | l4, d0.y), mk_ptr(d0.z | l4, d0.w), mk_ptr(d1.x | l4, d1.y), mk_ptr(d1.z | l4, d1.w)};
        const float i0 = rcp(__uint_as_float(sum.x)), i1 = rcp(__uint_as_float(sum.y));
#pragma unroll
        for (int i = 0; i < 4; i++) {
          const int t = i >> 1, e = 2 * (i & 1);
          const float y0 = WO_C == 2 ? d[t][e] : d[t][e] + d[(t + 2) % WO_C][e], y1 = WO_C == 2 ? d[t][e + 1] : d[t][e + 1] + d[(t + 2) % WO_C][e + 1];
          st_pub(dst[i], put_tag(pack_bf16(y0 * i0, y1 * i1), bit, s >> 1));
        }
        if (ANCH2) sts32(c.sb + SM_SUM + 64, clock_lo());
        mbar_arrive_warp(BAR(B_E2TRIG));
        TR(s, 6);
        sched_fence(c.sb);
        if (W_E2 == 2) mbar_spin(BAR(B_E2TRIG), s & 1);
#pragma unroll
        for (int k = PL_A; k < PL_0; k++)
#pragma unroll
          for (int i = 0; i < 4; i++) wa[k][i] = af[16 - PL_0 + k][i];
      }
      if (__builtin_expect(s + 2 < XEND, 1)) {
        const uint32_t tg0 = DLY_P ? clock_lo() + DLY_P : 0;
        if (LP_IN) ldp(PL_W, PL_A, PL_D);
        if (PL_A < PL_0 && c.m != ASY) ldp(PL_A, PL_0, PL_D, PL_A > PL_W ? PL_D : 0);
        auto late = [&](int at) {
          if (PL_A < PL_B && ASY_A == at && c.m == ASY) ldp(PL_A, PL_B, PL_DA);
          if (PL_B < PL_0 && ASY_AT == at && c.m == ASY) ldp(PL_B, PL_0, PL_DA);
        };
        float xa[16];
        uint32_t q[4];
        if (W_E2 == 1 && s >= 0) mbar_spin(BAR(B_E2TRIG), s & 1);
        TR(s, 7);
        constexpr int S1 = ORDER ? 0 : 2, S2 = ORDER == 0 ? 0 : ORDER == 1 ? 2 : 1, S3 = ORDER == 2 ? 2 : 1;
        if (ORDER) issue_qk<0, 16>(xa, wb, vary(dx, s, c.sb)); else issue_v(xa, wv, vary(dx, s, c.sb), vary(dh, s, c.sb));
        if (DLY_P) delay_until(tg0); else if (IS_F) sched_fence(c.sb);
        ldp(PL_0, PL_1, PL_D1);
        const uint32_t land = (t16 ^ ((t16 >> 3) & 0x60)) + vary(c.sb + SM_LAND + c.b * 4096, s, c.sb);
        TR(s, 14);
        if (LF_AT == 1) mbar_spin_if(BAR(B_LFREE), s & 1, s < 0); else if (!LF_AT) mbar_spin(BAR(B_LFREE), s & 1);
        TR(s, 15);
        late(0);
        WG_WAIT(0);
        TR(s, 8);
        park_own<S1 == 2>(q, xa, land, S1, c.sb);
        late(1);
        if (W_PUB == 4 && s >= 0) mbar_spin(BAR(B_PUB), s & 1);
        if (ORDER == 1) issue_v(xa, wv, vary(dx, s, c.sb + 32), vary(dh, s, c.sb)); else issue_qk<0, 16>(xa, ORDER ? wa : wb, vary(dx, s, c.sb + 32));
        if (IS_F) sched_fence(c.sb);
        ldp(PL_1, PL_2, PL_D1);
        if (W_PUB == 1) mbar_spin_if(BAR(B_PUB), s & 1, s >= 0);
        uint32_t tp = clock_lo(), q1[4] = {q[0], q[1], q[2], q[3]};
        if (PL_2B) ldp(PL_2, NP - PL_L, PL_D1);
        late(2);
        if (W_PUB != 3) park_peer(q, land, S1, c);
        if (!PL_2B) ldp(PL_2, NP - PL_L, PL_D1);
        late(3);
        TR(s, 13);
        WG_WAIT(0);
        TR(s, 9);
        park_own<S2 == 2>(q, xa, land, S2, c.sb);
        late(4);
        if (ORDER == 2) issue_v(xa, wv, vary(dx, s, c.sb + 64), vary(dh, s, c.sb));
        else {
          issue_qk<0, PL_L ? NP - PL_L : 16>(xa, wa, vary(dx, s, c.sb + 64));
          ldp(NP - PL_L, NP, PL_E);
          if (PL_L) issue_qk<NP - PL_L, 16>(xa, wa, vary(dx, s, c.sb + 64));
        }
        if ((W_PUB == 2 || W_PUB == 3) && s >= 0) { mbar_spin(BAR(B_PUB), s & 1); tp = clock_lo(); }
        if (W_PUB == 3) park_peer(q1, land, S1, c);
        if (DLY_S && s >= 0) delay_until(tp + DLY_S);
        park_peer(q, land, S2, c);
        WG_WAIT(0);
        TR(s, 10);
        mbar_arrive_warp(BAR(B_XEMPTY));
        park_own<S3 == 2>(q, xa, land, S3, c.sb);
        park_peer(q, land, S3, c);
        TR(s, 11);
      } else {
        if (s == NSEG - 1) break;
        if (EARLY2 && (XEND == NSEG || s == NSEG - 2) && c.m * 4 + c.w == 0) count_e(g_ctl + C_EARLY);
        ldp(PL_W, NP, 2);
      }
    }
    asm volatile("setmaxnreg.dec.sync.aligned.u32 %0;" :: "n"(BPRE == 2 ? 176 : 128));
    const int tid = tid_now(), lane = tid & 31, tile = tile_of(c), m0 = (tile >> 3) * 128, n0 = (tile & 7) * 128;
    float acc[64];
#pragma unroll
    for (int i = 0; i < 64; i++) acc[i] = 0.f;
    const uint32_t rel = mapa(BAR(B_GEMPTY), lane & 1), la = desc_lo(c.sb + c.m * 8192), lb = ((c.sb + 16384) & 0x3FFFF) >> 4 | (8192 >> 4) << 16;
    bool relon = false;
    const int skew = tile < 120 ? 0 : SKEW, kend = 64 + skew - c.m * skew, hold = c.m * (65 - LEAD) - 1;
    const float g0 = __ldcg(g_gate + m0 + (tid >> 5) * 16 + (lane >> 2)), g1 = __ldcg(g_gate + m0 + (tid >> 5) * 16 + (lane >> 2) + 8);
    uint32_t o = SM_XT, st = 0, ph = 0, prev = 0;
    if (tid == 0) TL(9);
    __syncwarp();
    GT(0);
#pragma unroll 1
    for (int kb = -c.m * skew; kb < max(kend - 4, 64); kb++, o = next_stage(o)) {
      if (LEAD && kb == hold) bar_sync(15, 256);
      mbar_lim(BAR(B_GFULL + st), ph);
      if ((uint32_t)kb < 64) {
        WG_FENCE();
#pragma unroll
        for (int k = 0; k < 4; k++) wgmma_ss_n128_tb(acc, desc128(la + (o >> 4) + k * 2), desc128(lb + (o >> 4) + k * 128));
        WG_COMMIT();
        WG_WAIT(1);
      } else WG_WAIT(0);
      arrive_remote_if(rel + 8 * prev, relon && kb < kend - 4);
      relon = (tid & 127) < 2;
      prev = st;
      if (++st == 5) { st = 0; ph ^= 1; }
    }
    if (LEAD && c.m == 0) asm volatile("bar.arrive 15, 256;" ::: "memory");
    const uint32_t row = (tid >> 5) * 2048 + (lane & 15) * 128 + (((lane >> 4) ^ (lane & 7)) << 4);
    if (!BPRE) WG_WAIT(0);
    mbar_lim(BAR(B_BT), 0);
    uint32_t b[2][4][4];
    const uint32_t rb = (tid >> 5) * 2048 + (lane >> 2) * 128 + (((lane & 7) ^ (lane >> 2)) << 4);
#pragma unroll
    for (int i = 0; i < 8; i++) lds_frag(b[i & 1][i >> 1], (rb ^ (i & 2) * 32) + (c.sb + SM_BT + (i >> 2) * 16384 + (i & 1) * 1024));
    float bl[2][4][4], bh[2][4][4];
    if (BPRE == 2) {
#pragma unroll
      for (int i = 0; i < 32; i++) {
        asm volatile("shl.b32 %0, %1, 16;" : "=f"(bl[i >> 4][i >> 2 & 3][i & 3]) : "r"(b[i >> 4][i >> 2 & 3][i & 3]));
        asm volatile("and.b32 %0, %1, 0xffff0000;" : "=f"(bh[i >> 4][i >> 2 & 3][i & 3]) : "r"(b[i >> 4][i >> 2 & 3][i & 3]));
      }
    }
    if (BPRE) { sched_fence(c.sb); WG_WAIT(0); sched_fence(c.sb); }
#pragma unroll
    for (int i = 0; i < 64; i++) asm volatile("" : "+f"(acc[i]) :: "memory");
    GT(17);
    if (tid == 0) TL(4);
    __syncwarp();
#pragma unroll
    for (int hf = 0; hf < 2; hf++) {
#pragma unroll
      for (int t = 0; t < 4; t++) {
        uint32_t y[4];
#pragma unroll
        for (int i = 0; i < 4; i++) {
          const float* a = acc + 32 * hf + 8 * t + 2 * i, g = i & 1 ? g1 : g0;
          const uint32_t* q = b[i & 1][2 * (t & 1) + (i >> 1)] + hf;
          const float* f = (t & 2 ? bh : bl)[i & 1][2 * (t & 1) + (i >> 1)] + hf;
          if (BPRE == 2) y[i] = pack_bf16(fmaf(g, a[0], f[0]), fmaf(g, a[1], f[2])); else
          y[i] = pack_bf16(fmaf(g, a[0], __uint_as_float(t & 2 ? q[0] & 0xFFFF0000u : q[0] << 16)), fmaf(g, a[1], __uint_as_float(t & 2 ? q[2] & 0xFFFF0000u : q[2] << 16)));
        }
        stsm4<false>((row ^ t * 32) + (c.sb + SM_BT + hf * 16384), y[0], y[1], y[2], y[3]);
      }
      if (EP_F && !hf) { sched_fence(c.sb); for (int i = 32; i < 64; i++) asm volatile("" : "+f"(acc[i]) :: "memory"); }
      FENCE_ASYNC_SMEM();
      __syncwarp();
      tma2d_out_e(&tout, n0 + hf * 64, m0 + (c.m * 4 + c.w) * 16, c.sb + SM_BT + hf * 16384 + (c.m * 4 + c.w) * 2048);
    }
    asm volatile("cp.async.bulk.commit_group; cp.async.bulk.wait_group" WAITRD " 0;" ::: "memory");
    GT(18);
    if ((tid & 127) == 0) TL(11);
    return;
  }
  constexpr int NH = NQ < 106 ? 4 * (106 - NQ) : 0;
  const bool col = c.r >= 128;
  const int tile = col ? 0 : tile_of(c);
  const int q0 = col ? 256 - NQ + (c.r - 128) + c.m * 4 : tile < 120 ? tile : 256, u = (tile >> 1 & 32) | (tile >> 3 & 7) | (tile & 6) << 2, e = QSH == 2 ? 2 * (u - (u > 39) - (u > 47) - (NQ < 110 && u > 55)) + c.b : tile,
            dq = col ? 16 : QSH ? 120 + (e < NH ? e >> 1 : (e + NH) >> 2) - tile : 120, qe = col ? 256 : 256 - NQ,
            qw = col || !QSH || (e < NH ? c.w >> 1 == c.b : c.w == ((e + NH) & 3)) ? qe : 120;
  const uint32_t zs = c.sb + (col ? COL_Z + c.m * 32768 : SM_BT), zb = BAR(B_Z + c.m);
  auto load_z = [&](int q) { if (c.w == 0 && q < qe) { mbar_expect_e(zb, 32768); tma2d_o<(ONCE & 4) != 0>(zs, &tz, q * 64, 0, zb); } };
  asm volatile("fence.proxy.async.global;" ::: "memory");
  load_z(q0);
  uint32_t ph = 0;
#pragma unroll 1
  for (int q = q0; q < qe; q += dq, ph ^= 1) {
    mbar_lim(zb, ph);
    const int p = q * 4 + c.w;
    if (EXP_INV && q < qw) fft_rows_inv(zs, (float2*)(smraw + (col ? 8192 + c.m * INV_BUF * 32 : SM_MEM)) + c.w * INV_BUF, (const float2*)(smraw + (col ? 0 : SM_TW)), p, tid_now() & 31, g_b,
                              [&]() { bar_sync(5 + c.m, 128); load_z(q + dq); });
    else { bar_sync(5 + c.m, 128); load_z(q + dq); }
  }
  if (B_ST) asm volatile("cp.async.bulk.wait_group 0; fence.proxy.async.global;" ::: "memory");
  asm volatile("fence.acq_rel.gpu;" ::: "memory");
  __syncwarp();
  { const int q = q0 + (tid_now() & 31) * dq; if (q < qw) asm volatile("red.relaxed.gpu.global.add.u32 [%0], 1;" :: "l"(g_ctl + C_ROWS + (q >> 5) * 32) : "memory"); }
  if (tid_now() == 256) { if (col) TL(27); else TL(3); }
  __syncwarp();
  if (!col && c.w == 0) {
    await_count<AW_NS>(g_ctl + C_ROWS + ((tile >> 3) & 7) * 32, 128);
    mbar_expect_e(BAR(B_BT), 32768);
    for (int i = 0; i < 2; i++) tma2d_o<(ONCE & 8) != 0>(c.sb + SM_BT + i * 16384, &tb, (tile & 7) * 128 + i * 64, (tile >> 3) * 128, BAR(B_BT));
    if (tid_now() == 256) TL(5);
  }
}

typedef CUresult (*EncodeFn)(CUtensorMap*, CUtensorMapDataType, cuuint32_t, void*, const cuuint64_t*, const cuuint64_t*,
                             const cuuint32_t*, const cuuint32_t*, CUtensorMapInterleave, CUtensorMapSwizzle,
                             CUtensorMapL2promotion, CUtensorMapFloatOOBfill);

void make_map(EncodeFn enc, CUtensorMap* tm, const void* p, int rank, const cuuint64_t* dims, const cuuint64_t* strides, const cuuint32_t* box, bool swz = true) {
  const cuuint32_t es[4] = {1, 1, 1, 1};
  enc(tm, CU_TENSOR_MAP_DATA_TYPE_BFLOAT16, rank, (void*)p, dims, strides, box, es, CU_TENSOR_MAP_INTERLEAVE_NONE,
      swz ? CU_TENSOR_MAP_SWIZZLE_128B : CU_TENSOR_MAP_SWIZZLE_NONE, swz ? CU_TENSOR_MAP_L2_PROMOTION_L2_128B : W_PROMO, CU_TENSOR_MAP_FLOAT_OOB_FILL_NONE);
}
void make_map2(EncodeFn enc, CUtensorMap* tm, const void* p, uint64_t cols, uint64_t rows, uint32_t boxrows) {
  const cuuint64_t dims[2] = {cols, rows}, strides[1] = {cols * 2};
  const cuuint32_t box[2] = {64, boxrows};
  make_map(enc, tm, p, 2, dims, strides, box);
}

}

extern "C" void kernel_launch(void* const* d_in, const int* in_sizes, int n_in, void* d_out, int out_size) {
  (void)in_sizes; (void)n_in; (void)out_size;
  const __nv_bfloat16* x = (const __nv_bfloat16*)d_in[0];
  const __nv_bfloat16* mem0 = (const __nv_bfloat16*)d_in[1];
  const __nv_bfloat16* gw = (const __nv_bfloat16*)d_in[10];

  EncodeFn enc = nullptr;
  cudaDriverEntryPointQueryResult qr;
  cudaGetDriverEntryPoint("cuTensorMapEncodeTiled", (void**)&enc, cudaEnableDefault, &qr);
  void *p_ox, *p_b, *p_z, *p_mail;
  cudaGetSymbolAddress(&p_ox, g_ox); cudaGetSymbolAddress(&p_b, g_b); cudaGetSymbolAddress(&p_z, g_z); cudaGetSymbolAddress(&p_mail, g_mail);
  CUtensorMap tq, tk, tv, tv16, to, tx, twr, twi, ta, tw, tb, tout, tz, tzs, ta32;
  make_map2(enc, &tq, d_in[2], 4096, 1024, 64);
  make_map2(enc, &tk, d_in[3], 4096, 1024, 64);
  make_map2(enc, &tv, d_in[4], 4096, 1024, 64);
  make_map2(enc, &tv16, d_in[4], 4096, 1024, 16);
  make_map2(enc, &to, d_in[5], 1024, 4096, 128);
  make_map2(enc, &tw, d_in[5], 1024, 4096, 64);
  {
    const cuuint64_t dims[3] = {64, 2048, 64}, strides[2] = {128, 262144};
    const cuuint32_t box[3] = {64, 32, 2}, box1[3] = {64, 32, 1};
    make_map(enc, &ta, p_ox, 3, dims, strides, box);
    make_map(enc, &ta32, p_ox, 3, dims, strides, box1);
  }
  make_map2(enc, &tb, p_b, 1024, 2048, 128);
  make_map2(enc, &tout, d_out, 1024, 2048, 16);
  make_map2(enc, &tz, p_z, 16384, 257, 256);
  {
    const cuuint64_t dims[4] = {64, 8, 16, 256}, strides[3] = {2048, 128, 16384};
    const cuuint32_t box[4] = {64, 8, 8, 2};
    make_map(enc, &tx, x, 4, dims, strides, box);
  }
  {
    const cuuint64_t dims[2] = {512, 257 * 32}, strides[1] = {1024};
    const cuuint32_t box[2] = {128, 16};
    make_map(enc, &tzs, p_z, 2, dims, strides, box, false);
  }
  {
    const cuuint64_t dims[2] = {8 * 513, 256}, strides[1] = {8 * 513 * 2};
    const cuuint32_t box[2] = {8, 256};
    make_map(enc, &twr, d_in[8], 2, dims, strides, box, false);
    make_map(enc, &twi, d_in[9], 2, dims, strides, box, false);
  }
  cudaFuncSetAttribute(chain_kernel, cudaFuncAttributeMaxDynamicSharedMemorySize, CHAIN_SMEM);

  cudaStream_t st = cudaStreamPerThread;
  char* mail = (char*)(((uintptr_t)p_mail + M_REG - 1) & ~(uintptr_t)(M_REG - 1));
  chain_kernel<<<132, 512, CHAIN_SMEM, st>>>(tq, tk, tv, tv16, to, tx, twr, twi, ta, tw, tb, tout, tz, tzs, ta32, mem0, mail, x, gw);
}
```

```cpp
#include <cuda_runtime.h>
#include <cuda_bf16.h>
#include <cuda.h>
#include <stdint.h>

#define DLY_E1 220
#define DLY_V 330
#define DLY_E2 300
#define DLY_E3 440
#define DLY_X 0
#define DLY_S 100
#define DLY_F 150
#define VM_AT 0
#define OM_F 1
#define C1_AT 5
#define NLAG 2
#define WO_D 2
#define WO_0 3
#define WO_1 11
#define PL_0 10
#define PL_1 11
#define PL_D 2
#define PL_L 0
#define HV_D 4
#define DLY_FK 0
#define REG_F 216
#define REG_H 24
#define SC_F 1
#define E2_F 0
#define X_AT 2
#define PL_2 11
#define PL_E 2
#define ORDER 1
#define SSPOS 1
#define W_PUB 1
#define FIN_AT 5
#define AWARE 1
#define NPROBE 2
#define NP_ 12
#define DLY_GRP 1000
#define EXP_CHK 1
#define EXP_NXT 2
#define EXP_PEER 1
#define EXP_FIN 7
#define EXP_NWG 16
#define ANCH2 1
#define IS_F 1
#define PL_D1 1
#define W_E2 0
#define V_TMA 2
#define V_W 3
#define RED_L 3
#define RED_T 1
#define RED_P 1
#define DLY_E3B 100
#define HV_E 2
#define HV_R 6
#define HOLD 0
#define PACE 500
#define PACE0 0
#define EXP_ST 7
#define WO_AT 38
#define WO_P 2
#define DLY_SEL 300
#define P1_AT 0
#define TMA_W tma2d_once
#define TMA_O tma2d_once
#define PACE_Z 580
#define EXP_INV 1
#define VF_AT 0
#define UP_F 0
#define WO_L (12 - NP_)
#define WO_C 4
#define WO_T 3
#define WO_LD 0
#define EXP_LIN 0
#define PL_W 5
#define PL_WA 10
#define PL_WD 0
#define PL_WF 2
#define EXP_FL 0
#define DLY_FS 0
#define DLY_F2 40
#define PF_D 4
#define PF_A 0
#define PF_B 0
#define SIDE 1
#define ROLE 1
#define E1OFF 1
#define EPI 0
#define WAITRD ".read"
#define START 1000
#define WUNR 1
#define WO_N 0
#define PL_2B 1
#define DLY_P 0
#define LP_IN 1
#define LF_AT 1
#define FINE 0
#define E30 1
#define WO_S 1
#define POOL_AT 12
#define COL_DLY 0
#define PAD0 2
#define PAD2 6
#define PAD3 6
#define WO_X 0
#define PRIOR 12
#define EARLY 1
#define SEL_AT 3000
#define FUNR 0
#define ZINIT 1
#define ZDLY 0
#define NQ 84
#define GATE 0
#define LASTM 1
#define X_ONCE 1
#define ONCE 31
#define Z_PF 0
#define EXP_W 1
#define W_PROMO CU_TENSOR_MAP_L2_PROMOTION_L2_128B
#define Z_ST 1
#define W_FINE 0
#define X128 2
#define T128_ 1
#define W_AT 0
#define SKEW 7
#define AW_NS 0
#define QSH 2
#define EARLY2 1
#define LEAD 3
#define BPRE 2
#define EP_F 1
#define TQ_AT 0
#define LAG_0 4
#define LAG_G 0
#define LAG_S 0
#define O_AT 0
#define XB 1
#define V_E 3
#define LAG_T 0
#define E3M 0
#define B_ST 1
#define TW_L 1
#define K_TMA 1
#define KL_AT 0
#define DLY_K 350
#define Q_TMA 0
#define Q_AT 2
#define IDLE 1
#define PL_AN 4
#define PL_A (PL_0 - PL_AN < PL_W ? PL_W : PL_0 - PL_AN)
#define ASY 1
#define ASY_AT 2
#define DLY_XL 0
#define SXP 3
#define DLY_SA 0
#define DLY_SB 0
#define XL_AT 1
#define DLY_Y 0
#define LX_AT 1
#define X_W 1
#define PL_BN 2
#define PL_B (PL_A + PL_BN > PL_0 ? PL_0 : PL_A + PL_BN)
#define ASY_A 0
#define PL_DA 3
#define XR_F 0
#define RDX 1
#define DLY_Z 0
#define DLY_O 0
#define OX_AT 0
#define OX_L 0
#define PRE_AT B_SC

namespace {
constexpr int wunr = WUNR;

constexpr int S_ = 2048, D_ = 1024, NSEG = 64;
constexpr uint32_t SENT = 0xFFFFFFFFu;
constexpr int NSLOT = 4;

constexpr uint32_t M_REG = 1 << 21, M_E3 = 64 * 16384, M_KVQ = M_E3 + 4 * 8192, M_SEL = M_KVQ + 32 * 24576;
__device__ __align__(1024) unsigned char g_mail[5 * M_REG];
constexpr int C_P1 = 0, C_COLS = C_P1 + 32, C_EARLY = C_COLS + 32, C_LAST = C_EARLY + 32, C_ROWS = C_LAST + 128, C_END = C_ROWS + 8 * 32;
__device__ __align__(1024) uint32_t g_ctl[C_END];
#define CLK(i)
#define TL(i)
#define TL2(i)
#define FT(i, v)
#define GT(i)
#define CNT(i)
__device__ __align__(1024) __nv_bfloat16 g_ox[S_ * 4096];
__device__ __align__(1024) float2 g_z[257 * 4096];
__device__ __align__(1024) __nv_bfloat16 g_b[S_ * D_];
__device__ float g_gate[S_];
__device__ __align__(1024) float2 g_tw[1024];

#define TRV(s, ev, val)
#define TR(s, ev)
#define TRSYNC(ev)
__device__ __forceinline__ uint32_t smem_u32(const void* p) { return (uint32_t)__cvta_generic_to_shared(p); }
__device__ __forceinline__ void watchdog(uint32_t& n, uint32_t limit) {
  asm volatile("{ .reg .pred p; add.u32 %0, %0, 1; setp.gt.u32 p, %0, %1; @p trap; }" : "+r"(n) : "r"(limit));
}
__device__ __forceinline__ void mbar_init(uint32_t bar, uint32_t cnt) {
  asm volatile("mbarrier.init.shared::cta.b64 [%0], %1;" :: "r"(bar), "r"(cnt) : "memory");
}
__device__ __forceinline__ void mbar_arrive_warp(uint32_t bar) {
  __syncwarp();
  asm volatile("{ .reg .pred p; elect.sync _|p, 0xffffffff; @p mbarrier.arrive.shared::cta.b64 _, [%0]; }" :: "r"(bar) : "memory");
}
__device__ __forceinline__ uint32_t clock_lo() {
  uint32_t r; asm volatile("{ .reg .u64 c; .reg .u32 h; mov.u64 c, %%clock64; mov.b64 {%0, h}, c; }" : "=r"(r) :: "memory"); return r;
}
__device__ __forceinline__ void delay_until(uint32_t t) {
  asm volatile("{ .reg .pred p; .reg .u64 c; .reg .u32 l, h;\n"
               "DLY: mov.u64 c, %%clock64; mov.b64 {l, h}, c; sub.s32 l, l, %0; setp.lt.s32 p, l, 0; @p bra.uni DLY; }" :: "r"(t) : "memory");
}
__device__ __forceinline__ void delay_fine(uint32_t t) {
  delay_until(t);
}
__device__ __forceinline__ void delay_cycles(uint32_t n) { delay_until(clock_lo() + n); }
__device__ __forceinline__ void sched_fence(uint32_t z) {
  asm volatile("{ .reg .pred p; setp.eq.u32 p, %0, 0x7fff0000; @p pmevent 1; }" :: "r"(z) : "memory");
}
__device__ __forceinline__ void pdl_wait() { asm volatile("griddepcontrol.wait;" ::: "memory"); }
__device__ __forceinline__ void pdl_launch() { asm volatile("griddepcontrol.launch_dependents;" ::: "memory"); }
__device__ __forceinline__ float ex2(float x) { float r; asm("ex2.approx.ftz.f32 %0, %1;" : "=f"(r) : "f"(x)); return r; }
__device__ __forceinline__ float rcp(float x) { float r; asm("rcp.approx.ftz.f32 %0, %1;" : "=f"(r) : "f"(x)); return r; }
__device__ __forceinline__ void mbar_expect(uint32_t bar, uint32_t bytes) {
  asm volatile("mbarrier.arrive.expect_tx.shared::cta.b64 _, [%0], %1;" :: "r"(bar), "r"(bytes) : "memory");
}
__device__ __forceinline__ bool mbar_try(uint32_t bar, uint32_t ph) {
  uint32_t ok;
  asm volatile("{ .reg .pred p; mbarrier.try_wait.parity.shared::cta.b64 p, [%1], %2; selp.u32 %0, 1, 0, p; }"
               : "=r"(ok) : "r"(bar), "r"(ph) : "memory");
  return ok;
}
__device__ __forceinline__ void mbar_wait(uint32_t bar, uint32_t ph) {
  uint32_t n = 0;
  while (!mbar_try(bar, ph)) { watchdog(n, (1u << 20)); }
}
__device__ __forceinline__ void mbar_spin(uint32_t bar, uint32_t ph) { while (!mbar_try(bar, ph)) {} }
__device__ __forceinline__ void mbar_idle(uint32_t bar, uint32_t ph) {
  if (!IDLE) { mbar_wait(bar, ph); return; }
  asm volatile("{ .reg .pred q; SPN: mbarrier.try_wait.parity.shared::cta.b64 q, [%0], %1; @!q bra.uni SPN; }" :: "r"(bar), "r"(ph) : "memory");
}
__device__ __forceinline__ void mbar_spin_if(uint32_t bar, uint32_t ph, bool on) {
  asm volatile("{ .reg .pred p, q; setp.ne.u32 p, %2, 0;\n"
               "SPN: setp.eq.u32 q, 0, 0; @p mbarrier.try_wait.parity.shared::cta.b64 q, [%0], %1; @!q bra.uni SPN; }" :: "r"(bar), "r"(ph), "r"((uint32_t)on) : "memory");
}
__device__ __forceinline__ void mbar_spin2_if(uint32_t bar, uint32_t bar2, uint32_t ph, bool on) {
  asm volatile("{ .reg .pred p, q, r; setp.ne.u32 p, %3, 0;\n"
               "SPN: setp.eq.u32 q, 0, 0; setp.eq.u32 r, 0, 0; @p mbarrier.try_wait.parity.shared::cta.b64 q, [%0], %2;\n"
               "@p mbarrier.try_wait.parity.shared::cta.b64 r, [%1], %2; and.pred q, q, r; @!q bra.uni SPN; }" :: "r"(bar), "r"(bar2), "r"(ph), "r"((uint32_t)on) : "memory");
}
__device__ __forceinline__ void mbar_spin_cluster(uint32_t bar, uint32_t ph) {
  uint32_t ok;
  do {
    asm volatile("{ .reg .pred p; mbarrier.try_wait.parity.acquire.cluster.shared::cta.b64 p, [%1], %2; selp.u32 %0, 1, 0, p; }"
                 : "=r"(ok) : "r"(bar), "r"(ph) : "memory");
  } while (!ok);
}
#define ONCE_H "mov.b64 h, 0x12F0000000000000; "
__device__ __forceinline__ void tma2d(uint32_t dst, const CUtensorMap* tm, int c0, int c1, uint32_t bar) {
  if (ONCE & 32) asm volatile("{ .reg .b64 h; " ONCE_H "cp.async.bulk.tensor.2d.shared::cluster.global.mbarrier::complete_tx::bytes.L2::cache_hint [%0], [%1, {%3, %4}], [%2], h; }"
               :: "r"(dst), "l"(tm), "r"(bar), "r"(c0), "r"(c1) : "memory");
  else asm volatile("cp.async.bulk.tensor.2d.shared::cluster.global.mbarrier::complete_tx::bytes [%0], [%1, {%3, %4}], [%2];"
               :: "r"(dst), "l"(tm), "r"(bar), "r"(c0), "r"(c1) : "memory");
}
__device__ __forceinline__ void mbar_expect_e(uint32_t bar, uint32_t bytes) {
  asm volatile("{ .reg .pred p; elect.sync _|p, 0xffffffff; @p mbarrier.arrive.expect_tx.shared::cta.b64 _, [%0], %1; }" :: "r"(bar), "r"(bytes) : "memory");
}
__device__ __forceinline__ void tma2d_e(uint32_t dst, const CUtensorMap* tm, int c0, int c1, uint32_t bar) {
  asm volatile("{ .reg .pred p; elect.sync _|p, 0xffffffff;\n"
               "@p cp.async.bulk.tensor.2d.shared::cluster.global.mbarrier::complete_tx::bytes [%0], [%1, {%3, %4}], [%2]; }"
               :: "r"(dst), "l"(tm), "r"(bar), "r"(c0), "r"(c1) : "memory");
}
__device__ __forceinline__ void tma2d_st_e(const CUtensorMap* tm, int c0, int c1, uint32_t src) {
  asm volatile("{ .reg .pred p; elect.sync _|p, 0xffffffff;\n"
               "@p cp.async.bulk.tensor.2d.global.shared::cta.bulk_group [%0, {%2, %3}], [%1]; }" :: "l"(tm), "r"(src), "r"(c0), "r"(c1) : "memory");
}
__device__ __forceinline__ void tma2d_out_e(const CUtensorMap* tm, int c0, int c1, uint32_t src) {
  if (EPI) asm volatile("{ .reg .pred p; elect.sync _|p, 0xffffffff;\n"
               "@p cp.reduce.async.bulk.tensor.2d.global.shared::cta.add.bulk_group [%0, {%2, %3}], [%1]; }" :: "l"(tm), "r"(src), "r"(c0), "r"(c1) : "memory");
  else if (ONCE & 16) asm volatile("{ .reg .pred p; .reg .b64 h; " ONCE_H "elect.sync _|p, 0xffffffff;\n"
               "@p cp.async.bulk.tensor.2d.global.shared::cta.bulk_group.L2::cache_hint [%0, {%2, %3}], [%1], h; }" :: "l"(tm), "r"(src), "r"(c0), "r"(c1) : "memory");
  else asm volatile("{ .reg .pred p; elect.sync _|p, 0xffffffff;\n"
               "@p cp.async.bulk.tensor.2d.global.shared::cta.bulk_group [%0, {%2, %3}], [%1]; }" :: "l"(tm), "r"(src), "r"(c0), "r"(c1) : "memory");
}
__device__ __forceinline__ void tma2d_once(uint32_t dst, const CUtensorMap* tm, int c0, int c1, uint32_t bar) {
  asm volatile("{ .reg .pred p; .reg .b64 h; " ONCE_H "elect.sync _|p, 0xffffffff;\n"
               "@p cp.async.bulk.tensor.2d.shared::cluster.global.mbarrier::complete_tx::bytes.L2::cache_hint [%0], [%1, {%3, %4}], [%2], h; }"
               :: "r"(dst), "l"(tm), "r"(bar), "r"(c0), "r"(c1) : "memory");
}
__device__ __forceinline__ void bulk_once(uint32_t dst, const void* src, uint32_t bytes, uint32_t bar) {
  asm volatile("{ .reg .pred p; .reg .b64 h; " ONCE_H "elect.sync _|p, 0xffffffff;\n"
               "@p cp.async.bulk.shared::cluster.global.mbarrier::complete_tx::bytes.L2::cache_hint [%0], [%1], %2, [%3], h; }"
               :: "r"(dst), "l"(src), "r"(bytes), "r"(bar) : "memory");
}
__device__ __forceinline__ void tma4d_e(uint32_t dst, const CUtensorMap* tm, int c2, int c3, uint32_t bar) {
  asm volatile("{ .reg .pred p; .reg .b64 h; " ONCE_H "elect.sync _|p, 0xffffffff;\n"
               "@p cp.async.bulk.tensor.4d.shared::cluster.global.mbarrier::complete_tx::bytes.L2::cache_hint [%0], [%1, {0, 0, %3, %4}], [%2], h; }"
               :: "r"(dst), "l"(tm), "r"(bar), "r"(c2), "r"(c3) : "memory");
}
__device__ __forceinline__ void bulk_load_e(uint32_t dst, const void* src, uint32_t bytes, uint32_t bar) {
  asm volatile("{ .reg .pred p; elect.sync _|p, 0xffffffff;\n"
               "@p cp.async.bulk.shared::cluster.global.mbarrier::complete_tx::bytes [%0], [%1], %2, [%3]; }"
               :: "r"(dst), "l"(src), "r"(bytes), "r"(bar) : "memory");
}
template<bool O> __device__ __forceinline__ void tma2d_o(uint32_t dst, const CUtensorMap* tm, int c0, int c1, uint32_t bar) {
  if (O) tma2d_once(dst, tm, c0, c1, bar); else tma2d_e(dst, tm, c0, c1, bar);
}
__device__ __forceinline__ float2 ld_once(const float2* p) {
  float2 v;
  if (ONCE & 64) asm volatile("{ .reg .b64 h; " ONCE_H "ld.global.cg.L2::cache_hint.v2.f32 {%0, %1}, [%2], h; }" : "=f"(v.x), "=f"(v.y) : "l"(p));
  else v = __ldcg(p);
  return v;
}
template<bool O = false> __device__ __forceinline__ void prefetch2d_e(const CUtensorMap* tm, int c0, int c1) {
  if (O) asm volatile("{ .reg .pred p; .reg .b64 h; " ONCE_H "elect.sync _|p, 0xffffffff;\n"
               "@p cp.async.bulk.prefetch.tensor.2d.L2.global.L2::cache_hint [%0, {%1, %2}], h; }" :: "l"(tm), "r"(c0), "r"(c1) : "memory");
  else asm volatile("{ .reg .pred p; elect.sync _|p, 0xffffffff;\n"
               "@p cp.async.bulk.prefetch.tensor.2d.L2.global [%0, {%1, %2}]; }" :: "l"(tm), "r"(c0), "r"(c1) : "memory");
}
__device__ __forceinline__ void st_pub4(void* p, uint4 v) {
  asm volatile("st.relaxed.gpu.global.v4.u32 [%0], {%1,%2,%3,%4};" :: "l"(p), "r"(v.x), "r"(v.y), "r"(v.z), "r"(v.w) : "memory");
}
__device__ __forceinline__ void st_pub_if(void* p, uint32_t v, bool on) {
  asm volatile("{ .reg .pred p; setp.ne.u32 p, %2, 0; @p st.relaxed.gpu.global.u32 [%0], %1; }" :: "l"(p), "r"(v), "r"((uint32_t)on) : "memory");
}
__device__ __forceinline__ uint32_t mapa(uint32_t a, uint32_t r) {
  uint32_t d; asm volatile("mapa.shared::cluster.u32 %0, %1, %2;" : "=r"(d) : "r"(a), "r"(r)); return d;
}
__device__ __forceinline__ void st_async4(uint32_t a, uint32_t x, uint32_t y, uint32_t z, uint32_t w, uint32_t bar) {
  asm volatile("st.async.shared::cluster.mbarrier::complete_tx::bytes.v4.u32 [%0], {%1,%2,%3,%4}, [%5];"
               :: "r"(a), "r"(x), "r"(y), "r"(z), "r"(w), "r"(bar) : "memory");
}
__device__ __forceinline__ uint4 ld_poll(const void* p) {
  uint4 v;
  asm volatile("ld.volatile.global.v4.u32 {%0,%1,%2,%3}, [%4];" : "=r"(v.x), "=r"(v.y), "=r"(v.z), "=r"(v.w) : "l"(p) : "memory");
  return v;
}
__device__ __forceinline__ uint2 ld_poll2(const void* p) {
  uint2 v; asm volatile("ld.volatile.global.v2.u32 {%0,%1}, [%2];" : "=r"(v.x), "=r"(v.y) : "l"(p) : "memory"); return v;
}
__device__ __forceinline__ void st_pub2(void* p, uint32_t a, uint32_t b) {
  asm volatile("st.relaxed.gpu.global.v2.u32 [%0], {%1,%2};" :: "l"(p), "r"(a), "r"(b) : "memory");
}
__device__ __forceinline__ uint32_t ld_poll1(const void* p) {
  uint32_t v; asm volatile("ld.volatile.global.u32 %0, [%1];" : "=r"(v) : "l"(p) : "memory"); return v;
}
__device__ __forceinline__ uint32_t ld_acquire(const uint32_t* p) {
  uint32_t v; asm volatile("ld.acquire.gpu.global.u32 %0, [%1];" : "=r"(v) : "l"(p) : "memory"); return v;
}
__device__ __forceinline__ void st_pub(void* p, uint32_t v) {
  asm volatile("st.relaxed.gpu.global.u32 [%0], %1;" :: "l"(p), "r"(v) : "memory");
}
__device__ __forceinline__ uint32_t lds32(uint32_t a) {
  uint32_t v; asm volatile("ld.shared.u32 %0, [%1];" : "=r"(v) : "r"(a) : "memory"); return v;
}
__device__ __forceinline__ int race_init(void* p0, void* p1, uint32_t val) {
  int t;
  asm volatile("{ .reg .pred r; .reg .u32 a, b, u, v;\n"
               "atom.relaxed.gpu.global.exch.b32 u, [%1], %3; atom.relaxed.gpu.global.exch.b32 v, [%2], %3;\n"
               "setp.eq.u32 r, u, 0x12345; @r pmevent 1; mov.u32 a, %%clock;\n"
               "setp.eq.u32 r, v, 0x12345; @r pmevent 1; mov.u32 b, %%clock; sub.u32 %0, b, a; }" : "=r"(t) : "l"(p0), "l"(p1), "r"(val) : "memory");
  return t;
}
__device__ __forceinline__ void race_init2(void* p0, void* p1, uint32_t val) {
  asm volatile("{ .reg .pred r; .reg .u32 a, b, u, v;\n"
               "atom.relaxed.gpu.global.exch.b32 u, [%0], %2; atom.relaxed.gpu.global.exch.b32 v, [%1], %2;\n"
               "atom.relaxed.gpu.global.exch.b32 a, [%0 + 4096], %2; atom.relaxed.gpu.global.exch.b32 b, [%1 + 4096], %2;\n"
               "lop3.b32 u, u, v, a, 0x96; setp.eq.u32 r, u, 0x12345; setp.eq.and.u32 r, b, u, r; @r pmevent 1; }" :: "l"(p0), "l"(p1), "r"(val) : "memory");
}
__device__ __forceinline__ uint4 lds128(uint32_t a) {
  uint4 v; asm volatile("ld.shared.v4.u32 {%0,%1,%2,%3}, [%4];" : "=r"(v.x), "=r"(v.y), "=r"(v.z), "=r"(v.w) : "r"(a) : "memory"); return v;
}
__device__ __forceinline__ uint2 lds64(uint32_t a) {
  uint2 v; asm volatile("ld.shared.v2.u32 {%0,%1}, [%2];" : "=r"(v.x), "=r"(v.y) : "r"(a) : "memory"); return v;
}
__device__ __forceinline__ void sts128(uint32_t a, uint4 v) {
  asm volatile("st.shared.v4.u32 [%0], {%1,%2,%3,%4};" :: "r"(a), "r"(v.x), "r"(v.y), "r"(v.z), "r"(v.w) : "memory");
}
__device__ __forceinline__ void sts64(uint32_t a, uint32_t x, uint32_t y) { asm volatile("st.shared.v2.u32 [%0], {%1,%2};" :: "r"(a), "r"(x), "r"(y) : "memory"); }
__device__ __forceinline__ void sts32(uint32_t a, uint32_t x) { asm volatile("st.shared.u32 [%0], %1;" :: "r"(a), "r"(x) : "memory"); }
__device__ __forceinline__ void ldsm4t(uint32_t (&r)[4], uint32_t a) {
  asm volatile("ldmatrix.sync.aligned.m8n8.x4.trans.shared.b16 {%0,%1,%2,%3}, [%4];"
               : "=r"(r[0]), "=r"(r[1]), "=r"(r[2]), "=r"(r[3]) : "r"(a) : "memory");
}
__device__ __forceinline__ void ldsm4(uint32_t (&r)[4], uint32_t a) {
  asm volatile("ldmatrix.sync.aligned.m8n8.x4.shared.b16 {%0,%1,%2,%3}, [%4];"
               : "=r"(r[0]), "=r"(r[1]), "=r"(r[2]), "=r"(r[3]) : "r"(a) : "memory");
}
template<bool TRANS> __device__ __forceinline__ void stsm4(uint32_t a, uint32_t r0, uint32_t r1, uint32_t r2, uint32_t r3) {
  if (TRANS) asm volatile("stmatrix.sync.aligned.m8n8.x4.trans.shared.b16 [%0], {%1,%2,%3,%4};" :: "r"(a), "r"(r0), "r"(r1), "r"(r2), "r"(r3) : "memory");
  else       asm volatile("stmatrix.sync.aligned.m8n8.x4.shared.b16 [%0], {%1,%2,%3,%4};" :: "r"(a), "r"(r0), "r"(r1), "r"(r2), "r"(r3) : "memory");
}
__device__ __forceinline__ void mma16816(float (&d)[4], uint32_t a0, uint32_t a1, uint32_t a2, uint32_t a3, uint32_t b0, uint32_t b1) {
  asm volatile("mma.sync.aligned.m16n8k16.row.col.f32.bf16.bf16.f32 {%0,%1,%2,%3}, {%4,%5,%6,%7}, {%8,%9}, {%0,%1,%2,%3};"
               : "+f"(d[0]), "+f"(d[1]), "+f"(d[2]), "+f"(d[3]) : "r"(a0), "r"(a1), "r"(a2), "r"(a3), "r"(b0), "r"(b1));
}
__device__ __forceinline__ void mma1688(float (&d)[4], uint32_t a0, uint32_t a1, uint32_t b0) {
  asm volatile("mma.sync.aligned.m16n8k8.row.col.f32.bf16.bf16.f32 {%0,%1,%2,%3}, {%4,%5}, {%6}, {%0,%1,%2,%3};"
               : "+f"(d[0]), "+f"(d[1]), "+f"(d[2]), "+f"(d[3]) : "r"(a0), "r"(a1), "r"(b0));
}
__device__ __forceinline__ uint32_t pack_bf16(float lo, float hi) {
  uint32_t r; asm("cvt.rn.bf16x2.f32 %0, %1, %2;" : "=r"(r) : "f"(hi), "f"(lo)); return r;
}
__device__ __forceinline__ uint32_t add_bf16x2(uint32_t a, uint32_t b) {
  uint32_t r; asm("add.rn.bf16x2 %0, %1, %2;" : "=r"(r) : "r"(a), "r"(b)); return r;
}
__device__ __forceinline__ uint32_t umax4(uint4 v) { return max(max(v.x, v.y), max(v.z, v.w)); }
__device__ __forceinline__ uint32_t opaque(uint32_t x) { uint32_t r; asm volatile("mov.u32 %0, %1;" : "=r"(r) : "r"(x)); return r; }
template<class T> __device__ __forceinline__ void pin(T*& p) { asm volatile("" : "+l"(p)); }
__device__ __forceinline__ void pin(uint32_t& v) { asm volatile("" : "+r"(v)); }
__device__ __forceinline__ uint32_t desc_lo(uint32_t addr) { return ((addr & 0x3FFFF) >> 4) | 0x10000; }
__device__ __forceinline__ uint64_t desc128(uint32_t lo) {
  uint64_t d; asm("mov.b64 %0, {%1, %2};" : "=l"(d) : "r"(lo), "r"(0x40000040)); return d;
}
#define WG_FENCE()  asm volatile("wgmma.fence.sync.aligned;" ::: "memory")
#define WG_COMMIT() asm volatile("wgmma.commit_group.sync.aligned;" ::: "memory")
#define WG_WAIT(n)  asm volatile("wgmma.wait_group.sync.aligned " #n ";" ::: "memory")
#define FENCE_ASYNC_SMEM() asm volatile("fence.proxy.async.shared::cta;" ::: "memory")
__device__ __forceinline__ void bar_sync(int id, int n) { asm volatile("bar.sync %0, %1;" :: "r"(id), "r"(n) : "memory"); }

#define D16(c) c(d[0]), c(d[1]), c(d[2]), c(d[3]), c(d[4]), c(d[5]), c(d[6]), c(d[7]), \
               c(d[8]), c(d[9]), c(d[10]), c(d[11]), c(d[12]), c(d[13]), c(d[14]), c(d[15])
template<bool FIRST> __device__ __forceinline__ void wgmma_rs_n32(float (&d)[16], const uint32_t (&a)[4], uint64_t b) {
  if (FIRST)
    asm volatile("wgmma.mma_async.sync.aligned.m64n32k16.f32.bf16.bf16 {%0,%1,%2,%3,%4,%5,%6,%7,%8,%9,%10,%11,%12,%13,%14,%15}, {%16,%17,%18,%19}, %20, 0, 1, 1, 0;"
      : D16("=f") : "r"(a[0]), "r"(a[1]), "r"(a[2]), "r"(a[3]), "l"(b));
  else
    asm volatile("wgmma.mma_async.sync.aligned.m64n32k16.f32.bf16.bf16 {%0,%1,%2,%3,%4,%5,%6,%7,%8,%9,%10,%11,%12,%13,%14,%15}, {%16,%17,%18,%19}, %20, 1, 1, 1, 0;"
      : D16("+f") : "r"(a[0]), "r"(a[1]), "r"(a[2]), "r"(a[3]), "l"(b));
}
template<bool FIRST> __device__ __forceinline__ void wgmma_ss_n32_ta(float (&d)[16], uint64_t a, uint64_t b) {
  if (FIRST)
    asm volatile("wgmma.mma_async.sync.aligned.m64n32k16.f32.bf16.bf16 {%0,%1,%2,%3,%4,%5,%6,%7,%8,%9,%10,%11,%12,%13,%14,%15}, %16, %17, 0, 1, 1, 1, 0;"
      : D16("=f") : "l"(a), "l"(b));
  else
    asm volatile("wgmma.mma_async.sync.aligned.m64n32k16.f32.bf16.bf16 {%0,%1,%2,%3,%4,%5,%6,%7,%8,%9,%10,%11,%12,%13,%14,%15}, %16, %17, 1, 1, 1, 1, 0;"
      : D16("+f") : "l"(a), "l"(b));
}
__device__ __forceinline__ void wgmma_ss_n128_tb(float (&d)[64], uint64_t a, uint64_t b) {
  asm volatile("wgmma.mma_async.sync.aligned.m64n128k16.f32.bf16.bf16 "
    "{%0,%1,%2,%3,%4,%5,%6,%7,%8,%9,%10,%11,%12,%13,%14,%15,%16,%17,%18,%19,%20,%21,%22,%23,%24,%25,%26,%27,%28,%29,%30,%31,"
    "%32,%33,%34,%35,%36,%37,%38,%39,%40,%41,%42,%43,%44,%45,%46,%47,%48,%49,%50,%51,%52,%53,%54,%55,%56,%57,%58,%59,%60,%61,%62,%63}, "
    "%64, %65, 1, 1, 1, 0, 1;"
    : "+f"(d[0]), "+f"(d[1]), "+f"(d[2]), "+f"(d[3]), "+f"(d[4]), "+f"(d[5]), "+f"(d[6]), "+f"(d[7]),
      "+f"(d[8]), "+f"(d[9]), "+f"(d[10]), "+f"(d[11]), "+f"(d[12]), "+f"(d[13]), "+f"(d[14]), "+f"(d[15]),
      "+f"(d[16]), "+f"(d[17]), "+f"(d[18]), "+f"(d[19]), "+f"(d[20]), "+f"(d[21]), "+f"(d[22]), "+f"(d[23]),
      "+f"(d[24]), "+f"(d[25]), "+f"(d[26]), "+f"(d[27]), "+f"(d[28]), "+f"(d[29]), "+f"(d[30]), "+f"(d[31]),
      "+f"(d[32]), "+f"(d[33]), "+f"(d[34]), "+f"(d[35]), "+f"(d[36]), "+f"(d[37]), "+f"(d[38]), "+f"(d[39]),
      "+f"(d[40]), "+f"(d[41]), "+f"(d[42]), "+f"(d[43]), "+f"(d[44]), "+f"(d[45]), "+f"(d[46]), "+f"(d[47]),
      "+f"(d[48]), "+f"(d[49]), "+f"(d[50]), "+f"(d[51]), "+f"(d[52]), "+f"(d[53]), "+f"(d[54]), "+f"(d[55]),
      "+f"(d[56]), "+f"(d[57]), "+f"(d[58]), "+f"(d[59]), "+f"(d[60]), "+f"(d[61]), "+f"(d[62]), "+f"(d[63])
    : "l"(a), "l"(b));
}

__device__ __forceinline__ void tma3d_mc_e(uint32_t dst, const CUtensorMap* tm, int c1, int c2, uint32_t bar) {
  asm volatile("{ .reg .pred p; .reg .b64 h; " ONCE_H "elect.sync _|p, 0xffffffff;\n"
               "@p cp.async.bulk.tensor.3d.shared::cluster.global.mbarrier::complete_tx::bytes.multicast::cluster.L2::cache_hint [%0], [%1, {0, %3, %4}], [%2], %5, h; }"
               :: "r"(dst), "l"(tm), "r"(bar), "r"(c1), "r"(c2), "h"((uint16_t)3) : "memory");
}
__device__ __forceinline__ void prefetch3d_e(const CUtensorMap* tm, int c1, int c2) {
  asm volatile("{ .reg .pred p; elect.sync _|p, 0xffffffff;\n"
               "@p cp.async.bulk.prefetch.tensor.3d.L2.global [%0, {0, %1, %2}]; }" :: "l"(tm), "r"(c1), "r"(c2) : "memory");
}

__device__ __forceinline__ void count_e(uint32_t* p) {
  asm volatile("fence.acq_rel.gpu;" ::: "memory");
  __syncwarp();
  asm volatile("{ .reg .pred p; elect.sync _|p, 0xffffffff; @p red.relaxed.gpu.global.add.u32 [%0], 1; }" :: "l"(p) : "memory");
}
template<int NS = 0> __device__ __forceinline__ void await_count(const uint32_t* p, uint32_t n) {
  for (uint32_t i = 0; ld_acquire(p) < n && i < (1u << 22); i++) { if (NS) __nanosleep(NS); }
  asm volatile("fence.proxy.async.global;" ::: "memory");
}
__device__ __forceinline__ void await_flags(const uint32_t* p) {
  for (uint32_t i = 0; i < (1u << 22); i++) {
    uint4 v;
    asm volatile("ld.acquire.gpu.global.v4.u32 {%0,%1,%2,%3}, [%4];" : "=r"(v.x), "=r"(v.y), "=r"(v.z), "=r"(v.w) : "l"(p) : "memory");
    if (__all_sync(~0u, (v.x & v.y & v.z & v.w) == 0x01010101u)) break;
  }
  asm volatile("fence.proxy.async.global;" ::: "memory");
}
__device__ __forceinline__ void mbar_lim(uint32_t bar, uint32_t ph) { for (uint32_t i = 0; !mbar_try(bar, ph) && i < (1u << 20); i++) {} }

struct cf { float x, y; };
__host__ __device__ constexpr float cos64(int k) {
  return k == 0 ? 1.0f : k == 1 ? 0.99518472667219689f : k == 2 ? 0.98078528040323045f : k == 3 ? 0.95694033573220887f :
         k == 4 ? 0.92387953251128676f : k == 5 ? 0.88192126434835503f : k == 6 ? 0.83146961230254524f : k == 7 ? 0.77301045336273696f :
         k == 8 ? 0.70710678118654752f : k == 9 ? 0.63439328416364550f : k == 10 ? 0.55557023301960222f : k == 11 ? 0.47139673682599765f :
         k == 12 ? 0.38268343236508977f : k == 13 ? 0.29028467725446236f : k == 14 ? 0.19509032201612827f : k == 15 ? 0.09801714032956060f : 0.0f;
}
__host__ __device__ constexpr float c64(int k) { return k <= 16 ? cos64(k) : -cos64(32 - k); }
__host__ __device__ constexpr float s64(int k) { return k <= 16 ? cos64(16 - k) : cos64(k - 16); }

template<int N, int ST, bool INV> struct Fft {
  template<int K> static __device__ __forceinline__ void bf(const cf* e, const cf* o, cf* out) {
    if constexpr (K < N / 2) {
      constexpr int idx = K * (64 / N);
      const cf a = e[K], b = o[K];
      if constexpr (idx == 0) {
        out[K] = {a.x + b.x, a.y + b.y}; out[K + N / 2] = {a.x - b.x, a.y - b.y};
      } else if constexpr (idx == 16) {
        if constexpr (INV) { out[K] = {a.x - b.y, a.y + b.x}; out[K + N / 2] = {a.x + b.y, a.y - b.x}; }
        else               { out[K] = {a.x + b.y, a.y - b.x}; out[K + N / 2] = {a.x - b.y, a.y + b.x}; }
      } else {
        constexpr float c = c64(idx), s = INV ? s64(idx) : -s64(idx);
        cf p; p.x = fmaf(-s, b.y, fmaf(c, b.x, a.x)); p.y = fmaf(s, b.x, fmaf(c, b.y, a.y));
        out[K] = p; out[K + N / 2] = {fmaf(2.0f, a.x, -p.x), fmaf(2.0f, a.y, -p.y)};
      }
      bf<K + 1>(e, o, out);
    }
  }
  static __device__ __forceinline__ void run(const cf* in, cf* out) {
    cf e[N / 2], o[N / 2];
    Fft<N / 2, 2 * ST, INV>::run(in, e);
    Fft<N / 2, 2 * ST, INV>::run(in + ST, o);
    bf<0>(e, o, out);
  }
};
template<int ST, bool INV> struct Fft<1, ST, INV> {
  static __device__ __forceinline__ void run(const cf* in, cf* out) { out[0] = in[0]; }
};
template<bool INV> __device__ __forceinline__ void fft32(cf (&v)[32]) {
  cf o[32]; Fft<32, 1, INV>::run(v, o);
#pragma unroll
  for (int i = 0; i < 32; i++) v[i] = o[i];
}
__device__ __forceinline__ cf cmul(cf a, float c, float s) { return {fmaf(-a.y, s, a.x * c), fmaf(a.x, s, a.y * c)}; }
__device__ __forceinline__ float bf2f(__nv_bfloat16 v) { return __bfloat162float(v); }

__device__ __forceinline__ int tw_at(int i) { return (i & ~63) | (i & 31) << 1 | (i >> 5 & 1); }
template<bool INV, bool T128 = true> __device__ __forceinline__ void twiddles(cf (&v)[32], const float4* __restrict__ tw) {
#pragma unroll
  for (int j = 0; j < 32; j += 2) {
    float4 w;
    if (T128) w = tw[j * 16];
    else { const uint2 a = lds64(smem_u32(tw + j * 16)), b = lds64(smem_u32(tw + j * 16) + 8); w = make_float4(__uint_as_float(a.x), __uint_as_float(a.y), __uint_as_float(b.x), __uint_as_float(b.y)); }
    if (j) v[j] = cmul(v[j], w.x, INV ? -w.y : w.y);
    v[j + 1] = cmul(v[j + 1], w.z, INV ? -w.w : w.w);
  }
}
template<bool INV, class F> __device__ __forceinline__ void warp_fft1024(cf (&v)[32], float2* __restrict__ buf, const float2* __restrict__ tw, int t, int u, F mid) {
#pragma unroll 1
  for (uint32_t h = 0; h < 2; h++) {
    fft32<INV>(v);
    if (FUNR ? h : opaque(h)) continue;
    twiddles<INV>(v, (const float4*)tw + u);
    if (INV) {
      float* f = (float*)buf;
#pragma unroll
      for (int j = 0; j < 32; j++) f[j * 36 + t] = v[j].x;
      __syncwarp();
#pragma unroll
      for (int j = 0; j < 32; j += 4) { const float4 r = *(const float4*)(f + u * 36 + j); v[j].x = r.x; v[j + 1].x = r.y; v[j + 2].x = r.z; v[j + 3].x = r.w; }
      __syncwarp();
#pragma unroll
      for (int j = 0; j < 32; j++) f[j * 36 + t] = v[j].y;
      __syncwarp();
#pragma unroll
      for (int j = 0; j < 32; j += 4) { const float4 r = *(const float4*)(f + u * 36 + j); v[j].y = r.x; v[j + 1].y = r.y; v[j + 2].y = r.z; v[j + 3].y = r.w; }
    } else {
#pragma unroll
      for (int j = 0; j < 32; j++) buf[j * 33 + t] = make_float2(v[j].x, v[j].y);
      __syncwarp();
#pragma unroll
      for (int j = 0; j < 32; j++) { const float2 r = buf[u * 33 + j]; v[j] = {r.x, r.y}; }
    }
    __syncwarp();
    mid();
  }
}
constexpr int ROW_BUF = 32 * 33, INV_BUF = 32 * 18;

__device__ __forceinline__ int z_row(int p) { return (p & ~31) | (p & 7) << 2 | (p & 31) >> 3; }
__device__ __forceinline__ int inv_lane(int t) { return (t & ~14) | (t & 12) >> 1 | (t & 2) << 2; }
__device__ __forceinline__ float2 twiddle(int i) { float s, c; sincospif(-(float)((i >> 5) * (i & 31)) * (1.0f / 512.0f), &s, &c); return make_float2(c, s); }
template<class F, class G> __device__ __forceinline__ void fft_rows_fwd(float2* sm2, const __nv_bfloat16* gw, int cta, int tid, uint32_t full_bar, uint32_t release_bar, F ev, G extra) {
  const int t = tid & 31, w = tid >> 5, n = z_row(cta * 8 + w);
#pragma unroll 1
  for (int i = tid; i < 1024; i += 256) sm2[tw_at(i)] = twiddle(i);
  ev(5);
  mbar_spin(full_bar, 0);
  if (tid == 0) TL2(6);
  __syncwarp();
  const __nv_bfloat16* xa = (const __nv_bfloat16*)(sm2 + 1024 + w * ROW_BUF) + t;
  cf v[32];
  float ga = 0.f, gb = 0.f;
#pragma unroll
  for (int j = 0; j < 32; j++) {
    v[j] = {bf2f(xa[32 * j]), bf2f(xa[D_ + 32 * j])};
    const float g = bf2f(gw[32 * j + t]); ga = fmaf(v[j].x, g, ga); gb = fmaf(v[j].y, g, gb);
  }
#pragma unroll
  for (int o = 16; o; o >>= 1) { ga += __shfl_xor_sync(~0u, ga, o); gb += __shfl_xor_sync(~0u, gb, o); }
  if (t < 2) g_gate[n + 1024 * t] = __fdividef(1.0f, 1.0f + __expf(-(t ? gb : ga)));
  ev(6);
  bar_sync(13, 256);
  warp_fft1024<false>(v, sm2 + 1024 + w * ROW_BUF, sm2, t, t, [&]() { FENCE_ASYNC_SMEM(); mbar_arrive_warp(release_bar); });
  float ws, wc; sincospif(-(float)n * (1.0f / 1024.0f), &ws, &wc);
  ev(12);
  uint32_t tz = clock_lo();
  float4* z = (float4*)g_z + ((size_t)(t >> 1) * 1024 + cta * 8 + w) * 2 + (t & 1);
#pragma unroll
  for (int j = 0; j < 17; j++) {
    cf q = v[(32 - j) & 31];
    if (j < 16) {
      const cf r = {__shfl_sync(~0u, v[31 - j].x, 32 - t), __shfl_sync(~0u, v[31 - j].y, 32 - t)};
      if (t != 0) q = r;
    }
    const cf a = {v[j].x + q.x, v[j].y - q.y}, b = {v[j].y + q.y, q.x - v[j].x};
    const cf d = cmul({a.x - b.x, a.y - b.y}, wc, ws);
    if (j == POOL_AT) extra();
    if (PACE_Z && j && j < 16) delay_until(tz += PACE_Z);
    if ((j < 16 || t == 0) && ((EXP_ST & 4) || d.x == 123.f)) z[j * 32768] = make_float4(a.x + b.x, a.y + b.y, d.x, d.y);
  }
}
constexpr int CP = X128 == 0 ? 33 : X128 == 2 ? 34 : 36, COL_FS = 32 * 36 + 8, COL_W = (8192 + 16 * COL_FS * 4 + 127) & ~127, COL_SMEM = COL_W + 131072 + 128;

__device__ __forceinline__ void fft_cols(float2* sm2, int cta, const CUtensorMap* twr, const CUtensorMap* twi, const CUtensorMap* tzs) {
  const int grp = __shfl_sync(~0u, (int)(threadIdx.x >> 7), 0), tid = threadIdx.x & 127, tp = tid >> 2, w = __shfl_sync(~0u, tid >> 5, 0);
  float* buf = (float*)(sm2 + 1024) + (grp * 4 + (tid & 3)) * COL_FS;
  const uint32_t wsm = smem_u32(sm2) + COL_W, wbar = wsm + 131072 + (W_FINE ? w * 32 : 0);
  const int res = w * 2 + (tid & 1), el = res + grp * 2 + ((tid >> 1) & 1);
  uint32_t wa = (el >> 3) * 65536 + res * 4096 + (tp & 7) * 16 + (el & 7) * 2;
  auto load_w = [&](int q) {
    const uint32_t bar = wbar + (q & 1) * 8;
    mbar_expect(bar, W_FINE ? 16384 : 65536);
#pragma unroll 1
    for (int i = W_FINE ? 4 * w : 0; i < (W_FINE ? 4 * w + 4 : 16); i++) tma2d(wsm + (q & 1) * 65536 + (i & 1) * 32768 + (i >> 1) * 4096, i & 1 ? twi : twr, (i >> 1) * 512 + q * 8, 0, bar);
  };
  const bool lead = (tid & (W_FINE ? 31 : 127)) == 0, first = grp < 2 && lead;
  if (first) { mbar_init(wbar + grp * 8, 1); sts32(wbar + 16 + grp * 4, grp ? 0 : w); asm volatile("fence.mbarrier_init.release.cluster;" ::: "memory"); }
#pragma unroll 1
  for (int i = threadIdx.x; i < 1024; i += 512) {
    const float2 t = twiddle(z_row(i));
    sm2[tw_at(i)] = t;
    if (cta == 0) g_tw[tw_at(inv_lane(z_row(i)))] = t;
  }
  for (uint32_t n = 0; ld_acquire(g_ctl + C_P1) < 128; ) { watchdog(n, 1u << 22); __nanosleep(200); }
  if (COL_DLY) delay_cycles(COL_DLY);
  if (first) load_w(cta * 16 + grp);
  __syncthreads();
  delay_cycles(1 + grp * DLY_GRP);
  mbar_wait(wbar, 0);
  const int end = cta * 64 + 64 + (cta == 3);
  for (int item = cta * 64 + grp; item < end; item += 4, wa ^= 65536) {
    float2* zp = g_z + (size_t)item * 4096;
    auto next_w = [&]() {
      const int q = (item >> 2) + (W_FINE && grp + w > 3);
      uint32_t n; asm volatile("atom.shared.inc.u32 %0, [%1], 3;" : "=r"(n) : "r"(wbar + 16 + (q & 1) * 4) : "memory");
      if (EXP_W && n == 3 && q < (cta * 16 + 15)) load_w(q + 2);
    };
    cf v[32];
#pragma unroll
    for (int j = 0; j < 32; j++) { const float2 a = ld_once(zp + tid + j * 128); v[j] = {a.x, a.y}; }
#pragma unroll 1
    for (int ph = 0; ; ph++) {
      fft32<false>(v);
      twiddles<false, T128_>(v, (const float4*)sm2 + tp);
      if (Z_ST) asm volatile("cp.async.bulk.wait_group.read 0;" ::: "memory");
      bar_sync(1 + grp, 128);
      if (lead) {
        if (ph) {
          if (!W_AT) next_w();
        } else if (Z_PF && item + 4 < end) asm volatile("cp.async.bulk.prefetch.L2.global [%0], %1;" :: "l"(zp + 4 * 4096 + w * 1024), "n"(W_FINE ? 8192 : 32768) : "memory");
      }
      __syncwarp();
#pragma unroll
      for (int j = 0; j < 32; j++) buf[((j & 3) * 8 + (j >> 2)) * CP + tp] = v[j].x;
      bar_sync(1 + grp, 128);
      if (X128 == 0) {
#pragma unroll
        for (int j = 0; j < 32; j++) v[j].x = buf[tp * CP + (j & 3) * 8 + (j >> 2)];
      } else if (X128 == 2) {
#pragma unroll
        for (int j = 0; j < 16; j++) { const float2 r = *(const float2*)(buf + tp * CP + 2 * j); cf* d = v + (j & 3) * 8 + (j >> 2); d[0].x = r.x; d[4].x = r.y; }
      } else
#pragma unroll
      for (int j = 0; j < 8; j++) {
        const float4 r = *(const float4*)(buf + tp * 36 + 4 * j);
        cf* d = v + (j & 1) * 16 + (j >> 1);
        d[0].x = r.x; d[4].x = r.y; d[8].x = r.z; d[12].x = r.w;
      }
      bar_sync(1 + grp, 128);
#pragma unroll
      for (int j = 0; j < 32; j++) buf[((j & 3) * 8 + (j >> 2)) * CP + tp] = v[j].y;
      bar_sync(1 + grp, 128);
      if (X128 == 0) {
#pragma unroll
        for (int j = 0; j < 32; j++) v[j].y = buf[tp * CP + (j & 3) * 8 + (j >> 2)];
      } else if (X128 == 2) {
#pragma unroll
        for (int j = 0; j < 16; j++) { const float2 r = *(const float2*)(buf + tp * CP + 2 * j); cf* d = v + (j & 3) * 8 + (j >> 2); d[0].y = r.x; d[4].y = r.y; }
      } else
#pragma unroll
      for (int j = 0; j < 8; j++) {
        const float4 r = *(const float4*)(buf + tp * 36 + 4 * j);
        cf* d = v + (j & 1) * 16 + (j >> 1);
        d[0].y = r.x; d[4].y = r.y; d[8].y = r.z; d[12].y = r.w;
      }
      fft32<false>(v);
      if (ph) break;
      const int q = min((item >> 2) + (!W_FINE || grp + w >= 3), 64);
      if (EXP_W) mbar_wait(wbar + (q & 1) * 8, (q >> 1) & 1);
#pragma unroll
      for (int j = 0; j < 32; j++) {
        uint32_t re, im;
        asm volatile("ld.shared.u16 %0, [%1];" : "=r"(re) : "r"(wsm + wa + j * 128) : "memory");
        asm volatile("ld.shared.u16 %0, [%1];" : "=r"(im) : "r"(wsm + wa + 32768 + j * 128) : "memory");
        const cf r = cmul(v[j], __uint_as_float(re << 16), __uint_as_float(im << 16));
        v[j] = {r.y, r.x};
      }
    }
    if (Z_ST) {
      float2* st = sm2 + 1024 + grp * (COL_FS * 2) + w * 512;
      bar_sync(1 + grp, 128);
#pragma unroll
      for (int h = 0; h < 2; h++) {
        if (h && Z_ST == 2) {
#pragma unroll
          for (int j = 16; j < 32; j++) zp[tid + j * 128] = make_float2(v[j].y, v[j].x);
          break;
        }
        if (h) { asm volatile("cp.async.bulk.wait_group.read 0;" ::: "memory"); __syncwarp(); }
#pragma unroll
        for (int j = 0; j < 16; j++) st[j * 32 + (tid & 31)] = make_float2(v[h * 16 + j].y, v[h * 16 + j].x);
        FENCE_ASYNC_SMEM();
        __syncwarp();
        tma2d_st_e(tzs, w * 128, item * 32 + h * 16, smem_u32(st));
        asm volatile("cp.async.bulk.commit_group;" ::: "memory");
      }
    } else {
#pragma unroll
      for (int j = 0; j < 32; j++) zp[tid + j * 128] = make_float2(v[j].y, v[j].x);
    }
    if (W_AT) { if (lead) next_w(); __syncwarp(); }
  }
  if (Z_ST) asm volatile("cp.async.bulk.wait_group 0; fence.proxy.async.global;" ::: "memory");
  const float4 t = ((const float4*)sm2)[threadIdx.x];
  __syncthreads();
  if (TW_L) ((float4*)sm2)[inv_lane(z_row(threadIdx.x))] = t;
  if (threadIdx.x < 32) {
    count_e(g_ctl + C_COLS);
    await_count(g_ctl + C_COLS, 4);
    g_ctl[C_P1] = 0;
  }
  __syncthreads();
  if (!TW_L) {
    ((float4*)sm2)[threadIdx.x] = __ldcg((const float4*)g_tw + threadIdx.x);
    __syncthreads();
  }
}

template<class F> __device__ __forceinline__ void fft_rows_inv(uint32_t zs, float2* buf, const float2* tw, int p, int lane, __nv_bfloat16* out, F read) {
  const int n = z_row(p), t = (lane & 17) | (lane & 6) << 1 | (lane & 8) >> 2, src = inv_lane(-t & 31);
  const uint32_t z = zs + (t >> 1) * 128 + ((((p & 3) * 2 + (t & 1)) ^ (t >> 1 & 7)) << 4);
  FT(0, 0.f);
  float4 e[17];
  uint32_t all = 0;
  e[16] = __ldcg((const float4*)g_z + ((size_t)256 * 1024 + p) * 2);
  const float g0 = __ldcg(g_gate + n), g1 = __ldcg(g_gate + n + 1024);
#pragma unroll
  for (int j = 0; j < 16; j++) { const uint4 u = lds128(z + j * 2048); e[j] = make_float4(__uint_as_float(u.x), __uint_as_float(u.y), __uint_as_float(u.z), __uint_as_float(u.w)); all |= u.x; }
  sched_fence(all);
  read();
  float ws, wc; sincospif((float)n * (1.0f / 1024.0f), &ws, &wc);
  cf v[32], q[17];
#pragma unroll
  for (int j = 0; j < 17; j++) {
    const cf d = cmul({e[j].z, e[j].w}, wc, ws);
    cf a = {e[j].x + d.x, e[j].y + d.y}, b = {e[j].x - d.x, e[j].y - d.y};
    if (j == 16 || (j == 0 && t == 0)) { a.y = 0.f; b.y = 0.f; }
    if (j < 16) v[j] = {a.x - b.y, a.y + b.x};
    q[j] = {a.x + b.y, b.x - a.y};
  }
#pragma unroll
  for (int j = 16; j < 32; j++) {
    v[j] = {__shfl_sync(~0u, q[31 - j].x, src), __shfl_sync(~0u, q[31 - j].y, src)};
    if (t == 0) v[j] = q[32 - j];
  }
  FT(1, v[0].x + v[16].x + v[31].x);
  if (B_ST) { asm volatile("cp.async.bulk.wait_group.read 0;" ::: "memory"); __syncwarp(); }
  warp_fft1024<true>(v, buf, tw, t, lane, []() {});
  FT(3, v[31].y + v[0].x);
  const float sc = 0.5f / (2048.0f * 1024.0f), s0 = (1.f - g0) * sc, s1 = (1.f - g1) * sc;
  uint2* o = (B_ST ? (uint2*)buf : (uint2*)(out + (size_t)n * D_)) + (lane ^ (n & 1) << 3);
#pragma unroll
  for (int j = 0; j < 32; j += 4) {
    o[8 * j] = make_uint2(pack_bf16(v[j].x * s0, v[j + 1].x * s0), pack_bf16(v[j + 2].x * s0, v[j + 3].x * s0));
    o[(B_ST ? 256 : 256 * D_) + 8 * j] = make_uint2(pack_bf16(v[j].y * s1, v[j + 1].y * s1), pack_bf16(v[j + 2].y * s1, v[j + 3].y * s1));
  }
  if (B_ST) {
    FENCE_ASYNC_SMEM();
    __syncwarp();
    asm volatile("{ .reg .pred p; setp.lt.u32 p, %2, 2; @p cp.async.bulk.global.shared::cta.bulk_group [%0], [%1], 2048; cp.async.bulk.commit_group; }"
                 :: "l"(out + (size_t)(n + 1024 * (lane & 1)) * D_), "r"(smem_u32(buf) + (lane & 1) * 2048), "r"(lane) : "memory");
  }
  FT(4, 0.f);
}

constexpr int NP = NP_, NHV = REG_F == 216 ? 5 : 7, NV = 16 - NHV;
constexpr int XEND = NSEG;
constexpr uint32_t SM_WO = 0, SM_V = 65536, SM_LAND = SM_V + 8192, SM_MEM = SM_LAND + 24576, SM_SP = SM_MEM, SM_SPM = SM_MEM + 5120, SM_OM = SM_MEM + 6144,
                   SM_OX = SM_MEM + 8192, SM_RED = SM_OX + 2048, SM_XCH = SM_RED + 1024, SM_SUM = SM_XCH + 4096, SM_VM = SM_SUM + 128, SM_TAB = SM_VM + 2048, SM_TRACE = SM_TAB + 2048, SM_K = SM_TRACE,
                   ST_WG = (32 - NP + NV) * 2048,
                   SM_XT = 2 * ST_WG, SM_POOL = SM_XT + 32768, SM_HV = SM_POOL + 2 * NP * 2048,
                   SM_BAR = SM_HV + 2 * NHV * 2048, SM_SEL = SM_BAR + 320, SM_Q = SM_SEL + 576, CHAIN_SMEM = SM_Q + (Q_TMA ? 2048 : 1024);
constexpr uint32_t SM_FFT = 49152, SM_GW = SM_XT - 2048;
static_assert((!OX_L || (XB && !OX_AT)) && (OX_AT < 3 || SXP >= 3) && (!OX_AT || LASTM) && NP % 4 == 0 && NV == 11 && SM_TRACE + 8192 <= SM_XT, "shared memory layout");
static_assert(CHAIN_SMEM <= 232448 && COL_SMEM <= SM_BAR && SM_FFT + (1024 + 8 * ROW_BUF) * 8 <= SM_GW && NP == 12, "shared memory budget");
enum { B_WFULL = 0, B_WREAD = 2, B_WOFULL, B_XFULL, B_XEMPTY, B_E1TRIG, B_E2TRIG, B_PVDONE, B_PUB, B_SC, B_PFULL, B_SPFREE,
       B_LAND, B_LFREE, B_DONE, B_SEL, B_PROBE, B_FREE, B_P1, B_ROWS, B_VFULL, B_VST, B_TW, B_BT, B_WREAD0, B_Z, B_GFULL = B_Z + 4, B_GEMPTY = B_GFULL + 5, B_END = B_GEMPTY + 5 };
static_assert(B_END * 8 <= 320, "barriers");
__host__ __device__ constexpr uint32_t bar_codes(int g) {
  uint32_t r = 0;
  for (int i = 16 * g; i < 16 * g + 16; i++)
    r |= (i == B_LAND ? 3u : i == B_WREAD || i == B_XEMPTY || i == B_E1TRIG || i == B_E2TRIG || i == B_LFREE || i == B_FREE || i == B_VST || i == B_P1 || i == B_ROWS ? 2u :
          i >= B_GEMPTY || i == B_WREAD0 || i == B_PROBE || i == B_DONE || i == B_PVDONE || i == B_PUB || i == B_SC || i == B_SPFREE ? 1u : 0u) << 2 * (i & 15);
  return r;
}
constexpr uint32_t SM_BT = 65536, SM_TW = SM_XT - 8192, COL_Z = 80 * 1024;
static_assert(SM_XT + 3 * 32768 <= SM_BAR && SM_BT + 32768 <= SM_MEM && SM_TRACE <= SM_TW && SM_MEM + 4 * INV_BUF * 8 <= SM_TRACE &&
              8192 + 16 * INV_BUF * 8 <= COL_Z && COL_Z + 131072 <= SM_BAR, "shared memory layout");
__device__ __forceinline__ uint32_t next_stage(uint32_t o) { return o == SM_XT + 65536 ? 0 : o == 32768 ? SM_XT : o + 32768; }

struct ChainCtx { char* mail; uint32_t sb, sel; int r, h, a, b, j, m, w, lane; };
#define BAR(i) (c.sb + SM_BAR + 8 * (i))

__device__ __forceinline__ uint32_t tile_off(int line, int lane) {
  return line * 128 + (((lane & 3) ^ line) << 5) + (lane >> 2) * 4;
}
__device__ __forceinline__ uint32_t read_off(int lane) {
  const int n = lane >> 2, jj = lane & 3, l = 2 * (jj >> 1) + (n & 1);
  return l * 128 + (((n >> 1) ^ l) << 5) + (jj & 1) * 16;
}
__device__ __forceinline__ uint32_t frag_off(int w, int lane) {
  const int mi = lane >> 3, r = lane & 7;
  return ((mi >> 1) * 8 + r) * 128 + (((2 * w + (mi & 1)) ^ r) << 4);
}
__device__ __forceinline__ uint32_t land_off(int w, int lane) { return w * 512 + ((lane ^ (((lane >> 4) | ((w & 1) << 1)) << 1)) << 4); }
__device__ __forceinline__ uint32_t tagged(uint32_t v, uint32_t tag) { return (v | 1u) ^ tag; }
__device__ __forceinline__ void mma_a(float (&d)[4], const uint32_t (&a)[4], uint32_t b0, uint32_t b1) { mma16816(d, a[0], a[1], a[2], a[3], b0, b1); }
__device__ __forceinline__ void mma_q(float (&d)[4], const uint4& a, uint32_t b0, uint32_t b1) { mma16816(d, a.x, a.y, a.z, a.w, b0, b1); }
__device__ __forceinline__ uint4 add4(uint4 a, uint4 b) {
  return make_uint4(add_bf16x2(a.x, b.x), add_bf16x2(a.y, b.y), add_bf16x2(a.z, b.z), add_bf16x2(a.w, b.w));
}
__device__ __forceinline__ void mbar_arrive_both(uint32_t bar, int peer) {
  __syncwarp();
  asm volatile("{ .reg .pred p; .reg .u32 a; mapa.shared::cluster.u32 a, %0, %1; elect.sync _|p, 0xffffffff;\n"
               "@p mbarrier.arrive.shared::cta.b64 _, [%0]; @p mbarrier.arrive.shared::cluster.b64 _, [a]; }" :: "r"(bar), "r"(peer) : "memory");
}

__device__ __forceinline__ void arrive_remote_if(uint32_t a, bool on) {
  asm volatile("{ .reg .pred p; setp.ne.u32 p, %1, 0; @p mbarrier.arrive.shared::cluster.b64 _, [%0]; }" :: "r"(a), "r"((uint32_t)on) : "memory");
}
__device__ __forceinline__ void store_count(void* p, uint4 v, void* cnt) {
  asm volatile("{ .reg .pred p, q; .reg .b128 a, b; .reg .b64 l, h; mov.b64 l, {%1, %2}; mov.b64 h, {%3, %4}; mov.b128 a, {l, h};\n"
               "atom.relaxed.gpu.global.exch.b128 b, [%0], a; mov.b128 {l, h}, b; setp.eq.u64 q, l, 0x7fc17fc17fc17fc1; @q pmevent 1;\n"
               "elect.sync _|p, 0xffffffff; @p red.relaxed.gpu.global.add.u32 [%5], 1; }"
               :: "l"(p), "r"(v.x), "r"(v.y), "r"(v.z), "r"(v.w), "l"(cnt) : "memory");
}

template<int N> __device__ __forceinline__ void pad() {
#pragma unroll
  for (int i = 0; i < N; i++) asm volatile("pmevent 3;");
}
__device__ __forceinline__ int lane_id() {
  int l; asm volatile("{ .reg .u32 t; mov.u32 t, %%laneid; shfl.sync.idx.b32 %0, t, t, 31, 0xffffffff; }" : "=r"(l)); return l;
}
__device__ __forceinline__ uint32_t tid_now() { uint32_t t; asm volatile("mov.u32 %0, %%tid.x;" : "=r"(t)); return t; }
enum { NB_ATT = 1, NB_OM = 2, NB_VM = 3, NB_XCH = 4, NB_MEM = 8, NB_HELP = 12 };
__device__ __forceinline__ uint32_t dep(uint32_t a, uint32_t v, uint32_t z) { uint32_t r; asm("shf.l.wrap.b32 %0, %2, %1, %3;" : "=r"(r) : "r"(a), "r"(v), "r"(z)); return r; }
__device__ __forceinline__ uint32_t vary(uint32_t a, int s, uint32_t z) { return dep(a, 0, z + 32 * s); }
__device__ __forceinline__ char* mk_ptr(uint32_t lo, uint32_t hi) { uint64_t r; asm("mov.b64 %0, {%1, %2};" : "=l"(r) : "r"(lo), "r"(hi)); return (char*)r; }
__device__ __forceinline__ void lds_frag(uint32_t (&r)[4], uint32_t a) {
  asm volatile("ld.shared.v4.u32 {%0,%1,%2,%3}, [%4];" : "=r"(r[0]), "=r"(r[1]), "=r"(r[2]), "=r"(r[3]) : "r"(a) : "memory");
}
__device__ __forceinline__ uint32_t stale2(uint32_t a, uint32_t b, uint32_t t) { uint32_t r; asm("lop3.b32 %0, %1, %2, %3, 0xbd;" : "=r"(r) : "r"(a), "r"(b), "r"(t)); return r; }
__device__ __forceinline__ uint32_t stale1(uint32_t acc, uint32_t a, uint32_t t) { uint32_t r; asm("lop3.b32 %0, %1, %2, %3, 0xf9;" : "=r"(r) : "r"(acc), "r"(a), "r"(t)); return r; }
__device__ __forceinline__ bool all_clear(uint32_t x, uint32_t m) {
  uint32_t r;
  asm volatile("{ .reg .pred p; .reg .u32 t; and.b32 t, %1, %2; setp.eq.u32 p, t, 0; vote.sync.all.pred p, p, 0xffffffff; selp.u32 %0, 1, 0, p; }" : "=r"(r) : "r"(x), "r"(m));
  return r;
}
__device__ __forceinline__ bool arrive_if_all(bool ok, int id, int n) {
  uint32_t r;
  asm volatile("{ .reg .pred p, q; setp.ne.u32 p, %1, 0; vote.sync.all.pred q, p, 0xffffffff; @q bar.arrive %2, %3; selp.u32 %0, 1, 0, q; }"
               : "=r"(r) : "r"((uint32_t)ok), "r"(id), "r"(n) : "memory");
  return r;
}
__device__ __forceinline__ bool arrive_if_clear(uint32_t x, uint32_t m, int id, int n) {
  uint32_t r;
  asm volatile("{ .reg .pred p; .reg .u32 t; and.b32 t, %1, %2; setp.eq.u32 p, t, 0; vote.sync.all.pred p, p, 0xffffffff; @p bar.arrive %3, %4; selp.u32 %0, 1, 0, p; }"
               : "=r"(r) : "r"(x), "r"(m), "r"(id), "r"(n) : "memory");
  return r;
}
__device__ __forceinline__ void touch(const void* p, uint32_t z) {
  asm volatile("{ .reg .pred p; setp.eq.u32 p, %1, 0x7fff0000; @p prefetch.global.L2 [%0]; }" :: "l"(p), "r"(z) : "memory");
}

__device__ __forceinline__ uint64_t desc_x(uint32_t lo, int k) {
  uint64_t d; asm("mov.b64 %0, {%1, %2};" : "=l"(d) : "r"(lo + (k >> 2) * 64 + (k & 3) * 2), "r"(0x40000200)); return d;
}
template<int K0, int K1> __device__ __forceinline__ void issue_qk(float (&xa)[16], const uint32_t (&wt)[16][4], uint32_t lo) {
  WG_FENCE();
#pragma unroll
  for (int k = K0; k < K1; k++) {
    if (k >= EXP_NWG) continue;
    if (k == 0) wgmma_rs_n32<true>(xa, wt[0], desc_x(lo, 0));
    else wgmma_rs_n32<false>(xa, wt[k], desc_x(lo, k));
  }
  WG_COMMIT();
}
__host__ __device__ constexpr int v_order(int i) { return SSPOS == 0 ? i : SSPOS == 2 ? (i + NV) % 16 : NHV == 5 ? (i % 3 == 2 ? NV + i / 3 : i - i / 3) : (i == 15 ? NV - 1 : i % 2 ? NV + i / 2 : i / 2); }
__device__ __forceinline__ void issue_v(float (&xa)[16], const uint32_t (&wv)[16][4], uint32_t lo, uint32_t la) {
  WG_FENCE();
#pragma unroll
  for (int i = 0; i < EXP_NWG; i++) {
    const int k = v_order(i);
    const uint64_t b = desc_x(lo, k);
    if (k < NV) { if (i == 0) wgmma_rs_n32<true>(xa, wv[k], b); else wgmma_rs_n32<false>(xa, wv[k], b); }
    else        { if (i == 0) wgmma_ss_n32_ta<true>(xa, desc128(la + (k - NV) * 128), b); else wgmma_ss_n32_ta<false>(xa, desc128(la + (k - NV) * 128), b); }
  }
  WG_COMMIT();
}
template<bool ISV> __device__ __forceinline__ void park_own(uint32_t (&q)[4], float (&xa)[16], uint32_t dst, int slot, uint32_t z) {
  uint32_t p[8];
#pragma unroll
  for (int i = 0; i < 16; i++) asm volatile("" : "+f"(xa[i]) :: "memory");
#pragma unroll
  for (int i = 0; i < 2; i++) {
    const float* k = xa + 8 * i;
    if (ISV) { p[4 * i] = pack_bf16(k[0], k[1]); p[4 * i + 1] = pack_bf16(k[2], k[3]); p[4 * i + 2] = pack_bf16(k[4], k[5]); p[4 * i + 3] = pack_bf16(k[6], k[7]); }
    else     { p[4 * i] = pack_bf16(k[0], k[2]); p[4 * i + 1] = pack_bf16(k[1], k[3]); p[4 * i + 2] = pack_bf16(k[4], k[6]); p[4 * i + 3] = pack_bf16(k[5], k[7]); }
  }
  sts128(dep(dep(dst, p[4] ^ p[5] ^ p[6], z), p[7], z) + slot * 8192, make_uint4(p[0], p[1], p[2], p[3]));
#pragma unroll
  for (int i = 0; i < 4; i++) q[i] = p[4 + i];
}
__device__ __forceinline__ void park_peer(const uint32_t (&q)[4], uint32_t dst, int slot, const ChainCtx& c) {
  const uint32_t bar = BAR(B_LAND);
  if (EXP_PEER) st_async4(mapa(dst + slot * 8192, c.b ^ 1), q[0], q[1], q[2], q[3], mapa(bar, c.b ^ 1));
  else touch((void*)(uintptr_t)(q[0] ^ q[1] ^ q[2] ^ q[3]), c.sb);
  mbar_arrive_warp(bar);
}
__device__ __forceinline__ uint32_t put_tag(uint32_t v, uint32_t bit, uint32_t t) {
  uint32_t r; asm("lop3.b32 %0, %1, %2, %3, 0x74;" : "=r"(r) : "r"(v), "r"(bit), "r"(t)); return r;
}
__device__ __forceinline__ void mem_proj(const uint32_t (&wa)[16][4], const uint32_t (&wb)[16][4], uint32_t (&wv)[16][4], uint32_t (&af)[16][4],
                                         uint32_t& wo, const char*& pa, uint32_t tab, uint32_t t16, uint32_t pk, const ChainCtx& c, int s) {
  const uint32_t mp = t16 & ~0x600u, id = NB_MEM + (t16 >> 11);
  uint32_t r[8][4];
  float la[4][4] = {}, lg[NLAG][4] = {}, lv[4][4] = {};
  auto lead = [&](int k) { mma_a(la[k & 3], wa[k], r[k >> 1][2 * (k & 1)], r[k >> 1][2 * (k & 1) + 1]); };
  auto lag = [&](int k) { mma_a(lg[k % NLAG], wb[k], r[k >> 1][2 * (k & 1)], r[k >> 1][2 * (k & 1) + 1]); };
  auto sum = [](const float (&d)[4][4], int i) { return (d[0][i] + d[1][i]) + (d[2][i] + d[3][i]); };
  bar_sync(id, 160);
  TR(s, 0);
#pragma unroll
  for (int i = 0; i < 4; i++) ldsm4t(r[i], mp + (c.sb + SM_MEM + i * 512));
  uint4 tq;
  if (!TQ_AT) tq = lds128(tab);
  bar_sync(id + 2, 160);
  uint32_t first = 0;
#pragma unroll
  for (int k = 0; k < 8; k++) { lead(k); if (k == C1_AT - 4) first = dep(mp, __float_as_uint(la[k & 3][0]), c.sb); }
  uint32_t ta, tb;
  if (!TQ_AT) { ta = tq.x | ((pk >> 16) & 511); tb = tq.z ^ ((pk >> 16) & 511); }
  const uint32_t mp1 = C1_AT >= 4 ? (TQ_AT ? first : dep(first, ta ^ tb, c.sb)) : dep(mp, __float_as_uint(la[C1_AT & 3][0]) ^ (TQ_AT ? 0 : ta ^ tb), c.sb);
#pragma unroll
  for (int i = 4; i < 8; i++) ldsm4t(r[i], mp1 + (c.sb + SM_MEM + 2048 + i * 512));
  if (TQ_AT) { tq = lds128(tab); ta = tq.x | ((pk >> 16) & 511); tb = tq.z ^ ((pk >> 16) & 511); }
  char* dst = mk_ptr(ta, tq.y);
  char* dst2 = mk_ptr(tb, tq.w);
  const uint32_t hv = pk & 0xFFFF;
#pragma unroll
  for (int k = NV; k < NV + HV_E; k++) ldsm4t(wv[k], dep(hv, r[HV_R][0], c.sb) + (c.sb + SM_HV + (k - NV) * 2048));
#pragma unroll
  for (int k = 0; k < LAG_0; k++) lag(k);
#pragma unroll
  for (int k = 8; k < 16; k++) lead(k);
  const uint32_t s0 = __float_as_uint(sum(la, 0)), s3 = __float_as_uint(sum(la, 3));
  sts128((HV_E ? dep(t16, wv[NV][0] ^ wv[NV + HV_E / 2][1] ^ wv[NV + HV_E - (HV_E > 0)][2], c.sb) : TQ_AT ? dep(t16, ta ^ tb, c.sb) : t16) + (c.sb + SM_XCH),
         make_uint4(s0, __float_as_uint(sum(la, 1)), __float_as_uint(sum(la, 2)), s3));
  if (XB) bar_sync(NB_XCH, 256); else bar_sync(NB_XCH | ((t16 >> 9) & 3), 64);
#pragma unroll
  for (int k = LAG_0; k < LAG_0 + LAG_G; k++) r[k >> 1][2 * (k & 1)] = dep(r[k >> 1][2 * (k & 1)], LAG_S == 0 ? s3 : __float_as_uint(la[LAG_S - 1][0]), c.sb);
#pragma unroll
  for (int k = LAG_0; k < O_AT; k++) lag(k);
  const uint4 o = lds128((O_AT > LAG_0 ? dep(t16 ^ 2048, __float_as_uint(lg[(O_AT - 1) % NLAG][0]), c.sb) : t16 ^ 2048) + (c.sb + SM_XCH));
#pragma unroll
  for (int k = O_AT > LAG_0 ? O_AT : LAG_0; k < 16; k++) lag(k);
#pragma unroll
  for (int k = 0; k < V_E; k++) mma_a(lv[k & 3], wv[k], r[k >> 1][2 * (k & 1)], r[k >> 1][2 * (k & 1) + 1]);
  float t[4];
#pragma unroll
  for (int i = 0; i < 4; i++) {
    const float oi = __uint_as_float(i == 0 ? o.x : i == 1 ? o.y : i == 2 ? o.z : o.w);
    t[i] = NLAG == 4 ? (LAG_T ? ((lg[0][i] + lg[1][i]) + oi) + (lg[2 % NLAG][i] + lg[3 % NLAG][i]) : (((lg[0][i] + lg[1][i]) + lg[2 % NLAG][i]) + lg[3 % NLAG][i]) + oi) : LAG_T && NLAG == 2 ? (lg[0][i] + lg[1][i]) + oi : NLAG == 3 ? (lg[1][i] + lg[2 % NLAG][i]) + (lg[0][i] + oi) : (lg[0][i] + oi) + lg[1][i];
  }
  const uint32_t y0 = put_tag(pack_bf16(t[0], t[2]), pk >> 31, s >> 1), y1 = put_tag(pack_bf16(t[1], t[3]), pk >> 31, s >> 1);
  st_pub(dst, y0); st_pub(dst2, y1);
  mbar_arrive_warp(BAR(B_E1TRIG));
  TR(s, 1);
  sched_fence(c.sb);
  const uint4 tv = lds128(tab + 16);
#pragma unroll
  for (int k = NV + HV_E; k < 16; k++) ldsm4t(wv[k], (k < NV + HV_E + HV_D ? hv : dep(hv, k == NV + HV_E + HV_D ? wv[k - HV_D][0] ^ tv.x : wv[k - HV_D][0], c.sb)) + (c.sb + SM_HV + (k - NV) * 2048));
  wo = (hv & 2047) | ((t16 & 2048) << 3);
  const uint32_t l8 = (t16 >> 1) & 255;
  char* dv = mk_ptr(tv.x | l8, tv.y);
  pa = mk_ptr(tv.z | l8, tv.w);
#pragma unroll
  for (int f = 0; f < WO_0; f++) ldsm4t(af[f], dep(wo, f < WO_D ? wv[16 - WO_D + f][0] : af[f < WO_D ? 0 : f - WO_D][0], c.sb) + (c.sb + SM_WO + (f & 1) * 32768 + (f >> 1) * 2048));
#pragma unroll
  for (int k = V_E; k < 16; k++) mma_a(lv[k & 3], wv[k], r[k >> 1][2 * (k & 1)], r[k >> 1][2 * (k & 1) + 1]);
  const uint32_t z0 = put_tag(pack_bf16(sum(lv, 0), sum(lv, 1)), (~t16 >> 4) & 1, s >> 1), z1 = pack_bf16(sum(lv, 2), sum(lv, 3));
  st_pub2(dv, z0, z1);
  if (FIN_AT >= 3) mbar_arrive_warp(BAR(B_VST));
  TR(s, 2);
}
__device__ __forceinline__ uint32_t max_bf16x2(uint32_t a, uint32_t b) { uint32_t r; asm("max.bf16x2 %0, %1, %2;" : "=r"(r) : "r"(a), "r"(b)); return r; }
constexpr float SCL = 0.08838834764831845f * 1.4426950408889634f;
__device__ __forceinline__ uint32_t max5(const uint32_t (&sc)[5]) { return max_bf16x2(max_bf16x2(max_bf16x2(max_bf16x2(sc[0], sc[1]), sc[2]), sc[3]), sc[4]); }
__device__ __forceinline__ float row_off(uint32_t m, uint32_t& m1) {
  m1 = __shfl_xor_sync(~0u, m, 1);
  const uint32_t m2 = __shfl_xor_sync(~0u, m, 2), m3 = __shfl_xor_sync(~0u, m, 3);
  const uint32_t mm = max_bf16x2(max_bf16x2(max_bf16x2(m, m1), m2), m3);
  return -SCL * fmaxf(__uint_as_float(mm << 16), __uint_as_float(mm & 0xFFFF0000u));
}
__device__ __forceinline__ void unpack(float (&f)[10], const uint32_t (&sc)[5]) {
#pragma unroll
  for (int i = 0; i < 5; i++) {
    asm volatile("shl.b32 %0, %1, 16;" : "=f"(f[2 * i]) : "r"(sc[i]));
    asm volatile("and.b32 %0, %1, 0xffff0000;" : "=f"(f[2 * i + 1]) : "r"(sc[i]));
  }
}
__device__ __forceinline__ uint32_t exp_pair(const float (&f)[10], int i, float off) {
  return pack_bf16(ex2(fmaf(f[2 * i], SCL, off)), ex2(fmaf(f[2 * i + 1], SCL, off)));
}
template<bool SPLIT> __device__ __forceinline__ void scores_x(float (&a)[2][4], const uint4 (&kf)[4], const uint4& q, uint32_t z) {
#pragma unroll
  for (int t = 0; t < 2; t++) { a[t][0] = a[t][1] = a[t][2] = a[t][3] = 0.f; }
  mma_q(a[0], kf[0], q.x, q.y); mma_q(a[1], kf[2], q.x, q.y);
  if (SPLIT) sched_fence(z);
  mma_q(a[0], kf[1], q.z, q.w); mma_q(a[1], kf[3], q.z, q.w);
}
__device__ __forceinline__ uint32_t scores_m(const uint4& q, const uint4& k) {
  float a[4] = {}, b[4] = {};
  mma_q(a, q, k.x, k.z); mma_q(b, q, k.y, k.w);
  return pack_bf16(a[0] + b[2], a[1] + b[3]);
}
__device__ __forceinline__ void store_scores(const float (&a)[2][4], uint32_t dst) {
  sts64(dst, pack_bf16(a[0][0], a[0][2]), pack_bf16(a[1][0], a[1][2]));
  sts64(dst + 320, pack_bf16(a[0][1], a[0][3]), pack_bf16(a[1][1], a[1][3]));
}
__device__ __forceinline__ uint32_t sum4(uint32_t a, uint32_t b, uint32_t d, uint32_t e) { return add_bf16x2(add_bf16x2(a, b), add_bf16x2(d, e)); }
__device__ __forceinline__ void load_scores(uint32_t (&sc)[5], uint32_t ax, uint32_t am) {
  uint4 p[4];
#pragma unroll
  for (int i = 0; i < 4; i++) p[i] = lds128(ax + i * 1280);
  const uint2 m0 = lds64(am), m1 = lds64(am + 256);
  const uint4 t = add4(add4(add4(p[0], p[1]), p[2]), p[3]);
  sc[1] = t.x; sc[2] = t.y; sc[3] = t.z; sc[4] = t.w;
  sc[0] = sum4(m0.x, m0.y, m1.x, m1.y);
}
constexpr uint32_t ONES = 0x3F803F80u;
__device__ __forceinline__ float pv(float (&o)[2][4], const uint32_t (&p)[5], const uint4 (&vf)[4], const uint4& vm) {
  float a[4] = {}, b[4] = {};
#pragma unroll
  for (int t = 0; t < 2; t++) { o[t][0] = o[t][1] = o[t][2] = o[t][3] = 0.f; }
  mma_q(o[0], vf[0], p[1], p[2]); mma_q(o[1], vf[2], p[1], p[2]);
  mma_q(o[0], vf[1], p[3], p[4]); mma_q(o[1], vf[3], p[3], p[4]);
  mma16816(a, p[1], p[2], p[3], p[4], ONES, ONES);
  mma1688(o[0], vm.x, vm.y, p[0]); mma1688(o[1], vm.z, vm.w, p[0]);
  mma1688(b, p[0], ONES, ONES);
  return (a[0] + a[2]) + b[0];
}
constexpr uint32_t POLL_LIMIT = 1u << 21;
__device__ __forceinline__ uint32_t box(int slot, int cta) { return (slot * 2 + (cta >> 6)) * M_REG + (cta & 63) * 16384; }
__device__ __forceinline__ uint32_t near_page(const ChainCtx& c, int cta, uint32_t off) {
  return off + (((lds32(c.sb + SM_SEL + cta * 4) >> (off >> 21)) ^ __popc(off & 0xB2000)) & 1) * 4096;
}
__device__ __forceinline__ uint32_t e1_box(const ChainCtx& c, int slot, int cta) { return near_page(c, E1OFF ? cta ^ 2 : cta, box(slot, cta) + 8192) ^ (E1OFF ? 0 : 4096); }
__device__ __forceinline__ uint32_t tile_key() {
  uint32_t sm; asm volatile("mov.u32 %0, %%smid;" : "=r"(sm));
  return (sm < 64 ? sm / 2 % 8 : sm < 120 ? 1 + (sm / 2 - 32) % 7 : 0) << 24 | sm << 16;
}
__device__ __forceinline__ uint32_t ox_at(int s, int row, int g, int jj) { return s * 131072 + ((g >> 1) * 32 + row) * 64 + (g & 1) * 32 + 8 * jj; }
__device__ __forceinline__ int tile_of(const ChainCtx& c) { return SIDE ? __shfl_sync(~0u, lds32(c.sb + SM_SEL + 528), 0) : c.r; }

__global__ void __cluster_dims__(2, 1, 1) __launch_bounds__(512, 1)
chain_kernel(const __grid_constant__ CUtensorMap tq, const __grid_constant__ CUtensorMap tk, const __grid_constant__ CUtensorMap tv,
             const __grid_constant__ CUtensorMap tv16, const __grid_constant__ CUtensorMap to, const __grid_constant__ CUtensorMap tx,
             const __grid_constant__ CUtensorMap twr, const __grid_constant__ CUtensorMap twi,
             const __grid_constant__ CUtensorMap ta, const __grid_constant__ CUtensorMap tw,
             const __grid_constant__ CUtensorMap tb, const __grid_constant__ CUtensorMap tout, const __grid_constant__ CUtensorMap tz,
             const __grid_constant__ CUtensorMap tzs, const __grid_constant__ CUtensorMap ta32,
             const __nv_bfloat16* __restrict__ mem0, char* __restrict__ mail, const __nv_bfloat16* __restrict__ x,
             const __nv_bfloat16* __restrict__ gw) {
  extern __shared__ __align__(1024) unsigned char smraw[];
  if (threadIdx.x == 0) TL(0);
  ChainCtx c;
  c.sb = __shfl_sync(~0u, smem_u32(smraw), 0);
  c.mail = mail; c.sel = 0; c.r = blockIdx.x;
  if (ROLE) {
    const uint32_t u = blockIdx.x >> 1, n = u < 36 ? 8 : 7, k = u - (u < 36 ? 4 : 36), q = k * (u < 36 ? 32 : 37) >> 8;
    c.r = __shfl_sync(~0u, 2 * (u - 4 < 60 ? u + k - q * n - (q & 1) * (n - 1) : u) + (blockIdx.x & 1) + (threadIdx.x >> 9), 0);
  }
  c.h = c.r >> 2; c.a = (c.r >> 1) & 1; c.b = c.r & 1; c.j = c.r & 3;
  c.m = __shfl_sync(~0u, (int)(threadIdx.x >> 7), 0); c.w = __shfl_sync(~0u, (int)((threadIdx.x >> 5) & 3), 0);
  char* own = c.mail + (uint32_t)(c.w * M_REG + M_E3 + (c.r >> 5) * 8192 + (c.r & 31) * 128 + (threadIdx.x & 31) * 4);
  uint32_t i0 = 0, i1 = 0;
  if (EARLY) asm volatile("{ .reg .pred p; setp.ne.u32 p, %4, 0; @p atom.relaxed.gpu.global.exch.b32 %0, [%2], %3; @p atom.relaxed.gpu.global.exch.b32 %1, [%2 + 4096], %3; }"
               : "+r"(i0), "+r"(i1) : "l"(own), "r"(SENT), "r"((uint32_t)(c.m == 2 && c.r < 128)) : "memory");
#pragma unroll
  for (int g = 0; g < 3; g++) {
    const int i = c.m * 4 + c.w;
    if (g < 2 || i < B_END - 32)
      asm volatile("{ .reg .pred p; elect.sync _|p, 0xffffffff; @p mbarrier.init.shared::cta.b64 [%0], %1; }"
                   :: "r"(BAR(g * 16 + i)), "r"(0x19080401u >> (bar_codes(g) >> 2 * i & 3) * 8 & 255) : "memory");
  }
  asm volatile("fence.mbarrier_init.release.cluster;" ::: "memory");
  __syncthreads();
  asm volatile("barrier.cluster.arrive.relaxed.aligned;" ::: "memory");

  if (c.r >= 128) {
    fft_cols((float2*)smraw, c.r - 128, &twr, &twi, &tzs);
    if ((threadIdx.x & 127) == 0) TL(7);
    __syncwarp();
  } else if (c.m == 3) {
    asm volatile("setmaxnreg.dec.sync.aligned.u32 %0;" :: "n"(REG_H));
    c.lane = lane_id();
    if (c.sb & 1023) asm volatile("trap;");
    const int col = c.h * 128 + c.a * 64, eq = E3M ? c.w & 1 : c.w >> 1, eh = E3M == 1 ? (c.w >> 1) ^ 1 : E3M ? c.w >> 1 : c.w & 1;
    uint32_t tl = clock_lo();
    TR(-2, 3);
    if (c.w == 0) {
      if (START) delay_until(tl + START);
      if (HOLD == 2) mbar_wait(BAR(B_PROBE), 0);
      if (HOLD == 3) mbar_wait(BAR(B_SEL), 0);
      if (HOLD == 1) mbar_wait(BAR(B_PROBE), 0);
      TR(-2, 4);
      tl = clock_lo();
      mbar_expect_e(BAR(B_PFULL), 2 * NP * 2048);
      mbar_expect_e(BAR(B_WFULL), (48 - NP) * 2048);
      mbar_expect_e(BAR(B_WFULL + 1), (48 - NP) * 2048);
    }
    auto dst_x = [&](int e, int w) {
      const uint32_t g2 = 2 * c.a + (w >> 1), u = w & 1;
      return M_KVQ + c.h * 24576 + (e == 0 ? 8192 + (2 * u + c.b) * 2048 + g2 * 512 : e == 1 ? g2 * 2048 + u * 1024 + c.b * 128 : 16384 + c.b * 4096 + g2 * 512 + u * 256);
    };
    if (c.w == 0) {
      tl += PACE0;
#pragma unroll wunr
      for (int i = 0; i < 24; i++) {
        const int m = i < 4 || i >= 16, k = i < 4 ? i : m ? i - 12 : i - 4;
        const int row = c.b * 512 + m * 256;
        const uint32_t st = c.sb + m * ST_WG, bar = BAR(k < 3 ? B_PFULL : B_WFULL + m);
        if (PACE) delay_until(tl += PACE);
        if (i == 14) { mbar_idle(BAR(B_FREE), 0); if (c.lane == 0) TL2(2); __syncwarp(); }
        if (k < 11) TMA_W(k < 3 ? c.sb + SM_POOL + m * NP * 2048 + k * 8192 : k == 3 ? c.sb + SM_HV + (m * NHV + 1) * 2048 : st + (k - 4) * 8192,
                          k == 3 || k > 8 ? &tv : (k >> 2 & 1) == m ? &tk : &tq, col, row + (k < 8 ? k & 3 : (k - 9) & 3) * 64, bar);
        else {
#pragma unroll 1
          for (int j = 8; j < 12; j++) TMA_W(j < NV ? st + (32 - NP + j) * 2048 : c.sb + SM_HV + m * NHV * 2048, &tv16, col, row + j * 16, bar);
        }
      }
      TR(-2, 7);
    } else if (c.w == 2) {
      const unsigned short* mp = (const unsigned short*)mem0 + (2 * (c.lane & 3)) * D_ + 8 * c.r + (c.lane >> 2);
      uint32_t mv = (uint32_t)mp[0] | (uint32_t)mp[D_] << 16;
      if (mv == SENT) mv = 0x7FFF7FFFu;
      mbar_idle(BAR(B_PROBE), 0);
      char* dst = c.mail + (uint32_t)(M_E3 + (c.r >> 5) * 8192 + (c.r & 31) * 128 + c.lane * 4);
      st_pub(dst, mv); st_pub(dst + 4096, mv);
    } else if (c.w == 3) {
      mbar_idle(BAR(B_FREE), 0);
      mbar_idle(BAR(B_PFULL), 0);
      mbar_expect_e(BAR(B_PFULL), 65536);
      for (int i = 0; i < 2; i++) tma4d_e(c.sb + SM_XT + i * 16384, &tx, c.b * 8, 4 + 2 * (c.b ^ i), BAR(B_PFULL));
    }
    {
      mbar_idle(BAR(B_SEL), 0);
      const int i = tid_now() & 127, sl = i & 3, e = (i >> 2) & 3;
      uint32_t ox = dst_x(e, i >> 5) + sl * M_REG;
      uint32_t oh = e & 1 ? (sl ^ (e & 2)) * M_REG + M_E3 + (c.r >> 5) * 8192 + (c.w & 1) * 4096 + (c.r & 31) * 128
                          : near_page(c, c.r, e ? sl * M_REG + M_E3 + (c.b * 2 + eq) * 8192 : box(~sl & 1, c.r)) + (e ? eh * 2048 : c.w * 1024), of;
      {
        const int e = i & 7, w = (i >> 3) & 3, m = (i >> 5) & 1, sl = i >> 6;
        const int cta = e < 2 ? c.r & ~1 : e == 2 ? c.r | 1 : e == 3 ? c.h * 4 + 2 * m + 1 : c.j * 32 + m * 8 + 2 * w + (e & 2) * 8 + (e & 1);
        const uint32_t off = e < 2 ? c.b * 2048 + m * 1024 + (w >> 1) * 512 + e * 160 : e == 2 ? c.b * 2048 + m * 1024 + w * 256 : e == 3 ? w * 256 : c.h * 128;
        of = (e < 4 ? e1_box(c, sl, cta) : near_page(c, cta, box(sl, cta))) + off;
      }
      char *px = c.mail + ox, *ph = c.mail + oh, *pf = c.mail + of;
      uint32_t at = sl * 128 + (i >> 5) * 32 + e * 8, af = i * 8;
      pin(px); pin(ph); pin(pf); pin(at); pin(af);
      asm volatile("barrier.cluster.wait;" ::: "memory");
      TR(-2, 0);
      mbar_idle(BAR(B_WREAD), 0);
      TR(-2, 1);
      mbar_arrive_both(BAR(B_LFREE), c.b ^ 1);
      sts64(at + (c.sb + SM_TAB + 1536), (uint32_t)(uintptr_t)px, (uint32_t)((uintptr_t)px >> 32));
      sts64(at + (c.sb + SM_TAB + 1024), (uint32_t)(uintptr_t)ph, (uint32_t)((uintptr_t)ph >> 32));
      sts64(af + (c.sb + SM_TAB), (uint32_t)(uintptr_t)pf, (uint32_t)((uintptr_t)pf >> 32));
      TR(-2, 2);
      if (tid_now() == 384) TL2(25);
      __syncwarp();
      bar_sync(14, 160);
    }
    pad<PAD3>();
    for (int s = -1; s < NSEG; s++) {
      if (E30 ? s != 0 : s >= 0) {
        const uint32_t tab = c.sb + SM_TAB + 1024 + (max(s, 0) & 3) * 128 + c.w * 32;
        uint32_t t0;
        if (s > 0) {
          const uint32_t ln = tid_now() & 31;
          const uint4 ta = lds128(tab);
          const char* src = mk_ptr(ta.x | ln * 4, ta.y);
          char* dst = mk_ptr(ta.z | ln * 4, ta.w);
          const uint32_t tg = (s - 1) >> 1, chk = (ln & 3) ? 0u : 1u, red = ln * (RED_L == 3 ? 4 : 8);
          touch(src, dep(c.sb, chk, c.sb)); touch(dst, dep(c.sb, red, c.sb));
          mbar_wait(BAR(B_E2TRIG), (s - 1) & 1);
          TR(s, 0);
          if (ANCH2) delay_fine(lds32(c.sb + SM_SUM + 64) + DLY_E2); else delay_cycles(DLY_E2);
          uint32_t n = 0;
          while (true) {
            uint32_t v[8];
#pragma unroll
            for (int i = 0; i < 8; i++) v[i] = ld_poll1(src + i * 128);
            if (E2_F) sched_fence(c.sb);
            const uint32_t bad = RED_T ? (stale2(v[0], v[1], tg) | stale2(v[2], v[3], tg) | stale2(v[4], v[5], tg)) | stale2(v[6], v[7], tg)
                                       : stale1(stale1(stale2(v[0], v[1], tg), v[2], tg), v[3], tg) | stale1(stale1(stale2(v[4], v[5], tg), v[6], tg), v[7], tg);
            const bool ok = all_clear(bad, chk);
#pragma unroll
            for (int l = 0; l < RED_L; l++)
#pragma unroll
              for (int i = 0; i < (4 >> l); i++) v[i] = add_bf16x2(v[2 * i], v[2 * i + 1]);
            if (RED_L == 3) sts32(red + (c.sb + SM_RED + c.w * 128), v[0]);
            else {
              float lo[8], hi[8];
#pragma unroll
              for (int i = 0; i < (8 >> RED_L); i++) { lo[i] = __uint_as_float(v[i] << 16); hi[i] = __uint_as_float(v[i] & 0xFFFF0000u); }
#pragma unroll
              for (int l = RED_L; l < 3; l++)
#pragma unroll
                for (int i = 0; i < (4 >> l); i++) { lo[i] = lo[2 * i] + lo[2 * i + 1]; hi[i] = hi[2 * i] + hi[2 * i + 1]; }
              sts64(red + (c.sb + SM_RED + c.w * 256), __float_as_uint(lo[0]), __float_as_uint(hi[0]));
            }
            if (ok) break;
            n++; CNT(0);
          }
          bar_sync(NB_HELP, 128);
          const uint32_t rd = red + (c.sb + SM_RED);
          if (!RED_P || c.w < 2) {
            if (RED_L == 3) st_pub_if(dst, sum4(lds32(rd), lds32(rd + 128), lds32(rd + 256), lds32(rd + 384)), c.w < 2);
            else {
              const uint2 p0 = lds64(rd), p1 = lds64(rd + 256), p2 = lds64(rd + 512), p3 = lds64(rd + 768);
              st_pub_if(dst, pack_bf16((__uint_as_float(p0.x) + __uint_as_float(p1.x)) + (__uint_as_float(p2.x) + __uint_as_float(p3.x)),
                                       (__uint_as_float(p0.y) + __uint_as_float(p1.y)) + (__uint_as_float(p2.y) + __uint_as_float(p3.y))), c.w < 2);
            }
          }
          t0 = clock_lo();
          mbar_arrive_warp(BAR(B_PUB));
          TRV(s, 15, n);
          mbar_wait(BAR(B_SPFREE), (s - 1) & 1);
        } else {
          if (tid_now() == 384) TL2(24);
          __syncwarp();
          if (!E30) mbar_wait(BAR(B_PROBE), 1);
          if (!WO_S) mbar_wait(BAR(B_WOFULL), 0);
          if (tid_now() == 384) TL2(19);
          __syncwarp();
          t0 = clock_lo() - DLY_E3;
        }
        TRV(s, 1, t0);
        {
          const uint32_t l16 = (tid_now() & 31) * 16, dst = vary(l16, s, c.sb) + (c.sb + SM_MEM + eh * 4096 + eq * 2048);
          const uint4 tb = lds128(tab + 16);
          st_pub_if(mk_ptr(tb.z | l16 >> 2, tb.w), SENT, c.w >= 2);
          const char* src = mk_ptr(tb.x | l16, tb.y);
          touch(src, dep(c.sb, dst, c.sb));
          delay_fine(t0 + (DLY_E3 + eh * DLY_E3B));
          uint32_t n = 0;
          while (true) {
            uint4 v[4];
#pragma unroll
            for (int i = 0; i < 4; i++) v[i] = ld_poll(src + i * 512);
#pragma unroll
            for (int i = 0; i < 4; i++) sts128(dst + i * 512, v[i]);
            if (arrive_if_all(max(max(v[0].x, v[1].x), max(v[2].x, v[3].x)) != SENT, NB_MEM + eh * 2 + eq, 160)) break;
            n++; CNT(1);
          }
          TR(s, 2); TRV(s, 14, n);
        }

        if (s == 1) CLK(1); if (s == 8) CLK(2); if (s == 56) CLK(3);
        if (c.w == 2 && s == 15) TRSYNC(8);
        if (c.w == 2 && s == 21) TRSYNC(10);
      }
      const int g = s + 1;
      auto load_v = [&]() {
        if (V_TMA && c.w == V_W) {
          mbar_expect_e(BAR(B_VFULL), (K_TMA ? 16384 : 8192) + (Q_TMA ? 2048 : 0));
          const char* src = c.mail + (uint32_t)(M_KVQ + (min(g, XEND - 1) & (NSLOT - 1)) * M_REG + c.h * 24576);
          bulk_load_e(c.sb + SM_V, src + 8192, 8192, BAR(B_VFULL));
          if (K_TMA > 1) delay_cycles(K_TMA);
          if (K_TMA) bulk_load_e(c.sb + SM_K, src, 8192, BAR(B_VFULL));
          if (Q_TMA > 1) delay_cycles(Q_TMA);
          if (Q_TMA) bulk_load_e(c.sb + SM_Q, src + (16384 + c.j * 2048), 2048, BAR(B_VFULL));
        }
      };
      if (XEND < NSEG && g >= XEND && g < NSEG) { mbar_wait(BAR(B_SC), s & 1); load_v(); }
      if (g < XEND) {
        const uint32_t tx_ = c.sb + SM_TAB + 1536 + (g & 3) * 128 + c.w * 32, tag = (g >> 2) & 1;
        if (c.w == 0) mbar_expect_e(BAR(B_LAND), EXP_PEER * 12288);
        auto load_x = [&]() {
          if (c.w == 3 && g + 1 < XEND) {
            mbar_wait(BAR(B_XEMPTY), g & 1);
            mbar_expect_e(BAR(B_XFULL), 16384 * EXP_NXT);
            for (int i = 0; i < EXP_NXT; i++) tma4d_e(c.sb + SM_XT + i * 16384, &tx, c.b * 8, (g + 1) * 4 + 2 * (c.b ^ i), BAR(B_XFULL));
          }
        };
        if (X_AT == 0 && g > 0) load_x();
        TR(s, 6);
        if (E30 && g == 0) mbar_idle(BAR(B_PROBE), 1);
        mbar_wait(BAR(B_LAND), g & 1);
        TR(s, 7);
        if (DLY_F && g > 0) delay_cycles(DLY_F);
        auto total = [&](int w, int lane, uint32_t o0, uint32_t o1) {
          const uint32_t a = c.sb + SM_LAND + land_off(w, lane);
          if (EXP_FL == 1) return make_uint4(a, a, a, a);
          const uint4 t = add4(lds128(a + o0), lds128(a + o1 + 2048));
          const uint32_t a2 = dep(dep(a, t.x ^ t.y ^ t.z, c.sb), t.w, c.sb);
          return add4(t, add4(lds128(a2 + o0 + 4096), lds128(a2 + o1 + 6144)));
        };
        auto get = [&](int e) {
          const int ln = tid_now() & 31;
          return e == 0 ? total(c.w, ln, 16384, 16384)
               : e == 1 ? total((c.w & 2) + ((ln >> 1) & 1), (ln & 1) * 16 + (c.w & 1) * 8 + (ln >> 2), 8192, 0)
                        : total((c.w & 2) + ((ln >> 1) & 1), (ln & 1) * 16 + (ln >> 3) * 4 + (c.w & 1) * 2 + ((ln >> 2) & 1), 0, 8192);
        };
        auto put = [&](int e, uint4 v) {
          const int ln = tid_now() & 31;
          const uint2 d = lds64(tx_ + e * 8);
          if (e < 2) {
            v.x = tagged(v.x, tag);
            st_pub4(mk_ptr(d.x | (e ? (ln & 24) * 32 + (ln & 7) * 16 : ln * 16), d.y), v);
          } else {
            char* dst = mk_ptr(d.x | ((ln & 7) * 16 + (ln >> 3) * 4), d.y);
            const uint32_t bit = ln < 8;
            st_pub(dst, put_tag(v.x, bit, tag)); st_pub(dst + 128, put_tag(v.y, bit, tag));
            st_pub(dst + 2048, put_tag(v.z, bit, tag)); st_pub(dst + 2176, put_tag(v.w, bit, tag));
          }
        };
        auto after_sc = [&]() { if (g > 0) { mbar_wait(BAR(B_SC), s & 1); if (DLY_FK) delay_cycles(DLY_FK); if (X_AT == 1) load_x(); } };
        if (FIN_AT == 5) {
          put(0, get(0));
          if (DLY_F2 && g > 0) delay_cycles(DLY_F2); else sched_fence(c.sb);
          const uint4 k = get(1);
          sched_fence(c.sb);
          const uint4 q = get(2);
          if (g > 0) mbar_wait(BAR(B_VST), s & 1);
          put(1, k); put(2, q);
          TR(s, 5);
          mbar_arrive_both(BAR(B_LFREE), c.b ^ 1);
          after_sc();
          load_v();
          continue;
        }
        if (FIN_AT < 3) {
          if (EXP_FIN & 1) put(0, get(0));
          TR(s, 3);
          if (FIN_AT == 1) after_sc();
          if (V_TMA == 1) load_v();
          if (EXP_FIN & 2) put(1, get(1));
        } else {
          const uint4 v = get(0);
          sched_fence(c.sb);
          const uint4 k = get(1);
          if (g > 0) { mbar_wait(BAR(B_VST), s & 1); if (DLY_FS) delay_cycles(DLY_FS); }
          put(0, v); put(1, k);
        }
        TR(s, 4);
        if (FIN_AT == 4) {
          const uint4 q = get(2);
          after_sc();
          load_v();
          put(2, q);
        } else {
          if (FIN_AT >= 2) after_sc();
          if (V_TMA == 2) load_v();
          if (EXP_FIN & 4) put(2, get(2));
        }
        mbar_arrive_both(BAR(B_LFREE), c.b ^ 1);
        if (V_TMA == 3) load_v();
        TR(s, 5);
        if (!FIN_AT && X_AT && g > 0) { mbar_wait(BAR(B_SC), s & 1); if (DLY_FK) delay_cycles(DLY_FK); load_x(); }
      }
    }
    const int tile = tile_of(c), s0 = (tile >> 3) * 4, n0 = (tile & 7) * 128;
    if (c.w == 1) {
      mbar_idle(BAR(B_PVDONE), 0);
      count_e(g_ctl + (EARLY2 ? C_LAST : C_EARLY));
      st_pub(c.mail + (uint32_t)((tid_now() & 6) * (M_REG / 2) + M_SEL + (tid_now() & 1) * 4096 + c.r * 4), 0);
      await_count(g_ctl + C_COLS, 4);
      if (K_TMA) mbar_idle(BAR(B_SC), 1);
      mbar_expect_e(BAR(B_TW), 8192);
      bulk_load_e(c.sb + SM_TW, g_tw, 8192, BAR(B_TW));
    } else if (c.w == 2) {
      const uint32_t ln = tid_now() & 31, rel = mapa(BAR(B_GEMPTY) + (ln >> 2) * 8, ln & 1);
      mbar_idle(BAR(B_VST), 1); mbar_idle(BAR(PRE_AT), 1);
      arrive_remote_if(rel, ln < 12);
      mbar_idle(BAR(B_E2TRIG), 1);
      if (GATE) mbar_wait(BAR(B_DONE), 0);
      arrive_remote_if(rel, ln >= 12 && ln < 20);
    } else {
      auto ahead = [&](int k) {
        if (c.w) { if (PF_A && (k & 3) == (tile >> 1 & 3)) prefetch3d_e(&ta, k * 32, s0 + 2 * c.b); }
        else if (PF_B && (k & 7) == (tile >> 4)) prefetch2d_e<(ONCE & 512) != 0>(&tw, n0 + (tile & 8) * 8, k * 64);
      };
#pragma unroll 1
      for (int k = 0; k < PF_D; k++) ahead(k);
      if (c.w == 3) await_count(g_ctl + C_EARLY, 128);
      const int skew = tile < 120 ? 0 : SKEW;
      uint32_t o = SM_XT, st = 0, ph = 0;
#pragma unroll 1
      for (int kb = 0; kb < 64 + skew; kb++, o = next_stage(o)) {
        const bool solo = kb < skew || kb >= 64;
        const uint32_t bar = BAR(B_GFULL + st), k = kb & 63;
        if (c.w && kb == skew) {
          if (tile >= 120) await_count(g_ctl + C_LAST, EARLY2 ? 640 : 512);
          if (tid_now() == 480) TL(10);
          __syncwarp();
        }
        mbar_wait(BAR(B_GEMPTY + st), ph);
        if (c.w) {
          const int r = solo ? (kb >> 5) + c.b : c.b * 2;
          tma3d_mc_e(c.sb + o + r * 4096, solo ? &ta32 : &ta, k * 32, s0 + r, bar);
        } else {
          mbar_expect_e(bar, solo ? 24576 : 32768);
          tma2d_o<(ONCE & 2) != 0>(c.sb + o + 16384, &tw, n0, k * 64, bar);
          tma2d_o<(ONCE & 2) != 0>(c.sb + o + 24576, &tw, n0 + 64, k * 64, bar);
        }
        if (kb + PF_D < 64) ahead(kb + PF_D);
        if (++st == 5) { st = 0; ph ^= 1; }
      }
    }
    return;
  } else if (c.m == 2) {
    asm volatile("setmaxnreg.dec.sync.aligned.u32 %0;" :: "n"(512 - 2 * REG_F - REG_H));
    c.lane = lane_id();
    {
      uint32_t tl = clock_lo() + (PACE0 + WO_AT * PACE);
      TR(-2, 0);
      sched_fence(i0 ^ i1);
      TR(-2, 7);
      int far1 = 0;
#pragma unroll 1
      for (int rep = EARLY; rep <= NPROBE; rep++) {
        const int lag = race_init(own + (rep & 1) * 4096, own + (~rep & 1) * 4096, SENT);
        if (rep) far1 += ((rep ^ c.r >> 5) & 1 ? 1 : -1) * min(lag, 200);
      }
      sts32(c.sb + SM_SEL + 512 + c.w * 4, (8 + far1 / (16 * NPROBE)) << 4 * c.w);
      TR(-2, 1);
      if (tid_now() == 256) TL2(14);
      __syncwarp();
      mbar_arrive_warp(BAR(B_PROBE));
      if (c.w == 0) {
        mbar_idle(BAR(B_PROBE), 0);
        const uint4 bits = lds128(c.sb + SM_SEL + 512);
        const uint32_t res = bits.x | bits.y | bits.z | bits.w;
        st_pub_if(c.mail + (uint32_t)((c.lane & 6) * (M_REG / 2) + M_SEL + (c.lane & 1) * 4096 + c.r * 4), res | tile_key(), c.lane < 8);
        const int q = (res >> 4 * ((c.lane + c.r) & 3) & 15) - 8, best = __reduce_max_sync(~0u, abs(q) * 64 + (c.lane & 3) * 16 + ((c.lane + c.r) & 3) * 2 + (q <= 0));
        const char* src = c.mail + (uint32_t)((best & 6) * (M_REG / 2) + M_SEL + (best & 1) * 4096 + c.lane * 16);
        if (SEL_AT) delay_until(tl - (PACE0 + WO_AT * PACE - SEL_AT));
        uint4 v; uint32_t n = 0;
        TR(-2, 4);
        while (true) {
          delay_cycles(DLY_SEL);
          TR(-2, 6);
          v = ld_poll(src);
          if (__all_sync(~0u, v.x && v.y && v.z && v.w)) break;
          watchdog(n, POLL_LIMIT);
        }
        TR(-2, 5);
        int ta = 0, tb = 0, pa = 0, pb = 0;
        uint32_t flip = 0;
#pragma unroll 1
        for (int i = 0; i < 4; i++) {
          const int a = (v.x >> 4 * i & 15) + (v.y >> 4 * i & 15) - 16, b = (v.z >> 4 * i & 15) + (v.w >> 4 * i & 15) - 16;
          const bool f = __reduce_add_sync(~0u, a * ta + b * tb) < 0;
          ta += f ? -a : a; tb += f ? -b : b; flip |= (uint32_t)f << i;
        }
#pragma unroll 1
        for (uint32_t g = 0; g < 8; g++) {
          const bool a = (v.x >> 16) - g * 256 < 120, b = (v.z >> 16) - g * 256 < 120;
          const int n = __reduce_add_sync(~0u, (a ? ta : 0) + (b ? tb : 0)) > 0 ? PRIOR : -PRIOR;
          if (a) pa = n;
          if (b) pb = n;
        }
        const uint32_t ka = AWARE && ta + pa > 0 ? ~flip : flip, kb = AWARE && tb + pb > 0 ? ~flip : flip;
        sts128(c.sb + SM_SEL + c.lane * 16, make_uint4(ka, ka, kb, kb));
        mbar_arrive_warp(BAR(B_SEL));
        const uint32_t key = __shfl_sync(~0u, c.a ? v.z : v.x, c.h);
        const int u = __popc(__ballot_sync(~0u, v.x < key)) + __popc(__ballot_sync(~0u, v.z < key));
        sts32(c.sb + SM_SEL + 528, (u & 32) * 2 + (u & 7) * 8 + (u >> 2 & 6) + c.b);
        TR(-2, 2);
        if (c.lane == 0) TL2(13);
        __syncwarp();
        bar_sync(14, 160);
        if (ZDLY) delay_cycles(ZDLY);
#pragma unroll 4
        for (int k = c.lane >> 3; k < (ZINIT ? 128 : 0); k += 4) {
          const int e = k & 7;
          const uint2 d = lds64(c.sb + SM_TAB + (e == 3 ? k - 1 : k) * 8);
          st_pub4(mk_ptr((d.x & ~127u) + (e < 2 ? (k & 8) * 32 : e == 3 ? 128 : 0) + (c.lane & 7) * 16, d.y), make_uint4(0, 0, 0, 0));
        }
        __syncwarp();
        if (c.lane < 4) asm volatile("mbarrier.arrive.shared::cta.b64 _, [%0];" :: "r"(BAR(B_PROBE)) : "memory");
        __syncwarp();
        TR(-2, 8);
      }
      if (c.w == 2) {
        mbar_idle(BAR(B_P1), 0);
        if (P1_AT) { mbar_idle(BAR(B_WFULL), 0); mbar_idle(BAR(B_WFULL + 1), 0); }
        st_pub_if(g_ctl + C_COLS + (c.r & 15) * 32 + c.lane, 0, c.r < (C_END - C_COLS) / 32);
        count_e(g_ctl + C_P1);
        TR(-2, 3);
      }
      if (c.w == 1) for (int i = 0; i < WO_N; i++) { delay_until(tl += WO_P * PACE); prefetch2d_e(&to, c.j * 256 + (i ^ WO_X) * 64, c.h * 128); }
      if (c.w == 3) {
        mbar_idle(BAR(B_WREAD0), 0);
        for (int i = 0; i < 2; i++) tma4d_e(c.sb + SM_WO + i * 16384, &tx, c.b * 8, 2 * (c.b ^ i), BAR(B_PFULL));
        mbar_expect_e(BAR(B_WOFULL), 65536);
#pragma unroll 1
        for (int i = 3; i >= 0; i--) {
          if (i & 1) mbar_idle(BAR(i < 2 ? B_XEMPTY : B_WREAD), 0);
          TMA_O(c.sb + SM_WO + i * 16384, &to, c.j * 256 + i * 64, c.h * 128, BAR(B_WOFULL));
        }
      }
    }
    asm volatile("barrier.cluster.wait;" ::: "memory");
    const int g = c.w, src0 = c.h * 4 + (g >> 1) * 2;
    mbar_wait(BAR(B_SEL), 0);
    c.sel = __shfl_sync(~0u, (e1_box(c, 0, src0 + (c.lane >> 5)) & 4096) | (e1_box(c, 1, src0) & 4096) * 2, 0);
    mbar_wait(BAR(B_WREAD), 0);
    uint32_t l16 = c.sb + g * 512 + c.lane * 16;
    auto lane = [&](uint32_t v) { l16 = dep(l16, v, c.sb); return (int)((l16 & 511) >> 4); };
    pad<PAD2>();
    for (int s = 0; s < NSEG; s++) {
      l16 = vary(l16, s, c.sb);
      int ln = (l16 & 511) >> 4;
      uint4 kf[4], qx;
      auto load_x = [&]() {
        if (X_AT >= 2 && g == X_W && s + 2 < XEND) {
          if (KL_AT != 2) mbar_wait(BAR(B_XEMPTY), ~s & 1);
          if (DLY_XL) delay_cycles(DLY_XL);
          mbar_expect_e(BAR(B_XFULL), 16384 * EXP_NXT);
          for (int i = 0; i < EXP_NXT; i++) tma4d_e(c.sb + SM_XT + i * 16384, &tx, c.b * 8, (s + 2) * 4 + 2 * (c.b ^ i), BAR(B_XFULL));
        }
      };
      {
        const int gs = min(s, XEND - 1);
        const char* pk = c.mail + (uint32_t)(M_KVQ + (gs & (NSLOT - 1)) * M_REG + c.h * 24576 + g * 2048 + ln * 16);
        const char* pq = pk + (16384 + c.j * 2048 - g * 1536);
        const uint32_t tg = (gs / NSLOT) & 1;
        touch(pk, c.sb); touch(pq, c.sb);
        TR(s, 0);
        mbar_wait(BAR(B_VFULL), s & 1);
        TR(s, 1);
        uint4 k[4];
        auto load_k = [&]() {
          if (Q_TMA && Q_AT == 0) qx = lds128(l16 + SM_Q);
          if (DLY_K) delay_cycles(DLY_K);
#pragma unroll
          for (int t = 0; t < 4; t++) k[t] = lds128(l16 + (g * 1536 + SM_K + t * 512));
          if (Q_TMA && Q_AT == 1) qx = lds128(l16 + SM_Q);
        };
        if (K_TMA && KL_AT == 1) load_k();
        if (Q_TMA && Q_AT == 2) qx = lds128(l16 + SM_Q);
        if (s > 0) mbar_wait(BAR(B_PUB), (s - 1) & 1);
        if (K_TMA) {
          if (!Q_TMA) qx = ld_poll(pq);
          if (KL_AT == 2) { mbar_spin_if(BAR(B_XEMPTY), ~s & 1, s + 1 < XEND); load_x(); }
          if (KL_AT != 1) load_k();
        }
        for (uint32_t n = 0; ; ) {
          if (!K_TMA) {
#pragma unroll
            for (int t = 0; t < 4; t++) k[t] = ld_poll(pk + t * 512);
            qx = ld_poll(pq);
          }
#pragma unroll
          for (int t = 0; t < 2; t++) {
            auto cp = [&](uint32_t v) { return dep(v, 0, c.sb); };
            kf[t] = make_uint4(cp(k[2 * t].x), cp(k[2 * t].y), cp(k[2 * t + 1].x), cp(k[2 * t + 1].y));
            kf[2 + t] = make_uint4(cp(k[2 * t].z), cp(k[2 * t].w), cp(k[2 * t + 1].z), cp(k[2 * t + 1].w));
          }
          if (all_clear(stale1(stale2(k[0].x, k[1].x, tg) | stale2(k[2].x, k[3].x, tg), qx.x, tg), EXP_CHK)) break;
          watchdog(n, POLL_LIMIT); CNT(4);
          if (K_TMA) {
#pragma unroll
            for (int t = 0; t < 4; t++) k[t] = ld_poll(pk + t * 512);
            qx = ld_poll(pq);
          }
        }
        TR(s, 2);
      }
      if (KL_AT != 2 && !LX_AT) load_x();
      ln = lane(kf[0].y);
      const char* pa = c.mail + (uint32_t)(box(s & 1, src0) + 8192 + (c.sel >> (s & 1) & 4096) + (g & 1) * 512 + (EXP_LIN ? ln * 16 : read_off(ln)));
      const uint32_t spw = c.sb + SM_SP + g * 1280 + (ln & 3) * 64 + ((((ln >> 3) ^ ln) & 2) << 4) + (ln & 4) * 4 + (ln & 8),
                     spr = c.sb + SM_SP + (ln & 4) * 80 + (ln >> 3) * 64 + (((ln & 3) ^ ((ln >> 3) & 2)) << 4), l8 = ln * 8;
      const uint32_t tg = s >> 1;
      float sx[2][4];
      uint32_t sm;
      uint4 km;
      auto causal = [&](uint32_t (&sc)[5], int l) {
        const int n = l >> 2, lim = 16 * (8 * c.j + (n & 4) + 2 * (n & 1) + ((n >> 1) & 1) - 2 * (l & 3) + 1);
#pragma unroll
        for (int w = 0; w < 4; w++) {
          uint32_t m; asm("shl.b32 %0, 0xffffffff, %1;" : "=r"(m) : "r"(max(lim - 128 * w, 0)));
          sc[1 + w] = (sc[1 + w] & ~m) | (0xD029D029u & m);
        }
      };
      auto put_rows = [&]() {
        if (s == 0) return;
        const int n = ln >> 2;
        *(uint4*)(g_ox + ox_at(s - 1, 8 * c.j + (n & 4) + 2 * (n & 1) + ((n >> 1) & 1), c.h * 4 + g, ln & 3)) = lds128((l16 ^ (ln & 24) * 2) + SM_OX);
        mbar_arrive_warp(BAR(B_PVDONE));
      };
      if (OX_AT == 1) put_rows();
      if (SXP) {
        scores_x<false>(sx, kf, qx, 0);
        if (DLY_SA) { sched_fence(dep(c.sb, __float_as_uint(sx[1][0]), c.sb)); delay_cycles(DLY_SA); }
        store_scores(sx, spw + (SM_K - SM_SP + g * 768));
        if (LX_AT == 1) load_x();
        if (OX_AT == 2) put_rows();
        if (DLY_SB) delay_cycles(DLY_SB);
        bar_sync(NB_ATT, 128);
        if (SXP >= 3) {
          const uint32_t t4 = (l16 - c.sb) >> 2, a = (t4 & 64) * 5 + ((t4 & 60) ^ (t4 >> 3 & 32)) + (t4 >> 1 & 192) + (c.sb + SM_K);
          const uint32_t t = add_bf16x2(add_bf16x2(add_bf16x2(lds32(a), lds32(a + 2048)), lds32(a + 4096)), lds32(a + 6144));
          const int lim = (int)((t4 >> 2 & 64) + (t4 >> 3 & 16) + (t4 >> 1 & 32) - (t4 * 2 & 96) - (t4 * 32 & 384)) + (128 * c.j + 16);
          uint32_t m; asm("shl.b32 %0, 0xffffffff, %1;" : "=r"(m) : "r"(max(lim, 0)));
          uint32_t y = (t & ~m) | (0xD029D029u & m);
          if (SXP == 4) {
            const float y0 = __uint_as_float(y << 16), y1 = __uint_as_float(y & 0xFFFF0000u);
            float mx = fmaxf(y0, y1);
            if (RDX) {
              int k = __float_as_int(mx); k ^= k >> 31 & 0x7FFFFFFF;
              const int k0 = __reduce_max_sync(~0u, t4 & 64 ? INT32_MIN : k), k1 = __reduce_max_sync(~0u, t4 & 64 ? k : INT32_MIN);
              k = t4 & 64 ? k1 : k0; mx = __int_as_float(k ^ (k >> 31 & 0x7FFFFFFF));
            } else {
#pragma unroll
              for (int d = 1; d < 16; d *= 2) mx = fmaxf(mx, __shfl_xor_sync(~0u, mx, d));
            }
            mx *= -SCL;
            y = pack_bf16(ex2(fmaf(y0, SCL, mx)), ex2(fmaf(y1, SCL, mx)));
            sts32((t4 >> 4 & 28) + (c.sb + SM_Q + 512), __float_as_uint(mx));
          }
          sts32(t4 + (c.sb + SM_Q), y);
        } else {
        const uint32_t ax = spr + (SM_K - SM_SP);
        uint4 t = add4(lds128(ax), lds128(ax + 2048));
        const uint32_t ay = SXP == 2 ? dep(ax, t.x, c.sb) : ax;
        t = add4(add4(t, lds128(ay + 4096)), lds128(ay + 6144));
        uint32_t sc[5] = {0, t.x, t.y, t.z, t.w};
        causal(sc, ln);
        sts128(l16 + SM_OX, make_uint4(sc[1], sc[2], sc[3], sc[4]));
        }
      }
      if (OX_AT == 3) { if (DLY_O) delay_cycles(DLY_O); put_rows(); }
      touch(pa, c.sb);
      mbar_wait(BAR(B_E1TRIG), s & 1);
      const uint32_t t0 = clock_lo();
      TRV(s, 3, t0);
      if (!SXP) {
        scores_x<false>(sx, kf, qx, 0);
        store_scores(sx, spw + 640);
      }
      if (DLY_E1) delay_fine(t0 + DLY_E1);
      uint32_t nr = 0;
      while (true) {
        const uint4 q0 = ld_poll(pa), q1 = ld_poll(pa + 2048), k0 = ld_poll(pa + 1024), k1 = ld_poll(pa + 3072);
        uint4 qm = add4(q0, q1);
        const uint32_t bq = stale2(q0.x, q1.x, tg);
        qm.x = dep(qm.x, bq, c.sb);
        scores_x<SC_F>(sx, kf, qm, c.sb);
        const uint32_t bk = stale2(k0.x, k1.x, tg);
        km = add4(k0, k1);
        km.x = dep(km.x, bk, c.sb);
        const bool ok = all_clear(bq | bk, 1);
        sm = scores_m(qm, km);
        store_scores(sx, spw);
        if (ok) break;
        nr++; CNT(2);
      }
      sts32(l8 + (c.sb + SM_SPM + (g >> 1) * 256 + (g & 1) * 4), sm);
      bar_sync(NB_ATT, 128);
      TR(s, 5); TRV(s, 13, nr);
      float o[2][4];
      uint32_t sp[5];
      uint4 vf[4];
      load_scores(sp, spr, l8 + (c.sb + SM_SPM));
      const uint32_t m5 = max5(sp);
      uint32_t m1;
      float off = row_off(m5, m1), f[10];
      l16 = dep(l16, VF_AT ? m1 : m5, c.sb);
#pragma unroll
      for (int t = 0; t < 4; t++) vf[(t >> 1) + 2 * (t & 1)] = lds128(l16 + SM_V + ((t >> 1) + 2 * (t & 1)) * 2048);
      qx.x = dep(qx.x, sp[0], c.sb);
      sts32(l8 + (c.sb + SM_SPM + 512 + (g >> 1) * 256 + (g & 1) * 4), scores_m(qx, km));
      mbar_arrive_warp(BAR(B_SC));
      unpack(f, sp);
      if (UP_F) sched_fence(c.sb);
      uint4 vm;
      if (VM_AT < 2) {
        bar_sync(NB_VM, 384);
        sp[1] = exp_pair(f, 1, off);
        const uint32_t av = dep(l8, VM_AT ? sp[1] : __float_as_uint(off), c.sb) + (c.sb + g * 512 + SM_VM);
        const uint2 vm0 = lds64(av), vm1 = lds64(av + 256);
        vm = make_uint4(vm0.x, vm0.y, vm1.x, vm1.y);
#pragma unroll
        for (int i = 2; i < 6; i++) sp[i % 5] = exp_pair(f, i % 5, off);
      } else {
#pragma unroll
        for (int i = 1; i < 6; i++) sp[i % 5] = exp_pair(f, i % 5, off);
        bar_sync(VM_AT == 2 ? dep(dep(0, sp[1] ^ sp[2], c.sb) + NB_VM, sp[0], c.sb) : dep(dep(0, sp[0] ^ sp[1] ^ sp[2], c.sb) + NB_VM, sp[3], c.sb), 384);
        const uint32_t av = l8 + (c.sb + g * 512 + SM_VM);
        const uint2 vm0 = lds64(av), vm1 = lds64(av + 256);
        vm = make_uint4(vm0.x, vm0.y, vm1.x, vm1.y);
      }
      uint2 u0, u1;
      uint4 sxx;
      auto load_sx = [&](uint32_t a8, int part = 3) {
        if (part & 1) { u0 = lds64(a8 + (c.sb + SM_SPM + 512)); u1 = lds64(a8 + (c.sb + SM_SPM + 768)); }
        if (part & 2) sxx = lds128(SXP >= 3 ? a8 * 2 + (c.sb + SM_Q) : l16 + SM_OX);
      };
      if (SXP && XL_AT && XL_AT < 4) load_sx(XL_AT == 2 ? dep(l8, vm.x, c.sb) : l8, XL_AT == 3 ? 1 : 3);
      float sum;
      auto rows_m = [&]() {
        const uint32_t tv = min(s, XEND - 1) / NSLOT;
        sum = pv(o, sp, vf, vm);
        stsm4<false>(l16 + SM_OM, pack_bf16(o[0][0], o[0][1]), pack_bf16(o[0][2], o[0][3]), pack_bf16(o[1][0], o[1][1]), pack_bf16(o[1][2], o[1][3]));
        sts32(c.sb + SM_SUM + ((l16 >> 4) & 28), __float_as_uint(sum));
        return arrive_if_clear(stale2(vf[0].x, vf[1].x, tv) | stale2(vf[2].x, vf[3].x, tv), EXP_CHK, NB_OM, 384);
      };
      const bool done = rows_m();
      if (SXP && XL_AT >= 3) load_sx(l8, XL_AT == 3 ? 2 : 3);
      if (!done) {
        const char* pv_ = c.mail + (uint32_t)(M_KVQ + (min(s, XEND - 1) & (NSLOT - 1)) * M_REG + c.h * 24576 + 8192 + (l16 - c.sb));
        uint32_t n = 0;
        do {
#pragma unroll
          for (int t = 0; t < 4; t++) vf[t] = ld_poll(pv_ + t * 2048);
          watchdog(n, POLL_LIMIT); CNT(5);
        } while (!rows_m());
        if (SXP && XL_AT) load_sx((l16 & 511) >> 1);
      }
      const uint32_t tom = clock_lo();
      TRV(s, 8, tom);
      if (XR_F) sched_fence(c.sb);
      ln = lane(tom);
      const int n = ln >> 2, jj = ln & 3, tq_ = 8 * c.j + (n & 4) + 2 * (n & 1) + ((n >> 1) & 1);
      if (DLY_X) delay_until(tom + DLY_X);
      if (SXP) {
        if (!XL_AT) load_sx(ln * 8);
        sp[0] = sum4(u0.x, u0.y, u1.x, u1.y); sp[1] = sxx.x; sp[2] = sxx.y; sp[3] = sxx.z; sp[4] = sxx.w;
      } else {
        load_scores(sp, spr + 640, c.sb + SM_SPM + 512 + ln * 8);
        causal(sp, ln);
      }
      mbar_arrive_warp(dep(dep(0, sp[0], c.sb), sp[1], c.sb) + BAR(B_SPFREE));
      float i0, i1;
      if (SXP == 4) {
        const float ox = __uint_as_float(lds32((ln & 28) + (c.sb + SM_Q + 512)));
        float sa[4] = {}, sb[4] = {}, om[2][4] = {};
#pragma unroll
        for (int t = 0; t < 2; t++) { o[t][0] = o[t][1] = o[t][2] = o[t][3] = 0.f; }
        off = row_off(sp[0], m1);
        mma_q(o[0], vf[0], sp[1], sp[2]); mma_q(o[1], vf[2], sp[1], sp[2]);
        mma16816(sa, sp[1], sp[2], sp[3], sp[4], ONES, ONES);
        mma_q(o[0], vf[1], sp[3], sp[4]); mma_q(o[1], vf[3], sp[3], sp[4]);
        off = fminf(off, ox);
        const uint32_t p0 = pack_bf16(ex2(fmaf(__uint_as_float(sp[0] << 16), SCL, off)), ex2(fmaf(__uint_as_float(sp[0] & 0xFFFF0000u), SCL, off)));
        float wx = ex2(off - ox);
        mma1688(sb, p0, ONES, ONES);
        mma1688(om[0], vm.x, vm.y, p0); mma1688(om[1], vm.z, vm.w, p0);
        if (DLY_Z) { sched_fence(dep(dep(c.sb, __float_as_uint(om[0][0]) ^ __float_as_uint(om[1][0]) ^ __float_as_uint(sb[0]), c.sb), __float_as_uint(o[0][0]) ^ __float_as_uint(o[1][0]) ^ __float_as_uint(sa[0]), c.sb)); delay_until(tom + DLY_Z); }
        const float j0 = __shfl_sync(~0u, wx, 8 * jj), j1 = __shfl_sync(~0u, wx, 8 * jj + 4);
        sum = fmaf(wx, sa[0] + sa[2], sb[0]);
#pragma unroll
        for (int i = 0; i < 8; i++) o[i >> 2][i & 3] = fmaf(o[i >> 2][i & 3], i & 1 ? j1 : j0, om[i >> 2][i & 3]);
      } else {
      off = row_off(max5(sp), m1);
      unpack(f, sp);
#pragma unroll
      for (int i = 1; i < 6; i++) sp[i % 5] = exp_pair(f, i % 5, off);
      if (DLY_Y) { sched_fence(dep(dep(c.sb, sp[0] ^ sp[1] ^ sp[2], c.sb), sp[3] ^ sp[4], c.sb)); delay_until(tom + DLY_Y); }
      sum = pv(o, sp, vf, vm);
      }
      TR(s, 7);
      sum = rcp(sum);
      i0 = __shfl_sync(~0u, sum, 8 * jj), i1 = __shfl_sync(~0u, sum, 8 * jj + 4);
      const uint32_t oxs = c.sb + SM_OX + g * 512;
      stsm4<true>(oxs + ((ln & 7) ^ (OX_L & l16 >> 9)) * 64 + (((ln >> 3) ^ ((ln >> 1) & 3)) << 4),
                  pack_bf16(o[0][0] * i0, o[0][1] * i1), pack_bf16(o[0][2] * i0, o[0][3] * i1), pack_bf16(o[1][0] * i0, o[1][1] * i1), pack_bf16(o[1][2] * i0, o[1][3] * i1));
      __syncwarp();
      if (OX_L) {
        const int r = l16 >> 7 & 7, hi = ln >> 2 & 1;
        bar_sync(5 + ((l16 - c.sb) >> 10), 64);
        *(uint4*)(g_ox + ox_at(s, 8 * c.j + (r & 4) + 2 * (r & 1) + ((r >> 1) & 1), c.h * 4 + g, (ln & 7) - (r & 4))) =
          lds128((l16 & ~1023u) + hi * 512 + (r ^ hi) * 64 + ((jj ^ (r >> 1)) << 4) + SM_OX);
        mbar_arrive_warp(BAR(B_PVDONE));
      } else if (!OX_AT) {
        *(uint4*)(g_ox + ox_at(s, tq_, c.h * 4 + g, jj)) = lds128(oxs + n * 64 + ((jj ^ (n >> 1)) << 4));
        mbar_arrive_warp(BAR(B_PVDONE));
      }
      TR(s, 9);
    }
    if (LASTM) {
      const int ln = tid_now() & 31, n = ln >> 2, jj = ln & 3, tq_ = 8 * c.j + (n & 4) + 2 * (n & 1) + ((n >> 1) & 1);
      store_count(g_ox + ox_at(NSEG - 1, tq_, c.h * 4 + g, jj), lds128(c.sb + SM_OX + g * 512 + (n ^ (OX_L & g)) * 64 + ((jj ^ (n >> 1)) << 4)), (char*)(g_ctl + C_LAST) + (LASTM == 2 ? c.r * 4 + g : 0));
    } else count_e(g_ctl + C_LAST);
    mbar_arrive_warp(BAR(B_DONE));
    if (tid_now() == 256) TL(8);
    __syncwarp();
    mbar_wait(BAR(B_E2TRIG), 1); mbar_idle(BAR(B_DONE), 0); mbar_wait(BAR(B_TW), 0);
    asm volatile("setmaxnreg.inc.sync.aligned.u32 128;");
  } else {
    {
      const int w = c.m * 4 + c.w;
      mbar_expect_e(BAR(B_ROWS), 4096 + 256);
      for (int i = 0; i < 2; i++) bulk_load_e(c.sb + SM_FFT + (1024 + w * ROW_BUF) * 8 + i * 2048, x + (size_t)(z_row(c.r * 8 + w) + i * 1024) * D_, 2048, BAR(B_ROWS));
      bulk_load_e(c.sb + SM_GW + w * 256, gw + w * 128, 256, BAR(B_ROWS));
    }
    asm volatile("setmaxnreg.inc.sync.aligned.u32 %0;" :: "n"(REG_F));
    c.lane = lane_id();
    uint32_t wa[16][4], wb[16][4], wv[16][4];
    TR(-2, 4);
    fft_rows_fwd((float2*)(smraw + SM_FFT), (const __nv_bfloat16*)(smraw + SM_GW), c.r, threadIdx.x, BAR(B_ROWS), BAR(B_FREE), [&](int e) { TR(-2, e); }, [&]() {
      mbar_spin(BAR(B_PFULL), 0);
#pragma unroll
      for (int k = 0; k < NP; k++) ldsm4t(wa[k], c.sb + SM_POOL + c.m * NP * 2048 + frag_off(c.w, c.lane) + k * 2048);
      bar_sync(NB_XCH, 256);
#pragma unroll
      for (int k = 0; k < NP; k++) sts128(c.sb + SM_POOL + c.m * 2048 + c.w * 512 + c.lane * 16 + k * 4096, make_uint4(wa[k][0], wa[k][1], wa[k][2], wa[k][3]));
    });
    mbar_arrive_warp(BAR(B_P1));
    TR(-2, 0);
    if (tid_now() == 0) TL2(1);
    __syncwarp();
    mbar_spin(BAR(B_WFULL + c.m), 0);
    TR(-2, 1);
    if ((tid_now() & 127) == 0) TL2(16);
    __syncwarp();
    {
      const uint32_t st = c.sb + c.m * ST_WG + frag_off(c.w, c.lane);
#pragma unroll
      for (int k = 0; k < 16; k++) ldsm4t(wb[k], st + k * 2048);
#pragma unroll
      for (int k = NP; k < 16; k++) ldsm4t(wa[k], st + (16 + k - NP) * 2048);
#pragma unroll
      for (int k = 0; k < NV; k++) ldsm4t(wv[k], st + (32 - NP + k) * 2048);
      mbar_arrive_warp(BAR(B_WREAD));
      if (c.m == 0) mbar_arrive_warp(BAR(B_WREAD0));
#pragma unroll
      for (int k = 0; k < (LP_IN == 2 ? 0 : NP); k++) lds_frag(wa[k], c.sb + SM_POOL + c.m * 2048 + c.w * 512 + c.lane * 16 + k * 4096);
      TR(-2, 2);
    }
    TR(-2, 3);
    if (tid_now() == 0) TL2(12);
    __syncwarp();
    asm volatile("barrier.cluster.wait;" ::: "memory");
    uint32_t t16 = c.m * 2048 + c.w * 512 + c.lane * 16;
    uint32_t pk = (c.m * NHV * 2048 + frag_off(c.w, c.lane)) | (tile_off(2 * (c.w & 1), c.lane) << 16) | ((c.lane & 12) ? 0u : 0x80000000u);
    const uint32_t dx1 = desc_lo(c.sb + SM_XT + c.m * 4096), dh = desc_lo(c.sb + SM_HV + c.m * NHV * 2048);
    mbar_spin(BAR(B_PFULL), 1);
    pad<PAD0>();
    for (int s = -2; ; s++) {
      t16 = vary(t16, s, c.sb); pk = vary(pk, s, c.sb);
      const uint32_t dx = dx1 - (s == -2 ? (SM_XT - SM_WO) / 16 : 0);
      auto ldp = [&](int k0, int k1, int d, int back = 0) {
#pragma unroll
        for (int k = k0; k < k1; k++) lds_frag(wa[k], (k < k0 + d - back ? t16 : dep(t16, wa[k < d ? 0 : k - d][0], c.sb)) + (c.sb + SM_POOL + k * 4096));
      };
      if (s >= 0) {
        uint32_t af[16][4], bf[4][4], wo;
        const uint32_t tab = ((t16 >> 3) & 0x1C0) + (c.sb + SM_TAB + (s & 1) * 512);
        const char* pa;
        mem_proj(wa, wb, wv, af, wo, pa, tab, t16, pk, c, s);
        const uint32_t t0 = clock_lo();
        t16 = dep(t16, t0, c.sb);
        auto ldwo = [&](int f) { ldsm4t(af[f], (f < WO_D ? wo : dep(wo, af[f < WO_D ? 0 : f - WO_D][0], c.sb)) + (c.sb + SM_WO + (f & 1) * 32768 + (f >> 1) * 2048)); };
        {
          const uint32_t tg = s >> 1, vm = t16 >> 1, chk = (~t16 >> 4) & 1;
          if (WO_S && s == 0) {
            mbar_spin(BAR(B_WOFULL), 0);
#pragma unroll
            for (int f = 0; f < WO_0; f++) ldwo(f);
          }
#pragma unroll
          for (int f = WO_0; f < WO_1; f++) ldwo(f);
          if (DLY_V) delay_fine(t0 + DLY_V); else sched_fence(c.sb);
          uint2 v0 = ld_poll2(pa), v1 = ld_poll2(pa + 1024), v2 = ld_poll2(pa + 2048), v3 = ld_poll2(pa + 3072);
          TR(s, 3);
#pragma unroll
          for (int f = WO_1; f < 16 - WO_L; f++) ldwo(f);
          TR(s, 4);
          uint32_t n = 0;
          while (true) {
            sts64(vm + (c.sb + SM_VM), sum4(v0.x, v1.x, v2.x, v3.x), sum4(v0.y, v1.y, v2.y, v3.y));
            if (arrive_if_clear(stale1(stale1(stale2(v0.x, v1.x, tg), v2.x, tg), v3.x, tg), chk, NB_VM, 384)) break;
            v0 = ld_poll2(pa); v1 = ld_poll2(pa + 1024); v2 = ld_poll2(pa + 2048); v3 = ld_poll2(pa + 3072);
            n++; CNT(3);
          }
          TR(s, 12); TRV(s, 15, n);
        }
        const uint32_t ob = dep(dep(t16 & 511, af[14 - WO_L][0], c.sb), af[15 - WO_L][0], c.sb);
        uint32_t l4 = ob >> 2;
        const uint32_t bit = (t16 & 48) ? 0u : 1u;
        if (LF_AT) mbar_spin2_if(BAR(B_XFULL), BAR(B_LFREE), s & 1, s + 2 < XEND); else mbar_spin_if(BAR(B_XFULL), s & 1, s + 2 < XEND);
        bar_sync(NB_OM, 384);
        TR(s, 5);
#pragma unroll
        for (int i = 0; i < 4; i++) ldsm4t(bf[i], ob + (c.sb + SM_OM + i * 512));
        uint2 sum = lds64(((t16 >> 1) & 24) + (c.sb + SM_SUM));
        if (OM_F) sched_fence(c.sb);
        float d[WO_C][4] = {};
        uint4 d0, d1;
#pragma unroll
        for (int f = 0; f < 16; f++) {
          mma_a(d[f % WO_C], af[f], bf[f >> 2][f & 2], bf[f >> 2][(f & 2) + 1]);
          if (f >= WO_C && f < WO_C + WO_L) {
            const int l = 16 - WO_L + f - WO_C;
            ldsm4t(af[l], (WO_LD ? dep(wo, __float_as_uint(d[(f + 1) % WO_C][0]), c.sb) : wo) + (c.sb + SM_WO + (l & 1) * 32768 + (l >> 1) * 2048));
          }
          if (f == WO_T) {
            const uint32_t tb2 = dep((t16 >> 3) & 0x1C0, __float_as_uint(d[f % WO_C][0]), c.sb) + (c.sb + SM_TAB + (s & 1) * 512);
            d0 = lds128(tb2 + 32); d1 = lds128(tb2 + 48);
          }
          if (f >= PL_WA && f < PL_WA + PL_W) lds_frag(wa[f - PL_WA], (PL_WD ? dep(t16, __float_as_uint(d[(f + PL_WD) % WO_C][0]), c.sb) : t16) + (c.sb + SM_POOL + (f - PL_WA) * 4096));
          if (PL_W && PL_WF == 1 && f == PL_WA + PL_W - 1) sched_fence(c.sb);
          if (f == 4) { sum.x = dep(sum.x, __float_as_uint(d[0][0]), c.sb); sum.y = dep(sum.y, __float_as_uint(d[0][0]), c.sb); }
        }
        if (PL_W && !PL_WF) {
          uint32_t all = 0;
#pragma unroll
          for (int k = 0; k < PL_W; k++) all ^= wa[k][0];
          l4 = dep(l4, all, c.sb);
        }
        char* dst[4] = {mk_ptr(d0.x | l4, d0.y), mk_ptr(d0.z | l4, d0.w), mk_ptr(d1.x | l4, d1.y), mk_ptr(d1.z | l4, d1.w)};
        const float i0 = rcp(__uint_as_float(sum.x)), i1 = rcp(__uint_as_float(sum.y));
#pragma unroll
        for (int i = 0; i < 4; i++) {
          const int t = i >> 1, e = 2 * (i & 1);
          const float y0 = WO_C == 2 ? d[t][e] : d[t][e] + d[(t + 2) % WO_C][e], y1 = WO_C == 2 ? d[t][e + 1] : d[t][e + 1] + d[(t + 2) % WO_C][e + 1];
          st_pub(dst[i], put_tag(pack_bf16(y0 * i0, y1 * i1), bit, s >> 1));
        }
        if (ANCH2) sts32(c.sb + SM_SUM + 64, clock_lo());
        mbar_arrive_warp(BAR(B_E2TRIG));
        TR(s, 6);
        sched_fence(c.sb);
        if (W_E2 == 2) mbar_spin(BAR(B_E2TRIG), s & 1);
#pragma unroll
        for (int k = PL_A; k < PL_0; k++)
#pragma unroll
          for (int i = 0; i < 4; i++) wa[k][i] = af[16 - PL_0 + k][i];
      }
      if (__builtin_expect(s + 2 < XEND, 1)) {
        const uint32_t tg0 = DLY_P ? clock_lo() + DLY_P : 0;
        if (LP_IN) ldp(PL_W, PL_A, PL_D);
        if (PL_A < PL_0 && c.m != ASY) ldp(PL_A, PL_0, PL_D, PL_A > PL_W ? PL_D : 0);
        auto late = [&](int at) {
          if (PL_A < PL_B && ASY_A == at && c.m == ASY) ldp(PL_A, PL_B, PL_DA);
          if (PL_B < PL_0 && ASY_AT == at && c.m == ASY) ldp(PL_B, PL_0, PL_DA);
        };
        float xa[16];
        uint32_t q[4];
        if (W_E2 == 1 && s >= 0) mbar_spin(BAR(B_E2TRIG), s & 1);
        TR(s, 7);
        constexpr int S1 = ORDER ? 0 : 2, S2 = ORDER == 0 ? 0 : ORDER == 1 ? 2 : 1, S3 = ORDER == 2 ? 2 : 1;
        if (ORDER) issue_qk<0, 16>(xa, wb, vary(dx, s, c.sb)); else issue_v(xa, wv, vary(dx, s, c.sb), vary(dh, s, c.sb));
        if (DLY_P) delay_until(tg0); else if (IS_F) sched_fence(c.sb);
        ldp(PL_0, PL_1, PL_D1);
        const uint32_t land = (t16 ^ ((t16 >> 3) & 0x60)) + vary(c.sb + SM_LAND + c.b * 4096, s, c.sb);
        TR(s, 14);
        if (LF_AT == 1) mbar_spin_if(BAR(B_LFREE), s & 1, s < 0); else if (!LF_AT) mbar_spin(BAR(B_LFREE), s & 1);
        TR(s, 15);
        late(0);
        WG_WAIT(0);
        TR(s, 8);
        park_own<S1 == 2>(q, xa, land, S1, c.sb);
        late(1);
        if (W_PUB == 4 && s >= 0) mbar_spin(BAR(B_PUB), s & 1);
        if (ORDER == 1) issue_v(xa, wv, vary(dx, s, c.sb + 32), vary(dh, s, c.sb)); else issue_qk<0, 16>(xa, ORDER ? wa : wb, vary(dx, s, c.sb + 32));
        if (IS_F) sched_fence(c.sb);
        ldp(PL_1, PL_2, PL_D1);
        if (W_PUB == 1) mbar_spin_if(BAR(B_PUB), s & 1, s >= 0);
        uint32_t tp = clock_lo(), q1[4] = {q[0], q[1], q[2], q[3]};
        if (PL_2B) ldp(PL_2, NP - PL_L, PL_D1);
        late(2);
        if (W_PUB != 3) park_peer(q, land, S1, c);
        if (!PL_2B) ldp(PL_2, NP - PL_L, PL_D1);
        late(3);
        TR(s, 13);
        WG_WAIT(0);
        TR(s, 9);
        park_own<S2 == 2>(q, xa, land, S2, c.sb);
        late(4);
        if (ORDER == 2) issue_v(xa, wv, vary(dx, s, c.sb + 64), vary(dh, s, c.sb));
        else {
          issue_qk<0, PL_L ? NP - PL_L : 16>(xa, wa, vary(dx, s, c.sb + 64));
          ldp(NP - PL_L, NP, PL_E);
          if (PL_L) issue_qk<NP - PL_L, 16>(xa, wa, vary(dx, s, c.sb + 64));
        }
        if ((W_PUB == 2 || W_PUB == 3) && s >= 0) { mbar_spin(BAR(B_PUB), s & 1); tp = clock_lo(); }
        if (W_PUB == 3) park_peer(q1, land, S1, c);
        if (DLY_S && s >= 0) delay_until(tp + DLY_S);
        park_peer(q, land, S2, c);
        WG_WAIT(0);
        TR(s, 10);
        mbar_arrive_warp(BAR(B_XEMPTY));
        park_own<S3 == 2>(q, xa, land, S3, c.sb);
        park_peer(q, land, S3, c);
        TR(s, 11);
      } else {
        if (s == NSEG - 1) break;
        if (EARLY2 && (XEND == NSEG || s == NSEG - 2) && c.m * 4 + c.w == 0) count_e(g_ctl + C_EARLY);
        ldp(PL_W, NP, 2);
      }
    }
    asm volatile("setmaxnreg.dec.sync.aligned.u32 %0;" :: "n"(BPRE == 2 ? 176 : 128));
    const int tid = tid_now(), lane = tid & 31, tile = tile_of(c), m0 = (tile >> 3) * 128, n0 = (tile & 7) * 128;
    float acc[64];
#pragma unroll
    for (int i = 0; i < 64; i++) acc[i] = 0.f;
    const uint32_t rel = mapa(BAR(B_GEMPTY), lane & 1), la = desc_lo(c.sb + c.m * 8192), lb = ((c.sb + 16384) & 0x3FFFF) >> 4 | (8192 >> 4) << 16;
    bool relon = false;
    const int skew = tile < 120 ? 0 : SKEW, kend = 64 + skew - c.m * skew, hold = c.m * (65 - LEAD) - 1;
    const float g0 = __ldcg(g_gate + m0 + (tid >> 5) * 16 + (lane >> 2)), g1 = __ldcg(g_gate + m0 + (tid >> 5) * 16 + (lane >> 2) + 8);
    uint32_t o = SM_XT, st = 0, ph = 0, prev = 0;
    if (tid == 0) TL(9);
    __syncwarp();
    GT(0);
#pragma unroll 1
    for (int kb = -c.m * skew; kb < max(kend - 4, 64); kb++, o = next_stage(o)) {
      if (LEAD && kb == hold) bar_sync(15, 256);
      mbar_lim(BAR(B_GFULL + st), ph);
      if ((uint32_t)kb < 64) {
        WG_FENCE();
#pragma unroll
        for (int k = 0; k < 4; k++) wgmma_ss_n128_tb(acc, desc128(la + (o >> 4) + k * 2), desc128(lb + (o >> 4) + k * 128));
        WG_COMMIT();
        WG_WAIT(1);
      } else WG_WAIT(0);
      arrive_remote_if(rel + 8 * prev, relon && kb < kend - 4);
      relon = (tid & 127) < 2;
      prev = st;
      if (++st == 5) { st = 0; ph ^= 1; }
    }
    if (LEAD && c.m == 0) asm volatile("bar.arrive 15, 256;" ::: "memory");
    const uint32_t row = (tid >> 5) * 2048 + (lane & 15) * 128 + (((lane >> 4) ^ (lane & 7)) << 4);
    if (!BPRE) WG_WAIT(0);
    mbar_lim(BAR(B_BT), 0);
    uint32_t b[2][4][4];
    const uint32_t rb = (tid >> 5) * 2048 + (lane >> 2) * 128 + (((lane & 7) ^ (lane >> 2)) << 4);
#pragma unroll
    for (int i = 0; i < 8; i++) lds_frag(b[i & 1][i >> 1], (rb ^ (i & 2) * 32) + (c.sb + SM_BT + (i >> 2) * 16384 + (i & 1) * 1024));
    float bl[2][4][4], bh[2][4][4];
    if (BPRE == 2) {
#pragma unroll
      for (int i = 0; i < 32; i++) {
        asm volatile("shl.b32 %0, %1, 16;" : "=f"(bl[i >> 4][i >> 2 & 3][i & 3]) : "r"(b[i >> 4][i >> 2 & 3][i & 3]));
        asm volatile("and.b32 %0, %1, 0xffff0000;" : "=f"(bh[i >> 4][i >> 2 & 3][i & 3]) : "r"(b[i >> 4][i >> 2 & 3][i & 3]));
      }
    }
    if (BPRE) { sched_fence(c.sb); WG_WAIT(0); sched_fence(c.sb); }
#pragma unroll
    for (int i = 0; i < 64; i++) asm volatile("" : "+f"(acc[i]) :: "memory");
    GT(17);
    if (tid == 0) TL(4);
    __syncwarp();
#pragma unroll
    for (int hf = 0; hf < 2; hf++) {
#pragma unroll
      for (int t = 0; t < 4; t++) {
        uint32_t y[4];
#pragma unroll
        for (int i = 0; i < 4; i++) {
          const float* a = acc + 32 * hf + 8 * t + 2 * i, g = i & 1 ? g1 : g0;
          const uint32_t* q = b[i & 1][2 * (t & 1) + (i >> 1)] + hf;
          const float* f = (t & 2 ? bh : bl)[i & 1][2 * (t & 1) + (i >> 1)] + hf;
          if (BPRE == 2) y[i] = pack_bf16(fmaf(g, a[0], f[0]), fmaf(g, a[1], f[2])); else
          y[i] = pack_bf16(fmaf(g, a[0], __uint_as_float(t & 2 ? q[0] & 0xFFFF0000u : q[0] << 16)), fmaf(g, a[1], __uint_as_float(t & 2 ? q[2] & 0xFFFF0000u : q[2] << 16)));
        }
        stsm4<false>((row ^ t * 32) + (c.sb + SM_BT + hf * 16384), y[0], y[1], y[2], y[3]);
      }
      if (EP_F && !hf) { sched_fence(c.sb); for (int i = 32; i < 64; i++) asm volatile("" : "+f"(acc[i]) :: "memory"); }
      FENCE_ASYNC_SMEM();
      __syncwarp();
      tma2d_out_e(&tout, n0 + hf * 64, m0 + (c.m * 4 + c.w) * 16, c.sb + SM_BT + hf * 16384 + (c.m * 4 + c.w) * 2048);
    }
    asm volatile("cp.async.bulk.commit_group; cp.async.bulk.wait_group" WAITRD " 0;" ::: "memory");
    GT(18);
    if ((tid & 127) == 0) TL(11);
    return;
  }
  constexpr int NH = NQ < 106 ? 4 * (106 - NQ) : 0;
  const bool col = c.r >= 128;
  const int tile = col ? 0 : tile_of(c);
  const int q0 = col ? 256 - NQ + (c.r - 128) + c.m * 4 : tile < 120 ? tile : 256, u = (tile >> 1 & 32) | (tile >> 3 & 7) | (tile & 6) << 2, e = QSH == 2 ? 2 * (u - (u > 39) - (u > 47) - (NQ < 110 && u > 55)) + c.b : tile,
            dq = col ? 16 : QSH ? 120 + (e < NH ? e >> 1 : (e + NH) >> 2) - tile : 120, qe = col ? 256 : 256 - NQ,
            qw = col || !QSH || (e < NH ? c.w >> 1 == c.b : c.w == ((e + NH) & 3)) ? qe : 120;
  const uint32_t zs = c.sb + (col ? COL_Z + c.m * 32768 : SM_BT), zb = BAR(B_Z + c.m);
  auto load_z = [&](int q) { if (c.w == 0 && q < qe) { mbar_expect_e(zb, 32768); tma2d_o<(ONCE & 4) != 0>(zs, &tz, q * 64, 0, zb); } };
  asm volatile("fence.proxy.async.global;" ::: "memory");
  load_z(q0);
  uint32_t ph = 0;
#pragma unroll 1
  for (int q = q0; q < qe; q += dq, ph ^= 1) {
    mbar_lim(zb, ph);
    const int p = q * 4 + c.w;
    if (EXP_INV && q < qw) fft_rows_inv(zs, (float2*)(smraw + (col ? 8192 + c.m * INV_BUF * 32 : SM_MEM)) + c.w * INV_BUF, (const float2*)(smraw + (col ? 0 : SM_TW)), p, tid_now() & 31, g_b,
                              [&]() { bar_sync(5 + c.m, 128); load_z(q + dq); });
    else { bar_sync(5 + c.m, 128); load_z(q + dq); }
  }
  if (B_ST) asm volatile("cp.async.bulk.wait_group 0; fence.proxy.async.global;" ::: "memory");
  asm volatile("fence.acq_rel.gpu;" ::: "memory");
  __syncwarp();
  { const int q = q0 + (tid_now() & 31) * dq; if (q < qw) asm volatile("red.relaxed.gpu.global.add.u32 [%0], 1;" :: "l"(g_ctl + C_ROWS + (q >> 5) * 32) : "memory"); }
  if (tid_now() == 256) { if (col) TL(27); else TL(3); }
  __syncwarp();
  if (!col && c.w == 0) {
    await_count<AW_NS>(g_ctl + C_ROWS + ((tile >> 3) & 7) * 32, 128);
    mbar_expect_e(BAR(B_BT), 32768);
    for (int i = 0; i < 2; i++) tma2d_o<(ONCE & 8) != 0>(c.sb + SM_BT + i * 16384, &tb, (tile & 7) * 128 + i * 64, (tile >> 3) * 128, BAR(B_BT));
    if (tid_now() == 256) TL(5);
  }
}

typedef CUresult (*EncodeFn)(CUtensorMap*, CUtensorMapDataType, cuuint32_t, void*, const cuuint64_t*, const cuuint64_t*,
                             const cuuint32_t*, const cuuint32_t*, CUtensorMapInterleave, CUtensorMapSwizzle,
                             CUtensorMapL2promotion, CUtensorMapFloatOOBfill);

void make_map(EncodeFn enc, CUtensorMap* tm, const void* p, int rank, const cuuint64_t* dims, const cuuint64_t* strides, const cuuint32_t* box, bool swz = true) {
  const cuuint32_t es[4] = {1, 1, 1, 1};
  enc(tm, CU_TENSOR_MAP_DATA_TYPE_BFLOAT16, rank, (void*)p, dims, strides, box, es, CU_TENSOR_MAP_INTERLEAVE_NONE,
      swz ? CU_TENSOR_MAP_SWIZZLE_128B : CU_TENSOR_MAP_SWIZZLE_NONE, swz ? CU_TENSOR_MAP_L2_PROMOTION_L2_128B : W_PROMO, CU_TENSOR_MAP_FLOAT_OOB_FILL_NONE);
}
void make_map2(EncodeFn enc, CUtensorMap* tm, const void* p, uint64_t cols, uint64_t rows, uint32_t boxrows) {
  const cuuint64_t dims[2] = {cols, rows}, strides[1] = {cols * 2};
  const cuuint32_t box[2] = {64, boxrows};
  make_map(enc, tm, p, 2, dims, strides, box);
}

}

extern "C" void kernel_launch(void* const* d_in, const int* in_sizes, int n_in, void* d_out, int out_size) {
  (void)in_sizes; (void)n_in; (void)out_size;
  const __nv_bfloat16* x = (const __nv_bfloat16*)d_in[0];
  const __nv_bfloat16* mem0 = (const __nv_bfloat16*)d_in[1];
  const __nv_bfloat16* gw = (const __nv_bfloat16*)d_in[10];

  EncodeFn enc = nullptr;
  cudaDriverEntryPointQueryResult qr;
  cudaGetDriverEntryPoint("cuTensorMapEncodeTiled", (void**)&enc, cudaEnableDefault, &qr);
  void *p_ox, *p_b, *p_z, *p_mail;
  cudaGetSymbolAddress(&p_ox, g_ox); cudaGetSymbolAddress(&p_b, g_b); cudaGetSymbolAddress(&p_z, g_z); cudaGetSymbolAddress(&p_mail, g_mail);
  CUtensorMap tq, tk, tv, tv16, to, tx, twr, twi, ta, tw, tb, tout, tz, tzs, ta32;
  make_map2(enc, &tq, d_in[2], 4096, 1024, 64);
  make_map2(enc, &tk, d_in[3], 4096, 1024, 64);
  make_map2(enc, &tv, d_in[4], 4096, 1024, 64);
  make_map2(enc, &tv16, d_in[4], 4096, 1024, 16);
  make_map2(enc, &to, d_in[5], 1024, 4096, 128);
  make_map2(enc, &tw, d_in[5], 1024, 4096, 64);
  {
    const cuuint64_t dims[3] = {64, 2048, 64}, strides[2] = {128, 262144};
    const cuuint32_t box[3] = {64, 32, 2}, box1[3] = {64, 32, 1};
    make_map(enc, &ta, p_ox, 3, dims, strides, box);
    make_map(enc, &ta32, p_ox, 3, dims, strides, box1);
  }
  make_map2(enc, &tb, p_b, 1024, 2048, 128);
  make_map2(enc, &tout, d_out, 1024, 2048, 16);
  make_map2(enc, &tz, p_z, 16384, 257, 256);
  {
    const cuuint64_t dims[4] = {64, 8, 16, 256}, strides[3] = {2048, 128, 16384};
    const cuuint32_t box[4] = {64, 8, 8, 2};
    make_map(enc, &tx, x, 4, dims, strides, box);
  }
  {
    const cuuint64_t dims[2] = {512, 257 * 32}, strides[1] = {1024};
    const cuuint32_t box[2] = {128, 16};
    make_map(enc, &tzs, p_z, 2, dims, strides, box, false);
  }
  {
    const cuuint64_t dims[2] = {8 * 513, 256}, strides[1] = {8 * 513 * 2};
    const cuuint32_t box[2] = {8, 256};
    make_map(enc, &twr, d_in[8], 2, dims, strides, box, false);
    make_map(enc, &twi, d_in[9], 2, dims, strides, box, false);
  }
  cudaFuncSetAttribute(chain_kernel, cudaFuncAttributeMaxDynamicSharedMemorySize, CHAIN_SMEM);

  cudaStream_t st = cudaStreamPerThread;
  char* mail = (char*)(((uintptr_t)p_mail + M_REG - 1) & ~(uintptr_t)(M_REG - 1));
  chain_kernel<<<132, 512, CHAIN_SMEM, st>>>(tq, tk, tv, tv16, to, tx, twr, twi, ta, tw, tb, tout, tz, tzs, ta32, mem0, mail, x, gw);
}
```
